```python
import torch

def _softmax(x, axis=-1):
    return torch.softmax(x, dim=axis)

def _gelu(x):
    return torch.nn.functional.gelu(x, approximate='tanh')

def _silu(x):
    return torch.nn.functional.silu(x)

def _sigmoid(x):
    return torch.sigmoid(x)

def _layernorm(x, axis=-1, eps=1e-05):
    m = x.mean(dim=axis, keepdim=True)
    v = x.var(dim=axis, keepdim=True, unbiased=False)
    return (x - m) / torch.sqrt(v + eps)

def _scatter_add(tgt, idx, src, axis=0):
    return tgt.clone().index_add_(axis, idx, src)

def _segment_sum(src, seg, n):
    out = torch.zeros((n,) + src.shape[1:], dtype=src.dtype)
    return out.index_add_(0, seg, src)

def _pad(x, pw):
    flat = tuple((v for pair in reversed(pw) for v in pair))
    return torch.nn.functional.pad(x, flat)
kernel_name = 'interleave_layers__memory_aug_recurrent_mem_tr__glu_gated_geglu__prompt'

def setup_inputs():

    _w = lambda a: (lambda t: t.to(torch.bfloat16) if t.is_floating_point() else t)(torch.as_tensor(a))

    def _A_setup():
        B, S, Dm = (1, 2048, 1024)
        H, Dh = (32, 128)
        M, seg = (8, 32)
        seg = min(seg, S)
        S = S // seg * seg
        return {'x': _w((lambda *s: torch.randn(*s, dtype=torch.bfloat16) * 0.05)(B, S, Dm)), 'mem0': _w((lambda *s: torch.randn(*s, dtype=torch.bfloat16) * 0.2)(B, M, Dm)), 'Wq': _w((lambda *s: torch.randn(*s, dtype=torch.bfloat16) * 1.6)(Dm, H, Dh) * Dm ** (-0.5)), 'Wk': _w((lambda *s: torch.randn(*s, dtype=torch.bfloat16) * 1.6)(Dm, H, Dh) * Dm ** (-0.5)), 'Wv': _w((lambda *s: torch.randn(*s, dtype=torch.bfloat16) * 0.2)(Dm, H, Dh) * Dm ** (-0.5)), 'Wo': _w((lambda *s: torch.randn(*s, dtype=torch.bfloat16) * 0.2)(H, Dh, Dm) * (H * Dh) ** (-0.5)), 'seg_len': seg}
    _A_in = _A_setup()

    def _B_setup():
        B, S, Dm, Df = (1, 2048, 1024, 3584)
        return {'x': _w((lambda *s: torch.randn(*s, dtype=torch.bfloat16) * 0.05)(B, S, Dm)), 'w_gate': _w((lambda *s: torch.randn(*s, dtype=torch.bfloat16) * 0.4)(Dm, Df) * Dm ** (-0.5)), 'w_up': _w((lambda *s: torch.randn(*s, dtype=torch.bfloat16) * 0.4)(Dm, Df) * Dm ** (-0.5)), 'w_down': _w((lambda *s: torch.randn(*s, dtype=torch.bfloat16) * 0.4)(Df, Dm) * Df ** (-0.5))}
    _B_in = _B_setup()
    return {'A_x': _A_in['x'], 'A_mem0': _A_in['mem0'], 'A_Wq': _A_in['Wq'], 'A_Wk': _A_in['Wk'], 'A_Wv': _A_in['Wv'], 'A_Wo': _A_in['Wo'], 'A_seg_len': _A_in['seg_len'], 'B_x': _B_in['x'], 'B_w_gate': _B_in['w_gate'], 'B_w_up': _B_in['w_up'], 'B_w_down': _B_in['w_down']}

def reference(A_x, A_mem0, A_Wq, A_Wk, A_Wv, A_Wo, A_seg_len, B_x, B_w_gate, B_w_up, B_w_down):

    def _A_ref(x, mem0, Wq, Wk, Wv, Wo, seg_len):
        B, S, Dm = x.shape
        H, Dh = (Wq.shape[1], Wq.shape[2])
        M = mem0.shape[1]
        scale = Dh ** (-0.5)
        n_seg = S // seg_len
        L = M + seg_len
        idx = torch.arange(L)
        mask = (idx[:, None] < M) | (idx[:, None] >= idx[None, :])
        mem = mem0
        outs = []
        for s in range(n_seg):
            xs = x[:, s * seg_len:(s + 1) * seg_len, :].clone()
            h = torch.concatenate([mem, xs], axis=1)
            q = torch.einsum('btd,dhe->bhte', h, Wq)
            k = torch.einsum('btd,dhe->bhte', h, Wk)
            v = torch.einsum('btd,dhe->bhte', h, Wv)
            scores = torch.einsum('bhqe,bhke->bhqk', q, k) * scale
            scores = torch.where(mask[None, None], scores, -1000000000.0)
            p = _softmax(scores, axis=-1)
            o = torch.einsum('bhqk,bhke->bhqe', p, v)
            o = torch.einsum('bhte,hed->btd', o, Wo)
            mem = o[:, :M, :].clone()
            outs.append(o[:, M:, :])
        return torch.concatenate(outs, axis=1)

    def _B_ref(x, w_gate, w_up, w_down):
        g = torch.einsum('bsd,df->bsf', x, w_gate)
        u = torch.einsum('bsd,df->bsf', x, w_up)
        h = _gelu(g) * u
        return torch.einsum('bsf,fd->bsd', h, w_down)
    x = A_x
    x = x + _A_ref(_layernorm(x, axis=-1), A_mem0, A_Wq, A_Wk, A_Wv, A_Wo, A_seg_len)
    x = x + _B_ref(_layernorm(x, axis=-1), B_w_gate, B_w_up, B_w_down)
    x = x + _A_ref(_layernorm(x, axis=-1), A_mem0, A_Wq, A_Wk, A_Wv, A_Wo, A_seg_len)
    x = x + _B_ref(_layernorm(x, axis=-1), B_w_gate, B_w_up, B_w_down)
    return x
```

```cpp
#include <cuda_runtime.h>
#include <cuda_bf16.h>
#include <cuda.h>
#include <stdint.h>

#define DEVI __device__ __forceinline__
typedef __nv_bfloat16 bf16;

constexpr int SEQ = 2048, DM = 1024, NH = 32, DH = 128, DF = 3584, NSEG = 64;
#define LAG 16
constexpr int NSTEP = NSEG + LAG;

constexpr size_t O_LAYER = 0;
__device__ __align__(1024) bf16 g_xn[SEQ * DM];
__device__ __align__(1024) bf16 g_ot[SEQ * NH * DH + O_LAYER];
__device__ __align__(1024) bf16 g_h[SEQ * DF];
__device__ __align__(1024) uint4 g_h1[2][256 * 256];
__device__ __align__(1024) uint4 g_h2[4][2048];
enum { Q_D1, Q_G1, Q_O1, Q_O2, Q_G2, Q_D2, L_I, L_X2, L_X1A, L_X1B, NQ };
__device__ __align__(128) int g_dep[NQ][32];
__device__ __align__(128) int g_claim[NQ][32];
__device__ __align__(128) int g_xa[2][32];

DEVI uint32_t smem_u32(const void* p) { return (uint32_t)__cvta_generic_to_shared(p); }
DEVI void mbar_init(uint32_t bar, uint32_t cnt) { asm volatile("mbarrier.init.shared::cta.b64 [%0], %1;" :: "r"(bar), "r"(cnt) : "memory"); }
DEVI void mbar_arrive(uint32_t bar) { asm volatile("mbarrier.arrive.shared::cta.b64 _, [%0];" :: "r"(bar) : "memory"); }
DEVI bool mbar_try(uint32_t bar, uint32_t parity) {
  uint32_t p;
  asm volatile("{.reg .pred p; mbarrier.try_wait.parity.shared::cta.b64 p, [%1], %2; selp.u32 %0, 1, 0, p;}" : "=r"(p) : "r"(bar), "r"(parity) : "memory");
  return p;
}
constexpr int SPIN_BUDGET = 1 << 18;
DEVI void mbar_wait(uint32_t bar, uint32_t parity, int& budget) {
  while (!mbar_try(bar, parity)) { if (--budget < 0) break; }
}
DEVI bool mbar_try_cluster(uint32_t bar, uint32_t parity) {
  uint32_t p;
  asm volatile("{.reg .pred p; mbarrier.try_wait.parity.acquire.cluster.shared::cta.b64 p, [%1], %2; selp.u32 %0, 1, 0, p;}" : "=r"(p) : "r"(bar), "r"(parity) : "memory");
  return p;
}
DEVI void mbar_wait_cluster(uint32_t bar, uint32_t parity, int& budget) {
  while (!mbar_try_cluster(bar, parity)) { if (--budget < 0) break; }
}
DEVI uint32_t mapa(uint32_t addr, uint32_t rank) { uint32_t r; asm("mapa.shared::cluster.u32 %0, %1, %2;" : "=r"(r) : "r"(addr), "r"(rank)); return r; }
DEVI void cluster_arrive() { asm volatile("barrier.cluster.arrive.release.aligned;" ::: "memory"); }
DEVI void cluster_wait() { asm volatile("barrier.cluster.wait.acquire.aligned;" ::: "memory"); }
DEVI void fence_mbar_init() { asm volatile("fence.mbarrier_init.release.cluster;" ::: "memory"); }
DEVI void fence_proxy_async() { asm volatile("fence.proxy.async.shared::cta;" ::: "memory"); }
DEVI void fence_proxy_global() { asm volatile("fence.proxy.async.global;" ::: "memory"); }
#define ELECT "{.reg .pred p; elect.sync _|p, 0xffffffff;\n @p "
DEVI void e_expect_tx(uint32_t bar, uint32_t bytes) { asm volatile(ELECT "mbarrier.arrive.expect_tx.shared::cta.b64 _, [%0], %1;}" :: "r"(bar), "r"(bytes) : "memory"); }
DEVI void e_arrive(uint32_t bar) { asm volatile(ELECT "mbarrier.arrive.shared::cta.b64 _, [%0];}" :: "r"(bar) : "memory"); }
DEVI void e_tma_2d(uint32_t dst, const CUtensorMap* m, int c0, int c1, uint32_t bar) {
  asm volatile(ELECT "cp.async.bulk.tensor.2d.shared::cluster.global.mbarrier::complete_tx::bytes [%0], [%1, {%3, %4}], [%2];}"
    :: "r"(dst), "l"(m), "r"(bar), "r"(c0), "r"(c1) : "memory");
}
DEVI void e_prefetch_2d(const CUtensorMap* m, int c0, int c1) {
  asm volatile(ELECT "cp.async.bulk.prefetch.tensor.2d.L2.global [%0, {%1, %2}];}" :: "l"(m), "r"(c0), "r"(c1) : "memory");
}
DEVI void p_arrive(uint32_t bar, bool c) { asm volatile("{.reg .pred p; setp.ne.u32 p, %1, 0; @p mbarrier.arrive.shared::cta.b64 _, [%0];}" :: "r"(bar), "r"((uint32_t)c) : "memory"); }
DEVI void tma_store_2d(const CUtensorMap* m, uint32_t src, int c0, int c1) {
  asm volatile("cp.async.bulk.tensor.2d.global.shared::cta.bulk_group [%0, {%2, %3}], [%1];" :: "l"(m), "r"(src), "r"(c0), "r"(c1) : "memory");
}
DEVI void tma_radd_2d(const CUtensorMap* m, uint32_t src, int c0, int c1) {
  asm volatile("cp.reduce.async.bulk.tensor.2d.global.shared::cta.add.bulk_group [%0, {%2, %3}], [%1];" :: "l"(m), "r"(src), "r"(c0), "r"(c1) : "memory");
}
DEVI void bulk_commit() { asm volatile("cp.async.bulk.commit_group;" ::: "memory"); }
template<int N> DEVI void bulk_wait_read() { asm volatile("cp.async.bulk.wait_group.read %0;" :: "n"(N) : "memory"); }
template<int N> DEVI void bulk_wait() { asm volatile("cp.async.bulk.wait_group %0;" :: "n"(N) : "memory"); }
template<int ID, int N> DEVI void nbar_sync() { asm volatile("bar.sync %0, %1;" :: "n"(ID), "n"(N) : "memory"); }
template<int ID, int N> DEVI void nbar_arrive() { asm volatile("bar.arrive %0, %1;" :: "n"(ID), "n"(N) : "memory"); }
DEVI void nbar_sync_r(int id, int n) { asm volatile("bar.sync %0, %1;" :: "r"(id), "r"(n) : "memory"); }
template<int R> DEVI void reg_inc() { asm volatile("setmaxnreg.inc.sync.aligned.u32 %0;" :: "n"(R)); }
template<int R> DEVI void reg_dec() { asm volatile("setmaxnreg.dec.sync.aligned.u32 %0;" :: "n"(R)); }
DEVI void wg_fence() { asm volatile("wgmma.fence.sync.aligned;" ::: "memory"); }
DEVI void wg_commit() { asm volatile("wgmma.commit_group.sync.aligned;" ::: "memory"); }
template<int N> DEVI void wg_wait() { asm volatile("wgmma.wait_group.sync.aligned %0;" :: "n"(N) : "memory"); }
DEVI uint64_t mkdesc(uint32_t addr, uint32_t lbo, uint32_t sbo, uint32_t sw = 1) {
  return ((uint64_t)((addr & 0x3FFFF) >> 4)) | ((uint64_t)(lbo >> 4) << 16) | ((uint64_t)(sbo >> 4) << 32) | ((uint64_t)sw << 62);
}
constexpr long long CD(uint32_t off, uint32_t lbo, uint32_t sbo, uint32_t sw) {
  return (long long)(((uint64_t)(off >> 4)) | ((uint64_t)(lbo >> 4) << 16) | ((uint64_t)(sbo >> 4) << 32) | ((uint64_t)sw << 62));
}
DEVI uint32_t pack_bf16(float lo, float hi) { uint32_t r; asm("cvt.rn.bf16x2.f32 %0, %1, %2;" : "=r"(r) : "f"(hi), "f"(lo)); return r; }
DEVI float bf_lo(uint32_t v) { return __uint_as_float(v << 16); }
DEVI float bf_hi(uint32_t v) { return __uint_as_float(v & 0xffff0000u); }
DEVI void ldsm4t(uint32_t addr, uint32_t& r0, uint32_t& r1, uint32_t& r2, uint32_t& r3) {
  asm volatile("ldmatrix.sync.aligned.m8n8.x4.trans.shared.b16 {%0,%1,%2,%3}, [%4];" : "=r"(r0), "=r"(r1), "=r"(r2), "=r"(r3) : "r"(addr) : "memory");
}
DEVI void stsm4(uint32_t addr, uint32_t r0, uint32_t r1, uint32_t r2, uint32_t r3) {
  asm volatile("stmatrix.sync.aligned.m8n8.x4.shared.b16 [%0], {%1,%2,%3,%4};" :: "r"(addr), "r"(r0), "r"(r1), "r"(r2), "r"(r3) : "memory");
}
DEVI uint2 lds64v(uint32_t a) { uint2 v; asm volatile("ld.volatile.shared.v2.u32 {%0,%1}, [%2];" : "=r"(v.x), "=r"(v.y) : "r"(a) : "memory"); return v; }
DEVI void sts64(uint32_t a, uint32_t x, uint32_t y) { asm volatile("st.shared.v2.u32 [%0], {%1,%2};" :: "r"(a), "r"(x), "r"(y) : "memory"); }
DEVI void sts128(uint32_t a, uint4 v) { asm volatile("st.shared.v4.u32 [%0], {%1,%2,%3,%4};" :: "r"(a), "r"(v.x), "r"(v.y), "r"(v.z), "r"(v.w) : "memory"); }
DEVI void st_async128(uint32_t a, uint32_t x, uint32_t y, uint32_t z, uint32_t w, uint32_t bar) {
  asm volatile("st.async.weak.shared::cluster.mbarrier::complete_tx::bytes.v4.b32 [%0], {%1,%2,%3,%4}, [%5];" :: "r"(a), "r"(x), "r"(y), "r"(z), "r"(w), "r"(bar) : "memory");
}
DEVI void st_async32(uint32_t a, uint32_t x, uint32_t bar) {
  asm volatile("st.async.weak.shared::cluster.mbarrier::complete_tx::bytes.b32 [%0], %1, [%2];" :: "r"(a), "r"(x), "r"(bar) : "memory");
}
DEVI uint4 ldg_rlx128(const void* p) {
  uint4 v;
  asm volatile("ld.relaxed.gpu.global.v4.b32 {%0,%1,%2,%3}, [%4];" : "=r"(v.x), "=r"(v.y), "=r"(v.z), "=r"(v.w) : "l"(p) : "memory");
  return v;
}
DEVI int ldg_rlx32(const void* p) { int v; asm volatile("ld.relaxed.gpu.global.b32 %0, [%1];" : "=r"(v) : "l"(p) : "memory"); return v; }
DEVI int ldg_acq32(const void* p) { int v; asm volatile("ld.acquire.gpu.global.b32 %0, [%1];" : "=r"(v) : "l"(p) : "memory"); return v; }
DEVI void stg_rlx128(void* p, uint32_t x, uint32_t y, uint32_t z, uint32_t w) {
  asm volatile("st.relaxed.gpu.global.v4.b32 [%0], {%1,%2,%3,%4};" :: "l"(p), "r"(x), "r"(y), "r"(z), "r"(w) : "memory");
}
DEVI void stg128(void* p, uint32_t x, uint32_t y, uint32_t z, uint32_t w) {
  asm volatile("st.global.v4.b32 [%0], {%1,%2,%3,%4};" :: "l"(p), "r"(x), "r"(y), "r"(z), "r"(w) : "memory");
}
DEVI void stg_rlx32(void* p, uint32_t x) { asm volatile("st.relaxed.gpu.global.b32 [%0], %1;" :: "l"(p), "r"(x) : "memory"); }
DEVI void flag_add(int* p) { asm volatile("fence.proxy.async.global; red.release.gpu.global.add.s32 [%0], 1;" :: "l"(p) : "memory"); }
DEVI uint32_t clock32() { uint32_t c; asm volatile("mov.u32 %0, %%clock;" : "=r"(c)); return c; }
DEVI uint32_t gtime() { uint32_t c; asm volatile("mov.u32 %0, %%globaltimer_lo;" : "=r"(c)); return c; }
DEVI uint32_t settag(uint32_t v, uint32_t tag) { return (v & ~1u) | tag; }

#define A4(c, o)  c(d[o+0]), c(d[o+1]), c(d[o+2]), c(d[o+3])
#define A8(c, o)  A4(c, o), A4(c, o+4)
#define A16(c, o) A8(c, o), A8(c, o+8)
#define A20(c, o) A16(c, o), A4(c, o+16)
#define A32(c, o) A16(c, o), A16(c, o+16)
#define RL8  "{%0,%1,%2,%3,%4,%5,%6,%7}"
#define RL16 "{%0,%1,%2,%3,%4,%5,%6,%7,%8,%9,%10,%11,%12,%13,%14,%15}"
#define RL20 "{%0,%1,%2,%3,%4,%5,%6,%7,%8,%9,%10,%11,%12,%13,%14,%15,%16,%17,%18,%19}"
#define RL32 "{%0,%1,%2,%3,%4,%5,%6,%7,%8,%9,%10,%11,%12,%13,%14,%15,%16,%17,%18,%19,%20,%21,%22,%23,%24,%25,%26,%27,%28,%29,%30,%31}"
#define RL64 "{%0,%1,%2,%3,%4,%5,%6,%7,%8,%9,%10,%11,%12,%13,%14,%15,%16,%17,%18,%19,%20,%21,%22,%23,%24,%25,%26,%27,%28,%29,%30,%31," \
  "%32,%33,%34,%35,%36,%37,%38,%39,%40,%41,%42,%43,%44,%45,%46,%47,%48,%49,%50,%51,%52,%53,%54,%55,%56,%57,%58,%59,%60,%61,%62,%63}"
#define WG_OP(shape) "wgmma.mma_async.sync.aligned." shape "k16.f32.bf16.bf16 "
#define DEF_WGMMA(N, RL, AL, i0, i1, i2, i3, i4, i5, i6)                                                                         \
  template<int SC, int TB, long long CB> DEVI void rs##N(float* d, const uint32_t* a, uint64_t b) {                              \
    if (SC) asm volatile("{.reg .b64 tb; add.s64 tb, %" #i4 ", %" #i5 ";\n" WG_OP("m64n" #N) RL ", {%" #i0 ",%" #i1 ",%" #i2 ",%" #i3 "}, tb, 1, 1, 1, %" #i6 ";}" \
      : AL("+f", 0) : "r"(a[0]), "r"(a[1]), "r"(a[2]), "r"(a[3]), "l"(b), "n"(CB), "n"(TB));                                     \
    else asm volatile("{.reg .b64 tb; add.s64 tb, %" #i4 ", %" #i5 ";\n" WG_OP("m64n" #N) RL ", {%" #i0 ",%" #i1 ",%" #i2 ",%" #i3 "}, tb, 0, 1, 1, %" #i6 ";}" \
      : AL("=f", 0) : "r"(a[0]), "r"(a[1]), "r"(a[2]), "r"(a[3]), "l"(b), "n"(CB), "n"(TB));                                     \
  }                                                                                                                              \
  template<int SC, int TA, int TB, long long CA, long long CB> DEVI void ss##N(float* d, uint64_t a, uint64_t b) {               \
    if (SC) asm volatile("{.reg .b64 ta, tb; add.s64 ta, %" #i0 ", %" #i2 "; add.s64 tb, %" #i1 ", %" #i3 ";\n" WG_OP("m64n" #N) RL ", ta, tb, 1, 1, 1, %" #i4 ", %" #i5 ";}" \
      : AL("+f", 0) : "l"(a), "l"(b), "n"(CA), "n"(CB), "n"(TA), "n"(TB));                                                       \
    else asm volatile("{.reg .b64 ta, tb; add.s64 ta, %" #i0 ", %" #i2 "; add.s64 tb, %" #i1 ", %" #i3 ";\n" WG_OP("m64n" #N) RL ", ta, tb, 0, 1, 1, %" #i4 ", %" #i5 ";}" \
      : AL("=f", 0) : "l"(a), "l"(b), "n"(CA), "n"(CB), "n"(TA), "n"(TB));                                                       \
  }
DEF_WGMMA(16, RL8, A8, 8, 9, 10, 11, 12, 13, 14)
DEF_WGMMA(32, RL16, A16, 16, 17, 18, 19, 20, 21, 22)
DEF_WGMMA(40, RL20, A20, 20, 21, 22, 23, 24, 25, 26)
DEF_WGMMA(64, RL32, A32, 32, 33, 34, 35, 36, 37, 38)
template<int TA> DEVI void wgmma_n128(float* d, uint64_t a, uint64_t b, int scale_d) {
  asm volatile("{.reg .pred p; setp.ne.b32 p, %66, 0;\n" WG_OP("m64n128") RL64 ", %64, %65, p, 1, 1, %67, 1;}"
    : A32("+f", 0), A32("+f", 32) : "l"(a), "l"(b), "r"(scale_d), "n"(TA));
}

namespace rec {
constexpr int KR = 43;
constexpr uint32_t WSZ = (64 - KR) * 2048, STG = KR * 2048;
constexpr uint32_t WS = 0;
constexpr uint32_t RING = 2 * WSZ;
constexpr uint32_t OB = RING + 3 * 8192;
constexpr uint32_t WO = RING + 32768;
constexpr uint32_t ATT = WO + 5 * 16384;
constexpr uint32_t AK = ATT + 10240, AV = ATT + 20480;
constexpr uint32_t PAD = ATT + 30720;
constexpr uint32_t BARS = PAD + 128;
constexpr uint32_t B_XF = BARS, B_XE = BARS + 32, B_MF = BARS + 64, B_MC = BARS + 96, B_ME = BARS + 128;
constexpr uint32_t B_AB = BARS + 160, B_OB = BARS + 168, B_ST = BARS + 176  , B_WS = BARS + 192, B_WO = BARS + 200;
constexpr uint32_t SMEM = 232448;
constexpr int NB_P = 1, NB_WO = 2;
constexpr long long D_W = CD(WS, 16, 1024, 1), D_X = CD(RING, 16, 1024, 1), D_M = CD(RING, 128, 256, 0), D_O = CD(OB, 128, 256, 0);
constexpr long long D_WO = CD(WO, 16, 1024, 1), D_Q = CD(ATT, 640, 128, 0), D_K = CD(AK, 640, 128, 0);
constexpr long long D_V = CD(AV, 128, 640, 0), D_P = CD(ATT, 128, 768, 0);
struct Maps { CUtensorMap w[3], wo, x; };

#define RPROF(i)

template<int K0, int K1> DEVI void seq_mem(float* d, const uint32_t* w, uint64_t dw, uint64_t d0) {
  if constexpr (K0 < K1) {
    if constexpr (K0 < KR) rs16<K0 != 0, 1, D_M + K0 * 32>(d, w + 4 * K0, d0);
    else ss16<1, 1, 1, D_W + (K0 - KR) * 128, D_M + K0 * 32>(d, dw, d0);
    seq_mem<K0 + 1, K1>(d, w, dw, d0);
  }
}
template<bool DUAL, int K0, int K1> DEVI void seq_tok(float* d, const uint32_t* w, uint64_t dw, uint64_t d0) {
  if constexpr (K0 < K1) {
    constexpr long long B = D_X + (DUAL ? ((K0 >> 2) & 3) * 512 : ((K0 >> 2) & 7) * 256) + (K0 & 3) * 2;
    if constexpr (DUAL) {
      if constexpr (K0 < KR) rs64<K0 != 0, 0, B>(d, w + 4 * K0, d0); else ss64<1, 1, 0, D_W + (K0 - KR) * 128, B>(d, dw, d0);
    } else {
      if constexpr (K0 < KR) rs32<K0 != 0, 0, B>(d, w + 4 * K0, d0); else ss32<1, 1, 0, D_W + (K0 - KR) * 128, B>(d, dw, d0);
    }
    seq_tok<DUAL, K0 + 1, K1>(d, w, dw, d0);
  }
}
template<int T, int K0> DEVI void seq_wo(float* d, uint64_t dw, uint64_t d0) {
  if constexpr (K0 < 8) { ss16<K0 != 0, 1, 1, D_WO + T * 1024 + K0 * 128, D_O + K0 * 32>(d, dw, d0); seq_wo<T, K0 + 1>(d, dw, d0); }
}
template<int K0> DEVI void seq_s(float* d, uint64_t d0) {
  if constexpr (K0 < 8) { ss40<K0 != 0, 1, 1, D_Q + K0 * 80, D_K + K0 * 80>(d, d0, d0); seq_s<K0 + 1>(d, d0); }
}
DEVI void load_x(uint32_t sb, const CUtensorMap* mX, int t, int j) {
  const bool a1 = t < NSEG, a2 = t >= LAG, dual = a1 && a2;
  const int r1 = t * 32, r2 = (t - LAG) * 32, k = dual ? j * 64 : j * 128;
  const uint32_t dst = sb + RING + (j & 3) * 8192, bar = sb + B_XF + (j & 3) * 8;
  e_expect_tx(bar, 8192);
  e_tma_2d(dst, mX, k, a1 ? r1 : r2, bar);
  e_tma_2d(dst + 4096, mX, dual ? k : k + 64, a2 ? r2 : r1, bar);
}
template<bool DUAL, int J> DEVI void tok_release(uint32_t sb, const CUtensorMap* mX, int t, int wi, bool lead, int& budget) {
  constexpr int NC = DUAL ? 16 : 8;
  if constexpr (J + 4 < NC) {
    p_arrive(sb + B_XE + (J & 3) * 8, lead);
    if (wi == (J & 1) * 4 + 1) {
      mbar_wait(sb + B_XE + (J & 3) * 8, (t + (J >> 2)) & 1, budget);
      load_x(sb, mX, t, J + 4);
    }
  } else p_arrive(sb + B_ME + (J & 3) * 8, lead);
}
template<bool DUAL, int J> DEVI void tok_pass(float* d, const uint32_t* w, uint64_t dw, uint64_t d0, uint32_t sb, const CUtensorMap* mX,
                                              int t, int wi, bool lead, int& budget) {
  constexpr int NC = DUAL ? 16 : 8, KC = 64 / NC;
  if constexpr (J < NC) {
    mbar_wait(sb + B_XF + (J & 3) * 8, (J >> 2) & 1, budget);
    wg_fence();
    seq_tok<DUAL, J * KC, (J + 1) * KC>(d, w, dw, d0);
    wg_commit();
    if constexpr (J > 0) { wg_wait<1>(); tok_release<DUAL, J - 1>(sb, mX, t, wi, lead, budget); }
    tok_pass<DUAL, J + 1>(d, w, dw, d0, sb, mX, t, wi, lead, budget);
  } else {
    wg_wait<0>();
    tok_release<DUAL, NC - 1>(sb, mX, t, wi, lead, budget);
  }
}
DEVI void push_tok(const float* d, uint32_t dst, uint32_t bar) {
#pragma unroll
  for (int hf = 0; hf < 2; hf++)
    st_async128(dst + hf * 640, pack_bf16(d[2*hf], d[2*hf+1]), pack_bf16(d[4+2*hf], d[5+2*hf]),
                pack_bf16(d[8+2*hf], d[9+2*hf]), pack_bf16(d[12+2*hf], d[13+2*hf]), bar);
}
DEVI void put_part(char* p, const float* c, uint32_t tag) {
  stg_rlx128(p, settag(pack_bf16(c[0], c[1]), tag), pack_bf16(c[2], c[3]), settag(pack_bf16(c[4], c[5]), tag), pack_bf16(c[6], c[7]));
}

DEVI void rec_math(const uint32_t sb, const int h, const int rank, const int wi, const CUtensorMap* mX) {
  const int lane = threadIdx.x & 31, warp = wi & 3, wg = wi >> 2;
  const bool lead = (threadIdx.x & 127) == 0;
  int budget = SPIN_BUDGET;
  uint32_t w[4 * KR];
  {
    const uint32_t a = sb + wg * STG + ((lane & 7) + (lane >> 4) * 8) * 128 + (((warp * 2 + ((lane >> 3) & 1)) ^ (lane & 7)) << 4);
    mbar_wait(sb + B_ST + wg * 8, 0, budget);
#pragma unroll
    for (int k = 0; k < KR; k++) ldsm4t(a + k * 2048, w[4*k], w[4*k+1], w[4*k+2], w[4*k+3]);
    nbar_arrive<NB_WO, 384>();
    mbar_wait(sb + B_WS, 0, budget);
  }
  const uint64_t d0 = (sb & 0x3FFFF) >> 4;
#pragma unroll 1
  for (int t = -1; t < NSTEP; t++) {
    const uint64_t dw = d0 + wg * (WSZ >> 4);
    if (t >= 0) {
      RPROF(0 + wg * 12);
      {
        float m[8];
        mbar_wait(sb + B_MF, t & 1, budget);
        RPROF(1 + wg * 12);
        wg_fence(); seq_mem<0, 16>(m, w, dw, d0); wg_commit();
        mbar_wait(sb + B_MF + 8, t & 1, budget);
        wg_fence(); seq_mem<16, 32>(m, w, dw, d0); wg_commit();
        wg_wait<1>(); p_arrive(sb + B_MC, lead);
        mbar_wait(sb + B_MF + 16, t & 1, budget);
        wg_fence(); seq_mem<32, 48>(m, w, dw, d0); wg_commit();
        wg_wait<1>(); p_arrive(sb + B_MC + 8, lead);
        mbar_wait(sb + B_MF + 24, t & 1, budget);
        wg_fence(); seq_mem<48, 64>(m, w, dw, d0); wg_commit();
        wg_wait<1>(); p_arrive(sb + B_MC + 16, lead);
        wg_wait<0>();
        const uint32_t o = ATT + rank * 10240 + wi * 1280 + lane * 4;
        if (t < NSEG) { const uint32_t r = mapa(sb, 0); st_async32(r + o, pack_bf16(m[0], m[1]), r + B_AB); st_async32(r + o + 640, pack_bf16(m[2], m[3]), r + B_AB); }
        if (t >= LAG) { const uint32_t r = mapa(sb, 1); st_async32(r + o, pack_bf16(m[4], m[5]), r + B_AB); st_async32(r + o + 640, pack_bf16(m[6], m[7]), r + B_AB); }
      }
      RPROF(2 + wg * 12);
      const int seg = t - rank * LAG;
      if (rank < 2 && (unsigned)seg < (unsigned)NSEG) {
        float s[20];
        mbar_wait_cluster(sb + B_AB, seg & 1, budget);
        fence_proxy_async();
        RPROF(3 + wg * 12);
        if (wg == 0) {
          wg_fence(); seq_s<0>(s, d0); wg_commit();
          const int g = lane >> 2, base = 8 * (g >> 1) + (g & 1) + 4 * warp - 8 * (lane & 3);
          wg_wait<0>();
          constexpr float SC = 0.08838834764831845f * 1.4426950408889634f;
          uint32_t p[12];
#pragma unroll
          for (int r = 0; r < 2; r++) {
            const int lim = (r == 0 && warp == 0) ? 64 : base + 2 * r - 2;
#pragma unroll
            for (int i = 0; i < 8; i++) { float& v = s[4 + 4 * (i >> 1) + 2 * r + (i & 1)]; v = i <= lim ? v : -INFINITY; }
            float mx = fmaxf(s[2*r], s[2*r+1]);
#pragma unroll
            for (int b = 1; b < 5; b++) mx = fmaxf(mx, fmaxf(s[4*b+2*r], s[4*b+2*r+1]));
            mx = fmaxf(mx, __shfl_xor_sync(0xffffffffu, mx, 1));
            mx = fmaxf(mx, __shfl_xor_sync(0xffffffffu, mx, 2));
            const float ms = -mx * SC;
            float sum = 0;
#pragma unroll
            for (int i = 0; i < 10; i++) {
              float& v = s[4 * (i >> 1) + 2 * r + (i & 1)];
              asm("ex2.approx.ftz.f32 %0, %1;" : "=f"(v) : "f"(fmaf(v, SC, ms)));
              sum += v;
            }
            sum += __shfl_xor_sync(0xffffffffu, sum, 1);
            sum += __shfl_xor_sync(0xffffffffu, sum, 2);
            float inv; asm("rcp.approx.ftz.f32 %0, %1;" : "=f"(inv) : "f"(sum));
#pragma unroll
            for (int b = 0; b < 5; b++) p[6*r+b] = pack_bf16(s[4*b+2*r] * inv, s[4*b+2*r+1] * inv);
            p[6*r+5] = 0;
          }
#pragma unroll
          for (int i = 0; i < 3; i++) stsm4(sb + ATT + warp * 1536 + i * 512 + lane * 16, p[4*i], p[4*i+1], p[4*i+2], p[4*i+3]);
          fence_proxy_async();
        }
        nbar_sync<NB_P, 256>();
        RPROF(4 + wg * 12);
        const uint64_t dv = d0 + wg * 320;
        wg_fence();
        ss40<0, 0, 0, D_V, D_P>(s, dv, d0); ss40<1, 0, 0, D_V + 16, D_P + 16>(s, dv, d0); ss40<1, 0, 0, D_V + 32, D_P + 32>(s, dv, d0);
        wg_commit();
        char* const og = (char*)(g_ot + rank * O_LAYER) + (size_t)(h * DH + wi * 16 + (lane >> 2)) * (SEQ * 2) + seg * 64 + (lane & 3) * 16;
        wg_wait<0>();
        if (t < NSTEP - 1) {
          const uint32_t o0 = pack_bf16(s[0], s[1]), o1 = pack_bf16(s[2], s[3]), o = OB + wi * 512 + rank * 256 + lane * 4;
#pragma unroll
          for (int c = 0; c < 3; c++) { const uint32_t r = mapa(sb, c); st_async32(r + o, o0, r + B_OB); st_async32(r + o + 128, o1, r + B_OB); }
        }
#pragma unroll
        for (int hf = 0; hf < 2; hf++)
          stg128(og + hf * (8 * SEQ * 2), pack_bf16(s[4+2*hf], s[5+2*hf]), pack_bf16(s[8+2*hf], s[9+2*hf]),
                 pack_bf16(s[12+2*hf], s[13+2*hf]), pack_bf16(s[16+2*hf], s[17+2*hf]));
      }
      RPROF(5 + wg * 12);
      char* const hp = (char*)g_h1 + (((rank * 5 + wg * 3) * 4 + warp) * 4 + (lane >> 3)) * 4096 + h * 128 + (lane & 7) * 16;
      const bool three = wg == 0 || rank == 2;
      if (t < NSTEP - 1) {
        float c[24];
        const uint64_t dt = d0 + wg * 3072;
        const uint32_t tag = ((t >> 1) & 1) ^ 1;
        char* const p = hp + (t & 1) * sizeof(g_h1[0]);
        if (t == 0) mbar_wait(sb + B_WO, 0, budget);
        mbar_wait_cluster(sb + B_OB, t & 1, budget);
        fence_proxy_async();
        RPROF(6 + wg * 12);
        if (three) {
          wg_fence();
          seq_wo<0, 0>(c, dt, d0); wg_commit(); seq_wo<1, 0>(c + 8, dt, d0); wg_commit(); seq_wo<2, 0>(c + 16, dt, d0); wg_commit();
          wg_wait<2>(); put_part(p, c, tag);
          wg_wait<1>(); put_part(p + 65536, c + 8, tag);
          wg_wait<0>(); put_part(p + 131072, c + 16, tag);
        } else {
          wg_fence();
          seq_wo<0, 0>(c, dt, d0); wg_commit(); seq_wo<1, 0>(c + 8, dt, d0); wg_commit();
          wg_wait<1>(); put_part(p, c, tag);
          wg_wait<0>(); put_part(p + 65536, c + 8, tag);
        }
      } else {
        for (int i = 0; i < (three ? 6 : 4); i++) stg_rlx128(hp + (i & 1) * sizeof(g_h1[0]) + (i >> 1) * 65536, 0, 0, 0, 0);
      }
      nbar_arrive<NB_WO, 384>();
      RPROF(7 + wg * 12);
    }
    const int n = t + 1;
    const uint32_t o = ATT + rank * 10240 + wi * 1280 + 128 + (lane & 3) * 128 + (lane >> 2) * 16;
    if (n >= LAG && n < NSEG) {
      float d[32];
      tok_pass<true, 0>(d, w, dw, d0, sb, mX, n, wi, lead, budget);
      RPROF(8 + wg * 12);
      const uint32_t r0 = mapa(sb, 0), r1 = mapa(sb, 1);
      push_tok(d, r0 + o, r0 + B_AB); push_tok(d + 16, r1 + o, r1 + B_AB);
    } else if (n < NSTEP) {
      float d[16];
      tok_pass<false, 0>(d, w, dw, d0, sb, mX, n, wi, lead, budget);
      RPROF(8 + wg * 12);
      const uint32_t r = mapa(sb, n >= NSEG);
      push_tok(d, r + o, r + B_AB);
    }
  }
}

DEVI void rec_comm(const uint32_t sb, const int h, const int rank, const int warp, const Maps& M, const bf16* __restrict__ mem0) {
  const int lane = threadIdx.x & 31;
  int budget = SPIN_BUDGET;
  const bool red = rank == 2 || warp < 2;
  const int task = h * 8 + (rank == 2 ? warp : 4 + rank * 2 + (warp & 1));
  const int j = lane >> 3, L = (task & 3) * 8 + (lane & 7);
  uint32_t m0;
  {
    const bf16* p = mem0 + (L & 3) * 2 * DM + (task >> 2) * 16 + (L >> 2) + (j & 1) * 8;
    m0 = (uint32_t)__bfloat16_as_ushort(p[0]) | (uint32_t)__bfloat16_as_ushort(p[DM]) << 16;
  }
  char* const h2w = (char*)g_h2 + (task >> 2) * 512 + j * 128 + L * 4;
#pragma unroll 1
  for (int t = -1; t < NSTEP; t++) {
    if (t >= 0) {
      if (warp == 3) {
        if (rank < 2 && (unsigned)(t - rank * LAG) < (unsigned)NSEG) e_expect_tx(sb + B_AB, 30720);
        if (t < NSTEP - 1) e_expect_tx(sb + B_OB, t < NSEG && t >= LAG ? 4096 : 2048);
      }
      const char* src = (const char*)g_h2[t & 3] + warp * 2048 + lane * 16;
#pragma unroll 1
      for (int c = 0; c < 4; c++) {
        uint4 v[4];
        while (true) {
#pragma unroll
          for (int i = 0; i < 4; i++) v[i] = ldg_rlx128(src + c * 8192 + i * 512);
          uint32_t mn = min(min(v[0].x, v[0].y), min(v[0].z, v[0].w));
#pragma unroll
          for (int i = 1; i < 4; i++) mn = min(min(mn, min(v[i].x, v[i].y)), min(v[i].z, v[i].w));
          if (!__any_sync(0xffffffffu, mn == 0) || --budget < 0) break;
        }
        if (c == 0) RPROF(24);
        mbar_wait(sb + B_ME + c * 8, t & 1, budget);
#pragma unroll
        for (int i = 0; i < 4; i++) sts128(sb + RING + c * 8192 + warp * 2048 + i * 512 + lane * 16, v[i]);
        fence_proxy_async();
        __syncwarp();
        e_arrive(sb + B_MF + c * 8);
      }
      RPROF(25);
    }
    const int n = t + 1;
    if (warp == 3 && n < NSTEP) {
      if (n < NSEG && (n & 3) == 0) { while (ldg_acq32(&g_xa[0][n >> 2]) < 64 && --budget > 0) {} fence_proxy_global(); }
      if (n >= LAG && ((n - LAG) & 3) == 0) { while (ldg_acq32(&g_xa[1][(n - LAG) >> 2]) < 64 && --budget > 0) {} fence_proxy_global(); }
      if (t >= 0)
        for (int c = 0; c < 3; c++) { mbar_wait(sb + B_MC + c * 8, t & 1, budget); load_x(sb, &M.x, n, c); }
    }
    nbar_sync<NB_WO, 384>();
    RPROF(26);
    if (t < 0 && warp == 2) {
      e_expect_tx(sb + B_WS, 2 * WSZ);
      for (int i = 0; i < 2 * (64 - KR); i++) e_tma_2d(sb + WS + (i & 1) * WSZ + (i >> 1) * 2048, &M.w[rank], h * DH + (i & 1) * 64, (KR + (i >> 1)) * 16, sb + B_WS);
      const int nt = rank == 2 ? 6 : 5;
      e_expect_tx(sb + B_WO, nt * 16384);
      for (int i = 0; i < nt; i++) e_tma_2d(sb + WO + i * 16384, &M.wo, (rank * 5 + i) * 64, h * DH, sb + B_WO);
    }
    if (warp == 3 && n < NSTEP)
      for (int c = t < 0 ? 0 : 3; c < 4; c++) load_x(sb, &M.x, n, c);
    if (warp == 2 && rank < 2 && (unsigned)(t - rank * LAG) < (unsigned)NSEG && lane == 0)
      flag_add(&g_dep[rank ? Q_O2 : Q_O1][(t - rank * LAG) >> 2]);
    if (red && n < NSTEP) {
      uint32_t out = m0;
      if (t >= 0) {
        const char* src = (const char*)g_h1[t & 1] + task * 4096 + lane * 16;
        const uint32_t tag = ((t >> 1) & 1) ^ 1;
        float a[8];
#pragma unroll
        for (int b = 0; b < 2; b++) {
          uint4 v[4];
          while (true) {
#pragma unroll
            for (int i = 0; i < 4; i++) v[i] = ldg_rlx128(src + b * 2048 + i * 512);
            uint32_t bad = 0;
#pragma unroll
            for (int i = 0; i < 4; i++) bad |= (v[i].x ^ tag) | (v[i].z ^ tag);
            if (!__any_sync(0xffffffffu, bad & 1) || --budget < 0) break;
          }
#pragma unroll
          for (int q = 0; q < 4; q++) {
            const uint32_t x0 = (&v[0].x)[q], x1 = (&v[1].x)[q], x2 = (&v[2].x)[q], x3 = (&v[3].x)[q];
            const float lo = (bf_lo(x0) + bf_lo(x1)) + (bf_lo(x2) + bf_lo(x3)), hi = (bf_hi(x0) + bf_hi(x1)) + (bf_hi(x2) + bf_hi(x3));
            a[2*q] = b ? a[2*q] + lo : lo; a[2*q+1] = b ? a[2*q+1] + hi : hi;
          }
        }
        RPROF(27);
#pragma unroll
        for (int i = 0; i < 4; i++) {
          const float keep = (lane & 16) ? a[4+i] : a[i], send = (lane & 16) ? a[i] : a[4+i];
          a[i] = keep + __shfl_xor_sync(0xffffffffu, send, 16);
        }
#pragma unroll
        for (int i = 0; i < 2; i++) {
          const float keep = (lane & 8) ? a[2+i] : a[i], send = (lane & 8) ? a[i] : a[2+i];
          a[i] = keep + __shfl_xor_sync(0xffffffffu, send, 8);
        }
        if ((lane & 16) ? t >= LAG : t < NSEG) out = pack_bf16(a[0], a[1]);
      }
      stg_rlx32(h2w + (n & 3) * sizeof(g_h2[0]), out ? out : 0x8000u);
      if (t >= 0) stg_rlx32(h2w + (t & 3) * sizeof(g_h2[0]), 0);
      RPROF(28);
    }
  }
  if (h == 0 && rank == 0 && warp < 2) g_xa[warp][lane] = 0;
}
}

__global__ void __cluster_dims__(3, 1, 1) __launch_bounds__(384, 1)
rec_kernel(const __grid_constant__ rec::Maps M, const bf16* __restrict__ mem0) {
  using namespace rec;
  extern __shared__ __align__(1024) uint8_t smem[];
  const uint32_t sb = __shfl_sync(0xffffffffu, smem_u32(smem), 0);
  const int tid = threadIdx.x, wi = __shfl_sync(0xffffffffu, tid >> 5, 0);
  const int h = blockIdx.x / 3, rank = blockIdx.x - h * 3;
  if (wi == 0) {
    if (tid < 26) mbar_init(sb + BARS + tid * 8, tid < 4 || tid >= 20 ? 1 : (tid >> 2) == 2 ? 4 : 2);
    ((uint32_t*)(smem + PAD))[tid] = 0;
    fence_mbar_init(); fence_proxy_async();
    __syncwarp();
    e_expect_tx(sb + B_ST, STG); e_expect_tx(sb + B_ST + 8, STG);
    for (int i = 0; i < 2 * KR; i++) e_tma_2d(sb + (i & 1) * STG + (i >> 1) * 2048, &M.w[rank], h * DH + (i & 1) * 64, (i >> 1) * 16, sb + B_ST + (i & 1) * 8);
    for (int i = 2 * KR; i < 128; i++) e_prefetch_2d(&M.w[rank], h * DH + (i & 1) * 64, (i >> 1) * 16);
    for (int i = 0; i < (rank == 2 ? 6 : 5); i++) e_prefetch_2d(&M.wo, (rank * 5 + i) * 64, h * DH);
  } else if (wi == 1) {
    if (blockIdx.x < NQ) { g_dep[blockIdx.x][tid & 31] = 0; g_claim[blockIdx.x][tid & 31] = 0; __threadfence(); }
    __syncwarp();
    asm volatile("griddepcontrol.launch_dependents;" ::: "memory");
  }
  cluster_arrive(); cluster_wait();
  if (wi < 8) { reg_inc<232>(); rec_math(sb, h, rank, wi, &M.x); cluster_arrive(); cluster_wait(); }
  else { reg_dec<40>(); rec_comm(sb, h, rank, wi & 3, M, mem0); cluster_arrive(); cluster_wait(); }
}

namespace gm {
struct Maps { CUtensorMap ot, wo, xn, wg, wu, h, wd, out; };
constexpr int STAGES = 6, STAGE = 32768;
constexpr uint32_t SO = STAGES * STAGE, BARS = SO + 32768;
constexpr uint32_t B_FULL = BARS, B_EMPTY = BARS + 48, B_TF = BARS + 96, B_TE = BARS + 112, B_ORD = BARS + 128, MAIL = BARS + 144;
constexpr uint32_t SMEM = BARS + 256;
constexpr int END = -1;

DEVI float geglu(float g, float u) {
  const float z = g * (0.7978845608028654f + 0.035677408136300125f * g * g);
  float t; asm("tanh.approx.f32 %0, %1;" : "=f"(t) : "f"(z));
  const float hg = 0.5f * g;
  return fmaf(hg, t, hg) * u;
}
struct Sched {
  int head, need, size, nev;
  template<int Q0, int NL> DEVI void init(int lane) {
    const int q = Q0 + lane;
    const bool d = q == Q_D1 || q == Q_D2, g = q == Q_G1 || q == Q_G2, o = q == Q_O1 || q == Q_O2;
    need = d ? 28 : g ? 64 : o ? 128 : q == L_I ? 0 : 16;
    size = d ? 8 : g ? 56 : o ? 16 : 64;
    nev = lane >= NL ? 0 : d ? 32 : 16;
    head = 0;
    int c[NL];
#pragma unroll
    for (int i = 0; i < NL; i++) c[i] = ldg_rlx32(&g_claim[Q0 + i][lane]);
#pragma unroll
    for (int i = 0; i < NL; i++) {
      const uint32_t open = __ballot_sync(0xffffffffu, c[i] < __shfl_sync(0xffffffffu, size, i));
      if (lane == i) head = open ? __ffs(open) - 1 : 32;
    }
  }
  template<int Q0> DEVI int next(int lane, int& budget) {
    while (--budget > 0) {
      const bool live = head < nev;
      if (!__any_sync(0xffffffffu, live)) break;
      int dep = -1, cl = 0;
      if (live) { cl = ldg_rlx32(&g_claim[Q0 + lane][head]); dep = ldg_acq32(&g_dep[Q0 + lane][head]); }
      const bool gone = live && cl >= size;
      const uint32_t ready = __ballot_sync(0xffffffffu, dep >= need && !gone), adv = __ballot_sync(0xffffffffu, gone);
      if (gone) head++;
      const int ql = __ffs(ready) - 1;
      if (ready && !(adv & ((1u << ql) - 1))) {
        int tk = 0;
        if (lane == ql) { tk = atomicAdd(&g_claim[Q0 + lane][head], 1); tk = tk < size ? (Q0 + lane) << 16 | head << 8 | tk : END; if (tk == END) head++; }
        tk = __shfl_sync(0xffffffffu, tk, ql);
        if (tk != END) { __syncwarp(); fence_proxy_global(); return tk; }
      } else if (!adv) __nanosleep(100);
    }
    return END;
  }
};

DEVI void producer(const uint32_t sb, const Maps& M) {
  const int lane = threadIdx.x & 31;
  int budget = SPIN_BUDGET, s = 0, ph = 0;
  Sched sc; sc.init<Q_D1, 6>(lane);
#pragma unroll 1
  for (int i = 0;; i++) {
    const int task = sc.next<Q_D1>(lane, budget);
    for (int z = 0; z < (task == END ? 2 : 1); z++) {
      const int g = (i + z) & 1;
      mbar_wait(sb + B_TE + g * 8, (((i + z) >> 1) & 1) ^ 1, budget);
      if (lane == 0) { sts64(sb + MAIL + g * 8, task, s | ph << 8); mbar_arrive(sb + B_TF + g * 8); }
      __syncwarp();
    }
    if (task == END) break;
    const int q = task >> 16, ev = (task >> 8) & 255, id = task & 255;
    const bool isO = q == Q_O1 || q == Q_O2, isG = q == Q_G1 || q == Q_G2;
    const int n = isO ? 32 : isG ? 16 : 28, row = (isO || isG ? ev : ev >> 1) * 128;
    int k = isO ? (id >> 3) * 2048 : isG ? 0 : (ev & 1) * 1792;
    const CUtensorMap* mA = isG ? &M.xn : &M.h;
    const CUtensorMap* mB0 = isO ? &M.wo : isG ? &M.wg : &M.wd;
    const CUtensorMap* mB1 = isG ? &M.wu : mB0;
    const int c0 = isG ? id * 64 : (id & 7) * 128, c1 = isG ? c0 : c0 + 64;
    const int ok = 0;
#pragma unroll 1
    for (int it = 0; it < n; it++, k += 64) {
      const uint32_t a = sb + s * STAGE, fb = sb + B_FULL + s * 8;
      mbar_wait(sb + B_EMPTY + s * 8, ph ^ 1, budget);
      e_expect_tx(fb, STAGE);
      if (isO) { e_tma_2d(a, &M.ot, row, k + ok, fb); e_tma_2d(a + 8192, &M.ot, row + 64, k + ok, fb); }
      else e_tma_2d(a, mA, k, row, fb);
      e_tma_2d(a + 16384, mB0, c0, k, fb); e_tma_2d(a + 24576, mB1, c1, k, fb);
      if (++s == STAGES) { s = 0; ph ^= 1; }
    }
  }
}

template<int TA> DEVI void mainloop(float* d0, float* d1, uint32_t sb, int n, int s, int ph, bool lead, uint32_t ord, int& budget) {
  int prev = 0;
#pragma unroll 1
  for (int i = 0; i < n; i++) {
    mbar_wait(sb + B_FULL + s * 8, ph, budget);
    const uint32_t a = sb + s * STAGE;
    const uint64_t da = mkdesc(a, 16, 1024), db = mkdesc(a + 16384, 8192, 1024);
    wg_fence();
#pragma unroll
    for (int k = 0; k < 4; k++) {
      wgmma_n128<TA>(d0, da + k * (TA ? 128 : 2), db + k * 128, (i | k) != 0);
      wgmma_n128<TA>(d1, da + 512 + k * (TA ? 128 : 2), db + k * 128, (i | k) != 0);
    }
    wg_commit();
    if (i > 0) { wg_wait<1>(); p_arrive(sb + B_EMPTY + prev * 8, lead); }
    prev = s;
    if (++s == STAGES) { s = 0; ph ^= 1; }
  }
  p_arrive(ord, lead);
  wg_wait<0>();
  p_arrive(sb + B_EMPTY + prev * 8, lead);
}

DEVI void consumer(const uint32_t sb, const Maps& M, const int wg) {
  const int tid = threadIdx.x, lane = tid & 31, warp = (tid >> 5) & 3;
  const bool lead = (tid & 127) == 0;
  const uint32_t so = sb + SO + wg * 16384;
  int budget = SPIN_BUDGET;
  float d0[64], d1[64];
#pragma unroll 1
  for (int m = 0;; m++) {
    mbar_wait(sb + B_TF + wg * 8, m & 1, budget);
    const uint2 mail = lds64v(sb + MAIL + wg * 8);
    const int task = __shfl_sync(0xffffffffu, (int)mail.x, 0), pos = __shfl_sync(0xffffffffu, (int)mail.y, 0);
    e_arrive(sb + B_TE + wg * 8);
    if (task == END || budget < 0) break;
    const int q = task >> 16, ev = (task >> 8) & 255, id = task & 255;
    const bool isO = q == Q_O1 || q == Q_O2, isG = q == Q_G1 || q == Q_G2;
    mbar_wait(sb + B_ORD + wg * 8, (m & 1) ^ wg ^ 1, budget);
    if (isO) mainloop<1>(d0, d1, sb, 32, pos & 255, pos >> 8, lead, sb + B_ORD + (wg ^ 1) * 8, budget);
    else mainloop<0>(d0, d1, sb, isG ? 16 : 28, pos & 255, pos >> 8, lead, sb + B_ORD + (wg ^ 1) * 8, budget);
    const uint32_t st = so + (warp * 16 + (lane & 15)) * 128;
    if (isG) {
#pragma unroll
      for (int mm = 0; mm < 2; mm++) {
        const float* d = mm ? d1 : d0;
#pragma unroll
        for (int c = 0; c < 4; c++) {
          uint32_t r[4];
#pragma unroll
          for (int i = 0; i < 4; i++) r[i] = pack_bf16(geglu(d[8*c+2*i], d[32+8*c+2*i]), geglu(d[8*c+2*i+1], d[33+8*c+2*i]));
          stsm4(st + mm * 8192 + (((2 * c + (lane >> 4)) ^ (lane & 7)) << 4), r[0], r[1], r[2], r[3]);
        }
      }
      fence_proxy_async();
      nbar_sync_r(1 + wg, 128);
      if (lead) {
        tma_store_2d(&M.h, so, id * 64, ev * 128);
        bulk_commit(); bulk_wait<0>();
        flag_add(&g_dep[q == Q_G1 ? Q_D1 : Q_D2][ev * 2 + (id >= 28)]);
      }
    } else {
      const int blk = isO ? ev : ev >> 1;
#pragma unroll
      for (int hf = 0; hf < 2; hf++) {
        if (hf) { if (lead) bulk_wait_read<0>(); nbar_sync_r(1 + wg, 128); }
#pragma unroll
        for (int mm = 0; mm < 2; mm++) {
          const float* d = (mm ? d1 : d0) + hf * 32;
#pragma unroll
          for (int c = 0; c < 4; c++)
            stsm4(st + mm * 8192 + (((2 * c + (lane >> 4)) ^ (lane & 7)) << 4), pack_bf16(d[8*c], d[8*c+1]), pack_bf16(d[8*c+2], d[8*c+3]),
                  pack_bf16(d[8*c+4], d[8*c+5]), pack_bf16(d[8*c+6], d[8*c+7]));
        }
        fence_proxy_async();
        nbar_sync_r(1 + wg, 128);
        if (lead) { tma_radd_2d(&M.out, so, (id & 7) * 128 + hf * 64, blk * 128); bulk_commit(); }
      }
      if (lead) {
        bulk_wait<0>();
        if (q != Q_D2) flag_add(&g_dep[q == Q_O1 ? L_X1A : q == Q_O2 ? L_X1B : L_X2][blk]);
      }
    }
    __syncwarp();
  }
}

DEVI void norm_helper(const bf16* __restrict__ x, bf16* out) {
  const int lane = threadIdx.x & 31;
  int budget = SPIN_BUDGET;
  Sched sc; sc.init<L_I, 4>(lane);
#pragma unroll 1
  while (true) {
    const int task = sc.next<L_I>(lane, budget);
    if (task == END) break;
    const int q = task >> 16, ev = (task >> 8) & 255;
    const size_t off = (size_t)(ev * 128 + (task & 255) * 2) * (DM * 2) + lane * 16;
    const char* src = (const char*)(q == L_I ? x : out) + off;
    uint4 u[8];
#pragma unroll
    for (int i = 0; i < 8; i++) u[i] = ldg_rlx128(src + i * 512);
    if (q == L_I) {
#pragma unroll
      for (int i = 0; i < 8; i++) stg128((char*)out + off + i * 512, u[i].x, u[i].y, u[i].z, u[i].w);
    }
    float mean[2], rs[2];
#pragma unroll
    for (int r = 0; r < 2; r++) {
      float s = 0;
#pragma unroll
      for (int i = 0; i < 16; i++) { const uint32_t v = (&u[4*r + (i >> 2)].x)[i & 3]; s += bf_lo(v) + bf_hi(v); }
      mean[r] = s;
    }
#pragma unroll
    for (int o = 16; o; o >>= 1) { mean[0] += __shfl_xor_sync(0xffffffffu, mean[0], o); mean[1] += __shfl_xor_sync(0xffffffffu, mean[1], o); }
#pragma unroll
    for (int r = 0; r < 2; r++) {
      mean[r] *= 1.f / DM;
      float s = 0;
#pragma unroll
      for (int i = 0; i < 16; i++) { const uint32_t v = (&u[4*r + (i >> 2)].x)[i & 3]; const float a = bf_lo(v) - mean[r], b = bf_hi(v) - mean[r]; s = fmaf(a, a, fmaf(b, b, s)); }
      rs[r] = s;
    }
#pragma unroll
    for (int o = 16; o; o >>= 1) { rs[0] += __shfl_xor_sync(0xffffffffu, rs[0], o); rs[1] += __shfl_xor_sync(0xffffffffu, rs[1], o); }
#pragma unroll
    for (int r = 0; r < 2; r++) rs[r] = rsqrtf(rs[r] * (1.f / DM) + 1e-5f);
#pragma unroll
    for (int i = 0; i < 8; i++) {
      uint32_t y[4];
#pragma unroll
      for (int c = 0; c < 4; c++) { const uint32_t v = (&u[i].x)[c]; y[c] = pack_bf16((bf_lo(v) - mean[i >> 2]) * rs[i >> 2], (bf_hi(v) - mean[i >> 2]) * rs[i >> 2]); }
      stg128((char*)g_xn + off + i * 512, y[0], y[1], y[2], y[3]);
    }
    fence_proxy_global();
    __syncwarp();
    if (lane == 0) flag_add(q == L_I ? &g_xa[0][ev] : q == L_X2 ? &g_xa[1][ev] : &g_dep[q == L_X1A ? Q_G1 : Q_G2][ev]);
    __syncwarp();
  }
}
}

__global__ void __launch_bounds__(384, 1) gemm_kernel(const __grid_constant__ gm::Maps M, const bf16* __restrict__ x, bf16* out) {
  using namespace gm;
  extern __shared__ __align__(1024) uint8_t smem[];
  const uint32_t sb = __shfl_sync(0xffffffffu, smem_u32(smem), 0);
  const int tid = threadIdx.x, wi = __shfl_sync(0xffffffffu, tid >> 5, 0);
  if (tid < 18) mbar_init(sb + BARS + tid * 8, tid == 14 || tid == 15 ? 4 : 1);
  fence_mbar_init();
  __syncthreads();
  if (wi < 8) { reg_inc<216>(); consumer(sb, M, wi >> 2); }
  else {
    reg_dec<72>();
    if (wi == 8) producer(sb, M);
    else {
      norm_helper(x, out);
      asm volatile("griddepcontrol.wait;" ::: "memory");
      if (wi == 9 && blockIdx.x < 64) g_h2[(NSTEP - 1) & 3][blockIdx.x * 32 + (tid & 31)] = make_uint4(0, 0, 0, 0);
    }
  }
}

typedef CUresult (*PFN_encodeTiled)(CUtensorMap*, CUtensorMapDataType, cuuint32_t, void*, const cuuint64_t*, const cuuint64_t*,
                                    const cuuint32_t*, const cuuint32_t*, CUtensorMapInterleave, CUtensorMapSwizzle,
                                    CUtensorMapL2promotion, CUtensorMapFloatOOBfill);
static PFN_encodeTiled g_encode = nullptr;
static CUtensorMap make_map(const void* ptr, uint64_t rows, uint64_t cols, uint32_t box_rows) {
  CUtensorMap m;
  cuuint64_t dims[2] = {cols, rows}, strides[1] = {cols * 2};
  cuuint32_t box[2] = {64, box_rows}, es[2] = {1, 1};
  g_encode(&m, CU_TENSOR_MAP_DATA_TYPE_BFLOAT16, 2, (void*)ptr, dims, strides, box, es, CU_TENSOR_MAP_INTERLEAVE_NONE,
           CU_TENSOR_MAP_SWIZZLE_128B, CU_TENSOR_MAP_L2_PROMOTION_L2_256B, CU_TENSOR_MAP_FLOAT_OOB_FILL_NONE);
  return m;
}

extern "C" void kernel_launch(void* const* d_in, const int* in_sizes, int n_in, void* d_out, int out_size) {
  const bf16* x = (const bf16*)d_in[0];
  const bf16* mem0 = (const bf16*)d_in[1];
  if (!g_encode) {
    void* p = nullptr; cudaDriverEntryPointQueryResult q;
    cudaGetDriverEntryPoint("cuTensorMapEncodeTiled", &p, cudaEnableDefault, &q);
    g_encode = (PFN_encodeTiled)p;
    cudaFuncSetAttribute(gemm_kernel, cudaFuncAttributeMaxDynamicSharedMemorySize, gm::SMEM);
    cudaFuncSetAttribute(rec_kernel, cudaFuncAttributeMaxDynamicSharedMemorySize, rec::SMEM);
  }
  bf16 *xn, *ot, *hh;
  cudaGetSymbolAddress((void**)&xn, g_xn); cudaGetSymbolAddress((void**)&ot, g_ot); cudaGetSymbolAddress((void**)&hh, g_h);
  rec::Maps R;
  for (int i = 0; i < 3; i++) R.w[i] = make_map(d_in[2 + i], DM, NH * DH, 16);
  R.wo = make_map(d_in[5], NH * DH, DM, 128); R.x = make_map(xn, SEQ, DM, 32);
  gm::Maps G;
  G.ot = make_map(ot, NH * DH + O_LAYER / SEQ, SEQ, 64); G.wo = make_map(d_in[5], NH * DH, DM, 64); G.xn = make_map(xn, SEQ, DM, 128);
  G.wg = make_map(d_in[8], DM, DF, 64); G.wu = make_map(d_in[9], DM, DF, 64); G.h = make_map(hh, SEQ, DF, 128);
  G.wd = make_map(d_in[10], DF, DM, 64); G.out = make_map(d_out, SEQ, DM, 128);
  rec_kernel<<<3 * NH, 384, rec::SMEM, cudaStreamPerThread>>>(R, mem0);
  cudaLaunchConfig_t cfg = {};
  cfg.gridDim = dim3(132); cfg.blockDim = dim3(384); cfg.dynamicSmemBytes = gm::SMEM; cfg.stream = cudaStreamPerThread;
  cudaLaunchAttribute at[1];
  at[0].id = cudaLaunchAttributeProgrammaticStreamSerialization; at[0].val.programmaticStreamSerializationAllowed = 1;
  cfg.attrs = at; cfg.numAttrs = 1;
  cudaLaunchKernelEx(&cfg, gemm_kernel, G, x, (bf16*)d_out);
}
```

```cpp
#include <cuda_runtime.h>
#include <cuda_bf16.h>
#include <cuda.h>
#include <stdint.h>

#define DEVI __device__ __forceinline__
typedef __nv_bfloat16 bf16;

constexpr int SEQ = 2048, DM = 1024, NH = 32, DH = 128, DF = 3584, NSEG = 64;
#define LAG 16
constexpr int NSTEP = NSEG + LAG;

constexpr size_t O_LAYER = 0;
__device__ __align__(1024) bf16 g_xn[SEQ * DM];
__device__ __align__(1024) bf16 g_ot[SEQ * NH * DH + O_LAYER];
__device__ __align__(1024) bf16 g_h[SEQ * DF];
__device__ __align__(1024) uint2 g_h1[4][256 * 256];
__device__ __align__(1024) uint4 g_h2[4][2048];
enum { E_D1 = 0, E_G1 = 32, E_O1 = 48, E_O2 = 64, E_G2 = 80, E_D2 = 96,
       E_LI = 128, E_LX2 = 144, E_LX1A = 160, E_LX1B = 176, NEV = 256 };
__device__ __align__(128) int g_dep[NEV];
__device__ __align__(128) int g_claim[NEV];
__device__ __align__(128) int g_xa[2][32];

#define TUNE_DEFAULTS 1600, 3000, 3, 250, 200, 4, 0xffff, 100
constexpr int c_D[8] = {TUNE_DEFAULTS};
template<int I> struct TPV { static constexpr int v = c_D[I]; };
#define TP(i) TPV<i>::v

DEVI uint32_t smem_u32(const void* p) { return (uint32_t)__cvta_generic_to_shared(p); }
DEVI void mbar_init(uint32_t bar, uint32_t cnt) { asm volatile("mbarrier.init.shared::cta.b64 [%0], %1;" :: "r"(bar), "r"(cnt) : "memory"); }
DEVI void mbar_arrive(uint32_t bar) { asm volatile("mbarrier.arrive.shared::cta.b64 _, [%0];" :: "r"(bar) : "memory"); }
DEVI bool mbar_try(uint32_t bar, uint32_t parity) {
  uint32_t p;
  asm volatile("{.reg .pred p; mbarrier.try_wait.parity.shared::cta.b64 p, [%1], %2; selp.u32 %0, 1, 0, p;}" : "=r"(p) : "r"(bar), "r"(parity) : "memory");
  return p;
}
constexpr int SPIN_BUDGET = 1 << 18;
DEVI void mbar_wait(uint32_t bar, uint32_t parity, int& budget) {
  while (!mbar_try(bar, parity)) { if (--budget < 0) break; }
}
DEVI bool mbar_try_cluster(uint32_t bar, uint32_t parity) {
  uint32_t p;
  asm volatile("{.reg .pred p; mbarrier.try_wait.parity.acquire.cluster.shared::cta.b64 p, [%1], %2; selp.u32 %0, 1, 0, p;}" : "=r"(p) : "r"(bar), "r"(parity) : "memory");
  return p;
}
DEVI void mbar_wait_cluster(uint32_t bar, uint32_t parity, int& budget) {
  while (!mbar_try_cluster(bar, parity)) { if (--budget < 0) break; }
}
DEVI uint32_t mapa(uint32_t addr, uint32_t rank) { uint32_t r; asm("mapa.shared::cluster.u32 %0, %1, %2;" : "=r"(r) : "r"(addr), "r"(rank)); return r; }
DEVI void cluster_arrive() { asm volatile("barrier.cluster.arrive.release.aligned;" ::: "memory"); }
DEVI void cluster_wait() { asm volatile("barrier.cluster.wait.acquire.aligned;" ::: "memory"); }
DEVI void fence_mbar_init() { asm volatile("fence.mbarrier_init.release.cluster;" ::: "memory"); }
DEVI void fence_proxy_async() { asm volatile("fence.proxy.async.shared::cta;" ::: "memory"); }
DEVI void fence_proxy_global() { asm volatile("fence.proxy.async.global;" ::: "memory"); }
#define ELECT "{.reg .pred p; elect.sync _|p, 0xffffffff;\n @p "
DEVI void e_expect_tx(uint32_t bar, uint32_t bytes) { asm volatile(ELECT "mbarrier.arrive.expect_tx.shared::cta.b64 _, [%0], %1;}" :: "r"(bar), "r"(bytes) : "memory"); }
DEVI void e_arrive(uint32_t bar) { asm volatile(ELECT "mbarrier.arrive.shared::cta.b64 _, [%0];}" :: "r"(bar) : "memory"); }
DEVI void e_tma_2d(uint32_t dst, const CUtensorMap* m, int c0, int c1, uint32_t bar) {
  asm volatile(ELECT "cp.async.bulk.tensor.2d.shared::cluster.global.mbarrier::complete_tx::bytes [%0], [%1, {%3, %4}], [%2];}"
    :: "r"(dst), "l"(m), "r"(bar), "r"(c0), "r"(c1) : "memory");
}
DEVI void e_prefetch_2d(const CUtensorMap* m, int c0, int c1) {
  asm volatile(ELECT "cp.async.bulk.prefetch.tensor.2d.L2.global [%0, {%1, %2}];}" :: "l"(m), "r"(c0), "r"(c1) : "memory");
}
DEVI void e_bulk_g2s(uint32_t dst, const void* src, uint32_t bytes, uint32_t bar) {
  asm volatile(ELECT "cp.async.bulk.shared::cluster.global.mbarrier::complete_tx::bytes [%0], [%1], %2, [%3];}" :: "r"(dst), "l"(src), "r"(bytes), "r"(bar) : "memory");
}
DEVI void e_tma_3d_mc(uint32_t dst, const CUtensorMap* m, int c0, int c1, int c2, uint32_t bar) {
  asm volatile(ELECT "cp.async.bulk.tensor.3d.shared::cluster.global.mbarrier::complete_tx::bytes.multicast::cluster [%0], [%1, {%3, %4, %5}], [%2], %6;}"
    :: "r"(dst), "l"(m), "r"(bar), "r"(c0), "r"(c1), "r"(c2), "h"((uint16_t)7) : "memory");
}
DEVI void e_tma_2d_mc(uint32_t dst, const CUtensorMap* m, int c0, int c1, uint32_t bar) {
  asm volatile(ELECT "cp.async.bulk.tensor.2d.shared::cluster.global.mbarrier::complete_tx::bytes.multicast::cluster [%0], [%1, {%3, %4}], [%2], %5;}"
    :: "r"(dst), "l"(m), "r"(bar), "r"(c0), "r"(c1), "h"((uint16_t)3) : "memory");
}
DEVI void p_arrive_at(uint32_t bar, uint32_t rank, bool c) {
  asm volatile("{.reg .pred p; .reg .b32 a; setp.ne.u32 p, %2, 0; mapa.shared::cluster.u32 a, %0, %1; @p mbarrier.arrive.shared::cluster.b64 _, [a];}"
    :: "r"(bar), "r"(rank), "r"((uint32_t)c) : "memory");
}
DEVI void p_expect_tx(uint32_t bar, uint32_t bytes, bool c) {
  asm volatile("{.reg .pred p; setp.ne.u32 p, %2, 0; @p mbarrier.arrive.expect_tx.shared::cta.b64 _, [%0], %1;}" :: "r"(bar), "r"(bytes), "r"((uint32_t)c) : "memory");
}
DEVI void p_arrive(uint32_t bar, bool c) { asm volatile("{.reg .pred p; setp.ne.u32 p, %1, 0; @p mbarrier.arrive.shared::cta.b64 _, [%0];}" :: "r"(bar), "r"((uint32_t)c) : "memory"); }
DEVI void tma_store_2d(const CUtensorMap* m, uint32_t src, int c0, int c1) {
  asm volatile("cp.async.bulk.tensor.2d.global.shared::cta.bulk_group [%0, {%2, %3}], [%1];" :: "l"(m), "r"(src), "r"(c0), "r"(c1) : "memory");
}
DEVI void tma_radd_2d(const CUtensorMap* m, uint32_t src, int c0, int c1) {
  asm volatile("cp.reduce.async.bulk.tensor.2d.global.shared::cta.add.bulk_group [%0, {%2, %3}], [%1];" :: "l"(m), "r"(src), "r"(c0), "r"(c1) : "memory");
}
DEVI void bulk_commit() { asm volatile("cp.async.bulk.commit_group;" ::: "memory"); }
template<int N> DEVI void bulk_wait_read() { asm volatile("cp.async.bulk.wait_group.read %0;" :: "n"(N) : "memory"); }
template<int N> DEVI void bulk_wait() { asm volatile("cp.async.bulk.wait_group %0;" :: "n"(N) : "memory"); }
template<int ID, int N> DEVI void nbar_sync() { asm volatile("bar.sync %0, %1;" :: "n"(ID), "n"(N) : "memory"); }
template<int ID, int N> DEVI void nbar_arrive() { asm volatile("bar.arrive %0, %1;" :: "n"(ID), "n"(N) : "memory"); }
DEVI void nbar_sync_r(int id, int n) { asm volatile("bar.sync %0, %1;" :: "r"(id), "r"(n) : "memory"); }
template<int R> DEVI void reg_inc() { asm volatile("setmaxnreg.inc.sync.aligned.u32 %0;" :: "n"(R)); }
template<int R> DEVI void reg_dec() { asm volatile("setmaxnreg.dec.sync.aligned.u32 %0;" :: "n"(R)); }
DEVI void wg_fence() { asm volatile("wgmma.fence.sync.aligned;" ::: "memory"); }
DEVI void wg_commit() { asm volatile("wgmma.commit_group.sync.aligned;" ::: "memory"); }
template<int N> DEVI void wg_wait() { asm volatile("wgmma.wait_group.sync.aligned %0;" :: "n"(N) : "memory"); }
DEVI uint64_t mkdesc(uint32_t addr, uint32_t lbo, uint32_t sbo, uint32_t sw = 1) {
  return ((uint64_t)((addr & 0x3FFFF) >> 4)) | ((uint64_t)(lbo >> 4) << 16) | ((uint64_t)(sbo >> 4) << 32) | ((uint64_t)sw << 62);
}
constexpr uint32_t SMEM_BASE = 1024;
__host__ __device__ constexpr long long CD(uint32_t off, uint32_t lbo, uint32_t sbo, uint32_t sw) {
  return (long long)(((uint64_t)((SMEM_BASE + off) >> 4)) | ((uint64_t)(lbo >> 4) << 16) | ((uint64_t)(sbo >> 4) << 32) | ((uint64_t)sw << 62));
}
DEVI uint32_t pack_bf16(float lo, float hi) { uint32_t r; asm("cvt.rn.bf16x2.f32 %0, %1, %2;" : "=r"(r) : "f"(hi), "f"(lo)); return r; }
DEVI float bf_lo(uint32_t v) { return __uint_as_float(v << 16); }
DEVI float bf_hi(uint32_t v) { return __uint_as_float(v & 0xffff0000u); }
DEVI void ldsm4t(uint32_t addr, uint32_t& r0, uint32_t& r1, uint32_t& r2, uint32_t& r3) {
  asm volatile("ldmatrix.sync.aligned.m8n8.x4.trans.shared.b16 {%0,%1,%2,%3}, [%4];" : "=r"(r0), "=r"(r1), "=r"(r2), "=r"(r3) : "r"(addr) : "memory");
}
DEVI void stsm4(uint32_t addr, uint32_t r0, uint32_t r1, uint32_t r2, uint32_t r3) {
  asm volatile("stmatrix.sync.aligned.m8n8.x4.shared.b16 [%0], {%1,%2,%3,%4};" :: "r"(addr), "r"(r0), "r"(r1), "r"(r2), "r"(r3) : "memory");
}
DEVI uint2 lds64v(uint32_t a) { uint2 v; asm volatile("ld.volatile.shared.v2.u32 {%0,%1}, [%2];" : "=r"(v.x), "=r"(v.y) : "r"(a) : "memory"); return v; }
DEVI uint32_t lds32v(uint32_t a) { uint32_t v; asm volatile("ld.volatile.shared.u32 %0, [%1];" : "=r"(v) : "r"(a) : "memory"); return v; }
DEVI uint4 lds128v(uint32_t a) { uint4 v; asm volatile("ld.volatile.shared.v4.u32 {%0,%1,%2,%3}, [%4];" : "=r"(v.x), "=r"(v.y), "=r"(v.z), "=r"(v.w) : "r"(a) : "memory"); return v; }
DEVI void cp_async16(uint32_t dst, const void* src) { asm volatile("cp.async.cg.shared.global [%0], [%1], 16;" :: "r"(dst), "l"(src) : "memory"); }
DEVI void cp_async_wait() { asm volatile("cp.async.wait_all;" ::: "memory"); }
DEVI void sts32(uint32_t a, uint32_t x) { asm volatile("st.shared.u32 [%0], %1;" :: "r"(a), "r"(x) : "memory"); }
DEVI int lane_id() { int r; asm volatile("mov.u32 %0, %%laneid;" : "=r"(r)); return r; }
DEVI void sts64(uint32_t a, uint32_t x, uint32_t y) { asm volatile("st.shared.v2.u32 [%0], {%1,%2};" :: "r"(a), "r"(x), "r"(y) : "memory"); }
DEVI void sts128(uint32_t a, uint4 v) { asm volatile("st.shared.v4.u32 [%0], {%1,%2,%3,%4};" :: "r"(a), "r"(v.x), "r"(v.y), "r"(v.z), "r"(v.w) : "memory"); }
DEVI void st_async128(uint32_t a, uint32_t x, uint32_t y, uint32_t z, uint32_t w, uint32_t bar) {
  asm volatile("st.async.weak.shared::cluster.mbarrier::complete_tx::bytes.v4.b32 [%0], {%1,%2,%3,%4}, [%5];" :: "r"(a), "r"(x), "r"(y), "r"(z), "r"(w), "r"(bar) : "memory");
}
DEVI void st_async32(uint32_t a, uint32_t x, uint32_t bar) {
  asm volatile("st.async.weak.shared::cluster.mbarrier::complete_tx::bytes.b32 [%0], %1, [%2];" :: "r"(a), "r"(x), "r"(bar) : "memory");
}
DEVI uint4 ldg_rlx128(const void* p) {
  uint4 v;
  asm volatile("ld.relaxed.gpu.global.v4.b32 {%0,%1,%2,%3}, [%4];" : "=r"(v.x), "=r"(v.y), "=r"(v.z), "=r"(v.w) : "l"(p) : "memory");
  return v;
}
DEVI int ldg_rlx32(const void* p) { int v; asm volatile("ld.relaxed.gpu.global.b32 %0, [%1];" : "=r"(v) : "l"(p) : "memory"); return v; }
DEVI int ldg_acq32(const void* p) { int v; asm volatile("ld.acquire.gpu.global.b32 %0, [%1];" : "=r"(v) : "l"(p) : "memory"); return v; }
DEVI void stg_rlx128(void* p, uint32_t x, uint32_t y, uint32_t z, uint32_t w) {
  asm volatile("st.relaxed.gpu.global.v4.b32 [%0], {%1,%2,%3,%4};" :: "l"(p), "r"(x), "r"(y), "r"(z), "r"(w) : "memory");
}
DEVI void stg128(void* p, uint32_t x, uint32_t y, uint32_t z, uint32_t w) {
  asm volatile("st.global.v4.b32 [%0], {%1,%2,%3,%4};" :: "l"(p), "r"(x), "r"(y), "r"(z), "r"(w) : "memory");
}
DEVI uint2 ldg_rlx64(const void* p) { uint2 v; asm volatile("{.reg .b64 a; ld.relaxed.gpu.global.b64 a, [%2]; mov.b64 {%0,%1}, a;}" : "=r"(v.x), "=r"(v.y) : "l"(p) : "memory"); return v; }
DEVI void stg_rlx64(void* p, uint32_t x, uint32_t y) { asm volatile("{.reg .b64 a; mov.b64 a, {%1,%2}; st.relaxed.gpu.global.b64 [%0], a;}" :: "l"(p), "r"(x), "r"(y) : "memory"); }
DEVI void stg_rlx32(void* p, uint32_t x) { asm volatile("st.relaxed.gpu.global.b32 [%0], %1;" :: "l"(p), "r"(x) : "memory"); }
DEVI void flag_add(int* p) { asm volatile("fence.proxy.async.global; red.release.gpu.global.add.s32 [%0], 1;" :: "l"(p) : "memory"); }
DEVI void e_flag_add(int* p) { asm volatile("fence.proxy.async.global;\n" ELECT "red.release.gpu.global.add.s32 [%0], 1;}" :: "l"(p) : "memory"); }
DEVI int cluster_rank() { int r; asm volatile("mov.u32 %0, %%cluster_ctarank;" : "=r"(r)); return __shfl_sync(0xffffffffu, r, 0); }
DEVI int cluster_id() { int r; asm volatile("mov.u32 %0, %%clusterid.x;" : "=r"(r)); return __shfl_sync(0xffffffffu, r, 0); }
DEVI uint32_t clock32() { uint32_t c; asm volatile("mov.u32 %0, %%clock;" : "=r"(c)); return c; }
DEVI uint32_t gtime() { uint32_t c; asm volatile("mov.u32 %0, %%globaltimer_lo;" : "=r"(c)); return c; }
DEVI void spin_until(uint32_t t0, int d) { while (__any_sync(0xffffffffu, (int)(clock32() - t0) < d)) {} }
DEVI void pin2(const void* a, const void* b) { asm volatile("{.reg .pred p; setp.eq.u64 p, %0, %1; @p st.volatile.global.u64 [%0], %1;}" :: "l"(a), "l"(b) : "memory"); }
DEVI void pin2(uint32_t a, uint32_t b) { asm volatile("{.reg .pred p; setp.eq.u32 p, %0, %1; @p st.volatile.shared.u32 [%0], %1;}" :: "r"(a), "r"(b) : "memory"); }
DEVI void p_stg_rlx64(void* p, uint32_t x, uint32_t y, bool c) {
  asm volatile("{.reg .pred p; .reg .b64 a; setp.ne.u32 p, %3, 0; mov.b64 a, {%1,%2}; @p st.relaxed.gpu.global.b64 [%0], a;}" :: "l"(p), "r"(x), "r"(y), "r"((uint32_t)c) : "memory");
}
DEVI void pin2(uint64_t a, uint64_t b) { pin2((const void*)a, (const void*)b); }
DEVI uint64_t pair(uint32_t a, uint32_t bar) { return a | (uint64_t)bar << 32; }
DEVI void st_async32(uint64_t q, uint32_t x) { st_async32((uint32_t)q, x, (uint32_t)(q >> 32)); }
DEVI void st_async128(uint64_t q, uint4 v) { st_async128((uint32_t)q, v.x, v.y, v.z, v.w, (uint32_t)(q >> 32)); }
DEVI float ex2(float x) { float r; asm("ex2.approx.ftz.f32 %0, %1;" : "=f"(r) : "f"(x)); return r; }
DEVI float rcp(float x) { float r; asm("rcp.approx.ftz.f32 %0, %1;" : "=f"(r) : "f"(x)); return r; }
DEVI uint32_t xor_or(uint32_t a, uint32_t t, uint32_t acc) { uint32_t r; asm("lop3.b32 %0, %1, %2, %3, 0xbe;" : "=r"(r) : "r"(a), "r"(t), "r"(acc)); return r; }
DEVI void stsm2(uint32_t addr, uint32_t r0, uint32_t r1) {
  asm volatile("stmatrix.sync.aligned.m8n8.x2.shared.b16 [%0], {%1,%2};" :: "r"(addr), "r"(r0), "r"(r1) : "memory");
}
DEVI uint32_t settag(uint32_t v, uint32_t tag) { return (v & ~1u) | tag; }

#define A4(c, o)  c(d[o+0]), c(d[o+1]), c(d[o+2]), c(d[o+3])
#define A8(c, o)  A4(c, o), A4(c, o+4)
#define A16(c, o) A8(c, o), A8(c, o+8)
#define A20(c, o) A16(c, o), A4(c, o+16)
#define A32(c, o) A16(c, o), A16(c, o+16)
#define RL8  "{%0,%1,%2,%3,%4,%5,%6,%7}"
#define RL16 "{%0,%1,%2,%3,%4,%5,%6,%7,%8,%9,%10,%11,%12,%13,%14,%15}"
#define RL20 "{%0,%1,%2,%3,%4,%5,%6,%7,%8,%9,%10,%11,%12,%13,%14,%15,%16,%17,%18,%19}"
#define RL32 "{%0,%1,%2,%3,%4,%5,%6,%7,%8,%9,%10,%11,%12,%13,%14,%15,%16,%17,%18,%19,%20,%21,%22,%23,%24,%25,%26,%27,%28,%29,%30,%31}"
#define RL64 "{%0,%1,%2,%3,%4,%5,%6,%7,%8,%9,%10,%11,%12,%13,%14,%15,%16,%17,%18,%19,%20,%21,%22,%23,%24,%25,%26,%27,%28,%29,%30,%31," \
  "%32,%33,%34,%35,%36,%37,%38,%39,%40,%41,%42,%43,%44,%45,%46,%47,%48,%49,%50,%51,%52,%53,%54,%55,%56,%57,%58,%59,%60,%61,%62,%63}"
#define WG_OP(shape) "wgmma.mma_async.sync.aligned." shape "k16.f32.bf16.bf16 "
#define DEF_WGMMA(N, RL, AL, i0, i1, i2, i3, i4, i5, i6)                                                                         \
  template<int SC, int TB, long long CB> DEVI void rs##N(float* d, const uint32_t* a) {                                          \
    if (SC) asm volatile("{.reg .b64 tb; mov.b64 tb, %" #i4 ";\n" WG_OP("m64n" #N) RL ", {%" #i0 ",%" #i1 ",%" #i2 ",%" #i3 "}, tb, 1, 1, 1, %" #i5 ";}" \
      : AL("+f", 0) : "r"(a[0]), "r"(a[1]), "r"(a[2]), "r"(a[3]), "n"(CB), "n"(TB));                                             \
    else asm volatile("{.reg .b64 tb; mov.b64 tb, %" #i4 ";\n" WG_OP("m64n" #N) RL ", {%" #i0 ",%" #i1 ",%" #i2 ",%" #i3 "}, tb, 0, 1, 1, %" #i5 ";}" \
      : AL("=f", 0) : "r"(a[0]), "r"(a[1]), "r"(a[2]), "r"(a[3]), "n"(CB), "n"(TB));                                             \
  }                                                                                                                              \
  template<int SC, int TA, int TB, long long CA, long long CB> DEVI void ss##N(float* d, uint32_t a) {                           \
    if (SC) asm volatile("{.reg .b64 ta, tb; .reg .b32 lo, hi; add.u32 lo, %" #i0 ", %" #i1 "; mov.b32 hi, %" #i2 "; mov.b64 ta, {lo, hi}; mov.b64 tb, %" #i3 ";\n" \
      WG_OP("m64n" #N) RL ", ta, tb, 1, 1, 1, %" #i4 ", %" #i5 ";}"                                                              \
      : AL("+f", 0) : "r"(a), "n"((int)CA), "n"((int)(CA >> 32)), "n"(CB), "n"(TA), "n"(TB));                                    \
    else asm volatile("{.reg .b64 ta, tb; .reg .b32 lo, hi; add.u32 lo, %" #i0 ", %" #i1 "; mov.b32 hi, %" #i2 "; mov.b64 ta, {lo, hi}; mov.b64 tb, %" #i3 ";\n" \
      WG_OP("m64n" #N) RL ", ta, tb, 0, 1, 1, %" #i4 ", %" #i5 ";}"                                                              \
      : AL("=f", 0) : "r"(a), "n"((int)CA), "n"((int)(CA >> 32)), "n"(CB), "n"(TA), "n"(TB));                                    \
  }
DEF_WGMMA(8, "{%0,%1,%2,%3}", A4, 4, 5, 6, 7, 8, 9, 10)
DEF_WGMMA(16, RL8, A8, 8, 9, 10, 11, 12, 13, 14)
DEF_WGMMA(32, RL16, A16, 16, 17, 18, 19, 20, 21, 22)
DEF_WGMMA(40, RL20, A20, 20, 21, 22, 23, 24, 25, 26)
DEF_WGMMA(64, RL32, A32, 32, 33, 34, 35, 36, 37, 38)
template<int TA> DEVI void wgmma_n128(float* d, uint64_t a, uint64_t b, int scale_d) {
  asm volatile("{.reg .pred p; setp.ne.b32 p, %66, 0;\n" WG_OP("m64n128") RL64 ", %64, %65, p, 1, 1, %67, 1;}"
    : A32("+f", 0), A32("+f", 32) : "l"(a), "l"(b), "r"(scale_d), "n"(TA));
}

namespace rec {
constexpr int KR = 43;
constexpr uint32_t WSZ = (64 - KR) * 2048, STG = KR * 2048;
constexpr uint32_t WS = 0;
constexpr uint32_t RING = 2 * WSZ;
constexpr uint32_t OB = RING + 3 * 8192;
constexpr uint32_t PB = OB + 4096;
constexpr uint32_t WO = RING + 32768;
constexpr uint32_t ATT = WO + 5 * 16384;
constexpr uint32_t AK = ATT + 10240, AV = ATT + 20480;
constexpr uint32_t PAD = ATT + 30720;
constexpr uint32_t BARS = PAD + 128;
constexpr uint32_t B_XE = BARS  , B_FA = BARS + 64  , B_FB = BARS + 88, B_FO = BARS + 96;
constexpr uint32_t B_ME = BARS + 104  , B_WE = BARS + 136  ;
constexpr uint32_t B_XF = BARS + 152  , B_MF = BARS + 216  , B_CP = BARS + 248  , B_WT = BARS + 280  ;
constexpr uint32_t B_AB = BARS + 296, B_OB = BARS + 304, B_ST = BARS + 312  , B_WS = BARS + 328, B_WO = BARS + 336;
constexpr int NBAR = 43;
constexpr uint32_t M0 = BARS + 384;
constexpr uint32_t SMEM = 232448;
constexpr int NB_P = 1, NB_ST = 2, NB_O = 3, NB_W0 = 4, NB_W1 = 5;
__host__ __device__ constexpr int wo_tile(int rank, int g, int i) { return i < 2 ? i * 6 + rank * 2 + g : 13 + rank - g; }
constexpr long long D_W = CD(WS, 16, 1024, 1), D_X = CD(0, 16, 1024, 1), D_M = CD(RING, 128, 256, 0), D_O = CD(OB, 128, 256, 0);
constexpr long long D_WO = CD(WO, 16, 1024, 1), D_QM = CD(ATT, 640, 0, 0), D_QT = CD(ATT + 128, 640, 64, 0), D_K = CD(AK, 640, 128, 0);
constexpr long long D_V = CD(AV, 128, 640, 0), D_P = CD(PB, 128, 768, 0);
struct Maps { CUtensorMap w[3], wo, xd, xs; };
__host__ __device__ constexpr uint32_t xslot(int s) { return s < 3 ? RING + s * 8192 : s < 5 ? WO + (s - 3) * 8192 : s < 7 ? WO + (s + 1) * 8192 : OB; }
__host__ __device__ constexpr bool k_smem(int k) { return k % 3 == 2; }
__host__ __device__ constexpr int k_idx(int k) { return k % 3 == 2 ? k / 3 : k - k / 3; }
__host__ __device__ constexpr int k_of_reg(int i) { return i + (i >> 1); }
__host__ __device__ constexpr int k_of_smem(int i) { return 3 * i + 2; }

#define RPROF(i)
#define RPROF_STEP
#define CPROF(i, v)

template<int K0, int K1> DEVI void seq_mem(float* d, const uint32_t* w, uint32_t dw) {
  if constexpr (K0 < K1) {
    constexpr long long B = D_M + K0 * 32;
    if constexpr (!k_smem(K0)) rs16<K0 != 0, 1, B>(d, w + 4 * k_idx(K0)); else ss16<1, 1, 1, D_W + k_idx(K0) * 128, B>(d, dw);
    seq_mem<K0 + 1, K1>(d, w, dw);
  }
}
template<bool DUAL, int K0, int K1> DEVI void seq_tok(float* d, const uint32_t* w, uint32_t dw) {
  if constexpr (K0 < K1) {
    constexpr long long B = D_X + (DUAL ? xslot((K0 >> 2) & 7) / 16 : xslot(K0 >> 3) / 16 + ((K0 >> 2) & 1) * 256) + (K0 & 3) * 2;
    if constexpr (DUAL) {
      if constexpr (!k_smem(K0)) rs64<K0 != 0, 0, B>(d, w + 4 * k_idx(K0)); else ss64<1, 1, 0, D_W + k_idx(K0) * 128, B>(d, dw);
    } else {
      if constexpr (!k_smem(K0)) rs32<K0 != 0, 0, B>(d, w + 4 * k_idx(K0)); else ss32<1, 1, 0, D_W + k_idx(K0) * 128, B>(d, dw);
    }
    seq_tok<DUAL, K0 + 1, K1>(d, w, dw);
  }
}
template<int T, int K0> DEVI void seq_wo(float* d, uint32_t dw) {
  if constexpr (K0 < 8) { ss16<K0 != 0, 1, 1, D_WO + T * 1024 + K0 * 128, D_O + K0 * 32>(d, dw); seq_wo<T, K0 + 1>(d, dw); }
}
template<long long Q, int K0> DEVI void seq_s(float* d) {
  if constexpr (K0 < 8) { ss40<K0 != 0, 1, 1, Q + K0 * 80, D_K + K0 * 80>(d, 0); seq_s<Q, K0 + 1>(d); }
}
template<bool DUAL, int J> DEVI void load_x(uint32_t sb, const Maps* M, int t) {
  if (DUAL) e_tma_3d_mc(sb + xslot(J & 7), &M->xd, J * 64, (t - LAG) * 32, 0, sb + B_XF + (J & 7) * 8);
  else e_tma_3d_mc(sb + xslot(J & 7), &M->xs, 0, (t < NSEG ? t : t - LAG) * 32, J * 2, sb + B_XF + (J & 7) * 8);
}
struct Ctx { uint32_t sb; const Maps* M; int h, rank, wi; bool lead; uint32_t par; };
#define XD 2
template<bool DUAL, int J> DEVI void tok_release(const Ctx& c, int t, int& budget) {
  constexpr int NC = DUAL ? 16 : 8, S = J & 7;
  if constexpr (J + 8 < NC) {
    p_arrive_at(c.sb + B_XE + S * 8, J % 3, c.lead);
    p_expect_tx(c.sb + B_XF + S * 8, 8192, c.lead && c.wi == 0);
  } else if constexpr (S == 4 || S == 6) {
    constexpr int g = S == 4;
    p_arrive(c.sb + B_WE + g * 8, c.lead);
    if (c.wi == g * 4 + 2) {
      mbar_wait(c.sb + B_WE + g * 8, t & 1, budget);
      e_expect_tx(c.sb + B_WT + g * 8, 16384);
      e_tma_2d(c.sb + WO + (1 - g) * 49152, &c.M->wo, wo_tile(c.rank, g, 0) * 64, c.h * DH, c.sb + B_WT + g * 8);
    }
  } else if constexpr (S < 3 || S == 7) p_arrive(c.sb + B_ME + (S & 3) * 8, c.lead);
  if constexpr (J == XD - 1) {
    if (c.rank == 1 && c.wi == 5) { mbar_wait(c.sb + B_FO, t & 1, budget); load_x<DUAL, 7>(c.sb, c.M, t); }
  } else if constexpr (J >= XD && J - XD + 8 < NC) {
    constexpr int I = J - XD;
    if (c.rank == I % 3 && c.wi == (I & 1) * 4 + 1) { mbar_wait(c.sb + B_XE + I * 8, (t - LAG) & 1, budget); load_x<DUAL, I + 8>(c.sb, c.M, t); }
  }
}
template<bool DUAL, int J> DEVI void tok_pass(float* d, const uint32_t* w, uint32_t dw, Ctx& c, int t, int& budget) {
  constexpr int NC = DUAL ? 16 : 8, KC = 64 / NC;
  if constexpr (J < NC) {
    mbar_wait(c.sb + B_XF + (J & 7) * 8, c.par ^ (J >> 3), budget);
    wg_fence();
    seq_tok<DUAL, J * KC, (J + 1) * KC>(d, w, dw);
    wg_commit();
    if constexpr (J > 0) { wg_wait<1>(); tok_release<DUAL, J - 1>(c, t, budget); }
    tok_pass<DUAL, J + 1>(d, w, dw, c, t, budget);
  } else {
    wg_wait<0>();
    tok_release<DUAL, NC - 1>(c, t, budget);
    if (!DUAL) c.par ^= 1;
  }
}
DEVI void pack_tok(uint32_t* e, const float* d) {
#pragma unroll
  for (int i = 0; i < 8; i++) e[i] = pack_bf16(d[4 * (i & 3) + 2 * (i >> 2)], d[4 * (i & 3) + 2 * (i >> 2) + 1]);
}
DEVI void push_tok(const uint32_t* e, uint32_t sb, uint32_t o, int r) {
  const uint32_t b = mapa(sb, r);
  st_async128(b + o, e[0], e[1], e[2], e[3], b + B_AB);
}
DEVI uint32_t h1_tag(int seg) { return ((seg >> 1) & 1) ^ 1; }
DEVI void put_part(char* p1, char* p2, const float* c, int t) {
  p_stg_rlx64(p1, settag(pack_bf16(c[0], c[1]), h1_tag(t)), pack_bf16(c[2], c[3]), t < NSEG);
  p_stg_rlx64(p2, settag(pack_bf16(c[4], c[5]), h1_tag(t - LAG)), pack_bf16(c[6], c[7]), t >= LAG);
}

DEVI void rec_math(const uint32_t sb, const int wi, const Maps& M) {
  const int h = cluster_id(), rank = cluster_rank();
  const int warp = wi & 3, wg = wi >> 2;
  const bool lead = (threadIdx.x & 127) == 0;
  int budget = SPIN_BUDGET;
  uint32_t w[4 * KR], e[16];
  Ctx cx{sb, &M, h, rank, wi, lead, 0};
  {
    const int lane = lane_id();
    const uint32_t a = sb + wg * STG + ((lane & 7) + (lane >> 4) * 8) * 128 + (((warp * 2 + ((lane >> 3) & 1)) ^ (lane & 7)) << 4);
    mbar_wait(sb + B_ST + wg * 8, 0, budget);
#pragma unroll
    for (int k = 0; k < KR; k++) ldsm4t(a + k * 2048, w[4*k], w[4*k+1], w[4*k+2], w[4*k+3]);
    nbar_arrive<NB_ST, 384>();
    nbar_sync_r(NB_W0 + wg, 128);
    for (int i = 0; i < 5; i++) p_arrive_at(sb + B_FA + i * 8, i == 4, lead);
    mbar_wait(sb + B_WS, 0, budget);
  }
#pragma unroll 1
  for (int t = -1; t < NSTEP; t++) {
    const uint32_t dw = wg * (WSZ >> 4);
    RPROF_STEP;
    if (t >= 0) {
      const int lane = lane_id();
      RPROF(0 + wg * 12);
      {
        float m[8];
        const uint32_t ao = ATT + rank * 10240 + wi * 1280, to = ao + 128 + (lane & 3) * 128 + (lane >> 2) * 16;
        const bool dual = t >= LAG && t < NSEG;
        mbar_wait(sb + B_MF, t & 1, budget);
        RPROF(1 + wg * 12);
        wg_fence(); seq_mem<0, 8>(m, w, dw);
        push_tok(e, sb, to, t >= NSEG);
        seq_mem<8, 16>(m, w, dw); wg_commit();
        push_tok(e + 4, sb, to + 640, t >= NSEG);
        mbar_wait(sb + B_MF + 8, t & 1, budget);
        wg_fence(); seq_mem<16, 32>(m, w, dw); wg_commit();
        if (dual) push_tok(e + 8, sb, to, 1);
        wg_wait<1>(); p_arrive_at(sb + B_FA, 0, lead);
        mbar_wait(sb + B_MF + 16, t & 1, budget);
        wg_fence(); seq_mem<32, 48>(m, w, dw); wg_commit();
        if (dual) push_tok(e + 12, sb, to + 640, 1);
        wg_wait<1>(); p_arrive_at(sb + B_FA + 8, 0, lead);
        const uint32_t r0 = mapa(sb, t >= NSEG), r1 = mapa(sb, 1), m0 = r0 + ao + lane * 4, m1 = r1 + ao + lane * 4;
        uint64_t q0 = pair(m0, r0 + B_AB), q1 = pair(m0 + 640, r0 + B_AB), q2 = pair(m1, r1 + B_AB), q3 = pair(m1 + 640, r1 + B_AB);
        pin2(q0, q1); pin2(q2, q3);
        mbar_wait(sb + B_MF + 24, t & 1, budget);
        wg_fence(); seq_mem<48, 64>(m, w, dw); wg_commit();
        wg_wait<1>(); p_arrive_at(sb + B_FA + 16, 0, lead);
        wg_wait<0>();
        const uint32_t a0 = pack_bf16(m[0], m[1]), a1 = pack_bf16(m[2], m[3]), a2 = pack_bf16(m[4], m[5]), a3 = pack_bf16(m[6], m[7]);
        st_async32(q0, t < NSEG ? a0 : a2); st_async32(q1, t < NSEG ? a1 : a3);
        if (dual) { st_async32(q2, a2); st_async32(q3, a3); }
      }
      RPROF(2 + wg * 12);
      if (t == 0) mbar_wait(sb + B_WO, 0, budget);
      mbar_wait(sb + B_WT + wg * 8, t & 1, budget);
      const int seg = t - rank * LAG;
      constexpr float SC = 0.08838834764831845f * 1.4426950408889634f;
      if (rank < 2 && (unsigned)seg < (unsigned)NSEG) {
        float s[32];
        if (wg) {
          const uint32_t pw = sb + PB + lane * 4, o = OB + (lane >> 4) * 2048 + warp * 512 + rank * 256 + (lane & 15) * 16;
          const uint32_t r0 = mapa(sb, 0), r1 = mapa(sb, 1), r2 = mapa(sb, 2);
          uint64_t q0 = pair(r0 + o, r0 + B_OB), q1 = pair(r1 + o, r1 + B_OB), q2 = pair(r2 + o, r2 + B_OB);
          uint32_t one[4];
#pragma unroll
          for (int i = 0; i < 4; i++) one[i] = 0x3F803F80u + (pw >> 31);
          pin2(q0, q1); pin2(q2, (uint64_t)pw);
          mbar_wait_cluster(sb + B_AB, seg & 1, budget);
          fence_proxy_async();
          RPROF(3 + 12);
          wg_fence(); seq_s<D_QM, 0>(s); wg_commit();
          nbar_arrive<NB_P, 256>();
          if (warp == 1) sts32(pw + 640, 0);
          wg_wait<0>();
          float mx = fmaxf(fmaxf(fmaxf(s[0], s[1]), fmaxf(s[4], s[5])), fmaxf(fmaxf(fmaxf(s[8], s[9]), fmaxf(s[12], s[13])), fmaxf(s[16], s[17])));
          const float x1 = __shfl_xor_sync(0xffffffffu, mx, 1), x2 = __shfl_xor_sync(0xffffffffu, mx, 2), x3 = __shfl_xor_sync(0xffffffffu, mx, 3);
          const float u = (warp & 2) ? ((warp & 1) ? s[16] : s[12]) : ((warp & 1) ? s[8] : s[4]);
          const float v = (warp & 2) ? ((warp & 1) ? s[17] : s[13]) : ((warp & 1) ? s[9] : s[5]);
          const float ms = -SC * fmaxf(fmaxf(mx, x1), fmaxf(x2, x3));
          sts32(pw + 128 + warp * 128, pack_bf16(ex2(fmaf(u, SC, ms)), ex2(fmaf(v, SC, ms))));
          if (warp == 0) sts32(pw, pack_bf16(ex2(fmaf(s[0], SC, ms)), ex2(fmaf(s[1], SC, ms))));
          fence_proxy_async();
          nbar_sync<NB_W1, 128>();
          RPROF(4 + 12);
          wg_fence();
          rs8<0, 0, D_P>(s + 8, one); rs8<1, 0, D_P + 16>(s + 8, one); rs8<1, 0, D_P + 32>(s + 8, one);
          wg_commit();
          ss8<0, 0, 0, D_V, D_P>(s, 0); ss8<0, 0, 0, D_V + 320, D_P>(s + 4, 0);
          ss8<1, 0, 0, D_V + 16, D_P + 16>(s, 0); ss8<1, 0, 0, D_V + 336, D_P + 16>(s + 4, 0);
          ss8<1, 0, 0, D_V + 32, D_P + 32>(s, 0); ss8<1, 0, 0, D_V + 352, D_P + 32>(s + 4, 0);
          wg_commit();
          wg_wait<1>();
          const float i0 = rcp(s[8]), i1 = rcp(s[9]);
          wg_wait<0>();
          stsm4(sb + o, pack_bf16(s[0] * i0, s[1] * i1), pack_bf16(s[2] * i0, s[3] * i1), pack_bf16(s[4] * i0, s[5] * i1), pack_bf16(s[6] * i0, s[7] * i1));
          __syncwarp();
          const uint4 z = lds128v(sb + o);
          if (t < NSTEP - 1) { st_async128(q2, z); st_async128(rank ? q0 : q1, z); st_async128(rank ? q1 : q0, z); }
        } else {
          const int g = lane >> 2, lim = 8 * (g >> 1) + (g & 1) + 2 * warp - 8 * (lane & 3);
          const uint32_t pw = sb + PB + 768 + warp * 768 + lane * 16;
          char* const og = (char*)(g_ot + rank * O_LAYER) + (size_t)(h * DH + warp * 16 + (lane >> 2)) * (SEQ * 2) + seg * 64 + (lane & 3) * 16;
          pin2(pw, lim); pin2(og, nullptr);
          mbar_wait_cluster(sb + B_AB, seg & 1, budget);
          fence_proxy_async();
          nbar_sync<NB_P, 256>();
          RPROF(3);
          wg_fence(); seq_s<D_QT, 0>(s); wg_commit();
          wg_wait<0>();
#pragma unroll
          for (int i = 0; i < 8; i++) { float& v = s[4 + 4 * (i >> 1) + (i & 1)]; v = i <= lim ? v : -INFINITY; }
          float mx = fmaxf(fmaxf(fmaxf(s[0], s[1]), fmaxf(s[4], s[5])), fmaxf(fmaxf(fmaxf(s[8], s[9]), fmaxf(s[12], s[13])), fmaxf(s[16], s[17])));
          const float x1 = __shfl_xor_sync(0xffffffffu, mx, 1), x2 = __shfl_xor_sync(0xffffffffu, mx, 2), x3 = __shfl_xor_sync(0xffffffffu, mx, 3);
          const float ms = -SC * fmaxf(fmaxf(mx, x1), fmaxf(x2, x3));
#pragma unroll
          for (int i = 0; i < 10; i++) { float& v = s[4 * (i >> 1) + (i & 1)]; v = ex2(fmaf(v, SC, ms)); }
          const float sum = (((s[0] + s[1]) + (s[4] + s[5])) + ((s[8] + s[9]) + (s[12] + s[13]))) + (s[16] + s[17]);
          const float y1 = __shfl_xor_sync(0xffffffffu, sum, 1), y2 = __shfl_xor_sync(0xffffffffu, sum, 2), y3 = __shfl_xor_sync(0xffffffffu, sum, 3);
          const float inv = rcp((sum + y1) + (y2 + y3));
          stsm4(pw, pack_bf16(s[0] * inv, s[1] * inv), pack_bf16(s[4] * inv, s[5] * inv), pack_bf16(s[8] * inv, s[9] * inv), pack_bf16(s[12] * inv, s[13] * inv));
          stsm2(pw + 512, pack_bf16(s[16] * inv, s[17] * inv), 0);
          fence_proxy_async();
          nbar_sync<NB_W0, 128>();
          RPROF(4);
          wg_fence();
          ss32<0, 0, 0, D_V, D_P + 48>(s, 0); ss32<0, 0, 0, D_V + 320, D_P + 48>(s + 16, 0);
          ss32<1, 0, 0, D_V + 16, D_P + 64>(s, 0); ss32<1, 0, 0, D_V + 336, D_P + 64>(s + 16, 0);
          ss32<1, 0, 0, D_V + 32, D_P + 80>(s, 0); ss32<1, 0, 0, D_V + 352, D_P + 80>(s + 16, 0);
          wg_commit();
          wg_wait<0>();
#pragma unroll
          for (int i = 0; i < 4; i++) {
            const float* d = s + (i >> 1) * 16 + (i & 1) * 2;
            stg128(og + ((i >> 1) * 64 + (i & 1) * 8) * (SEQ * 2), pack_bf16(d[0], d[1]), pack_bf16(d[4], d[5]), pack_bf16(d[8], d[9]), pack_bf16(d[12], d[13]));
          }
          nbar_arrive<NB_O, 160>();
        }
      }
      RPROF(5 + wg * 12);
      char* const p = (char*)g_h1 + ((wo_tile(rank, wg, 0) * 4 + warp) * 4 + (lane >> 3)) * 2048 + h * 64 + (lane & 7) * 8;
      const bool three = wg == 1 || rank == 2;
      if (t < NSTEP - 1) {
        float c[24];
        const uint32_t dt = wg ? 0 : 3072;
        const int o3 = (wo_tile(rank, wg, 2) - wo_tile(rank, wg, 0)) * 32768;
        char* const p1 = p + (t & 1) * sizeof(g_h1[0]);
        char* const p2 = p + (2 + ((t - LAG) & 1)) * sizeof(g_h1[0]);
        char* const p3 = p1 + o3;
        char* const p4 = p2 + o3;
        pin2(p1, p2); pin2(p3, p4);
        mbar_wait_cluster(sb + B_OB, t & 1, budget);
        fence_proxy_async();
        RPROF(6 + wg * 12);
        wg_fence(); seq_wo<0, 0>(c, dt); wg_commit(); seq_wo<1, 0>(c + 8, dt); wg_commit();
        wg_wait<1>(); put_part(p1, p2, c, t); p_arrive_at(sb + B_FB, 0, lead);
        if (three) {
          wg_fence(); seq_wo<2, 0>(c + 16, dt); wg_commit();
          wg_wait<1>(); put_part(p1 + 6 * 32768, p2 + 6 * 32768, c + 8, t);
          wg_wait<0>(); put_part(p3, p4, c + 16, t);
        } else { wg_wait<0>(); put_part(p1 + 6 * 32768, p2 + 6 * 32768, c + 8, t); }
        p_arrive_at(sb + B_FO, 1, lead);
      } else {
        for (int i = 0; i < (three ? 3 : 2); i++) stg_rlx64(p + 3 * sizeof(g_h1[0]) + (wo_tile(rank, wg, i) - wo_tile(rank, wg, 0)) * 32768, 0, 0);
      }
      RPROF(7 + wg * 12);
    }
    const int n = t + 1;
    if (n >= LAG && n < NSEG) {
      float d[32];
      tok_pass<true, 0>(d, w, dw, cx, n, budget);
      pack_tok(e, d + 16); pack_tok(e + 8, d);
    } else {
      float d[16];
      if (n == NSTEP) break;
      tok_pass<false, 0>(d, w, dw, cx, n, budget);
      pack_tok(e, d);
#pragma unroll
      for (int i = 8; i < 16; i++) e[i] = 0;
    }
    RPROF(8 + wg * 12);
  }
}

DEVI void wait_xa(const int* p, int& budget) {
  while (__any_sync(0xffffffffu, ldg_acq32(p) < 64) && --budget > 0) {}
  fence_proxy_global();
}
template<bool DUAL> DEVI void first_loads(uint32_t sb, const Maps* M, int n, int& budget) {
  mbar_wait(sb + B_FA, n & 1, budget); load_x<DUAL, 0>(sb, M, n);
  mbar_wait(sb + B_FA + 8, n & 1, budget); load_x<DUAL, 1>(sb, M, n);
  mbar_wait(sb + B_FA + 16, n & 1, budget); load_x<DUAL, 2>(sb, M, n);
  mbar_wait(sb + B_FB, n & 1, budget);
  load_x<DUAL, 3>(sb, M, n); load_x<DUAL, 4>(sb, M, n); load_x<DUAL, 5>(sb, M, n); load_x<DUAL, 6>(sb, M, n);
}
DEVI void rec_comm(const uint32_t sb, const int warp, const Maps& M, const bf16* __restrict__ mem0) {
  const int lane = threadIdx.x & 31, h = cluster_id(), rank = cluster_rank();
  int budget = SPIN_BUDGET;
  const bool two = warp == 3 || (rank == 2 && warp == 2);
  const int ntask = two ? 2 : 1, qi = two ? (warp == 3 ? rank : 3) : rank * 3 + warp;
  const int task0 = two ? h * 2 + (qi >> 1) : 64 + h * 4 + (qi >> 1);
  auto h2_word = [&](int i, int ln) {
    const int task = task0 + i * 192;
    return (char*)g_h2 + (task >> 2) * 512 + ((qi ^ i) & 1) * 256 + (task & 3) * 32 + (ln & 8) * 16 + (ln & 7) * 4;
  };
  auto first_x = [&](int t) {
    const int n = t + 1;
    p_expect_tx(sb + B_XF + (lane_id() & 7) * 8, 8192, lane_id() < 8);
    if (rank == 0) {
      if (n < NSEG && (n & 3) == 0) wait_xa(&g_xa[0][n >> 2], budget);
      if (n >= LAG && ((n - LAG) & 3) == 0) wait_xa(&g_xa[1][(n - LAG) >> 2], budget);
      if (n >= LAG && n < NSEG) first_loads<true>(sb, &M, n, budget); else first_loads<false>(sb, &M, n, budget);
    }
  };
  {
    const int task = task0 + (lane >> 4) * 192, L = (task & 3) * 8 + (lane & 7);
    if ((lane >> 4) < ntask) {
      const bf16* p = mem0 + (L & 3) * 2 * DM + (task >> 2) * 16 + (L >> 2) + (lane & 8);
      uint32_t m0 = (uint32_t)__bfloat16_as_ushort(p[0]) | (uint32_t)__bfloat16_as_ushort(p[DM]) << 16;
      m0 = m0 ? m0 : 0x8000u;
      stg_rlx32(h2_word(lane >> 4, lane), m0);
      sts32(sb + M0 + warp * 128 + lane * 4, m0);
    }
    __syncwarp();
    nbar_sync<NB_ST, 384>();
    if (warp == 2) {
      e_expect_tx(sb + B_WS, 2 * WSZ);
#pragma unroll 1
      for (int i = 0; i < 2 * (64 - KR); i++) e_tma_2d(sb + WS + (i & 1) * WSZ + (i >> 1) * 2048, &M.w[rank], h * DH + (i & 1) * 64, k_of_smem(i >> 1) * 16, sb + B_WS);
      const int nt = rank == 2 ? 6 : 5;
      e_expect_tx(sb + B_WO, (nt - 2) * 16384);
#pragma unroll 1
      for (int i = 1; i < nt; i++) if (i != 3) e_tma_2d(sb + WO + i * 16384, &M.wo, wo_tile(rank, 1 - i / 3, i % 3) * 64, h * DH, sb + B_WO);
    }
    if (warp == 3) first_x(-1);
  }
  uint32_t t0 = clock32(), cpp = 0;
  const uint32_t cp = sb + B_CP + warp * 8;
#pragma unroll 1
  for (int t = 0;; t++) {
    const int n = t + 1, seg = t - rank * LAG;
    RPROF_STEP;
    const bool att = rank < 2 && (unsigned)seg < (unsigned)NSEG;
    if (warp == 3) {
      if (att) e_expect_tx(sb + B_AB, 30720);
      if (n < NSTEP) e_expect_tx(sb + B_OB, t < NSEG && t >= LAG ? 4096 : 2048);
    }
    {
      const uint32_t dst = sb + RING + warp * 8192;
      mbar_wait(sb + B_ME + warp * 8, t & 1, budget);
      spin_until(t0, TP(1) + warp * TP(4));
      const int lane = lane_id();
      RPROF(24); CPROF(0, gtime());
      int tries = 0;
      while (true) {
        tries++;
        e_expect_tx(cp, 8192);
        e_bulk_g2s(dst, (const char*)g_h2[t & 3] + warp * 8192, 8192, cp);
        mbar_wait(cp, cpp, budget); cpp ^= 1;
        uint32_t mn = 0xffffffffu;
#pragma unroll
        for (int i = 0; i < 8; i++) mn = min(mn, lds32v(dst + i * 1024 + lane * 32 + (lane >> 2) * 4));
        if (!__any_sync(0xffffffffu, mn == 0) || --budget < 0) break;
      }
      e_arrive(sb + B_MF + warp * 8);
      RPROF(25); CPROF(1, gtime()); CPROF(2, tries);
    }
    {
      const int ln = lane_id(), i = ln >> 4;
      char* const w = h2_word(i, ln);
      if (i < ntask) {
        stg_rlx32(w + ((t + 3) & 3) * sizeof(g_h2[0]), 0);
        if (n < NSTEP && (((qi ^ i) & 1) ? t < LAG : t >= NSEG)) stg_rlx32(w + (n & 3) * sizeof(g_h2[0]), lds32v(sb + M0 + warp * 128 + ln * 4));
      }
      __syncwarp();
    }
    if (n < NSTEP) {
      if (warp == 3) first_x(t);
      mbar_wait(sb + B_OB, t & 1, budget);
      t0 = clock32() - (warp == 3 && rank == 0 ? 800 : 0);
    }
    if (warp == 2 && att) { nbar_sync<NB_O, 160>(); e_flag_add(&g_dep[E_O1 + rank * 16 + (seg >> 2)]); }
    if (n < NSTEP) {
      RPROF(26); CPROF(3, gtime());
#pragma unroll 1
      for (int i = 0; i < ntask; i++) {
        const int layer = (qi ^ i) & 1, sg = t - layer * LAG, task = task0 + i * 192;
        if ((unsigned)sg >= (unsigned)NSEG) continue;
        const uint32_t tag = h1_tag(sg);
        const int ln = lane_id();
        const char* const src = (const char*)g_h1[layer * 2 + (sg & 1)] + task * 2048 + ln * 8;
        char* const dst = h2_word(i, ln) + (n & 3) * sizeof(g_h2[0]);
        uint2 v[8];
        pin2(src, dst);
        spin_until(t0, TP(0) + (task < 96 ? 0 : task < 192 ? TP(3) : 2 * TP(3)));
        int tries = 0;
        while (true) {
          tries++;
#pragma unroll
          for (int k = 0; k < 8; k++) v[k] = ldg_rlx64(src + k * 256);
          uint32_t bad = 0;
#pragma unroll
          for (int k = 0; k < 8; k++) bad = xor_or(v[k].x, tag, bad);
          if (!__any_sync(0xffffffffu, bad & 1) || --budget < 0) break;
          }
        if (i == 0) { RPROF(27); CPROF(4, gtime()); CPROF(5, tries); }
        float a[4];
#pragma unroll
        for (int q = 0; q < 2; q++) {
          float lo[4], hi[4];
#pragma unroll
          for (int k = 0; k < 4; k++) { const uint32_t x = (&v[2*k].x)[q], y = (&v[2*k+1].x)[q]; lo[k] = bf_lo(x) + bf_lo(y); hi[k] = bf_hi(x) + bf_hi(y); }
          a[2*q] = (lo[0] + lo[1]) + (lo[2] + lo[3]); a[2*q+1] = (hi[0] + hi[1]) + (hi[2] + hi[3]);
        }
#pragma unroll
        for (int k = 0; k < 2; k++) {
          const float keep = (ln & 8) ? a[2+k] : a[k], send = (ln & 8) ? a[k] : a[2+k];
          a[k] = keep + __shfl_xor_sync(0xffffffffu, send, 8);
        }
#pragma unroll
        for (int k = 0; k < 2; k++) a[k] += __shfl_xor_sync(0xffffffffu, a[k], 16);
        const uint32_t out = pack_bf16(a[0], a[1]);
        if (ln < 16) stg_rlx32(dst, out ? out : 0x8000u);
        __syncwarp();
        if (i == 0) { RPROF(28); CPROF(6, gtime()); } else CPROF(7, gtime());
      }
    }
    if (n == NSTEP) break;
  }
  if (h == 0 && rank == 0 && warp < 2) g_xa[warp][lane_id()] = 0;
}
}

__global__ void __cluster_dims__(3, 1, 1) __launch_bounds__(384, 1)
rec_kernel(const __grid_constant__ rec::Maps M, const bf16* __restrict__ mem0) {
  using namespace rec;
  extern __shared__ __align__(1024) uint8_t smem[];
  const uint32_t sb = __shfl_sync(0xffffffffu, smem_u32(smem), 0);
  const int tid = threadIdx.x, wi = __shfl_sync(0xffffffffu, tid >> 5, 0);
  if ((sb & 0x3FFFF) != SMEM_BASE) __trap();
  if (wi == 0) {
    const int h = cluster_id(), rank = cluster_rank();
    for (int i = tid; i < NBAR; i += 32) mbar_init(sb + BARS + i * 8, i < 13 ? 6 : i < 19 ? 2 : 1);
    ((uint32_t*)(smem + PAD))[tid] = 0;
    fence_mbar_init(); fence_proxy_async();
    __syncwarp();
    e_expect_tx(sb + B_ST, STG); e_expect_tx(sb + B_ST + 8, STG);
    for (int i = 0; i < 2 * KR; i++) e_tma_2d(sb + (i & 1) * STG + (i >> 1) * 2048, &M.w[rank], h * DH + (i & 1) * 64, k_of_reg(i >> 1) * 16, sb + B_ST + (i & 1) * 8);
    for (int i = 0; i < 2 * (64 - KR); i++) e_prefetch_2d(&M.w[rank], h * DH + (i & 1) * 64, k_of_smem(i >> 1) * 16);
    for (int i = 0; i < (rank == 2 ? 6 : 5); i++) e_prefetch_2d(&M.wo, wo_tile(rank, 1 - i / 3, i % 3) * 64, h * DH);
  } else if (wi == 1) {
    if (blockIdx.x < NEV / 32) { g_dep[blockIdx.x * 32 + (tid & 31)] = 0; g_claim[blockIdx.x * 32 + (tid & 31)] = 0; __threadfence(); }
    __syncwarp();
    asm volatile("griddepcontrol.launch_dependents;" ::: "memory");
  }
  cluster_arrive(); cluster_wait();
  if (wi < 8) { reg_inc<232>(); rec_math(sb, wi, M); cluster_arrive(); cluster_wait(); }
  else { reg_dec<40>(); rec_comm(sb, wi & 3, M, mem0); cluster_arrive(); cluster_wait(); }
}

namespace gm {
struct Maps { CUtensorMap ot, wo, xn, wg, wu, hl, hs, wd, out; };
constexpr int STAGES = 6, STAGE = 32768;
constexpr uint32_t SO = STAGES * STAGE, BARS = SO + 32768;
constexpr uint32_t B_FULL = BARS, B_EMPTY = BARS + 48, B_TF = BARS + 96, B_TE = BARS + 112, B_ORD = BARS + 128, B_PM = BARS + 144;
constexpr uint32_t MAIL = BARS + 160, PMAIL = BARS + 176;
constexpr uint32_t SMEM = BARS + 256;
constexpr int END = -1;
struct Tile {
  bool isO, isG, l2; int blk, col, k0, n;
  DEVI Tile(int task, int rank) {
    const int e = task >> 8, id = task & 255;
    const bool isD = e < E_G1 || e >= E_D2;
    isO = e >= E_O1 && e < E_G2; isG = !isD && !isO; l2 = e >= E_O2;
    blk = isG && l2 ? (e & 15) * 2 + rank : isD && !l2 ? e >> 1 : e & 15;
    col = isG ? (l2 ? id : id * 2 + rank) : (id & 3) * 2 + rank;
    k0 = isO ? (id >> 2) * 2048 : isG ? 0 : ((l2 ? e >> 4 : e) & 1) * 1792;
    n = isO ? 32 : isG ? 16 : 28;
  }
};

DEVI float geglu(float g, float u) {
  const float z = g * (0.7978845608028654f + 0.035677408136300125f * g * g);
  float t; asm("tanh.approx.f32 %0, %1;" : "=f"(t) : "f"(z));
  const float hg = 0.5f * g;
  return fmaf(hg, t, hg) * u;
}
struct Sched {
  int need, size;
  bool filler;
  uint4 dep, cl;
  DEVI void init(int lane) {
    const int e = lane * 4;
    const bool d = e < E_G1 || e >= E_D2, o = e >= E_O1 && e < E_G2;
    need = d ? 28 : e < E_O1 ? 64 : 128;
    size = d ? 4 : o ? 8 : e < E_O1 ? 28 : e < E_G2 + 8 ? 56 : 0;
    filler = (int)blockIdx.x < TP(5);
  }
  DEVI void scan(int lane) { cl = ldg_rlx128(g_claim + lane * 4); dep = ldg_rlx128(g_dep + lane * 4); }
  DEVI int next(int lane, int& budget) {
    while (--budget > 0) {
      int av[4], open = 0;
#pragma unroll
      for (int i = 0; i < 4; i++) { const int r = max(size - (int)(&cl.x)[i], 0); open |= r; av[i] = ((int)(&dep.x)[i] >= need ? r : 0) + (i ? av[i - 1] : 0); }
      const uint32_t mo = __ballot_sync(0xffffffffu, open);
      if (!mo) break;
      if (!filler && (mo & TP(6)) && lane >= E_O2 / 4) av[3] = 0;
      int inc = av[3], pos = 0;
      while (true) {
        const uint32_t m = __ballot_sync(0xffffffffu, inc > pos && av[3]);
        if (!m) break;
        const int l = __ffs(m) - 1, rel = pos - (inc - av[3]), i = (rel >= av[0]) + (rel >= av[1]) + (rel >= av[2]);
        int r = 0;
        if (lane == l) {
          const int tk = atomicAdd(g_claim + lane * 4 + i, 1);
          r = tk < size ? (lane * 4 + i) << 8 | tk : -1 - (inc - av[3] + (i == 0 ? av[0] : i == 1 ? av[1] : i == 2 ? av[2] : av[3]) + tk - size);
        }
        r = __shfl_sync(0xffffffffu, r, l);
        if (r >= 0) { fence_proxy_global(); return r; }
        if (pos == 0) {
#pragma unroll
          for (int o = 1; o < 32; o <<= 1) { const int v = __shfl_up_sync(0xffffffffu, inc, o); if (lane >= o) inc += v; }
        }
        pos = -1 - r;
      }
      if (pos == 0) __nanosleep(TP(7));
      scan(lane);
    }
    return END;
  }
};

DEVI void producer(const uint32_t sb, const Maps& M) {
  const int lane = threadIdx.x & 31, rank = cluster_rank();
  int budget = SPIN_BUDGET, s = 0, ph = 0;
  Sched sc; sc.init(lane);
  if (rank == 0) sc.scan(lane);
#pragma unroll 1
  for (int i = 0;; i++) {
    int task;
    if (rank == 0) {
      task = sc.next(lane, budget);
      const uint32_t r = mapa(sb, 1);
      if (lane == 0) st_async32(r + PMAIL + (i & 1) * 4, task, r + B_PM + (i & 1) * 8);
      __syncwarp();
    } else {
      e_expect_tx(sb + B_PM + (i & 1) * 8, 4);
      mbar_wait_cluster(sb + B_PM + (i & 1) * 8, (i >> 1) & 1, budget);
      task = budget < 0 ? END : __shfl_sync(0xffffffffu, (int)lds32v(sb + PMAIL + (i & 1) * 4), 0);
      fence_proxy_global();
    }
    for (int z = 0; z < (task == END ? 2 : 1); z++) {
      const int g = (i + z) & 1;
      mbar_wait(sb + B_TE + g * 8, (((i + z) >> 1) & 1) ^ 1, budget);
      if (lane == 0) { sts64(sb + MAIL + g * 8, task, s | ph << 8); mbar_arrive(sb + B_TF + g * 8); }
      __syncwarp();
    }
    if (task == END) break;
    const Tile T(task, rank);
    const bool shareB = T.isG && T.l2;
    const CUtensorMap* mA = T.isO ? &M.ot : T.isG ? &M.xn : &M.hl;
    const CUtensorMap* mB0 = T.isO ? &M.wo : T.isG ? &M.wg : &M.wd;
    const CUtensorMap* mB1 = T.isG ? &M.wu : mB0;
    const int c0 = T.col * (T.isG ? 64 : 128), c1 = T.isG ? c0 : c0 + 64, row = T.blk * 128;
    const int ok = 0;
    int k = T.k0;
#pragma unroll 1
    for (int it = 0; it < T.n; it++, k += 64) {
      const uint32_t a = sb + s * STAGE, fb = sb + B_FULL + s * 8;
      mbar_wait(sb + B_EMPTY + s * 8, ph ^ 1, budget);
      e_expect_tx(fb, STAGE);
      if (shareB) {
        e_tma_2d_mc(a + 16384 + rank * 8192, rank ? mB1 : mB0, c0, k, fb);
        e_tma_2d(a, mA, k, row, fb); e_tma_2d(a + 8192, mA, k, row + 64, fb);
      } else {
        e_tma_2d_mc(a + rank * 8192, mA, T.isO ? row + rank * 64 : k, T.isO ? k + ok : row + rank * 64, fb);
        e_tma_2d(a + 16384, mB0, c0, k, fb); e_tma_2d(a + 24576, mB1, c1, k, fb);
      }
      if (it == T.n - TP(2) && rank == 0) sc.scan(lane);
      if (++s == STAGES) { s = 0; ph ^= 1; }
    }
  }
}

template<int TA> DEVI void mainloop(float* d0, float* d1, uint32_t sb, int n, int s, int ph, bool lead, uint32_t ord, int& budget) {
  int prev = 0;
  const uint32_t rel = threadIdx.x & 127;
#pragma unroll 1
  for (int i = 0; i < n; i++) {
    mbar_wait(sb + B_FULL + s * 8, ph, budget);
    const uint32_t a = sb + s * STAGE;
    const uint64_t da = mkdesc(a, 16, 1024), db = mkdesc(a + 16384, 8192, 1024);
    wg_fence();
#pragma unroll
    for (int k = 0; k < 4; k++) {
      wgmma_n128<TA>(d0, da + k * (TA ? 128 : 2), db + k * 128, (i | k) != 0);
      wgmma_n128<TA>(d1, da + 512 + k * (TA ? 128 : 2), db + k * 128, (i | k) != 0);
    }
    wg_commit();
    if (i > 0) { wg_wait<1>(); p_arrive_at(sb + B_EMPTY + prev * 8, rel & 1, rel < 2); }
    prev = s;
    if (++s == STAGES) { s = 0; ph ^= 1; }
  }
  p_arrive(ord, lead);
  wg_wait<0>();
  p_arrive_at(sb + B_EMPTY + prev * 8, rel & 1, rel < 2);
}

DEVI void consumer(const uint32_t sb, const Maps& M, const int wg) {
  const int tid = threadIdx.x, lane = tid & 31, warp = (tid >> 5) & 3;
  const bool lead = (tid & 127) == 0;
  const uint32_t so = sb + SO + wg * 16384;
  int budget = SPIN_BUDGET;
  float d0[64], d1[64];
#pragma unroll 1
  for (int m = 0;; m++) {
    mbar_wait(sb + B_TF + wg * 8, m & 1, budget);
    const uint2 mail = lds64v(sb + MAIL + wg * 8);
    const int task = __shfl_sync(0xffffffffu, (int)mail.x, 0), pos = __shfl_sync(0xffffffffu, (int)mail.y, 0);
    e_arrive(sb + B_TE + wg * 8);
    if (task == END || budget < 0) break;
    const Tile T(task, cluster_rank());
    mbar_wait(sb + B_ORD + wg * 8, (m & 1) ^ wg ^ 1, budget);
    if (T.isO) mainloop<1>(d0, d1, sb, 32, pos & 255, pos >> 8, lead, sb + B_ORD + (wg ^ 1) * 8, budget);
    else mainloop<0>(d0, d1, sb, T.n, pos & 255, pos >> 8, lead, sb + B_ORD + (wg ^ 1) * 8, budget);
    const uint32_t st = so + (warp * 16 + (lane & 15)) * 128;
    if (T.isG) {
#pragma unroll
      for (int mm = 0; mm < 2; mm++) {
        const float* d = mm ? d1 : d0;
#pragma unroll
        for (int c = 0; c < 4; c++) {
          uint32_t r[4];
#pragma unroll
          for (int i = 0; i < 4; i++) r[i] = pack_bf16(geglu(d[8*c+2*i], d[32+8*c+2*i]), geglu(d[8*c+2*i+1], d[33+8*c+2*i]));
          stsm4(st + mm * 8192 + (((2 * c + (lane >> 4)) ^ (lane & 7)) << 4), r[0], r[1], r[2], r[3]);
        }
      }
      fence_proxy_async();
      nbar_sync_r(1 + wg, 128);
      if (lead) {
        tma_store_2d(&M.hs, so, T.col * 64, T.blk * 128);
        bulk_commit(); bulk_wait<0>();
        flag_add(&g_dep[T.l2 ? E_D2 + (T.col >= 28) * 16 + T.blk : E_D1 + T.blk * 2 + (T.col >= 28)]);
      }
    } else {
#pragma unroll
      for (int hf = 0; hf < 2; hf++) {
        if (hf) { if (lead) bulk_wait_read<0>(); nbar_sync_r(1 + wg, 128); }
#pragma unroll
        for (int mm = 0; mm < 2; mm++) {
          const float* d = (mm ? d1 : d0) + hf * 32;
#pragma unroll
          for (int c = 0; c < 4; c++)
            stsm4(st + mm * 8192 + (((2 * c + (lane >> 4)) ^ (lane & 7)) << 4), pack_bf16(d[8*c], d[8*c+1]), pack_bf16(d[8*c+2], d[8*c+3]),
                  pack_bf16(d[8*c+4], d[8*c+5]), pack_bf16(d[8*c+6], d[8*c+7]));
        }
        fence_proxy_async();
        nbar_sync_r(1 + wg, 128);
        if (lead) { tma_radd_2d(&M.out, so, T.col * 128 + hf * 64, T.blk * 128); bulk_commit(); }
      }
      if (lead) {
        bulk_wait<0>();
        if (T.isO || !T.l2) flag_add(&g_dep[(!T.isO ? E_LX2 : T.l2 ? E_LX1B : E_LX1A) + T.blk]);
      }
    }
    __syncwarp();
  }
}

DEVI void norm_helper(const bf16* __restrict__ x, bf16* out) {
  const int lane = threadIdx.x & 31;
  int budget = SPIN_BUDGET, tk = lane < 4 ? -1 : 1024;
#pragma unroll 1
  while (--budget > 0) {
    if (tk < 0) tk = atomicAdd(g_claim + E_LI + lane, 1);
    if (__all_sync(0xffffffffu, tk >= 1024)) break;
    const uint32_t m = __ballot_sync(0xffffffffu, tk < 1024 && (lane == 0 || ldg_acq32(g_dep + E_LI + lane * 16 + (tk >> 6)) >= 16));
    if (!m) { __nanosleep(TP(7)); continue; }
    const int ql = __ffs(m) - 1, task = __shfl_sync(0xffffffffu, tk, ql), q = E_LI + ql * 16, ev = task >> 6;
    if (lane == ql) tk = -1;
    const size_t off = (size_t)task * (DM * 4) + lane * 16;
    const char* src = (const char*)(q == E_LI ? x : out) + off;
    uint4 u[8];
#pragma unroll
    for (int i = 0; i < 8; i++) u[i] = ldg_rlx128(src + i * 512);
    if (q == E_LI) {
#pragma unroll
      for (int i = 0; i < 8; i++) stg128((char*)out + off + i * 512, u[i].x, u[i].y, u[i].z, u[i].w);
    }
    float mean[2], rs[2];
#pragma unroll
    for (int r = 0; r < 2; r++) {
      float s0 = 0, s1 = 0;
#pragma unroll
      for (int i = 0; i < 16; i++) { const uint32_t v = (&u[4*r + (i >> 2)].x)[i & 3]; s0 += bf_lo(v); s1 += bf_hi(v); }
      mean[r] = (s0 + s1) * (1.f / 32);
      s0 = s1 = 0;
#pragma unroll
      for (int i = 0; i < 16; i++) { const uint32_t v = (&u[4*r + (i >> 2)].x)[i & 3]; const float a = bf_lo(v) - mean[r], b = bf_hi(v) - mean[r]; s0 = fmaf(a, a, s0); s1 = fmaf(b, b, s1); }
      rs[r] = s0 + s1;
    }
    {
      const bool hi = lane & 16;
      float m1 = hi ? mean[1] : mean[0], q1 = hi ? rs[1] : rs[0], m2 = hi ? mean[0] : mean[1], q2 = hi ? rs[0] : rs[1], cnt = 16;
#pragma unroll
      for (int o = 16; o; o >>= 1) {
        m2 = __shfl_xor_sync(0xffffffffu, m2, o); q2 = __shfl_xor_sync(0xffffffffu, q2, o);
        const float dl = m1 - m2;
        q2 = q1 = fmaf(dl * dl, cnt, q1 + q2); m2 = m1 = 0.5f * (m1 + m2);
        cnt *= 2;
      }
      q1 = rsqrtf(q1 * (1.f / DM) + 1e-5f);
      m2 = __shfl_xor_sync(0xffffffffu, m1, 16); q2 = __shfl_xor_sync(0xffffffffu, q1, 16);
      mean[0] = hi ? m2 : m1; mean[1] = hi ? m1 : m2; rs[0] = hi ? q2 : q1; rs[1] = hi ? q1 : q2;
    }
#pragma unroll
    for (int i = 0; i < 8; i++) {
      uint32_t y[4];
#pragma unroll
      for (int c = 0; c < 4; c++) { const uint32_t v = (&u[i].x)[c]; y[c] = pack_bf16((bf_lo(v) - mean[i >> 2]) * rs[i >> 2], (bf_hi(v) - mean[i >> 2]) * rs[i >> 2]); }
      stg128((char*)g_xn + off + i * 512, y[0], y[1], y[2], y[3]);
    }
    fence_proxy_global();
    __syncwarp();
    if (lane == 0) flag_add(q == E_LI ? &g_xa[0][ev] : q == E_LX2 ? &g_xa[1][ev] : &g_dep[q == E_LX1A ? E_G1 + ev : E_G2 + (ev >> 1)]);
    __syncwarp();
  }
}
}

__global__ void __cluster_dims__(2, 1, 1) __launch_bounds__(384, 1)
gemm_kernel(const __grid_constant__ gm::Maps M, const bf16* __restrict__ x, bf16* out) {
  using namespace gm;
  extern __shared__ __align__(1024) uint8_t smem[];
  const uint32_t sb = __shfl_sync(0xffffffffu, smem_u32(smem), 0);
  const int tid = threadIdx.x, wi = __shfl_sync(0xffffffffu, tid >> 5, 0);
  if (tid < 20) mbar_init(sb + BARS + tid * 8, tid == 14 || tid == 15 ? 4 : tid >= 6 && tid < 12 ? 2 : 1);
  fence_mbar_init();
  cluster_arrive(); cluster_wait();
  if (wi < 8) { reg_inc<208>(); consumer(sb, M, wi >> 2); cluster_arrive(); cluster_wait(); }
  else {
    reg_dec<88>();
    if (wi == 8) producer(sb, M);
    else {
      norm_helper(x, out);
      asm volatile("griddepcontrol.wait;" ::: "memory");
      if (wi == 9 && blockIdx.x < 64) g_h2[(NSTEP - 1) & 3][blockIdx.x * 32 + (tid & 31)] = make_uint4(0, 0, 0, 0);
    }
    __syncwarp();
    cluster_arrive(); cluster_wait();
  }
}

typedef CUresult (*PFN_encodeTiled)(CUtensorMap*, CUtensorMapDataType, cuuint32_t, void*, const cuuint64_t*, const cuuint64_t*,
                                    const cuuint32_t*, const cuuint32_t*, CUtensorMapInterleave, CUtensorMapSwizzle,
                                    CUtensorMapL2promotion, CUtensorMapFloatOOBfill);
static PFN_encodeTiled g_encode = nullptr;
static CUtensorMap make_map(const void* ptr, uint64_t rows, uint64_t cols, uint32_t box_rows) {
  CUtensorMap m;
  cuuint64_t dims[2] = {cols, rows}, strides[1] = {cols * 2};
  cuuint32_t box[2] = {64, box_rows}, es[2] = {1, 1};
  g_encode(&m, CU_TENSOR_MAP_DATA_TYPE_BFLOAT16, 2, (void*)ptr, dims, strides, box, es, CU_TENSOR_MAP_INTERLEAVE_NONE,
           CU_TENSOR_MAP_SWIZZLE_128B, CU_TENSOR_MAP_L2_PROMOTION_L2_256B, CU_TENSOR_MAP_FLOAT_OOB_FILL_NONE);
  return m;
}

static CUtensorMap make_map3(const void* ptr, uint64_t d0, uint64_t d1, uint64_t d2, uint64_t stride2) {
  CUtensorMap m;
  cuuint64_t dims[3] = {d0, d1, d2}, strides[2] = {DM * 2, stride2};
  cuuint32_t box[3] = {64, 32, 2}, es[3] = {1, 1, 1};
  g_encode(&m, CU_TENSOR_MAP_DATA_TYPE_BFLOAT16, 3, (void*)ptr, dims, strides, box, es, CU_TENSOR_MAP_INTERLEAVE_NONE,
           CU_TENSOR_MAP_SWIZZLE_128B, CU_TENSOR_MAP_L2_PROMOTION_L2_256B, CU_TENSOR_MAP_FLOAT_OOB_FILL_NONE);
  return m;
}

extern "C" void kernel_launch(void* const* d_in, const int* in_sizes, int n_in, void* d_out, int out_size) {
  const bf16* x = (const bf16*)d_in[0];
  const bf16* mem0 = (const bf16*)d_in[1];
  if (!g_encode) {
    void* p = nullptr; cudaDriverEntryPointQueryResult q;
    cudaGetDriverEntryPoint("cuTensorMapEncodeTiled", &p, cudaEnableDefault, &q);
    g_encode = (PFN_encodeTiled)p;
    cudaFuncSetAttribute(gemm_kernel, cudaFuncAttributeMaxDynamicSharedMemorySize, gm::SMEM);
    cudaFuncSetAttribute(rec_kernel, cudaFuncAttributeMaxDynamicSharedMemorySize, rec::SMEM);
  }
  bf16 *xn, *ot, *hh;
  cudaGetSymbolAddress((void**)&xn, g_xn); cudaGetSymbolAddress((void**)&ot, g_ot); cudaGetSymbolAddress((void**)&hh, g_h);
  rec::Maps R;
  for (int i = 0; i < 3; i++) R.w[i] = make_map(d_in[2 + i], DM, NH * DH, 16);
  R.wo = make_map(d_in[5], NH * DH, DM, 128);
  R.xd = make_map3(xn, DM, SEQ - LAG * 32, 2, (uint64_t)LAG * 32 * DM * 2); R.xs = make_map3(xn, 64, SEQ, DM / 64, 128);
  gm::Maps G;
  G.ot = make_map(ot, NH * DH + O_LAYER / SEQ, SEQ, 64); G.wo = make_map(d_in[5], NH * DH, DM, 64); G.xn = make_map(xn, SEQ, DM, 64);
  G.wg = make_map(d_in[8], DM, DF, 64); G.wu = make_map(d_in[9], DM, DF, 64); G.hl = make_map(hh, SEQ, DF, 64); G.hs = make_map(hh, SEQ, DF, 128);
  G.wd = make_map(d_in[10], DF, DM, 64); G.out = make_map(d_out, SEQ, DM, 128);
  rec_kernel<<<3 * NH, 384, rec::SMEM, cudaStreamPerThread>>>(R, mem0);
  cudaLaunchConfig_t cfg = {};
  cfg.gridDim = dim3(132); cfg.blockDim = dim3(384); cfg.dynamicSmemBytes = gm::SMEM; cfg.stream = cudaStreamPerThread;
  cudaLaunchAttribute at[1];
  at[0].id = cudaLaunchAttributeProgrammaticStreamSerialization; at[0].val.programmaticStreamSerializationAllowed = 1;
  cfg.attrs = at; cfg.numAttrs = 1;
  cudaLaunchKernelEx(&cfg, gemm_kernel, G, x, (bf16*)d_out);
}
```

```cpp
#include <cuda_runtime.h>
#include <cuda_bf16.h>
#include <cuda.h>
#include <stdint.h>

#define DEVI __device__ __forceinline__
typedef __nv_bfloat16 bf16;

constexpr int SEQ = 2048, DM = 1024, NH = 32, DH = 128, DF = 3584, NSEG = 64;
#define LAG 18
constexpr int NSTEP = NSEG + LAG;

#define TSS 1
#define TSD 1100
constexpr size_t O_LAYER = 0;
__device__ __align__(1024) bf16 g_xn[SEQ * DM];
__device__ __align__(1024) bf16 g_ot[SEQ * NH * DH + O_LAYER];
__device__ __align__(1024) bf16 g_h[SEQ * DF];
__device__ __align__(1024) uint2 g_h1[4][256 * 256];
__device__ __align__(1024) uint4 g_h2[4][2048];
__device__ __align__(128) uint32_t g_ts[2][32 * TSS];
enum { E_D1 = 0, E_G1 = 32, E_O1 = 48, E_O2 = 64, E_G2 = 80, E_D2 = 96,
       E_LI = 128, E_LX2 = 144, E_LX1A = 160, E_LX1B = 176, NEV = 256 };
__device__ __align__(128) int g_dep[NEV];
__device__ __align__(128) int g_claim[NEV];
__device__ __align__(128) int g_xa[2][32];

#define TUNE_DEFAULTS 1500, 2500, 3, 100, 100, 12, 0xffff, 100
constexpr int c_D[8] = {TUNE_DEFAULTS};
template<int I> struct TPV { static constexpr int v = c_D[I]; };
#define TP(i) TPV<i>::v

DEVI uint32_t smem_u32(const void* p) { return (uint32_t)__cvta_generic_to_shared(p); }
DEVI void mbar_init(uint32_t bar, uint32_t cnt) { asm volatile("mbarrier.init.shared::cta.b64 [%0], %1;" :: "r"(bar), "r"(cnt) : "memory"); }
DEVI void mbar_arrive(uint32_t bar) { asm volatile("mbarrier.arrive.shared::cta.b64 _, [%0];" :: "r"(bar) : "memory"); }
DEVI bool mbar_try(uint32_t bar, uint32_t parity) {
  uint32_t p;
  asm volatile("{.reg .pred p; mbarrier.try_wait.parity.shared::cta.b64 p, [%1], %2; selp.u32 %0, 1, 0, p;}" : "=r"(p) : "r"(bar), "r"(parity) : "memory");
  return p;
}
constexpr int SPIN_BUDGET = 1 << 18;
DEVI void mbar_wait(uint32_t bar, uint32_t parity, int& budget) {
  while (!mbar_try(bar, parity)) { if (--budget < 0) break; }
}
DEVI bool mbar_try_cluster(uint32_t bar, uint32_t parity) {
  uint32_t p;
  asm volatile("{.reg .pred p; mbarrier.try_wait.parity.acquire.cluster.shared::cta.b64 p, [%1], %2; selp.u32 %0, 1, 0, p;}" : "=r"(p) : "r"(bar), "r"(parity) : "memory");
  return p;
}
DEVI void mbar_wait_cluster(uint32_t bar, uint32_t parity, int& budget) {
  while (!mbar_try_cluster(bar, parity)) { if (--budget < 0) break; }
}
DEVI uint32_t mapa(uint32_t addr, uint32_t rank) { uint32_t r; asm("mapa.shared::cluster.u32 %0, %1, %2;" : "=r"(r) : "r"(addr), "r"(rank)); return r; }
DEVI void cluster_arrive() { asm volatile("barrier.cluster.arrive.release.aligned;" ::: "memory"); }
DEVI void cluster_wait() { asm volatile("barrier.cluster.wait.acquire.aligned;" ::: "memory"); }
DEVI void fence_mbar_init() { asm volatile("fence.mbarrier_init.release.cluster;" ::: "memory"); }
DEVI void fence_proxy_async() { asm volatile("fence.proxy.async.shared::cta;" ::: "memory"); }
DEVI void fence_proxy_global() { asm volatile("fence.proxy.async.global;" ::: "memory"); }
#define ELECT "{.reg .pred p; elect.sync _|p, 0xffffffff;\n @p "
DEVI void e_expect_tx(uint32_t bar, uint32_t bytes) { asm volatile(ELECT "mbarrier.arrive.expect_tx.shared::cta.b64 _, [%0], %1;}" :: "r"(bar), "r"(bytes) : "memory"); }
DEVI void e_arrive(uint32_t bar) { asm volatile(ELECT "mbarrier.arrive.shared::cta.b64 _, [%0];}" :: "r"(bar) : "memory"); }
DEVI void e_tma_2d(uint32_t dst, const CUtensorMap* m, int c0, int c1, uint32_t bar) {
  asm volatile(ELECT "cp.async.bulk.tensor.2d.shared::cluster.global.mbarrier::complete_tx::bytes [%0], [%1, {%3, %4}], [%2];}"
    :: "r"(dst), "l"(m), "r"(bar), "r"(c0), "r"(c1) : "memory");
}
DEVI void e_prefetch_2d(const CUtensorMap* m, int c0, int c1) {
  asm volatile(ELECT "cp.async.bulk.prefetch.tensor.2d.L2.global [%0, {%1, %2}];}" :: "l"(m), "r"(c0), "r"(c1) : "memory");
}
DEVI void e_prefetch_3d(const CUtensorMap* m, int c0, int c1, int c2) {
  asm volatile(ELECT "cp.async.bulk.prefetch.tensor.3d.L2.global [%0, {%1, %2, %3}];}" :: "l"(m), "r"(c0), "r"(c1), "r"(c2) : "memory");
}
DEVI void e_bulk_g2s(uint32_t dst, const void* src, uint32_t bytes, uint32_t bar) {
  asm volatile(ELECT "cp.async.bulk.shared::cluster.global.mbarrier::complete_tx::bytes [%0], [%1], %2, [%3];}" :: "r"(dst), "l"(src), "r"(bytes), "r"(bar) : "memory");
}
DEVI void e_tma_3d_mc(uint32_t dst, const CUtensorMap* m, int c0, int c1, int c2, uint32_t bar) {
  asm volatile(ELECT "cp.async.bulk.tensor.3d.shared::cluster.global.mbarrier::complete_tx::bytes.multicast::cluster [%0], [%1, {%3, %4, %5}], [%2], %6;}"
    :: "r"(dst), "l"(m), "r"(bar), "r"(c0), "r"(c1), "r"(c2), "h"((uint16_t)7) : "memory");
}
DEVI void e_tma_2d_mc(uint32_t dst, const CUtensorMap* m, int c0, int c1, uint32_t bar) {
  asm volatile(ELECT "cp.async.bulk.tensor.2d.shared::cluster.global.mbarrier::complete_tx::bytes.multicast::cluster [%0], [%1, {%3, %4}], [%2], %5;}"
    :: "r"(dst), "l"(m), "r"(bar), "r"(c0), "r"(c1), "h"((uint16_t)3) : "memory");
}
DEVI void p_arrive_at(uint32_t bar, uint32_t rank, bool c) {
  asm volatile("{.reg .pred p; .reg .b32 a; setp.ne.u32 p, %2, 0; mapa.shared::cluster.u32 a, %0, %1; @p mbarrier.arrive.shared::cluster.b64 _, [a];}"
    :: "r"(bar), "r"(rank), "r"((uint32_t)c) : "memory");
}
DEVI void p_expect_tx(uint32_t bar, uint32_t bytes, bool c) {
  asm volatile("{.reg .pred p; setp.ne.u32 p, %2, 0; @p mbarrier.arrive.expect_tx.shared::cta.b64 _, [%0], %1;}" :: "r"(bar), "r"(bytes), "r"((uint32_t)c) : "memory");
}
DEVI void p_arrive(uint32_t bar, bool c) { asm volatile("{.reg .pred p; setp.ne.u32 p, %1, 0; @p mbarrier.arrive.shared::cta.b64 _, [%0];}" :: "r"(bar), "r"((uint32_t)c) : "memory"); }
DEVI void tma_store_2d(const CUtensorMap* m, uint32_t src, int c0, int c1) {
  asm volatile("cp.async.bulk.tensor.2d.global.shared::cta.bulk_group [%0, {%2, %3}], [%1];" :: "l"(m), "r"(src), "r"(c0), "r"(c1) : "memory");
}
DEVI void tma_radd_2d(const CUtensorMap* m, uint32_t src, int c0, int c1) {
  asm volatile("cp.reduce.async.bulk.tensor.2d.global.shared::cta.add.bulk_group [%0, {%2, %3}], [%1];" :: "l"(m), "r"(src), "r"(c0), "r"(c1) : "memory");
}
DEVI void bulk_commit() { asm volatile("cp.async.bulk.commit_group;" ::: "memory"); }
template<int N> DEVI void bulk_wait_read() { asm volatile("cp.async.bulk.wait_group.read %0;" :: "n"(N) : "memory"); }
template<int N> DEVI void bulk_wait() { asm volatile("cp.async.bulk.wait_group %0;" :: "n"(N) : "memory"); }
template<int ID, int N> DEVI void nbar_sync() { asm volatile("bar.sync %0, %1;" :: "n"(ID), "n"(N) : "memory"); }
template<int ID, int N> DEVI void nbar_arrive() { asm volatile("bar.arrive %0, %1;" :: "n"(ID), "n"(N) : "memory"); }
DEVI void nbar_sync_r(int id, int n) { asm volatile("bar.sync %0, %1;" :: "r"(id), "r"(n) : "memory"); }
template<int R> DEVI void reg_inc() { asm volatile("setmaxnreg.inc.sync.aligned.u32 %0;" :: "n"(R)); }
template<int R> DEVI void reg_dec() { asm volatile("setmaxnreg.dec.sync.aligned.u32 %0;" :: "n"(R)); }
DEVI void wg_fence() { asm volatile("wgmma.fence.sync.aligned;" ::: "memory"); }
DEVI void wg_commit() { asm volatile("wgmma.commit_group.sync.aligned;" ::: "memory"); }
template<int N> DEVI void wg_wait() { asm volatile("wgmma.wait_group.sync.aligned %0;" :: "n"(N) : "memory"); }
DEVI uint64_t mkdesc(uint32_t addr, uint32_t lbo, uint32_t sbo, uint32_t sw = 1) {
  return ((uint64_t)((addr & 0x3FFFF) >> 4)) | ((uint64_t)(lbo >> 4) << 16) | ((uint64_t)(sbo >> 4) << 32) | ((uint64_t)sw << 62);
}
constexpr uint32_t SMEM_BASE = 1024;
__host__ __device__ constexpr long long CD(uint32_t off, uint32_t lbo, uint32_t sbo, uint32_t sw) {
  return (long long)(((uint64_t)((SMEM_BASE + off) >> 4)) | ((uint64_t)(lbo >> 4) << 16) | ((uint64_t)(sbo >> 4) << 32) | ((uint64_t)sw << 62));
}
DEVI uint32_t pack_bf16(float lo, float hi) { uint32_t r; asm("cvt.rn.bf16x2.f32 %0, %1, %2;" : "=r"(r) : "f"(hi), "f"(lo)); return r; }
DEVI float bf_lo(uint32_t v) { return __uint_as_float(v << 16); }
DEVI float bf_hi(uint32_t v) { return __uint_as_float(v & 0xffff0000u); }
DEVI void ldsm4t(uint32_t addr, uint32_t& r0, uint32_t& r1, uint32_t& r2, uint32_t& r3) {
  asm volatile("ldmatrix.sync.aligned.m8n8.x4.trans.shared.b16 {%0,%1,%2,%3}, [%4];" : "=r"(r0), "=r"(r1), "=r"(r2), "=r"(r3) : "r"(addr) : "memory");
}
DEVI void stsm4(uint32_t addr, uint32_t r0, uint32_t r1, uint32_t r2, uint32_t r3) {
  asm volatile("stmatrix.sync.aligned.m8n8.x4.shared.b16 [%0], {%1,%2,%3,%4};" :: "r"(addr), "r"(r0), "r"(r1), "r"(r2), "r"(r3) : "memory");
}
DEVI uint2 lds64v(uint32_t a) { uint2 v; asm volatile("ld.volatile.shared.v2.u32 {%0,%1}, [%2];" : "=r"(v.x), "=r"(v.y) : "r"(a) : "memory"); return v; }
DEVI uint32_t lds32v(uint32_t a) { uint32_t v; asm volatile("ld.volatile.shared.u32 %0, [%1];" : "=r"(v) : "r"(a) : "memory"); return v; }
DEVI uint4 lds128v(uint32_t a) { uint4 v; asm volatile("ld.volatile.shared.v4.u32 {%0,%1,%2,%3}, [%4];" : "=r"(v.x), "=r"(v.y), "=r"(v.z), "=r"(v.w) : "r"(a) : "memory"); return v; }
DEVI void cp_async16(uint32_t dst, const void* src) { asm volatile("cp.async.cg.shared.global [%0], [%1], 16;" :: "r"(dst), "l"(src) : "memory"); }
DEVI void cp_async_wait() { asm volatile("cp.async.wait_all;" ::: "memory"); }
DEVI void sts32(uint32_t a, uint32_t x) { asm volatile("st.shared.u32 [%0], %1;" :: "r"(a), "r"(x) : "memory"); }
DEVI int lane_id() { int r; asm volatile("mov.u32 %0, %%laneid;" : "=r"(r)); return r; }
DEVI void sts64(uint32_t a, uint32_t x, uint32_t y) { asm volatile("st.shared.v2.u32 [%0], {%1,%2};" :: "r"(a), "r"(x), "r"(y) : "memory"); }
DEVI void sts128(uint32_t a, uint4 v) { asm volatile("st.shared.v4.u32 [%0], {%1,%2,%3,%4};" :: "r"(a), "r"(v.x), "r"(v.y), "r"(v.z), "r"(v.w) : "memory"); }
DEVI void st_async128(uint32_t a, uint32_t x, uint32_t y, uint32_t z, uint32_t w, uint32_t bar) {
  asm volatile("st.async.weak.shared::cluster.mbarrier::complete_tx::bytes.v4.b32 [%0], {%1,%2,%3,%4}, [%5];" :: "r"(a), "r"(x), "r"(y), "r"(z), "r"(w), "r"(bar) : "memory");
}
DEVI void st_async32(uint32_t a, uint32_t x, uint32_t bar) {
  asm volatile("st.async.weak.shared::cluster.mbarrier::complete_tx::bytes.b32 [%0], %1, [%2];" :: "r"(a), "r"(x), "r"(bar) : "memory");
}
DEVI uint4 ldg_rlx128(const void* p) {
  uint4 v;
  asm volatile("ld.relaxed.gpu.global.v4.b32 {%0,%1,%2,%3}, [%4];" : "=r"(v.x), "=r"(v.y), "=r"(v.z), "=r"(v.w) : "l"(p) : "memory");
  return v;
}
DEVI int ldg_rlx32(const void* p) { int v; asm volatile("ld.relaxed.gpu.global.b32 %0, [%1];" : "=r"(v) : "l"(p) : "memory"); return v; }
DEVI int ldg_acq32(const void* p) { int v; asm volatile("ld.acquire.gpu.global.b32 %0, [%1];" : "=r"(v) : "l"(p) : "memory"); return v; }
DEVI void stg_rlx128(void* p, uint32_t x, uint32_t y, uint32_t z, uint32_t w) {
  asm volatile("st.relaxed.gpu.global.v4.b32 [%0], {%1,%2,%3,%4};" :: "l"(p), "r"(x), "r"(y), "r"(z), "r"(w) : "memory");
}
DEVI void stg128(void* p, uint32_t x, uint32_t y, uint32_t z, uint32_t w) {
  asm volatile("st.global.v4.b32 [%0], {%1,%2,%3,%4};" :: "l"(p), "r"(x), "r"(y), "r"(z), "r"(w) : "memory");
}
DEVI uint2 ldg_rlx64(const void* p) { uint2 v; asm volatile("{.reg .b64 a; ld.relaxed.gpu.global.b64 a, [%2]; mov.b64 {%0,%1}, a;}" : "=r"(v.x), "=r"(v.y) : "l"(p) : "memory"); return v; }
DEVI void stg_rlx64(void* p, uint32_t x, uint32_t y) { asm volatile("{.reg .b64 a; mov.b64 a, {%1,%2}; st.relaxed.gpu.global.b64 [%0], a;}" :: "l"(p), "r"(x), "r"(y) : "memory"); }
DEVI void stg_rlx32(void* p, uint32_t x) { asm volatile("st.relaxed.gpu.global.b32 [%0], %1;" :: "l"(p), "r"(x) : "memory"); }
DEVI void flag_add(int* p) { asm volatile("fence.proxy.async.global; red.release.gpu.global.add.s32 [%0], 1;" :: "l"(p) : "memory"); }
DEVI void e_stg_rlx32(void* p, uint32_t x) { asm volatile(ELECT "st.relaxed.gpu.global.b32 [%0], %1;}" :: "l"(p), "r"(x) : "memory"); }
DEVI void e_flag_add(int* p) { asm volatile("fence.proxy.async.global;\n" ELECT "red.release.gpu.global.add.s32 [%0], 1;}" :: "l"(p) : "memory"); }
DEVI int cluster_rank() { int r; asm volatile("mov.u32 %0, %%cluster_ctarank;" : "=r"(r)); return __shfl_sync(0xffffffffu, r, 0); }
DEVI int cluster_id() { int r; asm volatile("mov.u32 %0, %%clusterid.x;" : "=r"(r)); return __shfl_sync(0xffffffffu, r, 0); }
DEVI uint32_t clock32() { uint32_t c; asm volatile("mov.u32 %0, %%clock;" : "=r"(c)); return c; }
DEVI uint32_t gtime() { uint32_t c; asm volatile("mov.u32 %0, %%globaltimer_lo;" : "=r"(c)); return c; }
DEVI void wait_time(uint32_t t) { while (__any_sync(0xffffffffu, t - gtime() - 1 < 4000u)) {} }
DEVI void spin_until(uint32_t t0, int d) { while (__any_sync(0xffffffffu, (int)(clock32() - t0) < d)) {} }
DEVI void pin2(const void* a, const void* b) { asm volatile("{.reg .pred p; setp.eq.u64 p, %0, %1; @p st.volatile.global.u64 [%0], %1;}" :: "l"(a), "l"(b) : "memory"); }
DEVI void pin2(uint32_t a, uint32_t b) { asm volatile("{.reg .pred p; setp.eq.u32 p, %0, %1; @p st.volatile.shared.u32 [%0], %1;}" :: "r"(a), "r"(b) : "memory"); }
DEVI void p_stg_rlx64(void* p, uint32_t x, uint32_t y, bool c) {
  asm volatile("{.reg .pred p; .reg .b64 a; setp.ne.u32 p, %3, 0; mov.b64 a, {%1,%2}; @p st.relaxed.gpu.global.b64 [%0], a;}" :: "l"(p), "r"(x), "r"(y), "r"((uint32_t)c) : "memory");
}
DEVI void pin2(uint64_t a, uint64_t b) { pin2((const void*)a, (const void*)b); }
DEVI uint64_t pair(uint32_t a, uint32_t bar) { return a | (uint64_t)bar << 32; }
DEVI void st_async32(uint64_t q, uint32_t x) { st_async32((uint32_t)q, x, (uint32_t)(q >> 32)); }
DEVI void st_async128(uint64_t q, uint4 v) { st_async128((uint32_t)q, v.x, v.y, v.z, v.w, (uint32_t)(q >> 32)); }
DEVI float ex2(float x) { float r; asm("ex2.approx.ftz.f32 %0, %1;" : "=f"(r) : "f"(x)); return r; }
DEVI float rcp(float x) { float r; asm("rcp.approx.ftz.f32 %0, %1;" : "=f"(r) : "f"(x)); return r; }
DEVI uint32_t xor_or(uint32_t a, uint32_t t, uint32_t acc) { uint32_t r; asm("lop3.b32 %0, %1, %2, %3, 0xbe;" : "=r"(r) : "r"(a), "r"(t), "r"(acc)); return r; }
DEVI void stsm2(uint32_t addr, uint32_t r0, uint32_t r1) {
  asm volatile("stmatrix.sync.aligned.m8n8.x2.shared.b16 [%0], {%1,%2};" :: "r"(addr), "r"(r0), "r"(r1) : "memory");
}
DEVI uint32_t settag(uint32_t v, uint32_t tag) { return (v & ~1u) | tag; }

#define A4(c, o)  c(d[o+0]), c(d[o+1]), c(d[o+2]), c(d[o+3])
#define A8(c, o)  A4(c, o), A4(c, o+4)
#define A16(c, o) A8(c, o), A8(c, o+8)
#define A20(c, o) A16(c, o), A4(c, o+16)
#define A32(c, o) A16(c, o), A16(c, o+16)
#define RL8  "{%0,%1,%2,%3,%4,%5,%6,%7}"
#define RL16 "{%0,%1,%2,%3,%4,%5,%6,%7,%8,%9,%10,%11,%12,%13,%14,%15}"
#define RL20 "{%0,%1,%2,%3,%4,%5,%6,%7,%8,%9,%10,%11,%12,%13,%14,%15,%16,%17,%18,%19}"
#define RL32 "{%0,%1,%2,%3,%4,%5,%6,%7,%8,%9,%10,%11,%12,%13,%14,%15,%16,%17,%18,%19,%20,%21,%22,%23,%24,%25,%26,%27,%28,%29,%30,%31}"
#define RL64 "{%0,%1,%2,%3,%4,%5,%6,%7,%8,%9,%10,%11,%12,%13,%14,%15,%16,%17,%18,%19,%20,%21,%22,%23,%24,%25,%26,%27,%28,%29,%30,%31," \
  "%32,%33,%34,%35,%36,%37,%38,%39,%40,%41,%42,%43,%44,%45,%46,%47,%48,%49,%50,%51,%52,%53,%54,%55,%56,%57,%58,%59,%60,%61,%62,%63}"
#define WG_OP(shape) "wgmma.mma_async.sync.aligned." shape "k16.f32.bf16.bf16 "
#define DEF_WGMMA(N, RL, AL, i0, i1, i2, i3, i4, i5, i6)                                                                         \
  template<int SC, int TB, long long CB> DEVI void rs##N(float* d, const uint32_t* a) {                                          \
    if (SC) asm volatile("{.reg .b64 tb; mov.b64 tb, %" #i4 ";\n" WG_OP("m64n" #N) RL ", {%" #i0 ",%" #i1 ",%" #i2 ",%" #i3 "}, tb, 1, 1, 1, %" #i5 ";}" \
      : AL("+f", 0) : "r"(a[0]), "r"(a[1]), "r"(a[2]), "r"(a[3]), "n"(CB), "n"(TB));                                             \
    else asm volatile("{.reg .b64 tb; mov.b64 tb, %" #i4 ";\n" WG_OP("m64n" #N) RL ", {%" #i0 ",%" #i1 ",%" #i2 ",%" #i3 "}, tb, 0, 1, 1, %" #i5 ";}" \
      : AL("=f", 0) : "r"(a[0]), "r"(a[1]), "r"(a[2]), "r"(a[3]), "n"(CB), "n"(TB));                                             \
  }                                                                                                                              \
  template<int SC, int TA, int TB, long long CA, long long CB> DEVI void ss##N(float* d, uint32_t a) {                           \
    if (SC) asm volatile("{.reg .b64 ta, tb; .reg .b32 lo, hi; add.u32 lo, %" #i0 ", %" #i1 "; mov.b32 hi, %" #i2 "; mov.b64 ta, {lo, hi}; mov.b64 tb, %" #i3 ";\n" \
      WG_OP("m64n" #N) RL ", ta, tb, 1, 1, 1, %" #i4 ", %" #i5 ";}"                                                              \
      : AL("+f", 0) : "r"(a), "n"((int)CA), "n"((int)(CA >> 32)), "n"(CB), "n"(TA), "n"(TB));                                    \
    else asm volatile("{.reg .b64 ta, tb; .reg .b32 lo, hi; add.u32 lo, %" #i0 ", %" #i1 "; mov.b32 hi, %" #i2 "; mov.b64 ta, {lo, hi}; mov.b64 tb, %" #i3 ";\n" \
      WG_OP("m64n" #N) RL ", ta, tb, 0, 1, 1, %" #i4 ", %" #i5 ";}"                                                              \
      : AL("=f", 0) : "r"(a), "n"((int)CA), "n"((int)(CA >> 32)), "n"(CB), "n"(TA), "n"(TB));                                    \
  }
DEF_WGMMA(8, "{%0,%1,%2,%3}", A4, 4, 5, 6, 7, 8, 9, 10)
DEF_WGMMA(16, RL8, A8, 8, 9, 10, 11, 12, 13, 14)
DEF_WGMMA(32, RL16, A16, 16, 17, 18, 19, 20, 21, 22)
DEF_WGMMA(40, RL20, A20, 20, 21, 22, 23, 24, 25, 26)
DEF_WGMMA(64, RL32, A32, 32, 33, 34, 35, 36, 37, 38)
template<int TA> DEVI void wgmma_n128(float* d, uint64_t a, uint64_t b, int scale_d) {
  asm volatile("{.reg .pred p; setp.ne.b32 p, %66, 0;\n" WG_OP("m64n128") RL64 ", %64, %65, p, 1, 1, %67, 1;}"
    : A32("+f", 0), A32("+f", 32) : "l"(a), "l"(b), "r"(scale_d), "n"(TA));
}

namespace rec {
constexpr int KR = 43;
constexpr uint32_t WSZ = (64 - KR) * 2048, STG = KR * 2048;
constexpr uint32_t WS = 0;
constexpr uint32_t RING = 2 * WSZ;
constexpr uint32_t OB = RING + 3 * 8192;
constexpr uint32_t PB = OB + 4096;
constexpr uint32_t WO = RING + 32768;
constexpr uint32_t ATT = WO + 5 * 16384;
constexpr uint32_t AK = ATT + 10240, AV = ATT + 20480;
constexpr uint32_t PAD = ATT + 30720;
constexpr uint32_t BARS = PAD + 128;
constexpr uint32_t B_XE = BARS  , B_FA = BARS + 64  , B_FB = BARS + 88, B_FO = BARS + 96;
constexpr uint32_t B_ME = BARS + 104  , B_WE = BARS + 136  ;
constexpr uint32_t B_XF = BARS + 152  , B_MF = BARS + 216  , B_CP = BARS + 248  , B_WT = BARS + 280  ;
constexpr uint32_t B_AB = BARS + 296, B_OB = BARS + 304, B_ST = BARS + 312  , B_WS = BARS + 328, B_WO = BARS + 336, B_PD = BARS + 344;
constexpr int NBAR = 44;
constexpr uint32_t M0 = BARS + 384;
constexpr uint32_t SMEM = 232448;
constexpr int NB_P = 1, NB_ST = 2, NB_O = 3, NB_W0 = 4, NB_W1 = 5;
__host__ __device__ constexpr int wo_tile(int rank, int g, int i) { return i < 2 ? i * 6 + rank * 2 + g : 13 + rank - g; }
constexpr long long D_W = CD(WS, 16, 1024, 1), D_X = CD(0, 16, 1024, 1), D_M = CD(RING, 128, 256, 0), D_O = CD(OB, 128, 256, 0);
constexpr long long D_WO = CD(WO, 16, 1024, 1), D_QM = CD(ATT, 640, 0, 0), D_QT = CD(ATT + 128, 640, 64, 0), D_K = CD(AK, 640, 128, 0);
constexpr long long D_V = CD(AV, 128, 640, 0), D_P = CD(PB, 128, 768, 0);
struct Maps { CUtensorMap w[3], wo, xd, xs; };
__host__ __device__ constexpr uint32_t xslot(int s) { return s < 3 ? RING + s * 8192 : s < 5 ? WO + (s - 3) * 8192 : s < 7 ? WO + (s + 1) * 8192 : OB; }
__host__ __device__ constexpr bool k_smem(int k) { return k % 3 == 2; }
__host__ __device__ constexpr int k_idx(int k) { return k % 3 == 2 ? k / 3 : k - k / 3; }
__host__ __device__ constexpr int k_of_reg(int i) { return i + (i >> 1); }
__host__ __device__ constexpr int k_of_smem(int i) { return 3 * i + 2; }

#define RPROF(i)
#define RPROF_STEP
#define CPROF(i, v)

template<int K0, int K1> DEVI void seq_mem(float* d, const uint32_t* w, uint32_t dw) {
  if constexpr (K0 < K1) {
    constexpr long long B = D_M + K0 * 32;
    if constexpr (!k_smem(K0)) rs16<K0 != 0, 1, B>(d, w + 4 * k_idx(K0)); else ss16<1, 1, 1, D_W + k_idx(K0) * 128, B>(d, dw);
    seq_mem<K0 + 1, K1>(d, w, dw);
  }
}
template<bool DUAL, int K0, int K1> DEVI void seq_tok(float* d, const uint32_t* w, uint32_t dw) {
  if constexpr (K0 < K1) {
    constexpr long long B = D_X + (DUAL ? xslot((K0 >> 2) & 7) / 16 : xslot(K0 >> 3) / 16 + ((K0 >> 2) & 1) * 256) + (K0 & 3) * 2;
    if constexpr (DUAL) {
      if constexpr (!k_smem(K0)) rs64<K0 != 0, 0, B>(d, w + 4 * k_idx(K0)); else ss64<1, 1, 0, D_W + k_idx(K0) * 128, B>(d, dw);
    } else {
      if constexpr (!k_smem(K0)) rs32<K0 != 0, 0, B>(d, w + 4 * k_idx(K0)); else ss32<1, 1, 0, D_W + k_idx(K0) * 128, B>(d, dw);
    }
    seq_tok<DUAL, K0 + 1, K1>(d, w, dw);
  }
}
template<int T, int K0> DEVI void seq_wo(float* d, uint32_t dw) {
  if constexpr (K0 < 8) { ss16<K0 != 0, 1, 1, D_WO + T * 1024 + K0 * 128, D_O + K0 * 32>(d, dw); seq_wo<T, K0 + 1>(d, dw); }
}
template<long long Q, int K0> DEVI void seq_s(float* d) {
  if constexpr (K0 < 8) { ss40<K0 != 0, 1, 1, Q + K0 * 80, D_K + K0 * 80>(d, 0); seq_s<Q, K0 + 1>(d); }
}
template<bool DUAL, int J> DEVI void load_x(uint32_t sb, const Maps* M, int t) {
  if (DUAL) e_tma_3d_mc(sb + xslot(J & 7), &M->xd, J * 64, (t - LAG) * 32, 0, sb + B_XF + (J & 7) * 8);
  else e_tma_3d_mc(sb + xslot(J & 7), &M->xs, 0, (t < NSEG ? t : t - LAG) * 32, J * 2, sb + B_XF + (J & 7) * 8);
}
struct Ctx { uint32_t sb; const Maps* M; int h, rank, wi; bool lead; uint32_t par; };
#define PFN 2
#define XD 2
template<bool DUAL, int J> DEVI void tok_release(const Ctx& c, int t, int& budget) {
  constexpr int NC = DUAL ? 16 : 8, S = J & 7;
  if constexpr (J + 8 < NC) {
    p_arrive_at(c.sb + B_XE + S * 8, J % 3, c.lead);
    p_expect_tx(c.sb + B_XF + S * 8, 8192, c.lead && c.wi == 0);
  } else if constexpr (S == 4 || S == 6) {
    constexpr int g = S == 4;
    p_arrive(c.sb + B_WE + g * 8, c.lead);
    if (c.wi == g * 4 + 2) {
      mbar_wait(c.sb + B_WE + g * 8, t & 1, budget);
      e_expect_tx(c.sb + B_WT + g * 8, 16384);
      e_tma_2d(c.sb + WO + (1 - g) * 49152, &c.M->wo, wo_tile(c.rank, g, 0) * 64, c.h * DH, c.sb + B_WT + g * 8);
    }
  } else if constexpr (S < 3 || S == 7) p_arrive(c.sb + B_ME + (S & 3) * 8, c.lead);
  if constexpr (J == XD - 1) {
    if (c.rank == 1 && c.wi == 5) { mbar_wait(c.sb + B_FO, t & 1, budget); load_x<DUAL, 7>(c.sb, c.M, t); }
  } else if constexpr (J >= XD && J - XD + 8 < NC) {
    constexpr int I = J - XD;
    if (c.rank == I % 3 && c.wi == (I & 1) * 4 + 1) { mbar_wait(c.sb + B_XE + I * 8, (t - LAG) & 1, budget); load_x<DUAL, I + 8>(c.sb, c.M, t); }
  }
}
template<bool DUAL, int J> DEVI void tok_pass(float* d, const uint32_t* w, uint32_t dw, Ctx& c, int t, int& budget) {
  constexpr int NC = DUAL ? 16 : 8, KC = 64 / NC;
  if constexpr (J < NC) {
    mbar_wait(c.sb + B_XF + (J & 7) * 8, c.par ^ (J >> 3), budget);
    wg_fence();
    seq_tok<DUAL, J * KC, (J + 1) * KC>(d, w, dw);
    wg_commit();
    if constexpr (J > 0) { wg_wait<1>(); tok_release<DUAL, J - 1>(c, t, budget); }
    tok_pass<DUAL, J + 1>(d, w, dw, c, t, budget);
  } else {
    wg_wait<0>();
    tok_release<DUAL, NC - 1>(c, t, budget);
    if (!DUAL) c.par ^= 1;
  }
}
DEVI void pack_tok(uint32_t* e, const float* d) {
#pragma unroll
  for (int i = 0; i < 8; i++) e[i] = pack_bf16(d[4 * (i & 3) + 2 * (i >> 2)], d[4 * (i & 3) + 2 * (i >> 2) + 1]);
}
DEVI void push_tok(const uint32_t* e, uint32_t sb, uint32_t o, int r) {
  const uint32_t b = mapa(sb, r);
  st_async128(b + o, e[0], e[1], e[2], e[3], b + B_AB);
}
DEVI uint32_t h1_tag(int seg) { return ((seg >> 1) & 1) ^ 1; }
DEVI void put_part(char* p1, char* p2, const float* c, int t) {
  p_stg_rlx64(p1, settag(pack_bf16(c[0], c[1]), h1_tag(t)), pack_bf16(c[2], c[3]), t < NSEG);
  p_stg_rlx64(p2, settag(pack_bf16(c[4], c[5]), h1_tag(t - LAG)), pack_bf16(c[6], c[7]), t >= LAG);
}

DEVI void rec_math(const uint32_t sb, const int wi, const Maps& M) {
  const int h = cluster_id(), rank = cluster_rank();
  const int warp = wi & 3, wg = wi >> 2;
  const bool lead = (threadIdx.x & 127) == 0;
  int budget = SPIN_BUDGET;
  uint32_t w[4 * KR], e[16];
  Ctx cx{sb, &M, h, rank, wi, lead, 0};
  {
    const int lane = lane_id();
    const uint32_t a = sb + wg * STG + ((lane & 7) + (lane >> 4) * 8) * 128 + (((warp * 2 + ((lane >> 3) & 1)) ^ (lane & 7)) << 4);
    mbar_wait(sb + B_ST + wg * 8, 0, budget);
#pragma unroll
    for (int k = 0; k < KR; k++) ldsm4t(a + k * 2048, w[4*k], w[4*k+1], w[4*k+2], w[4*k+3]);
    nbar_arrive<NB_ST, 384>();
    nbar_sync_r(NB_W0 + wg, 128);
    for (int i = 0; i < 5; i++) p_arrive_at(sb + B_FA + i * 8, i == 4, lead);
    mbar_wait(sb + B_WS, 0, budget);
  }
#pragma unroll 1
  for (int t = -1; t < NSTEP; t++) {
    const uint32_t dw = wg * (WSZ >> 4);
    RPROF_STEP;
    if (t >= 0) {
      const int lane = lane_id();
      RPROF(0 + wg * 12);
      {
        float m[8];
        const uint32_t ao = ATT + rank * 10240 + wi * 1280, to = ao + 128 + (lane & 3) * 128 + (lane >> 2) * 16;
        const bool dual = t >= LAG && t < NSEG;
        mbar_wait(sb + B_MF, t & 1, budget);
        RPROF(1 + wg * 12);
        wg_fence(); seq_mem<0, 8>(m, w, dw);
        push_tok(e, sb, to, t >= NSEG);
        seq_mem<8, 16>(m, w, dw); wg_commit();
        push_tok(e + 4, sb, to + 640, t >= NSEG);
        mbar_wait(sb + B_MF + 8, t & 1, budget);
        wg_fence(); seq_mem<16, 32>(m, w, dw); wg_commit();
        if (dual) push_tok(e + 8, sb, to, 1);
        wg_wait<1>(); p_arrive_at(sb + B_FA, 0, lead);
        mbar_wait(sb + B_MF + 16, t & 1, budget);
        wg_fence(); seq_mem<32, 48>(m, w, dw); wg_commit();
        if (dual) push_tok(e + 12, sb, to + 640, 1);
        wg_wait<1>(); p_arrive_at(sb + B_FA + 8, 0, lead);
        const uint32_t r0 = mapa(sb, t >= NSEG), r1 = mapa(sb, 1), m0 = r0 + ao + lane * 4, m1 = r1 + ao + lane * 4;
        uint64_t q0 = pair(m0, r0 + B_AB), q1 = pair(m0 + 640, r0 + B_AB), q2 = pair(m1, r1 + B_AB), q3 = pair(m1 + 640, r1 + B_AB);
        pin2(q0, q1); pin2(q2, q3);
        mbar_wait(sb + B_MF + 24, t & 1, budget);
        wg_fence(); seq_mem<48, 64>(m, w, dw); wg_commit();
        wg_wait<1>(); p_arrive_at(sb + B_FA + 16, 0, lead);
        wg_wait<0>();
        const uint32_t a0 = pack_bf16(m[0], m[1]), a1 = pack_bf16(m[2], m[3]), a2 = pack_bf16(m[4], m[5]), a3 = pack_bf16(m[6], m[7]);
        st_async32(q0, t < NSEG ? a0 : a2); st_async32(q1, t < NSEG ? a1 : a3);
        if (dual) { st_async32(q2, a2); st_async32(q3, a3); }
        p_arrive(sb + B_PD, threadIdx.x == 0);
      }
      RPROF(2 + wg * 12);
      if (t == 0) mbar_wait(sb + B_WO, 0, budget);
      mbar_wait(sb + B_WT + wg * 8, t & 1, budget);
      const int seg = t - rank * LAG;
      constexpr float SC = 0.08838834764831845f * 1.4426950408889634f;
      if (rank < 2 && (unsigned)seg < (unsigned)NSEG) {
        float s[32];
        if (wg) {
          const uint32_t pw = sb + PB + lane * 4, o = OB + (lane >> 4) * 2048 + warp * 512 + rank * 256 + (lane & 15) * 16;
          const uint32_t r0 = mapa(sb, 0), r1 = mapa(sb, 1), r2 = mapa(sb, 2);
          uint64_t q0 = pair(r0 + o, r0 + B_OB), q1 = pair(r1 + o, r1 + B_OB), q2 = pair(r2 + o, r2 + B_OB);
          uint32_t one[4];
#pragma unroll
          for (int i = 0; i < 4; i++) one[i] = 0x3F803F80u + (pw >> 31);
          pin2(q0, q1); pin2(q2, (uint64_t)pw);
          mbar_wait_cluster(sb + B_AB, seg & 1, budget);
          fence_proxy_async();
          RPROF(3 + 12);
          wg_fence(); seq_s<D_QM, 0>(s); wg_commit();
          nbar_arrive<NB_P, 256>();
          if (warp == 1) sts32(pw + 640, 0);
          wg_wait<0>();
          float mx = fmaxf(fmaxf(fmaxf(s[0], s[1]), fmaxf(s[4], s[5])), fmaxf(fmaxf(fmaxf(s[8], s[9]), fmaxf(s[12], s[13])), fmaxf(s[16], s[17])));
          const float x1 = __shfl_xor_sync(0xffffffffu, mx, 1), x2 = __shfl_xor_sync(0xffffffffu, mx, 2), x3 = __shfl_xor_sync(0xffffffffu, mx, 3);
          const float u = (warp & 2) ? ((warp & 1) ? s[16] : s[12]) : ((warp & 1) ? s[8] : s[4]);
          const float v = (warp & 2) ? ((warp & 1) ? s[17] : s[13]) : ((warp & 1) ? s[9] : s[5]);
          const float ms = -SC * fmaxf(fmaxf(mx, x1), fmaxf(x2, x3));
          sts32(pw + 128 + warp * 128, pack_bf16(ex2(fmaf(u, SC, ms)), ex2(fmaf(v, SC, ms))));
          if (warp == 0) sts32(pw, pack_bf16(ex2(fmaf(s[0], SC, ms)), ex2(fmaf(s[1], SC, ms))));
          fence_proxy_async();
          nbar_sync<NB_W1, 128>();
          RPROF(4 + 12);
          wg_fence();
          rs8<0, 0, D_P>(s + 8, one); rs8<1, 0, D_P + 16>(s + 8, one); rs8<1, 0, D_P + 32>(s + 8, one);
          wg_commit();
          ss8<0, 0, 0, D_V, D_P>(s, 0); ss8<0, 0, 0, D_V + 320, D_P>(s + 4, 0);
          ss8<1, 0, 0, D_V + 16, D_P + 16>(s, 0); ss8<1, 0, 0, D_V + 336, D_P + 16>(s + 4, 0);
          ss8<1, 0, 0, D_V + 32, D_P + 32>(s, 0); ss8<1, 0, 0, D_V + 352, D_P + 32>(s + 4, 0);
          wg_commit();
          wg_wait<1>();
          const float i0 = rcp(s[8]), i1 = rcp(s[9]);
          wg_wait<0>();
          stsm4(sb + o, pack_bf16(s[0] * i0, s[1] * i1), pack_bf16(s[2] * i0, s[3] * i1), pack_bf16(s[4] * i0, s[5] * i1), pack_bf16(s[6] * i0, s[7] * i1));
          __syncwarp();
          const uint4 z = lds128v(sb + o);
          if (t < NSTEP - 1) { st_async128(q2, z); st_async128(rank ? q0 : q1, z); st_async128(rank ? q1 : q0, z); }
        } else {
          const int g = lane >> 2, lim = 8 * (g >> 1) + (g & 1) + 2 * warp - 8 * (lane & 3);
          const uint32_t pw = sb + PB + 768 + warp * 768 + lane * 16;
          char* const og = (char*)(g_ot + rank * O_LAYER) + (size_t)(h * DH + warp * 16 + (lane >> 2)) * (SEQ * 2) + seg * 64 + (lane & 3) * 16;
          pin2(pw, lim); pin2(og, nullptr);
          mbar_wait_cluster(sb + B_AB, seg & 1, budget);
          fence_proxy_async();
          nbar_sync<NB_P, 256>();
          RPROF(3);
          wg_fence(); seq_s<D_QT, 0>(s); wg_commit();
          wg_wait<0>();
#pragma unroll
          for (int i = 0; i < 8; i++) { float& v = s[4 + 4 * (i >> 1) + (i & 1)]; v = i <= lim ? v : -INFINITY; }
          float mx = fmaxf(fmaxf(fmaxf(s[0], s[1]), fmaxf(s[4], s[5])), fmaxf(fmaxf(fmaxf(s[8], s[9]), fmaxf(s[12], s[13])), fmaxf(s[16], s[17])));
          const float x1 = __shfl_xor_sync(0xffffffffu, mx, 1), x2 = __shfl_xor_sync(0xffffffffu, mx, 2), x3 = __shfl_xor_sync(0xffffffffu, mx, 3);
          const float ms = -SC * fmaxf(fmaxf(mx, x1), fmaxf(x2, x3));
#pragma unroll
          for (int i = 0; i < 10; i++) { float& v = s[4 * (i >> 1) + (i & 1)]; v = ex2(fmaf(v, SC, ms)); }
          const float sum = (((s[0] + s[1]) + (s[4] + s[5])) + ((s[8] + s[9]) + (s[12] + s[13]))) + (s[16] + s[17]);
          const float y1 = __shfl_xor_sync(0xffffffffu, sum, 1), y2 = __shfl_xor_sync(0xffffffffu, sum, 2), y3 = __shfl_xor_sync(0xffffffffu, sum, 3);
          const float inv = rcp((sum + y1) + (y2 + y3));
          stsm4(pw, pack_bf16(s[0] * inv, s[1] * inv), pack_bf16(s[4] * inv, s[5] * inv), pack_bf16(s[8] * inv, s[9] * inv), pack_bf16(s[12] * inv, s[13] * inv));
          stsm2(pw + 512, pack_bf16(s[16] * inv, s[17] * inv), 0);
          fence_proxy_async();
          nbar_sync<NB_W0, 128>();
          RPROF(4);
          wg_fence();
          ss32<0, 0, 0, D_V, D_P + 48>(s, 0); ss32<0, 0, 0, D_V + 320, D_P + 48>(s + 16, 0);
          ss32<1, 0, 0, D_V + 16, D_P + 64>(s, 0); ss32<1, 0, 0, D_V + 336, D_P + 64>(s + 16, 0);
          ss32<1, 0, 0, D_V + 32, D_P + 80>(s, 0); ss32<1, 0, 0, D_V + 352, D_P + 80>(s + 16, 0);
          wg_commit();
          wg_wait<0>();
#pragma unroll
          for (int i = 0; i < 4; i++) {
            const float* d = s + (i >> 1) * 16 + (i & 1) * 2;
            stg128(og + ((i >> 1) * 64 + (i & 1) * 8) * (SEQ * 2), pack_bf16(d[0], d[1]), pack_bf16(d[4], d[5]), pack_bf16(d[8], d[9]), pack_bf16(d[12], d[13]));
          }
          nbar_arrive<NB_O, 160>();
        }
      }
      RPROF(5 + wg * 12);
      char* const p = (char*)g_h1 + ((wo_tile(rank, wg, 0) * 4 + warp) * 4 + (lane >> 3)) * 2048 + h * 64 + (lane & 7) * 8;
      const bool three = wg == 1 || rank == 2;
      if (t < NSTEP - 1) {
        float c[24];
        const uint32_t dt = wg ? 0 : 3072;
        const int o3 = (wo_tile(rank, wg, 2) - wo_tile(rank, wg, 0)) * 32768;
        char* const p1 = p + (t & 1) * sizeof(g_h1[0]);
        char* const p2 = p + (2 + ((t - LAG) & 1)) * sizeof(g_h1[0]);
        char* const p3 = p1 + o3;
        char* const p4 = p2 + o3;
        pin2(p1, p2); pin2(p3, p4);
        mbar_wait_cluster(sb + B_OB, t & 1, budget);
        fence_proxy_async();
        RPROF(6 + wg * 12);
        wg_fence(); seq_wo<0, 0>(c, dt); wg_commit(); seq_wo<1, 0>(c + 8, dt); wg_commit();
        wg_wait<1>(); put_part(p1, p2, c, t); p_arrive_at(sb + B_FB, 0, lead);
        if (three) {
          wg_fence(); seq_wo<2, 0>(c + 16, dt); wg_commit();
          wg_wait<1>(); put_part(p1 + 6 * 32768, p2 + 6 * 32768, c + 8, t);
          wg_wait<0>(); put_part(p3, p4, c + 16, t);
        } else { wg_wait<0>(); put_part(p1 + 6 * 32768, p2 + 6 * 32768, c + 8, t); }
        p_arrive_at(sb + B_FO, 1, lead);
      } else {
        for (int i = 0; i < (three ? 3 : 2); i++) stg_rlx64(p + 3 * sizeof(g_h1[0]) + (wo_tile(rank, wg, i) - wo_tile(rank, wg, 0)) * 32768, 0, 0);
      }
      RPROF(7 + wg * 12);
    }
    const int n = t + 1;
    if (n >= LAG && n < NSEG) {
      float d[32];
      tok_pass<true, 0>(d, w, dw, cx, n, budget);
      pack_tok(e, d + 16); pack_tok(e + 8, d);
    } else {
      float d[16];
      if (n == NSTEP) break;
      tok_pass<false, 0>(d, w, dw, cx, n, budget);
      pack_tok(e, d);
#pragma unroll
      for (int i = 8; i < 16; i++) e[i] = 0;
    }
    RPROF(8 + wg * 12);
  }
}

DEVI void wait_xa(const int* p, int& budget) {
  while (__any_sync(0xffffffffu, ldg_acq32(p) < 64) && --budget > 0) {}
  fence_proxy_global();
}
template<bool DUAL> DEVI void first_loads(uint32_t sb, const Maps* M, int n, int h, int& budget) {
#pragma unroll
  for (int i = 0; i < PFN; i++) {
    if (DUAL) e_prefetch_3d(&M->xd, ((h + i * (16 / PFN)) & 15) * 64, (n - LAG) * 32, 0);
    else e_prefetch_3d(&M->xs, 0, (n < NSEG ? n : n - LAG) * 32, ((h + i * (8 / PFN)) & 7) * 2);
  }
  mbar_wait(sb + B_FA, n & 1, budget); load_x<DUAL, 0>(sb, M, n);
  mbar_wait(sb + B_FA + 8, n & 1, budget); load_x<DUAL, 1>(sb, M, n);
  mbar_wait(sb + B_FA + 16, n & 1, budget); load_x<DUAL, 2>(sb, M, n);
}
template<bool DUAL> DEVI void lent_loads(uint32_t sb, const Maps* M, int n, int& budget) {
  mbar_wait(sb + B_FB, n & 1, budget);
  load_x<DUAL, 3>(sb, M, n); load_x<DUAL, 4>(sb, M, n); load_x<DUAL, 5>(sb, M, n); load_x<DUAL, 6>(sb, M, n);
}
DEVI void rec_comm(const uint32_t sb, const int warp, const Maps& M, const bf16* __restrict__ mem0) {
  const int lane = threadIdx.x & 31, h = cluster_id(), rank = cluster_rank();
  int budget = SPIN_BUDGET;
  const bool two = warp == 3 || (rank == 2 && warp == 2);
  const int ntask = two ? 2 : 1, qi = two ? (warp == 3 ? rank : 3) : rank * 3 + warp;
  const int task0 = two ? h * 2 + (qi >> 1) : 64 + h * 4 + (qi >> 1);
  auto h2_word = [&](int i, int ln) {
    const int task = task0 + i * 192;
    return (char*)g_h2 + (task >> 2) * 512 + ((qi ^ i) & 1) * 256 + (task & 3) * 32 + (ln & 8) * 16 + (ln & 7) * 4;
  };
  auto first_x = [&](int t) {
    const int n = t + 1;
    p_expect_tx(sb + B_XF + (lane_id() & 7) * 8, 8192, lane_id() < 8);
    if (rank == 0) {
      if (n < NSEG && (n & 3) == 0) wait_xa(&g_xa[0][n >> 2], budget);
      if (n >= LAG && ((n - LAG) & 3) == 0) wait_xa(&g_xa[1][(n - LAG) >> 2], budget);
      if (n >= LAG && n < NSEG) first_loads<true>(sb, &M, n, h, budget); else first_loads<false>(sb, &M, n, h, budget);
    }
  };
  {
    const int task = task0 + (lane >> 4) * 192, L = (task & 3) * 8 + (lane & 7);
    if ((lane >> 4) < ntask) {
      const bf16* p = mem0 + (L & 3) * 2 * DM + (task >> 2) * 16 + (L >> 2) + (lane & 8);
      uint32_t m0 = (uint32_t)__bfloat16_as_ushort(p[0]) | (uint32_t)__bfloat16_as_ushort(p[DM]) << 16;
      m0 = m0 ? m0 : 0x8000u;
      stg_rlx32(h2_word(lane >> 4, lane), m0);
      sts32(sb + M0 + warp * 128 + lane * 4, m0);
    }
    __syncwarp();
    nbar_sync<NB_ST, 384>();
    if (warp == 2) {
      e_expect_tx(sb + B_WS, 2 * WSZ);
#pragma unroll 1
      for (int i = 0; i < 2 * (64 - KR); i++) e_tma_2d(sb + WS + (i & 1) * WSZ + (i >> 1) * 2048, &M.w[rank], h * DH + (i & 1) * 64, k_of_smem(i >> 1) * 16, sb + B_WS);
      const int nt = rank == 2 ? 6 : 5;
      e_expect_tx(sb + B_WO, (nt - 2) * 16384);
#pragma unroll 1
      for (int i = 1; i < nt; i++) if (i != 3) e_tma_2d(sb + WO + i * 16384, &M.wo, wo_tile(rank, 1 - i / 3, i % 3) * 64, h * DH, sb + B_WO);
    }
    if (warp == 3) { first_x(-1); if (rank == 0) lent_loads<false>(sb, &M, 0, budget); }
  }
  uint32_t t0 = gtime() - 4000, cpp = 0;
  const uint32_t cp = sb + B_CP + warp * 8;
#pragma unroll 1
  for (int t = 0;; t++) {
    const int n = t + 1, seg = t - rank * LAG;
    RPROF_STEP;
    const bool att = rank < 2 && (unsigned)seg < (unsigned)NSEG;
    if (warp == 3) {
      if (att) e_expect_tx(sb + B_AB, 30720);
      if (n < NSTEP) e_expect_tx(sb + B_OB, t < NSEG && t >= LAG ? 4096 : 2048);
    }
    {
      const uint32_t dst = sb + RING + warp * 8192;
      mbar_wait(sb + B_ME + warp * 8, t & 1, budget);
      wait_time(t0 + TP(1) + warp * TP(4));
      const int lane = lane_id();
      RPROF(24); CPROF(0, gtime());
      int tries = 0;
      while (true) {
        tries++;
        e_expect_tx(cp, 8192);
        e_bulk_g2s(dst, (const char*)g_h2[t & 3] + warp * 8192, 8192, cp);
        mbar_wait(cp, cpp, budget); cpp ^= 1;
        uint32_t mn = 0xffffffffu;
#pragma unroll
        for (int i = 0; i < 8; i++) mn = min(mn, lds32v(dst + i * 1024 + lane * 32 + (lane >> 2) * 4));
        if (!__any_sync(0xffffffffu, mn == 0) || --budget < 0) break;
      }
      e_arrive(sb + B_MF + warp * 8);
      RPROF(25); CPROF(1, gtime()); CPROF(2, tries);
    }
    {
      const int ln = lane_id(), i = ln >> 4;
      char* const w = h2_word(i, ln);
      if (i < ntask) {
        stg_rlx32(w + ((t + 3) & 3) * sizeof(g_h2[0]), 0);
        if (n < NSTEP && (((qi ^ i) & 1) ? t < LAG : t >= NSEG)) stg_rlx32(w + (n & 3) * sizeof(g_h2[0]), lds32v(sb + M0 + warp * 128 + ln * 4));
      }
      __syncwarp();
    }
    if (n < NSTEP) {
      const uint32_t tag = (n >> 1) & 31;
      if (warp == 3) first_x(t);
      mbar_wait(sb + B_PD, t & 1, budget);
      t0 = clock32();
      if (warp == 0 && rank == (t >= NSEG)) { mbar_wait(sb + B_AB, seg & 1, budget); e_stg_rlx32(&g_ts[t & 1][h * TSS], (gtime() & ~31u) | tag); }
      spin_until(t0, TSD);
      uint32_t v;
      do { v = ldg_rlx32(&g_ts[t & 1][lane_id() * TSS]); } while (__any_sync(0xffffffffu, (v & 31) != tag) && --budget > 0);
      const uint32_t now = __shfl_sync(0xffffffffu, v, 0);
      t0 = now + __reduce_max_sync(0xffffffffu, (int)(v - now));
      if (warp == 3) mbar_wait(sb + B_OB, t & 1, budget);
      if (warp == 3 && rank == 0) { if (n >= LAG && n < NSEG) lent_loads<true>(sb, &M, n, budget); else lent_loads<false>(sb, &M, n, budget); }
    }
    if (n < NSTEP) {
      RPROF(26); CPROF(3, t0);
#pragma unroll 1
      for (int i = 0; i < ntask; i++) {
        const int layer = (qi ^ i) & 1, sg = t - layer * LAG, task = task0 + i * 192;
        if ((unsigned)sg >= (unsigned)NSEG) continue;
        const uint32_t tag = h1_tag(sg);
        const int ln = lane_id();
        const char* const src = (const char*)g_h1[layer * 2 + (sg & 1)] + task * 2048 + ln * 8;
        char* const dst = h2_word(i, ln) + (n & 3) * sizeof(g_h2[0]);
        uint2 v[8];
        pin2(src, dst);
        wait_time(t0 + TP(0) + (task < 96 ? 0 : task < 192 ? TP(3) : 2 * TP(3)));
        int tries = 0;
        float a[4];
        while (true) {
          tries++;
#pragma unroll
          for (int k = 0; k < 8; k++) v[k] = ldg_rlx64(src + k * 256);
          uint32_t bad = 0;
#pragma unroll
          for (int k = 0; k < 8; k++) {
            bad = xor_or(v[k].x, tag, bad);
            a[0] = k ? a[0] + bf_lo(v[k].x) : bf_lo(v[k].x); a[1] = k ? a[1] + bf_hi(v[k].x) : bf_hi(v[k].x);
            a[2] = k ? a[2] + bf_lo(v[k].y) : bf_lo(v[k].y); a[3] = k ? a[3] + bf_hi(v[k].y) : bf_hi(v[k].y);
          }
#pragma unroll
        for (int k = 0; k < 2; k++) {
          const float keep = (ln & 8) ? a[2+k] : a[k], send = (ln & 8) ? a[k] : a[2+k];
          a[k] = keep + __shfl_xor_sync(0xffffffffu, send, 8);
        }
#pragma unroll
        for (int k = 0; k < 2; k++) a[k] += __shfl_xor_sync(0xffffffffu, a[k], 16);
          if (!__any_sync(0xffffffffu, bad & 1) || --budget < 0) break;
        }
        const uint32_t out = pack_bf16(a[0], a[1]);
        if (ln < 16) stg_rlx32(dst, out ? out : 0x8000u);
        __syncwarp();
        if (i == 0) { RPROF(28); CPROF(6, gtime()); CPROF(4, gtime()); CPROF(5, tries); } else CPROF(7, gtime());
      }
    }
    if (warp == 1 && att) { nbar_sync<NB_O, 160>(); e_flag_add(&g_dep[E_O1 + rank * 16 + (seg >> 2)]); }
    if (n == NSTEP) break;
  }
  if (h == 0 && rank == 0 && warp < 2) g_xa[warp][lane_id()] = 0;
}
}

__global__ void __cluster_dims__(3, 1, 1) __launch_bounds__(384, 1)
rec_kernel(const __grid_constant__ rec::Maps M, const bf16* __restrict__ mem0) {
  using namespace rec;
  extern __shared__ __align__(1024) uint8_t smem[];
  const uint32_t sb = __shfl_sync(0xffffffffu, smem_u32(smem), 0);
  const int tid = threadIdx.x, wi = __shfl_sync(0xffffffffu, tid >> 5, 0);
  if ((sb & 0x3FFFF) != SMEM_BASE) __trap();
  if (wi == 0) {
    const int h = cluster_id(), rank = cluster_rank();
    for (int i = tid; i < NBAR; i += 32) mbar_init(sb + BARS + i * 8, i < 13 ? 6 : i < 19 ? 2 : 1);
    ((uint32_t*)(smem + PAD))[tid] = 0;
    fence_mbar_init(); fence_proxy_async();
    __syncwarp();
    e_expect_tx(sb + B_ST, STG); e_expect_tx(sb + B_ST + 8, STG);
    for (int i = 0; i < 2 * KR; i++) e_tma_2d(sb + (i & 1) * STG + (i >> 1) * 2048, &M.w[rank], h * DH + (i & 1) * 64, k_of_reg(i >> 1) * 16, sb + B_ST + (i & 1) * 8);
    for (int i = 0; i < 2 * (64 - KR); i++) e_prefetch_2d(&M.w[rank], h * DH + (i & 1) * 64, k_of_smem(i >> 1) * 16);
    for (int i = 0; i < (rank == 2 ? 6 : 5); i++) e_prefetch_2d(&M.wo, wo_tile(rank, 1 - i / 3, i % 3) * 64, h * DH);
  } else if (wi == 1) {
    if (blockIdx.x < NEV / 32) { g_dep[blockIdx.x * 32 + (tid & 31)] = 0; g_claim[blockIdx.x * 32 + (tid & 31)] = 0; __threadfence(); }
    __syncwarp();
    asm volatile("griddepcontrol.launch_dependents;" ::: "memory");
  }
  cluster_arrive(); cluster_wait();
  if (wi < 8) { reg_inc<232>(); rec_math(sb, wi, M); cluster_arrive(); cluster_wait(); }
  else { reg_dec<40>(); rec_comm(sb, wi & 3, M, mem0); cluster_arrive(); cluster_wait(); }
}

namespace gm {
struct Maps { CUtensorMap ot, wo, xn, wg, wu, hl, hs, wd, out; };
constexpr int STAGES = 6, STAGE = 32768;
constexpr uint32_t SO = STAGES * STAGE, BARS = SO + 32768;
constexpr uint32_t B_FULL = BARS, B_EMPTY = BARS + 48, B_TF = BARS + 96, B_TE = BARS + 112, B_ORD = BARS + 128, B_PM = BARS + 144;
constexpr uint32_t MAIL = BARS + 160, PMAIL = BARS + 176;
constexpr uint32_t SMEM = BARS + 256;
constexpr int END = -1;
struct Tile {
  bool isO, isG, l2; int blk, col, k0, n;
  DEVI Tile(int task, int rank) {
    const int e = task >> 8, id = task & 255;
    const bool isD = e < E_G1 || e >= E_D2;
    isO = e >= E_O1 && e < E_G2; isG = !isD && !isO; l2 = e >= E_O2;
    blk = isG && l2 ? (e & 15) * 2 + rank : isD && !l2 ? e >> 1 : e & 15;
    col = isG ? (l2 ? id : id * 2 + rank) : (id & 3) * 2 + rank;
    k0 = isO ? (id >> 2) * 2048 : isG ? 0 : ((l2 ? e >> 4 : e) & 1) * 1792;
    n = isO ? 32 : isG ? 16 : 28;
  }
};

DEVI float geglu(float g, float u) {
  const float z = g * (0.7978845608028654f + 0.035677408136300125f * g * g);
  float t; asm("tanh.approx.f32 %0, %1;" : "=f"(t) : "f"(z));
  const float hg = 0.5f * g;
  return fmaf(hg, t, hg) * u;
}
struct Sched {
  int need, size;
  bool filler;
  uint4 dep, cl;
  DEVI void init(int lane) {
    const int e = lane * 4;
    const bool d = e < E_G1 || e >= E_D2, o = e >= E_O1 && e < E_G2;
    need = d ? 28 : e < E_O1 ? 64 : 128;
    size = d ? 4 : o ? 8 : e < E_O1 ? 28 : e < E_G2 + 8 ? 56 : 0;
    filler = (int)blockIdx.x < TP(5);
  }
  DEVI void scan(int lane) { cl = ldg_rlx128(g_claim + lane * 4); dep = ldg_rlx128(g_dep + lane * 4); }
  DEVI int next(int lane, int& budget) {
    while (--budget > 0) {
      int av[4], open = 0;
#pragma unroll
      for (int i = 0; i < 4; i++) { const int r = max(size - (int)(&cl.x)[i], 0); open |= r; av[i] = ((int)(&dep.x)[i] >= need ? r : 0) + (i ? av[i - 1] : 0); }
      const uint32_t mo = __ballot_sync(0xffffffffu, open);
      if (!mo) break;
      if (!filler && (mo & TP(6)) && lane >= E_O2 / 4) av[3] = 0;
      int inc = av[3], pos = 0;
      while (true) {
        const uint32_t m = __ballot_sync(0xffffffffu, inc > pos && av[3]);
        if (!m) break;
        const int l = __ffs(m) - 1, rel = pos - (inc - av[3]), i = (rel >= av[0]) + (rel >= av[1]) + (rel >= av[2]);
        int r = 0;
        if (lane == l) {
          const int tk = atomicAdd(g_claim + lane * 4 + i, 1);
          r = tk < size ? (lane * 4 + i) << 8 | tk : -1 - (inc - av[3] + (i == 0 ? av[0] : i == 1 ? av[1] : i == 2 ? av[2] : av[3]) + tk - size);
        }
        r = __shfl_sync(0xffffffffu, r, l);
        if (r >= 0) { fence_proxy_global(); return r; }
        if (pos == 0) {
#pragma unroll
          for (int o = 1; o < 32; o <<= 1) { const int v = __shfl_up_sync(0xffffffffu, inc, o); if (lane >= o) inc += v; }
        }
        pos = -1 - r;
      }
      if (pos == 0) __nanosleep(TP(7));
      scan(lane);
    }
    return END;
  }
};

DEVI void producer(const uint32_t sb, const Maps& M) {
  const int lane = threadIdx.x & 31, rank = cluster_rank();
  int budget = SPIN_BUDGET, s = 0, ph = 0;
  Sched sc; sc.init(lane);
  if (rank == 0) sc.scan(lane);
#pragma unroll 1
  for (int i = 0;; i++) {
    int task;
    if (rank == 0) {
      task = sc.next(lane, budget);
      const uint32_t r = mapa(sb, 1);
      if (lane == 0) st_async32(r + PMAIL + (i & 1) * 4, task, r + B_PM + (i & 1) * 8);
      __syncwarp();
    } else {
      e_expect_tx(sb + B_PM + (i & 1) * 8, 4);
      mbar_wait_cluster(sb + B_PM + (i & 1) * 8, (i >> 1) & 1, budget);
      task = budget < 0 ? END : __shfl_sync(0xffffffffu, (int)lds32v(sb + PMAIL + (i & 1) * 4), 0);
      fence_proxy_global();
    }
    for (int z = 0; z < (task == END ? 2 : 1); z++) {
      const int g = (i + z) & 1;
      mbar_wait(sb + B_TE + g * 8, (((i + z) >> 1) & 1) ^ 1, budget);
      if (lane == 0) { sts64(sb + MAIL + g * 8, task, s | ph << 8); mbar_arrive(sb + B_TF + g * 8); }
      __syncwarp();
    }
    if (task == END) break;
    const Tile T(task, rank);
    const bool shareB = T.isG && T.l2;
    const CUtensorMap* mA = T.isO ? &M.ot : T.isG ? &M.xn : &M.hl;
    const CUtensorMap* mB0 = T.isO ? &M.wo : T.isG ? &M.wg : &M.wd;
    const CUtensorMap* mB1 = T.isG ? &M.wu : mB0;
    const int c0 = T.col * (T.isG ? 64 : 128), c1 = T.isG ? c0 : c0 + 64, row = T.blk * 128;
    const int ok = 0;
    int k = T.k0;
#pragma unroll 1
    for (int it = 0; it < T.n; it++, k += 64) {
      const uint32_t a = sb + s * STAGE, fb = sb + B_FULL + s * 8;
      mbar_wait(sb + B_EMPTY + s * 8, ph ^ 1, budget);
      e_expect_tx(fb, STAGE);
      if (shareB) {
        e_tma_2d_mc(a + 16384 + rank * 8192, rank ? mB1 : mB0, c0, k, fb);
        e_tma_2d(a, mA, k, row, fb); e_tma_2d(a + 8192, mA, k, row + 64, fb);
      } else {
        e_tma_2d_mc(a + rank * 8192, mA, T.isO ? row + rank * 64 : k, T.isO ? k + ok : row + rank * 64, fb);
        e_tma_2d(a + 16384, mB0, c0, k, fb); e_tma_2d(a + 24576, mB1, c1, k, fb);
      }
      if (it == T.n - TP(2) && rank == 0) sc.scan(lane);
      if (++s == STAGES) { s = 0; ph ^= 1; }
    }
  }
}

template<int TA> DEVI void mainloop(float* d0, float* d1, uint32_t sb, int n, int s, int ph, bool lead, uint32_t ord, int& budget) {
  int prev = 0;
  const uint32_t rel = threadIdx.x & 127;
#pragma unroll 1
  for (int i = 0; i < n; i++) {
    mbar_wait(sb + B_FULL + s * 8, ph, budget);
    const uint32_t a = sb + s * STAGE;
    const uint64_t da = mkdesc(a, 16, 1024), db = mkdesc(a + 16384, 8192, 1024);
    wg_fence();
#pragma unroll
    for (int k = 0; k < 4; k++) {
      wgmma_n128<TA>(d0, da + k * (TA ? 128 : 2), db + k * 128, (i | k) != 0);
      wgmma_n128<TA>(d1, da + 512 + k * (TA ? 128 : 2), db + k * 128, (i | k) != 0);
    }
    wg_commit();
    if (i > 0) { wg_wait<1>(); p_arrive_at(sb + B_EMPTY + prev * 8, rel & 1, rel < 2); }
    prev = s;
    if (++s == STAGES) { s = 0; ph ^= 1; }
  }
  p_arrive(ord, lead);
  wg_wait<0>();
  p_arrive_at(sb + B_EMPTY + prev * 8, rel & 1, rel < 2);
}

DEVI void consumer(const uint32_t sb, const Maps& M, const int wg) {
  const int tid = threadIdx.x, lane = tid & 31, warp = (tid >> 5) & 3;
  const bool lead = (tid & 127) == 0;
  const uint32_t so = sb + SO + wg * 16384;
  int budget = SPIN_BUDGET;
  float d0[64], d1[64];
#pragma unroll 1
  for (int m = 0;; m++) {
    mbar_wait(sb + B_TF + wg * 8, m & 1, budget);
    const uint2 mail = lds64v(sb + MAIL + wg * 8);
    const int task = __shfl_sync(0xffffffffu, (int)mail.x, 0), pos = __shfl_sync(0xffffffffu, (int)mail.y, 0);
    e_arrive(sb + B_TE + wg * 8);
    if (task == END || budget < 0) break;
    const Tile T(task, cluster_rank());
    mbar_wait(sb + B_ORD + wg * 8, (m & 1) ^ wg ^ 1, budget);
    if (T.isO) mainloop<1>(d0, d1, sb, 32, pos & 255, pos >> 8, lead, sb + B_ORD + (wg ^ 1) * 8, budget);
    else mainloop<0>(d0, d1, sb, T.n, pos & 255, pos >> 8, lead, sb + B_ORD + (wg ^ 1) * 8, budget);
    const uint32_t st = so + (warp * 16 + (lane & 15)) * 128;
    if (T.isG) {
#pragma unroll
      for (int mm = 0; mm < 2; mm++) {
        const float* d = mm ? d1 : d0;
#pragma unroll
        for (int c = 0; c < 4; c++) {
          uint32_t r[4];
#pragma unroll
          for (int i = 0; i < 4; i++) r[i] = pack_bf16(geglu(d[8*c+2*i], d[32+8*c+2*i]), geglu(d[8*c+2*i+1], d[33+8*c+2*i]));
          stsm4(st + mm * 8192 + (((2 * c + (lane >> 4)) ^ (lane & 7)) << 4), r[0], r[1], r[2], r[3]);
        }
      }
      fence_proxy_async();
      nbar_sync_r(1 + wg, 128);
      if (lead) {
        tma_store_2d(&M.hs, so, T.col * 64, T.blk * 128);
        bulk_commit(); bulk_wait<0>();
        flag_add(&g_dep[T.l2 ? E_D2 + (T.col >= 28) * 16 + T.blk : E_D1 + T.blk * 2 + (T.col >= 28)]);
      }
    } else {
#pragma unroll
      for (int hf = 0; hf < 2; hf++) {
        if (hf) { if (lead) bulk_wait_read<0>(); nbar_sync_r(1 + wg, 128); }
#pragma unroll
        for (int mm = 0; mm < 2; mm++) {
          const float* d = (mm ? d1 : d0) + hf * 32;
#pragma unroll
          for (int c = 0; c < 4; c++)
            stsm4(st + mm * 8192 + (((2 * c + (lane >> 4)) ^ (lane & 7)) << 4), pack_bf16(d[8*c], d[8*c+1]), pack_bf16(d[8*c+2], d[8*c+3]),
                  pack_bf16(d[8*c+4], d[8*c+5]), pack_bf16(d[8*c+6], d[8*c+7]));
        }
        fence_proxy_async();
        nbar_sync_r(1 + wg, 128);
        if (lead) { tma_radd_2d(&M.out, so, T.col * 128 + hf * 64, T.blk * 128); bulk_commit(); }
      }
      if (lead) {
        bulk_wait<0>();
        if (T.isO || !T.l2) flag_add(&g_dep[(!T.isO ? E_LX2 : T.l2 ? E_LX1B : E_LX1A) + T.blk]);
      }
    }
    __syncwarp();
  }
}

DEVI void norm_helper(const bf16* __restrict__ x, bf16* out) {
  const int lane = threadIdx.x & 31;
  int budget = SPIN_BUDGET, tk = lane < 4 ? -1 : 1024;
#pragma unroll 1
  while (--budget > 0) {
    if (tk < 0) tk = atomicAdd(g_claim + E_LI + lane, 1);
    if (__all_sync(0xffffffffu, tk >= 1024)) break;
    const uint32_t m = __ballot_sync(0xffffffffu, tk < 1024 && (lane == 0 || ldg_acq32(g_dep + E_LI + lane * 16 + (tk >> 6)) >= 16));
    if (!m) { __nanosleep(TP(7)); continue; }
    const int ql = __ffs(m) - 1, task = __shfl_sync(0xffffffffu, tk, ql), q = E_LI + ql * 16, ev = task >> 6;
    if (lane == ql) tk = -1;
    const size_t off = (size_t)task * (DM * 4) + lane * 16;
    const char* src = (const char*)(q == E_LI ? x : out) + off;
    uint4 u[8];
#pragma unroll
    for (int i = 0; i < 8; i++) u[i] = ldg_rlx128(src + i * 512);
    if (q == E_LI) {
#pragma unroll
      for (int i = 0; i < 8; i++) stg128((char*)out + off + i * 512, u[i].x, u[i].y, u[i].z, u[i].w);
    }
    float mean[2], rs[2];
#pragma unroll
    for (int r = 0; r < 2; r++) {
      float s0 = 0, s1 = 0;
#pragma unroll
      for (int i = 0; i < 16; i++) { const uint32_t v = (&u[4*r + (i >> 2)].x)[i & 3]; s0 += bf_lo(v); s1 += bf_hi(v); }
      mean[r] = (s0 + s1) * (1.f / 32);
      s0 = s1 = 0;
#pragma unroll
      for (int i = 0; i < 16; i++) { const uint32_t v = (&u[4*r + (i >> 2)].x)[i & 3]; const float a = bf_lo(v) - mean[r], b = bf_hi(v) - mean[r]; s0 = fmaf(a, a, s0); s1 = fmaf(b, b, s1); }
      rs[r] = s0 + s1;
    }
    {
      const bool hi = lane & 16;
      float m1 = hi ? mean[1] : mean[0], q1 = hi ? rs[1] : rs[0], m2 = hi ? mean[0] : mean[1], q2 = hi ? rs[0] : rs[1], cnt = 16;
#pragma unroll
      for (int o = 16; o; o >>= 1) {
        m2 = __shfl_xor_sync(0xffffffffu, m2, o); q2 = __shfl_xor_sync(0xffffffffu, q2, o);
        const float dl = m1 - m2;
        q2 = q1 = fmaf(dl * dl, cnt, q1 + q2); m2 = m1 = 0.5f * (m1 + m2);
        cnt *= 2;
      }
      q1 = rsqrtf(q1 * (1.f / DM) + 1e-5f);
      m2 = __shfl_xor_sync(0xffffffffu, m1, 16); q2 = __shfl_xor_sync(0xffffffffu, q1, 16);
      mean[0] = hi ? m2 : m1; mean[1] = hi ? m1 : m2; rs[0] = hi ? q2 : q1; rs[1] = hi ? q1 : q2;
    }
#pragma unroll
    for (int i = 0; i < 8; i++) {
      uint32_t y[4];
#pragma unroll
      for (int c = 0; c < 4; c++) { const uint32_t v = (&u[i].x)[c]; y[c] = pack_bf16((bf_lo(v) - mean[i >> 2]) * rs[i >> 2], (bf_hi(v) - mean[i >> 2]) * rs[i >> 2]); }
      stg128((char*)g_xn + off + i * 512, y[0], y[1], y[2], y[3]);
    }
    fence_proxy_global();
    __syncwarp();
    if (lane == 0) flag_add(q == E_LI ? &g_xa[0][ev] : q == E_LX2 ? &g_xa[1][ev] : &g_dep[q == E_LX1A ? E_G1 + ev : E_G2 + (ev >> 1)]);
    __syncwarp();
  }
}
}

__global__ void __cluster_dims__(2, 1, 1) __launch_bounds__(384, 1)
gemm_kernel(const __grid_constant__ gm::Maps M, const bf16* __restrict__ x, bf16* out) {
  using namespace gm;
  extern __shared__ __align__(1024) uint8_t smem[];
  const uint32_t sb = __shfl_sync(0xffffffffu, smem_u32(smem), 0);
  const int tid = threadIdx.x, wi = __shfl_sync(0xffffffffu, tid >> 5, 0);
  if (tid < 20) mbar_init(sb + BARS + tid * 8, tid == 14 || tid == 15 ? 4 : tid >= 6 && tid < 12 ? 2 : 1);
  fence_mbar_init();
  cluster_arrive(); cluster_wait();
  if (wi < 8) { reg_inc<208>(); consumer(sb, M, wi >> 2); cluster_arrive(); cluster_wait(); }
  else {
    reg_dec<88>();
    if (wi == 8) producer(sb, M);
    else {
      norm_helper(x, out);
      asm volatile("griddepcontrol.wait;" ::: "memory");
      if (wi == 9 && blockIdx.x < 64) g_h2[(NSTEP - 1) & 3][blockIdx.x * 32 + (tid & 31)] = make_uint4(0, 0, 0, 0);
    }
    __syncwarp();
    cluster_arrive(); cluster_wait();
  }
}

typedef CUresult (*PFN_encodeTiled)(CUtensorMap*, CUtensorMapDataType, cuuint32_t, void*, const cuuint64_t*, const cuuint64_t*,
                                    const cuuint32_t*, const cuuint32_t*, CUtensorMapInterleave, CUtensorMapSwizzle,
                                    CUtensorMapL2promotion, CUtensorMapFloatOOBfill);
static PFN_encodeTiled g_encode = nullptr;
static CUtensorMap make_map(const void* ptr, uint64_t rows, uint64_t cols, uint32_t box_rows) {
  CUtensorMap m;
  cuuint64_t dims[2] = {cols, rows}, strides[1] = {cols * 2};
  cuuint32_t box[2] = {64, box_rows}, es[2] = {1, 1};
  g_encode(&m, CU_TENSOR_MAP_DATA_TYPE_BFLOAT16, 2, (void*)ptr, dims, strides, box, es, CU_TENSOR_MAP_INTERLEAVE_NONE,
           CU_TENSOR_MAP_SWIZZLE_128B, CU_TENSOR_MAP_L2_PROMOTION_L2_256B, CU_TENSOR_MAP_FLOAT_OOB_FILL_NONE);
  return m;
}

static CUtensorMap make_map3(const void* ptr, uint64_t d0, uint64_t d1, uint64_t d2, uint64_t stride2) {
  CUtensorMap m;
  cuuint64_t dims[3] = {d0, d1, d2}, strides[2] = {DM * 2, stride2};
  cuuint32_t box[3] = {64, 32, 2}, es[3] = {1, 1, 1};
  g_encode(&m, CU_TENSOR_MAP_DATA_TYPE_BFLOAT16, 3, (void*)ptr, dims, strides, box, es, CU_TENSOR_MAP_INTERLEAVE_NONE,
           CU_TENSOR_MAP_SWIZZLE_128B, CU_TENSOR_MAP_L2_PROMOTION_L2_256B, CU_TENSOR_MAP_FLOAT_OOB_FILL_NONE);
  return m;
}

extern "C" void kernel_launch(void* const* d_in, const int* in_sizes, int n_in, void* d_out, int out_size) {
  const bf16* x = (const bf16*)d_in[0];
  const bf16* mem0 = (const bf16*)d_in[1];
  if (!g_encode) {
    void* p = nullptr; cudaDriverEntryPointQueryResult q;
    cudaGetDriverEntryPoint("cuTensorMapEncodeTiled", &p, cudaEnableDefault, &q);
    g_encode = (PFN_encodeTiled)p;
    cudaFuncSetAttribute(gemm_kernel, cudaFuncAttributeMaxDynamicSharedMemorySize, gm::SMEM);
    cudaFuncSetAttribute(rec_kernel, cudaFuncAttributeMaxDynamicSharedMemorySize, rec::SMEM);
  }
  bf16 *xn, *ot, *hh;
  cudaGetSymbolAddress((void**)&xn, g_xn); cudaGetSymbolAddress((void**)&ot, g_ot); cudaGetSymbolAddress((void**)&hh, g_h);
  rec::Maps R;
  for (int i = 0; i < 3; i++) R.w[i] = make_map(d_in[2 + i], DM, NH * DH, 16);
  R.wo = make_map(d_in[5], NH * DH, DM, 128);
  R.xd = make_map3(xn, DM, SEQ - LAG * 32, 2, (uint64_t)LAG * 32 * DM * 2); R.xs = make_map3(xn, 64, SEQ, DM / 64, 128);
  gm::Maps G;
  G.ot = make_map(ot, NH * DH + O_LAYER / SEQ, SEQ, 64); G.wo = make_map(d_in[5], NH * DH, DM, 64); G.xn = make_map(xn, SEQ, DM, 64);
  G.wg = make_map(d_in[8], DM, DF, 64); G.wu = make_map(d_in[9], DM, DF, 64); G.hl = make_map(hh, SEQ, DF, 64); G.hs = make_map(hh, SEQ, DF, 128);
  G.wd = make_map(d_in[10], DF, DM, 64); G.out = make_map(d_out, SEQ, DM, 128);
  rec_kernel<<<3 * NH, 384, rec::SMEM, cudaStreamPerThread>>>(R, mem0);
  cudaLaunchConfig_t cfg = {};
  cfg.gridDim = dim3(132); cfg.blockDim = dim3(384); cfg.dynamicSmemBytes = gm::SMEM; cfg.stream = cudaStreamPerThread;
  cudaLaunchAttribute at[1];
  at[0].id = cudaLaunchAttributeProgrammaticStreamSerialization; at[0].val.programmaticStreamSerializationAllowed = 1;
  cfg.attrs = at; cfg.numAttrs = 1;
  cudaLaunchKernelEx(&cfg, gemm_kernel, G, x, (bf16*)d_out);
}
```

```cpp
#include <cuda_runtime.h>
#include <cuda_bf16.h>
#include <cuda.h>
#include <stdint.h>

#define DEVI __device__ __forceinline__
typedef __nv_bfloat16 bf16;

constexpr int SEQ = 2048, DM = 1024, NH = 32, DH = 128, DF = 3584, NSEG = 64;
#define LAG 18
constexpr int NSTEP = NSEG + LAG;

#define TSS 1
#define TSD 1100
constexpr size_t O_LAYER = 0;
__device__ __align__(1024) bf16 g_xn[SEQ * DM];
__device__ __align__(1024) bf16 g_ot[SEQ * NH * DH + O_LAYER];
__device__ __align__(1024) bf16 g_h[SEQ * DF];
__device__ __align__(1024) uint2 g_h1[4][256 * 256];
__device__ __align__(1024) uint4 g_h2[4][2048];
__device__ __align__(128) uint32_t g_ts[2][32 * TSS];
enum { E_D1 = 0, E_G1 = 32, E_O1 = 48, E_O2 = 64, E_G2 = 80, E_D2 = 96,
       E_LI = 128, E_LX2 = 144, E_LX1A = 160, E_LX1B = 176, NEV = 256 };
__device__ __align__(128) int g_dep[NEV];
__device__ __align__(128) int g_claim[NEV];
__device__ __align__(128) int g_xa[2][32];

#define TUNE_DEFAULTS 1550, 2400, 5, 100, 100, 8, 0xffff, 100
constexpr int c_D[8] = {TUNE_DEFAULTS};
template<int I> struct TPV { static constexpr int v = c_D[I]; };
#define TP(i) TPV<i>::v

DEVI uint32_t smem_u32(const void* p) { return (uint32_t)__cvta_generic_to_shared(p); }
DEVI void mbar_init(uint32_t bar, uint32_t cnt) { asm volatile("mbarrier.init.shared::cta.b64 [%0], %1;" :: "r"(bar), "r"(cnt) : "memory"); }
DEVI void mbar_arrive(uint32_t bar) { asm volatile("mbarrier.arrive.shared::cta.b64 _, [%0];" :: "r"(bar) : "memory"); }
DEVI bool mbar_try(uint32_t bar, uint32_t parity) {
  uint32_t p;
  asm volatile("{.reg .pred p; mbarrier.try_wait.parity.shared::cta.b64 p, [%1], %2; selp.u32 %0, 1, 0, p;}" : "=r"(p) : "r"(bar), "r"(parity) : "memory");
  return p;
}
constexpr int SPIN_BUDGET = 1 << 18;
DEVI void mbar_wait(uint32_t bar, uint32_t parity, int& budget) {
  while (!mbar_try(bar, parity)) { if (--budget < 0) break; }
}
DEVI bool mbar_try_cluster(uint32_t bar, uint32_t parity) {
  uint32_t p;
  asm volatile("{.reg .pred p; mbarrier.try_wait.parity.acquire.cluster.shared::cta.b64 p, [%1], %2; selp.u32 %0, 1, 0, p;}" : "=r"(p) : "r"(bar), "r"(parity) : "memory");
  return p;
}
DEVI void mbar_wait_cluster(uint32_t bar, uint32_t parity, int& budget) {
  while (!mbar_try_cluster(bar, parity)) { if (--budget < 0) break; }
}
DEVI uint32_t mapa(uint32_t addr, uint32_t rank) { uint32_t r; asm("mapa.shared::cluster.u32 %0, %1, %2;" : "=r"(r) : "r"(addr), "r"(rank)); return r; }
DEVI void cluster_arrive() { asm volatile("barrier.cluster.arrive.release.aligned;" ::: "memory"); }
DEVI void cluster_wait() { asm volatile("barrier.cluster.wait.acquire.aligned;" ::: "memory"); }
DEVI void fence_mbar_init() { asm volatile("fence.mbarrier_init.release.cluster;" ::: "memory"); }
DEVI void fence_proxy_async() { asm volatile("fence.proxy.async.shared::cta;" ::: "memory"); }
DEVI void fence_proxy_global() { asm volatile("fence.proxy.async.global;" ::: "memory"); }
#define ELECT "{.reg .pred p; elect.sync _|p, 0xffffffff;\n @p "
DEVI void e_expect_tx(uint32_t bar, uint32_t bytes) { asm volatile(ELECT "mbarrier.arrive.expect_tx.shared::cta.b64 _, [%0], %1;}" :: "r"(bar), "r"(bytes) : "memory"); }
DEVI void e_arrive(uint32_t bar) { asm volatile(ELECT "mbarrier.arrive.shared::cta.b64 _, [%0];}" :: "r"(bar) : "memory"); }
DEVI void e_tma_2d(uint32_t dst, const CUtensorMap* m, int c0, int c1, uint32_t bar) {
  asm volatile(ELECT "cp.async.bulk.tensor.2d.shared::cluster.global.mbarrier::complete_tx::bytes [%0], [%1, {%3, %4}], [%2];}"
    :: "r"(dst), "l"(m), "r"(bar), "r"(c0), "r"(c1) : "memory");
}
DEVI void e_prefetch_2d(const CUtensorMap* m, int c0, int c1) {
  asm volatile(ELECT "cp.async.bulk.prefetch.tensor.2d.L2.global [%0, {%1, %2}];}" :: "l"(m), "r"(c0), "r"(c1) : "memory");
}
DEVI void e_prefetch_3d(const CUtensorMap* m, int c0, int c1, int c2) {
  asm volatile(ELECT "cp.async.bulk.prefetch.tensor.3d.L2.global [%0, {%1, %2, %3}];}" :: "l"(m), "r"(c0), "r"(c1), "r"(c2) : "memory");
}
DEVI void e_bulk_g2s(uint32_t dst, const void* src, uint32_t bytes, uint32_t bar) {
  asm volatile(ELECT "cp.async.bulk.shared::cluster.global.mbarrier::complete_tx::bytes [%0], [%1], %2, [%3];}" :: "r"(dst), "l"(src), "r"(bytes), "r"(bar) : "memory");
}
DEVI void e_tma_3d(uint32_t dst, const CUtensorMap* m, int c0, int c1, int c2, uint32_t bar) {
  asm volatile(ELECT "cp.async.bulk.tensor.3d.shared::cluster.global.mbarrier::complete_tx::bytes [%0], [%1, {%3, %4, %5}], [%2];}"
    :: "r"(dst), "l"(m), "r"(bar), "r"(c0), "r"(c1), "r"(c2) : "memory");
}
DEVI void e_tma_3d_mc(uint32_t dst, const CUtensorMap* m, int c0, int c1, int c2, uint32_t bar) {
  asm volatile(ELECT "cp.async.bulk.tensor.3d.shared::cluster.global.mbarrier::complete_tx::bytes.multicast::cluster [%0], [%1, {%3, %4, %5}], [%2], %6;}"
    :: "r"(dst), "l"(m), "r"(bar), "r"(c0), "r"(c1), "r"(c2), "h"((uint16_t)7) : "memory");
}
DEVI void e_tma_2d_mc(uint32_t dst, const CUtensorMap* m, int c0, int c1, uint32_t bar) {
  asm volatile(ELECT "cp.async.bulk.tensor.2d.shared::cluster.global.mbarrier::complete_tx::bytes.multicast::cluster [%0], [%1, {%3, %4}], [%2], %5;}"
    :: "r"(dst), "l"(m), "r"(bar), "r"(c0), "r"(c1), "h"((uint16_t)3) : "memory");
}
DEVI void p_arrive_at(uint32_t bar, uint32_t rank, bool c) {
  asm volatile("{.reg .pred p; .reg .b32 a; setp.ne.u32 p, %2, 0; mapa.shared::cluster.u32 a, %0, %1; @p mbarrier.arrive.shared::cluster.b64 _, [a];}"
    :: "r"(bar), "r"(rank), "r"((uint32_t)c) : "memory");
}
DEVI void p_expect_tx(uint32_t bar, uint32_t bytes, bool c) {
  asm volatile("{.reg .pred p; setp.ne.u32 p, %2, 0; @p mbarrier.arrive.expect_tx.shared::cta.b64 _, [%0], %1;}" :: "r"(bar), "r"(bytes), "r"((uint32_t)c) : "memory");
}
DEVI void p_arrive(uint32_t bar, bool c) { asm volatile("{.reg .pred p; setp.ne.u32 p, %1, 0; @p mbarrier.arrive.shared::cta.b64 _, [%0];}" :: "r"(bar), "r"((uint32_t)c) : "memory"); }
DEVI void tma_store_2d(const CUtensorMap* m, uint32_t src, int c0, int c1) {
  asm volatile("cp.async.bulk.tensor.2d.global.shared::cta.bulk_group [%0, {%2, %3}], [%1];" :: "l"(m), "r"(src), "r"(c0), "r"(c1) : "memory");
}
DEVI void tma_radd_2d(const CUtensorMap* m, uint32_t src, int c0, int c1) {
  asm volatile("cp.reduce.async.bulk.tensor.2d.global.shared::cta.add.bulk_group [%0, {%2, %3}], [%1];" :: "l"(m), "r"(src), "r"(c0), "r"(c1) : "memory");
}
DEVI void bulk_commit() { asm volatile("cp.async.bulk.commit_group;" ::: "memory"); }
template<int N> DEVI void bulk_wait_read() { asm volatile("cp.async.bulk.wait_group.read %0;" :: "n"(N) : "memory"); }
template<int N> DEVI void bulk_wait() { asm volatile("cp.async.bulk.wait_group %0;" :: "n"(N) : "memory"); }
template<int ID, int N> DEVI void nbar_sync() { asm volatile("bar.sync %0, %1;" :: "n"(ID), "n"(N) : "memory"); }
template<int ID, int N> DEVI void nbar_arrive() { asm volatile("bar.arrive %0, %1;" :: "n"(ID), "n"(N) : "memory"); }
DEVI void nbar_sync_r(int id, int n) { asm volatile("bar.sync %0, %1;" :: "r"(id), "r"(n) : "memory"); }
template<int R> DEVI void reg_inc() { asm volatile("setmaxnreg.inc.sync.aligned.u32 %0;" :: "n"(R)); }
template<int R> DEVI void reg_dec() { asm volatile("setmaxnreg.dec.sync.aligned.u32 %0;" :: "n"(R)); }
DEVI void wg_fence() { asm volatile("wgmma.fence.sync.aligned;" ::: "memory"); }
DEVI void wg_commit() { asm volatile("wgmma.commit_group.sync.aligned;" ::: "memory"); }
template<int N> DEVI void wg_wait() { asm volatile("wgmma.wait_group.sync.aligned %0;" :: "n"(N) : "memory"); }
DEVI uint64_t mkdesc(uint32_t addr, uint32_t lbo, uint32_t sbo, uint32_t sw = 1) {
  return ((uint64_t)((addr & 0x3FFFF) >> 4)) | ((uint64_t)(lbo >> 4) << 16) | ((uint64_t)(sbo >> 4) << 32) | ((uint64_t)sw << 62);
}
constexpr uint32_t SMEM_BASE = 1024;
__host__ __device__ constexpr long long CD(uint32_t off, uint32_t lbo, uint32_t sbo, uint32_t sw) {
  return (long long)(((uint64_t)((SMEM_BASE + off) >> 4)) | ((uint64_t)(lbo >> 4) << 16) | ((uint64_t)(sbo >> 4) << 32) | ((uint64_t)sw << 62));
}
DEVI uint32_t pack_bf16(float lo, float hi) { uint32_t r; asm("cvt.rn.bf16x2.f32 %0, %1, %2;" : "=r"(r) : "f"(hi), "f"(lo)); return r; }
DEVI float bf_lo(uint32_t v) { return __uint_as_float(v << 16); }
DEVI float bf_hi(uint32_t v) { return __uint_as_float(v & 0xffff0000u); }
DEVI void ldsm4t(uint32_t addr, uint32_t& r0, uint32_t& r1, uint32_t& r2, uint32_t& r3) {
  asm volatile("ldmatrix.sync.aligned.m8n8.x4.trans.shared.b16 {%0,%1,%2,%3}, [%4];" : "=r"(r0), "=r"(r1), "=r"(r2), "=r"(r3) : "r"(addr) : "memory");
}
DEVI void stsm4(uint32_t addr, uint32_t r0, uint32_t r1, uint32_t r2, uint32_t r3) {
  asm volatile("stmatrix.sync.aligned.m8n8.x4.shared.b16 [%0], {%1,%2,%3,%4};" :: "r"(addr), "r"(r0), "r"(r1), "r"(r2), "r"(r3) : "memory");
}
DEVI uint2 lds64v(uint32_t a) { uint2 v; asm volatile("ld.volatile.shared.v2.u32 {%0,%1}, [%2];" : "=r"(v.x), "=r"(v.y) : "r"(a) : "memory"); return v; }
DEVI uint32_t lds32v(uint32_t a) { uint32_t v; asm volatile("ld.volatile.shared.u32 %0, [%1];" : "=r"(v) : "r"(a) : "memory"); return v; }
DEVI uint4 lds128v(uint32_t a) { uint4 v; asm volatile("ld.volatile.shared.v4.u32 {%0,%1,%2,%3}, [%4];" : "=r"(v.x), "=r"(v.y), "=r"(v.z), "=r"(v.w) : "r"(a) : "memory"); return v; }
DEVI void cp_async16(uint32_t dst, const void* src) { asm volatile("cp.async.cg.shared.global [%0], [%1], 16;" :: "r"(dst), "l"(src) : "memory"); }
DEVI void cp_async_wait() { asm volatile("cp.async.wait_all;" ::: "memory"); }
DEVI void sts32(uint32_t a, uint32_t x) { asm volatile("st.shared.u32 [%0], %1;" :: "r"(a), "r"(x) : "memory"); }
DEVI int lane_id() { int r; asm volatile("mov.u32 %0, %%laneid;" : "=r"(r)); return r; }
DEVI void sts64(uint32_t a, uint32_t x, uint32_t y) { asm volatile("st.shared.v2.u32 [%0], {%1,%2};" :: "r"(a), "r"(x), "r"(y) : "memory"); }
DEVI void sts128(uint32_t a, uint4 v) { asm volatile("st.shared.v4.u32 [%0], {%1,%2,%3,%4};" :: "r"(a), "r"(v.x), "r"(v.y), "r"(v.z), "r"(v.w) : "memory"); }
DEVI void st_async128(uint32_t a, uint32_t x, uint32_t y, uint32_t z, uint32_t w, uint32_t bar) {
  asm volatile("st.async.weak.shared::cluster.mbarrier::complete_tx::bytes.v4.b32 [%0], {%1,%2,%3,%4}, [%5];" :: "r"(a), "r"(x), "r"(y), "r"(z), "r"(w), "r"(bar) : "memory");
}
DEVI void st_async32(uint32_t a, uint32_t x, uint32_t bar) {
  asm volatile("st.async.weak.shared::cluster.mbarrier::complete_tx::bytes.b32 [%0], %1, [%2];" :: "r"(a), "r"(x), "r"(bar) : "memory");
}
DEVI uint4 ldg_rlx128(const void* p) {
  uint4 v;
  asm volatile("ld.relaxed.gpu.global.v4.b32 {%0,%1,%2,%3}, [%4];" : "=r"(v.x), "=r"(v.y), "=r"(v.z), "=r"(v.w) : "l"(p) : "memory");
  return v;
}
DEVI int ldg_rlx32(const void* p) { int v; asm volatile("ld.relaxed.gpu.global.b32 %0, [%1];" : "=r"(v) : "l"(p) : "memory"); return v; }
DEVI int ldg_acq32(const void* p) { int v; asm volatile("ld.acquire.gpu.global.b32 %0, [%1];" : "=r"(v) : "l"(p) : "memory"); return v; }
DEVI void stg_rlx128(void* p, uint32_t x, uint32_t y, uint32_t z, uint32_t w) {
  asm volatile("st.relaxed.gpu.global.v4.b32 [%0], {%1,%2,%3,%4};" :: "l"(p), "r"(x), "r"(y), "r"(z), "r"(w) : "memory");
}
DEVI void stg128(void* p, uint32_t x, uint32_t y, uint32_t z, uint32_t w) {
  asm volatile("st.global.v4.b32 [%0], {%1,%2,%3,%4};" :: "l"(p), "r"(x), "r"(y), "r"(z), "r"(w) : "memory");
}
DEVI uint2 ldg_rlx64(const void* p) { uint2 v; asm volatile("{.reg .b64 a; ld.relaxed.gpu.global.b64 a, [%2]; mov.b64 {%0,%1}, a;}" : "=r"(v.x), "=r"(v.y) : "l"(p) : "memory"); return v; }
DEVI void stg_rlx64(void* p, uint32_t x, uint32_t y) { asm volatile("{.reg .b64 a; mov.b64 a, {%1,%2}; st.relaxed.gpu.global.b64 [%0], a;}" :: "l"(p), "r"(x), "r"(y) : "memory"); }
DEVI void stg_rlx32(void* p, uint32_t x) { asm volatile("st.relaxed.gpu.global.b32 [%0], %1;" :: "l"(p), "r"(x) : "memory"); }
DEVI void flag_add(int* p) { asm volatile("fence.proxy.async.global; red.release.gpu.global.add.s32 [%0], 1;" :: "l"(p) : "memory"); }
DEVI void e_stg_rlx32(void* p, uint32_t x) { asm volatile(ELECT "st.relaxed.gpu.global.b32 [%0], %1;}" :: "l"(p), "r"(x) : "memory"); }
DEVI void e_flag_add(int* p) { asm volatile("fence.proxy.async.global;\n" ELECT "red.release.gpu.global.add.s32 [%0], 1;}" :: "l"(p) : "memory"); }
DEVI int cluster_rank() { int r; asm volatile("mov.u32 %0, %%cluster_ctarank;" : "=r"(r)); return __shfl_sync(0xffffffffu, r, 0); }
DEVI int cluster_id() { int r; asm volatile("mov.u32 %0, %%clusterid.x;" : "=r"(r)); return __shfl_sync(0xffffffffu, r, 0); }
DEVI uint32_t clock32() { uint32_t c; asm volatile("mov.u32 %0, %%clock;" : "=r"(c)); return c; }
DEVI uint32_t gtime() { uint32_t c; asm volatile("mov.u32 %0, %%globaltimer_lo;" : "=r"(c)); return c; }
DEVI void wait_time(uint32_t t) { while (__any_sync(0xffffffffu, t - gtime() - 1 < 4000u)) {} }
DEVI void spin_until(uint32_t t0, int d) { while (__any_sync(0xffffffffu, (int)(clock32() - t0) < d)) {} }
DEVI void pin2(const void* a, const void* b) { asm volatile("{.reg .pred p; setp.eq.u64 p, %0, %1; @p st.volatile.global.u64 [%0], %1;}" :: "l"(a), "l"(b) : "memory"); }
DEVI void pin2(uint32_t a, uint32_t b) { asm volatile("{.reg .pred p; setp.eq.u32 p, %0, %1; @p st.volatile.shared.u32 [%0], %1;}" :: "r"(a), "r"(b) : "memory"); }
DEVI void p_stg_rlx64(void* p, uint32_t x, uint32_t y, bool c) {
  asm volatile("{.reg .pred p; .reg .b64 a; setp.ne.u32 p, %3, 0; mov.b64 a, {%1,%2}; @p st.relaxed.gpu.global.b64 [%0], a;}" :: "l"(p), "r"(x), "r"(y), "r"((uint32_t)c) : "memory");
}
DEVI void pin2(uint64_t a, uint64_t b) { pin2((const void*)a, (const void*)b); }
DEVI uint64_t pair(uint32_t a, uint32_t bar) { return a | (uint64_t)bar << 32; }
DEVI void st_async32(uint64_t q, uint32_t x) { st_async32((uint32_t)q, x, (uint32_t)(q >> 32)); }
DEVI void st_async128(uint64_t q, uint4 v) { st_async128((uint32_t)q, v.x, v.y, v.z, v.w, (uint32_t)(q >> 32)); }
DEVI float ex2(float x) { float r; asm("ex2.approx.ftz.f32 %0, %1;" : "=f"(r) : "f"(x)); return r; }
DEVI float rcp(float x) { float r; asm("rcp.approx.ftz.f32 %0, %1;" : "=f"(r) : "f"(x)); return r; }
DEVI uint32_t xor_or(uint32_t a, uint32_t t, uint32_t acc) { uint32_t r; asm("lop3.b32 %0, %1, %2, %3, 0xbe;" : "=r"(r) : "r"(a), "r"(t), "r"(acc)); return r; }
DEVI void stsm2(uint32_t addr, uint32_t r0, uint32_t r1) {
  asm volatile("stmatrix.sync.aligned.m8n8.x2.shared.b16 [%0], {%1,%2};" :: "r"(addr), "r"(r0), "r"(r1) : "memory");
}
DEVI uint32_t settag(uint32_t v, uint32_t tag) { return (v & ~1u) | tag; }

#define A4(c, o)  c(d[o+0]), c(d[o+1]), c(d[o+2]), c(d[o+3])
#define A8(c, o)  A4(c, o), A4(c, o+4)
#define A16(c, o) A8(c, o), A8(c, o+8)
#define A20(c, o) A16(c, o), A4(c, o+16)
#define A32(c, o) A16(c, o), A16(c, o+16)
#define RL8  "{%0,%1,%2,%3,%4,%5,%6,%7}"
#define RL16 "{%0,%1,%2,%3,%4,%5,%6,%7,%8,%9,%10,%11,%12,%13,%14,%15}"
#define RL20 "{%0,%1,%2,%3,%4,%5,%6,%7,%8,%9,%10,%11,%12,%13,%14,%15,%16,%17,%18,%19}"
#define RL32 "{%0,%1,%2,%3,%4,%5,%6,%7,%8,%9,%10,%11,%12,%13,%14,%15,%16,%17,%18,%19,%20,%21,%22,%23,%24,%25,%26,%27,%28,%29,%30,%31}"
#define RL64 "{%0,%1,%2,%3,%4,%5,%6,%7,%8,%9,%10,%11,%12,%13,%14,%15,%16,%17,%18,%19,%20,%21,%22,%23,%24,%25,%26,%27,%28,%29,%30,%31," \
  "%32,%33,%34,%35,%36,%37,%38,%39,%40,%41,%42,%43,%44,%45,%46,%47,%48,%49,%50,%51,%52,%53,%54,%55,%56,%57,%58,%59,%60,%61,%62,%63}"
#define WG_OP(shape) "wgmma.mma_async.sync.aligned." shape "k16.f32.bf16.bf16 "
#define DEF_WGMMA(N, RL, AL, i0, i1, i2, i3, i4, i5, i6)                                                                         \
  template<int SC, int TB, long long CB> DEVI void rs##N(float* d, const uint32_t* a) {                                          \
    if (SC) asm volatile("{.reg .b64 tb; mov.b64 tb, %" #i4 ";\n" WG_OP("m64n" #N) RL ", {%" #i0 ",%" #i1 ",%" #i2 ",%" #i3 "}, tb, 1, 1, 1, %" #i5 ";}" \
      : AL("+f", 0) : "r"(a[0]), "r"(a[1]), "r"(a[2]), "r"(a[3]), "n"(CB), "n"(TB));                                             \
    else asm volatile("{.reg .b64 tb; mov.b64 tb, %" #i4 ";\n" WG_OP("m64n" #N) RL ", {%" #i0 ",%" #i1 ",%" #i2 ",%" #i3 "}, tb, 0, 1, 1, %" #i5 ";}" \
      : AL("=f", 0) : "r"(a[0]), "r"(a[1]), "r"(a[2]), "r"(a[3]), "n"(CB), "n"(TB));                                             \
  }                                                                                                                              \
  template<int SC, int TA, int TB, long long CA, long long CB> DEVI void ss##N(float* d, uint32_t a) {                           \
    if (SC) asm volatile("{.reg .b64 ta, tb; .reg .b32 lo, hi; add.u32 lo, %" #i0 ", %" #i1 "; mov.b32 hi, %" #i2 "; mov.b64 ta, {lo, hi}; mov.b64 tb, %" #i3 ";\n" \
      WG_OP("m64n" #N) RL ", ta, tb, 1, 1, 1, %" #i4 ", %" #i5 ";}"                                                              \
      : AL("+f", 0) : "r"(a), "n"((int)CA), "n"((int)(CA >> 32)), "n"(CB), "n"(TA), "n"(TB));                                    \
    else asm volatile("{.reg .b64 ta, tb; .reg .b32 lo, hi; add.u32 lo, %" #i0 ", %" #i1 "; mov.b32 hi, %" #i2 "; mov.b64 ta, {lo, hi}; mov.b64 tb, %" #i3 ";\n" \
      WG_OP("m64n" #N) RL ", ta, tb, 0, 1, 1, %" #i4 ", %" #i5 ";}"                                                              \
      : AL("=f", 0) : "r"(a), "n"((int)CA), "n"((int)(CA >> 32)), "n"(CB), "n"(TA), "n"(TB));                                    \
  }
DEF_WGMMA(8, "{%0,%1,%2,%3}", A4, 4, 5, 6, 7, 8, 9, 10)
DEF_WGMMA(16, RL8, A8, 8, 9, 10, 11, 12, 13, 14)
DEF_WGMMA(32, RL16, A16, 16, 17, 18, 19, 20, 21, 22)
DEF_WGMMA(40, RL20, A20, 20, 21, 22, 23, 24, 25, 26)
DEF_WGMMA(64, RL32, A32, 32, 33, 34, 35, 36, 37, 38)
template<int TA> DEVI void wgmma_n128(float* d, uint64_t a, uint64_t b, int scale_d) {
  asm volatile("{.reg .pred p; setp.ne.b32 p, %66, 0;\n" WG_OP("m64n128") RL64 ", %64, %65, p, 1, 1, %67, 1;}"
    : A32("+f", 0), A32("+f", 32) : "l"(a), "l"(b), "r"(scale_d), "n"(TA));
}

namespace rec {
constexpr int KR = 43;
constexpr uint32_t WSZ = (64 - KR) * 2048, STG = KR * 2048;
constexpr uint32_t WS = 0;
constexpr uint32_t RING = 2 * WSZ;
constexpr uint32_t OB = RING + 3 * 8192;
constexpr uint32_t PB = OB + 4096;
constexpr uint32_t WO = RING + 32768;
constexpr uint32_t ATT = WO + 5 * 16384;
constexpr uint32_t AK = ATT + 10240, AV = ATT + 20480;
constexpr uint32_t PAD = ATT + 30720;
constexpr uint32_t BARS = PAD + 128;
constexpr uint32_t B_XE = BARS  , B_FA = BARS + 64  , B_FB = BARS + 88, B_FO = BARS + 96;
constexpr uint32_t B_ME = BARS + 104  , B_WE = BARS + 136  ;
constexpr uint32_t B_XF = BARS + 152  , B_MF = BARS + 216  , B_CP = BARS + 248  , B_WT = BARS + 280  ;
constexpr uint32_t B_AB = BARS + 296, B_OB = BARS + 304, B_ST = BARS + 312  , B_WS = BARS + 328, B_WO = BARS + 336, B_PD = BARS + 344;
constexpr int NBAR = 44;
constexpr uint32_t M0 = BARS + 384;
constexpr uint32_t SMEM = 232448;
constexpr int NB_P = 1, NB_ST = 2, NB_O = 3, NB_W0 = 4, NB_W1 = 5;
__host__ __device__ constexpr int wo_tile(int rank, int g, int i) { return i < 2 ? i * 6 + rank * 2 + g : 13 + rank - g; }
constexpr long long D_W = CD(WS, 16, 1024, 1), D_X = CD(0, 16, 1024, 1), D_M = CD(RING, 128, 256, 0), D_O = CD(OB, 128, 256, 0);
constexpr long long D_WO = CD(WO, 16, 1024, 1), D_QM = CD(ATT, 640, 0, 0), D_QT = CD(ATT + 128, 640, 64, 0), D_K = CD(AK, 640, 128, 0);
constexpr long long D_V = CD(AV, 128, 640, 0), D_P = CD(PB, 128, 768, 0);
struct Maps { CUtensorMap w[3], wo, xd, xs; };
__host__ __device__ constexpr uint32_t xslot(int s) { return s < 3 ? RING + s * 8192 : s < 5 ? WO + (s - 3) * 8192 : s < 7 ? WO + (s + 1) * 8192 : OB; }
__host__ __device__ constexpr bool k_smem(int k) { return k % 3 == 2; }
__host__ __device__ constexpr int k_idx(int k) { return k % 3 == 2 ? k / 3 : k - k / 3; }
__host__ __device__ constexpr int k_of_reg(int i) { return i + (i >> 1); }
__host__ __device__ constexpr int k_of_smem(int i) { return 3 * i + 2; }

#define RPROF(i)
#define RPROF_STEP
#define CPROF(i, v)

template<int K0, int K1> DEVI void seq_mem(float* d, const uint32_t* w, uint32_t dw) {
  if constexpr (K0 < K1) {
    constexpr long long B = D_M + K0 * 32;
    if constexpr (!k_smem(K0)) rs16<K0 != 0, 1, B>(d, w + 4 * k_idx(K0)); else ss16<1, 1, 1, D_W + k_idx(K0) * 128, B>(d, dw);
    seq_mem<K0 + 1, K1>(d, w, dw);
  }
}
template<bool DUAL, int K0, int K1> DEVI void seq_tok(float* d, const uint32_t* w, uint32_t dw) {
  if constexpr (K0 < K1) {
    constexpr long long B = D_X + (DUAL ? xslot((K0 >> 2) & 7) / 16 : xslot(K0 >> 3) / 16 + ((K0 >> 2) & 1) * 256) + (K0 & 3) * 2;
    if constexpr (DUAL) {
      if constexpr (!k_smem(K0)) rs64<K0 != 0, 0, B>(d, w + 4 * k_idx(K0)); else ss64<1, 1, 0, D_W + k_idx(K0) * 128, B>(d, dw);
    } else {
      if constexpr (!k_smem(K0)) rs32<K0 != 0, 0, B>(d, w + 4 * k_idx(K0)); else ss32<1, 1, 0, D_W + k_idx(K0) * 128, B>(d, dw);
    }
    seq_tok<DUAL, K0 + 1, K1>(d, w, dw);
  }
}
template<int T, int K0> DEVI void seq_wo(float* d, uint32_t dw) {
  if constexpr (K0 < 8) { ss16<K0 != 0, 1, 1, D_WO + T * 1024 + K0 * 128, D_O + K0 * 32>(d, dw); seq_wo<T, K0 + 1>(d, dw); }
}
template<long long Q, int K0> DEVI void seq_s(float* d) {
  if constexpr (K0 < 8) { ss40<K0 != 0, 1, 1, Q + K0 * 80, D_K + K0 * 80>(d, 0); seq_s<Q, K0 + 1>(d); }
}
template<bool DUAL, int J> DEVI void load_x(uint32_t sb, const Maps* M, int t) {
  if (DUAL) e_tma_3d_mc(sb + xslot(J & 7), &M->xd, J * 64, (t - LAG) * 32, 0, sb + B_XF + (J & 7) * 8);
  else e_tma_3d_mc(sb + xslot(J & 7), &M->xs, 0, (t < NSEG ? t : t - LAG) * 32, J * 2, sb + B_XF + (J & 7) * 8);
}
DEVI void load_x_lent(uint32_t sb, const Maps* M, int t, int j) {
  const bool dual = t >= LAG && t < NSEG;
  const uint32_t dst = sb + (j == 3 ? xslot(3) : xslot(5));
#pragma unroll
  for (int i = 0; i < 2; i++)
    e_tma_3d(dst + i * 8192, dual ? &M->xd : &M->xs, dual ? (j + i) * 64 : 0, (t < LAG ? t : t - LAG) * 32, dual ? 0 : (j + i) * 2, sb + B_XF + (j + i) * 8);
}
struct Ctx { uint32_t sb; const Maps* M; int h, rank, wi; bool lead; uint32_t par; };
#define PFN 2
#define XD 2
template<bool DUAL, int J> DEVI void tok_release(const Ctx& c, int t, int& budget) {
  constexpr int NC = DUAL ? 16 : 8, S = J & 7;
  if constexpr (J + 8 < NC) {
    p_arrive_at(c.sb + B_XE + S * 8, J % 3, c.lead);
    p_expect_tx(c.sb + B_XF + S * 8, 8192, c.lead && c.wi == 0);
  } else if constexpr (S == 4 || S == 6) {
    constexpr int g = S == 4;
    p_arrive(c.sb + B_WE + g * 8, c.lead);
    if (c.wi == g * 4 + 2) {
      mbar_wait(c.sb + B_WE + g * 8, t & 1, budget);
      e_expect_tx(c.sb + B_WT + g * 8, 16384);
      e_tma_2d(c.sb + WO + (1 - g) * 49152, &c.M->wo, wo_tile(c.rank, g, 0) * 64, c.h * DH, c.sb + B_WT + g * 8);
    }
  } else if constexpr (S < 3 || S == 7) p_arrive(c.sb + B_ME + (S & 3) * 8, c.lead);
  if constexpr (J == XD - 1) {
    if (c.rank == 1 && c.wi == 5) { mbar_wait(c.sb + B_FO, t & 1, budget); load_x<DUAL, 7>(c.sb, c.M, t); }
  } else if constexpr (J >= XD && J - XD + 8 < NC) {
    constexpr int I = J - XD;
    if (c.rank == I % 3 && c.wi == (I & 1) * 4 + 1) { mbar_wait(c.sb + B_XE + I * 8, (t - LAG) & 1, budget); load_x<DUAL, I + 8>(c.sb, c.M, t); }
  }
}
template<bool DUAL, int J> DEVI void tok_pass(float* d, const uint32_t* w, uint32_t dw, Ctx& c, int t, int& budget) {
  constexpr int NC = DUAL ? 16 : 8, KC = 64 / NC;
  if constexpr (J < NC) {
    mbar_wait(c.sb + B_XF + (J & 7) * 8, c.par ^ (J >> 3), budget);
    wg_fence();
    seq_tok<DUAL, J * KC, (J + 1) * KC>(d, w, dw);
    wg_commit();
    if constexpr (J > 0) { wg_wait<1>(); tok_release<DUAL, J - 1>(c, t, budget); }
    tok_pass<DUAL, J + 1>(d, w, dw, c, t, budget);
  } else {
    wg_wait<0>();
    tok_release<DUAL, NC - 1>(c, t, budget);
    if (!DUAL) c.par ^= 1;
  }
}
DEVI void pack_tok(uint32_t* e, const float* d) {
#pragma unroll
  for (int i = 0; i < 8; i++) e[i] = pack_bf16(d[4 * (i & 3) + 2 * (i >> 2)], d[4 * (i & 3) + 2 * (i >> 2) + 1]);
}
DEVI void push_tok(const uint32_t* e, uint32_t sb, uint32_t o, int r) {
  const uint32_t b = mapa(sb, r);
  st_async128(b + o, e[0], e[1], e[2], e[3], b + B_AB);
}
DEVI uint32_t h1_tag(int seg) { return ((seg >> 1) & 1) ^ 1; }
DEVI void put_part(char* p1, char* p2, const float* c, int t) {
  p_stg_rlx64(p1, settag(pack_bf16(c[0], c[1]), h1_tag(t)), pack_bf16(c[2], c[3]), t < NSEG);
  p_stg_rlx64(p2, settag(pack_bf16(c[4], c[5]), h1_tag(t - LAG)), pack_bf16(c[6], c[7]), t >= LAG);
}

DEVI void rec_math(const uint32_t sb, const int wi, const Maps& M) {
  const int h = cluster_id(), rank = cluster_rank();
  const int warp = wi & 3, wg = wi >> 2;
  const bool lead = (threadIdx.x & 127) == 0;
  int budget = SPIN_BUDGET;
  uint32_t w[4 * KR], e[16];
  Ctx cx{sb, &M, h, rank, wi, lead, 0};
  {
    const int lane = lane_id();
    const uint32_t a = sb + wg * STG + ((lane & 7) + (lane >> 4) * 8) * 128 + (((warp * 2 + ((lane >> 3) & 1)) ^ (lane & 7)) << 4);
    mbar_wait(sb + B_ST + wg * 8, 0, budget);
#pragma unroll
    for (int k = 0; k < KR; k++) ldsm4t(a + k * 2048, w[4*k], w[4*k+1], w[4*k+2], w[4*k+3]);
    nbar_arrive<NB_ST, 384>();
    nbar_sync_r(NB_W0 + wg, 128);
    for (int i = 0; i < 5; i++) p_arrive_at(sb + B_FA + i * 8, i == 4, lead);
    mbar_wait(sb + B_WS, 0, budget);
  }
#pragma unroll 1
  for (int t = -1; t < NSTEP; t++) {
    const uint32_t dw = wg * (WSZ >> 4);
    RPROF_STEP;
    if (t >= 0) {
      const int lane = lane_id();
      RPROF(0 + wg * 12);
      {
        float m[8];
        const uint32_t ao = ATT + rank * 10240 + wi * 1280, to = ao + 128 + (lane & 3) * 128 + (lane >> 2) * 16;
        const bool dual = t >= LAG && t < NSEG;
        mbar_wait(sb + B_MF, t & 1, budget);
        RPROF(1 + wg * 12);
        wg_fence(); seq_mem<0, 8>(m, w, dw);
        push_tok(e, sb, to, t >= NSEG);
        seq_mem<8, 16>(m, w, dw); wg_commit();
        push_tok(e + 4, sb, to + 640, t >= NSEG);
        mbar_wait(sb + B_MF + 8, t & 1, budget);
        wg_fence(); seq_mem<16, 32>(m, w, dw); wg_commit();
        if (dual) push_tok(e + 8, sb, to, 1);
        wg_wait<1>(); p_arrive_at(sb + B_FA, 0, lead);
        mbar_wait(sb + B_MF + 16, t & 1, budget);
        wg_fence(); seq_mem<32, 48>(m, w, dw); wg_commit();
        if (dual) push_tok(e + 12, sb, to + 640, 1);
        wg_wait<1>(); p_arrive_at(sb + B_FA + 8, 0, lead);
        const uint32_t r0 = mapa(sb, t >= NSEG), r1 = mapa(sb, 1), m0 = r0 + ao + lane * 4, m1 = r1 + ao + lane * 4;
        uint64_t q0 = pair(m0, r0 + B_AB), q1 = pair(m0 + 640, r0 + B_AB), q2 = pair(m1, r1 + B_AB), q3 = pair(m1 + 640, r1 + B_AB);
        pin2(q0, q1); pin2(q2, q3);
        mbar_wait(sb + B_MF + 24, t & 1, budget);
        wg_fence(); seq_mem<48, 64>(m, w, dw); wg_commit();
        wg_wait<1>(); p_arrive_at(sb + B_FA + 16, 0, lead);
        wg_wait<0>();
        const uint32_t a0 = pack_bf16(m[0], m[1]), a1 = pack_bf16(m[2], m[3]), a2 = pack_bf16(m[4], m[5]), a3 = pack_bf16(m[6], m[7]);
        st_async32(q0, t < NSEG ? a0 : a2); st_async32(q1, t < NSEG ? a1 : a3);
        if (dual) { st_async32(q2, a2); st_async32(q3, a3); }
        p_arrive(sb + B_PD, threadIdx.x == 0);
      }
      RPROF(2 + wg * 12);
      if (t == 0) mbar_wait(sb + B_WO, 0, budget);
      mbar_wait(sb + B_WT + wg * 8, t & 1, budget);
      const int seg = t - rank * LAG;
      constexpr float SC = 0.08838834764831845f * 1.4426950408889634f;
      if (rank < 2 && (unsigned)seg < (unsigned)NSEG) {
        float s[32];
        if (wg) {
          const uint32_t pw = sb + PB + lane * 4, o = OB + (lane >> 4) * 2048 + warp * 512 + rank * 256 + (lane & 15) * 16;
          const uint32_t r0 = mapa(sb, 0), r1 = mapa(sb, 1), r2 = mapa(sb, 2);
          uint64_t q0 = pair(r0 + o, r0 + B_OB), q1 = pair(r1 + o, r1 + B_OB), q2 = pair(r2 + o, r2 + B_OB);
          uint32_t one[4];
#pragma unroll
          for (int i = 0; i < 4; i++) one[i] = 0x3F803F80u + (pw >> 31);
          pin2(q0, q1); pin2(q2, (uint64_t)pw);
          mbar_wait_cluster(sb + B_AB, seg & 1, budget);
          fence_proxy_async();
          RPROF(3 + 12);
          wg_fence(); seq_s<D_QM, 0>(s); wg_commit();
          nbar_arrive<NB_P, 256>();
          if (warp == 1) sts32(pw + 640, 0);
          wg_wait<0>();
          float mx = fmaxf(fmaxf(fmaxf(s[0], s[1]), fmaxf(s[4], s[5])), fmaxf(fmaxf(fmaxf(s[8], s[9]), fmaxf(s[12], s[13])), fmaxf(s[16], s[17])));
          const float x1 = __shfl_xor_sync(0xffffffffu, mx, 1), x2 = __shfl_xor_sync(0xffffffffu, mx, 2), x3 = __shfl_xor_sync(0xffffffffu, mx, 3);
          const float u = (warp & 2) ? ((warp & 1) ? s[16] : s[12]) : ((warp & 1) ? s[8] : s[4]);
          const float v = (warp & 2) ? ((warp & 1) ? s[17] : s[13]) : ((warp & 1) ? s[9] : s[5]);
          const float ms = -SC * fmaxf(fmaxf(mx, x1), fmaxf(x2, x3));
          sts32(pw + 128 + warp * 128, pack_bf16(ex2(fmaf(u, SC, ms)), ex2(fmaf(v, SC, ms))));
          if (warp == 0) sts32(pw, pack_bf16(ex2(fmaf(s[0], SC, ms)), ex2(fmaf(s[1], SC, ms))));
          fence_proxy_async();
          nbar_sync<NB_W1, 128>();
          RPROF(4 + 12);
          wg_fence();
          rs8<0, 0, D_P>(s + 8, one); rs8<1, 0, D_P + 16>(s + 8, one); rs8<1, 0, D_P + 32>(s + 8, one);
          wg_commit();
          ss8<0, 0, 0, D_V, D_P>(s, 0); ss8<0, 0, 0, D_V + 320, D_P>(s + 4, 0);
          ss8<1, 0, 0, D_V + 16, D_P + 16>(s, 0); ss8<1, 0, 0, D_V + 336, D_P + 16>(s + 4, 0);
          ss8<1, 0, 0, D_V + 32, D_P + 32>(s, 0); ss8<1, 0, 0, D_V + 352, D_P + 32>(s + 4, 0);
          wg_commit();
          wg_wait<1>();
          const float i0 = rcp(s[8]), i1 = rcp(s[9]);
          wg_wait<0>();
          stsm4(sb + o, pack_bf16(s[0] * i0, s[1] * i1), pack_bf16(s[2] * i0, s[3] * i1), pack_bf16(s[4] * i0, s[5] * i1), pack_bf16(s[6] * i0, s[7] * i1));
          __syncwarp();
          const uint4 z = lds128v(sb + o);
          if (t < NSTEP - 1) { st_async128(q2, z); st_async128(rank ? q0 : q1, z); st_async128(rank ? q1 : q0, z); }
        } else {
          const int g = lane >> 2, lim = 8 * (g >> 1) + (g & 1) + 2 * warp - 8 * (lane & 3);
          const uint32_t pw = sb + PB + 768 + warp * 768 + lane * 16;
          char* const og = (char*)(g_ot + rank * O_LAYER) + (size_t)(h * DH + warp * 16 + (lane >> 2)) * (SEQ * 2) + seg * 64 + (lane & 3) * 16;
          pin2(pw, lim); pin2(og, nullptr);
          mbar_wait_cluster(sb + B_AB, seg & 1, budget);
          fence_proxy_async();
          nbar_sync<NB_P, 256>();
          RPROF(3);
          wg_fence(); seq_s<D_QT, 0>(s); wg_commit();
          wg_wait<0>();
#pragma unroll
          for (int i = 0; i < 8; i++) { float& v = s[4 + 4 * (i >> 1) + (i & 1)]; v = i <= lim ? v : -INFINITY; }
          float mx = fmaxf(fmaxf(fmaxf(s[0], s[1]), fmaxf(s[4], s[5])), fmaxf(fmaxf(fmaxf(s[8], s[9]), fmaxf(s[12], s[13])), fmaxf(s[16], s[17])));
          const float x1 = __shfl_xor_sync(0xffffffffu, mx, 1), x2 = __shfl_xor_sync(0xffffffffu, mx, 2), x3 = __shfl_xor_sync(0xffffffffu, mx, 3);
          const float ms = -SC * fmaxf(fmaxf(mx, x1), fmaxf(x2, x3));
#pragma unroll
          for (int i = 0; i < 10; i++) { float& v = s[4 * (i >> 1) + (i & 1)]; v = ex2(fmaf(v, SC, ms)); }
          const float sum = (((s[0] + s[1]) + (s[4] + s[5])) + ((s[8] + s[9]) + (s[12] + s[13]))) + (s[16] + s[17]);
          const float y1 = __shfl_xor_sync(0xffffffffu, sum, 1), y2 = __shfl_xor_sync(0xffffffffu, sum, 2), y3 = __shfl_xor_sync(0xffffffffu, sum, 3);
          const float inv = rcp((sum + y1) + (y2 + y3));
          stsm4(pw, pack_bf16(s[0] * inv, s[1] * inv), pack_bf16(s[4] * inv, s[5] * inv), pack_bf16(s[8] * inv, s[9] * inv), pack_bf16(s[12] * inv, s[13] * inv));
          stsm2(pw + 512, pack_bf16(s[16] * inv, s[17] * inv), 0);
          fence_proxy_async();
          nbar_sync<NB_W0, 128>();
          RPROF(4);
          wg_fence();
          ss32<0, 0, 0, D_V, D_P + 48>(s, 0); ss32<0, 0, 0, D_V + 320, D_P + 48>(s + 16, 0);
          ss32<1, 0, 0, D_V + 16, D_P + 64>(s, 0); ss32<1, 0, 0, D_V + 336, D_P + 64>(s + 16, 0);
          ss32<1, 0, 0, D_V + 32, D_P + 80>(s, 0); ss32<1, 0, 0, D_V + 352, D_P + 80>(s + 16, 0);
          wg_commit();
          wg_wait<0>();
#pragma unroll
          for (int i = 0; i < 4; i++) {
            const float* d = s + (i >> 1) * 16 + (i & 1) * 2;
            stg128(og + ((i >> 1) * 64 + (i & 1) * 8) * (SEQ * 2), pack_bf16(d[0], d[1]), pack_bf16(d[4], d[5]), pack_bf16(d[8], d[9]), pack_bf16(d[12], d[13]));
          }
          nbar_arrive<NB_O, 160>();
        }
      }
      RPROF(5 + wg * 12);
      char* const p = (char*)g_h1 + ((wo_tile(rank, wg, 0) * 4 + warp) * 4 + (lane >> 3)) * 2048 + h * 64 + (lane & 7) * 8;
      const bool three = wg == 1 || rank == 2;
      if (t < NSTEP - 1) {
        float c[24];
        const uint32_t dt = wg ? 0 : 3072;
        const int o3 = (wo_tile(rank, wg, 2) - wo_tile(rank, wg, 0)) * 32768;
        char* const p1 = p + (t & 1) * sizeof(g_h1[0]);
        char* const p2 = p + (2 + ((t - LAG) & 1)) * sizeof(g_h1[0]);
        char* const p3 = p1 + o3;
        char* const p4 = p2 + o3;
        pin2(p1, p2); pin2(p3, p4);
        if (warp == 2) mbar_wait(sb + B_XF, cx.par, budget);
        mbar_wait_cluster(sb + B_OB, t & 1, budget);
        fence_proxy_async();
        RPROF(6 + wg * 12);
        wg_fence(); seq_wo<0, 0>(c, dt); wg_commit(); seq_wo<1, 0>(c + 8, dt); wg_commit();
        wg_wait<1>();
        if (warp == 2) load_x_lent(sb, &M, t + 1, wg ? 3 : 5);
        put_part(p1, p2, c, t);
        if (three) {
          wg_fence(); seq_wo<2, 0>(c + 16, dt); wg_commit();
          wg_wait<1>(); put_part(p1 + 6 * 32768, p2 + 6 * 32768, c + 8, t);
          wg_wait<0>(); put_part(p3, p4, c + 16, t);
        } else { wg_wait<0>(); put_part(p1 + 6 * 32768, p2 + 6 * 32768, c + 8, t); }
        p_arrive_at(sb + B_FO, 1, lead);
      } else {
        for (int i = 0; i < (three ? 3 : 2); i++) stg_rlx64(p + 3 * sizeof(g_h1[0]) + (wo_tile(rank, wg, i) - wo_tile(rank, wg, 0)) * 32768, 0, 0);
      }
      RPROF(7 + wg * 12);
    }
    const int n = t + 1;
    if (n >= LAG && n < NSEG) {
      float d[32];
      tok_pass<true, 0>(d, w, dw, cx, n, budget);
      pack_tok(e, d + 16); pack_tok(e + 8, d);
    } else {
      float d[16];
      if (n == NSTEP) break;
      tok_pass<false, 0>(d, w, dw, cx, n, budget);
      pack_tok(e, d);
#pragma unroll
      for (int i = 8; i < 16; i++) e[i] = 0;
    }
    RPROF(8 + wg * 12);
  }
}

DEVI void wait_xa(const int* p, int& budget) {
  while (__any_sync(0xffffffffu, ldg_acq32(p) < 64) && --budget > 0) {}
  fence_proxy_global();
}
template<bool DUAL> DEVI void first_loads(uint32_t sb, const Maps* M, int n, int h, int& budget) {
#pragma unroll
  for (int i = 0; i < PFN; i++) {
    if (DUAL) e_prefetch_3d(&M->xd, ((h + i * (16 / PFN)) & 15) * 64, (n - LAG) * 32, 0);
    else e_prefetch_3d(&M->xs, 0, (n < NSEG ? n : n - LAG) * 32, ((h + i * (8 / PFN)) & 7) * 2);
  }
  mbar_wait(sb + B_FA, n & 1, budget); load_x<DUAL, 0>(sb, M, n);
  mbar_wait(sb + B_FA + 8, n & 1, budget); load_x<DUAL, 1>(sb, M, n);
  mbar_wait(sb + B_FA + 16, n & 1, budget); load_x<DUAL, 2>(sb, M, n);
}
template<bool DUAL> DEVI void lent_loads(uint32_t sb, const Maps* M, int n, int& budget) {
  mbar_wait(sb + B_FB, n & 1, budget);
  load_x<DUAL, 3>(sb, M, n); load_x<DUAL, 4>(sb, M, n); load_x<DUAL, 5>(sb, M, n); load_x<DUAL, 6>(sb, M, n);
}
DEVI void rec_comm(const uint32_t sb, const int warp, const Maps& M, const bf16* __restrict__ mem0) {
  const int lane = threadIdx.x & 31, h = cluster_id(), rank = cluster_rank();
  int budget = SPIN_BUDGET;
  const bool two = warp == 3 || (rank == 2 && warp == 2);
  const int ntask = two ? 2 : 1, qi = two ? (warp == 3 ? rank : 3) : rank * 3 + warp;
  const int task0 = two ? h * 2 + (qi >> 1) : 64 + h * 4 + (qi >> 1);
  auto h2_word = [&](int i, int ln) {
    const int task = task0 + i * 192;
    return (char*)g_h2 + (task >> 2) * 512 + ((qi ^ i) & 1) * 256 + (task & 3) * 32 + (ln & 8) * 16 + (ln & 7) * 4;
  };
  auto first_x = [&](int t) {
    const int n = t + 1;
    p_expect_tx(sb + B_XF + (lane_id() & 7) * 8, 8192, lane_id() < 8);
    if (rank == 0) {
      if (n < NSEG && (n & 3) == 0) wait_xa(&g_xa[0][n >> 2], budget);
      if (n >= LAG && ((n - LAG) & 3) == 0) wait_xa(&g_xa[1][(n - LAG) >> 2], budget);
      if (n >= LAG && n < NSEG) first_loads<true>(sb, &M, n, h, budget); else first_loads<false>(sb, &M, n, h, budget);
    }
  };
  {
    const int task = task0 + (lane >> 4) * 192, L = (task & 3) * 8 + (lane & 7);
    if ((lane >> 4) < ntask) {
      const bf16* p = mem0 + (L & 3) * 2 * DM + (task >> 2) * 16 + (L >> 2) + (lane & 8);
      uint32_t m0 = (uint32_t)__bfloat16_as_ushort(p[0]) | (uint32_t)__bfloat16_as_ushort(p[DM]) << 16;
      m0 = m0 ? m0 : 0x8000u;
      stg_rlx32(h2_word(lane >> 4, lane), m0);
      sts32(sb + M0 + warp * 128 + lane * 4, m0);
    }
    __syncwarp();
    nbar_sync<NB_ST, 384>();
    if (warp == 2) {
      e_expect_tx(sb + B_WS, 2 * WSZ);
#pragma unroll 1
      for (int i = 0; i < 2 * (64 - KR); i++) e_tma_2d(sb + WS + (i & 1) * WSZ + (i >> 1) * 2048, &M.w[rank], h * DH + (i & 1) * 64, k_of_smem(i >> 1) * 16, sb + B_WS);
      const int nt = rank == 2 ? 6 : 5;
      e_expect_tx(sb + B_WO, (nt - 2) * 16384);
#pragma unroll 1
      for (int i = 1; i < nt; i++) if (i != 3) e_tma_2d(sb + WO + i * 16384, &M.wo, wo_tile(rank, 1 - i / 3, i % 3) * 64, h * DH, sb + B_WO);
    }
    if (warp == 3) { first_x(-1); if (rank == 0) lent_loads<false>(sb, &M, 0, budget); }
  }
  uint32_t t0 = gtime() - 4000, cpp = 0;
  const uint32_t cp = sb + B_CP + warp * 8;
#pragma unroll 1
  for (int t = 0;; t++) {
    const int n = t + 1, seg = t - rank * LAG;
    RPROF_STEP;
    const bool att = rank < 2 && (unsigned)seg < (unsigned)NSEG;
    if (warp == 3) {
      if (att) e_expect_tx(sb + B_AB, 30720);
      if (n < NSTEP) e_expect_tx(sb + B_OB, t < NSEG && t >= LAG ? 4096 : 2048);
    }
    {
      const uint32_t dst = sb + RING + warp * 8192;
      mbar_wait(sb + B_ME + warp * 8, t & 1, budget);
      wait_time(t0 + TP(1) + warp * TP(4));
      const int lane = lane_id();
      RPROF(24); CPROF(0, gtime());
      int tries = 0;
      while (true) {
        tries++;
        e_expect_tx(cp, 8192);
        e_bulk_g2s(dst, (const char*)g_h2[t & 3] + warp * 8192, 8192, cp);
        mbar_wait(cp, cpp, budget); cpp ^= 1;
        uint32_t mn = 0xffffffffu;
#pragma unroll
        for (int i = 0; i < 8; i++) mn = min(mn, lds32v(dst + i * 1024 + lane * 32 + (lane >> 2) * 4));
        if (!__any_sync(0xffffffffu, mn == 0) || --budget < 0) break;
      }
      e_arrive(sb + B_MF + warp * 8);
      RPROF(25); CPROF(1, gtime()); CPROF(2, tries);
    }
    {
      const int ln = lane_id(), i = ln >> 4;
      char* const w = h2_word(i, ln);
      if (i < ntask) {
        stg_rlx32(w + ((t + 3) & 3) * sizeof(g_h2[0]), 0);
        if (n < NSTEP && (((qi ^ i) & 1) ? t < LAG : t >= NSEG)) stg_rlx32(w + (n & 3) * sizeof(g_h2[0]), lds32v(sb + M0 + warp * 128 + ln * 4));
      }
      __syncwarp();
    }
    if (n < NSTEP) {
      const uint32_t tag = (n >> 1) & 31;
      if (warp == 3) first_x(t);
      mbar_wait(sb + B_PD, t & 1, budget);
      t0 = clock32();
      if (warp == 0 && rank == (t >= NSEG)) { mbar_wait(sb + B_AB, seg & 1, budget); e_stg_rlx32(&g_ts[t & 1][h * TSS], (gtime() & ~31u) | tag); }
      spin_until(t0, TSD);
      uint32_t v;
      do { v = ldg_rlx32(&g_ts[t & 1][lane_id() * TSS]); } while (__any_sync(0xffffffffu, (v & 31) != tag) && --budget > 0);
      const uint32_t now = __shfl_sync(0xffffffffu, v, 0);
      t0 = now + __reduce_max_sync(0xffffffffu, (int)(v - now));
      if (warp == 3) mbar_wait(sb + B_OB, t & 1, budget);
    }
    if (n < NSTEP) {
      RPROF(26); CPROF(3, t0);
#pragma unroll 1
      for (int i = 0; i < ntask; i++) {
        const int layer = (qi ^ i) & 1, sg = t - layer * LAG, task = task0 + i * 192;
        if ((unsigned)sg >= (unsigned)NSEG) continue;
        const uint32_t tag = h1_tag(sg);
        const int ln = lane_id();
        const char* const src = (const char*)g_h1[layer * 2 + (sg & 1)] + task * 2048 + ln * 8;
        char* const dst = h2_word(i, ln) + (n & 3) * sizeof(g_h2[0]);
        uint2 v[8];
        pin2(src, dst);
        wait_time(t0 + TP(0) + (task < 96 ? 0 : task < 192 ? TP(3) : 2 * TP(3)));
        int tries = 0;
        float a[4];
        while (true) {
          tries++;
#pragma unroll
          for (int k = 0; k < 8; k++) v[k] = ldg_rlx64(src + k * 256);
          uint32_t bad = 0;
#pragma unroll
          for (int k = 0; k < 8; k++) {
            bad = xor_or(v[k].x, tag, bad);
            a[0] = k ? a[0] + bf_lo(v[k].x) : bf_lo(v[k].x); a[1] = k ? a[1] + bf_hi(v[k].x) : bf_hi(v[k].x);
            a[2] = k ? a[2] + bf_lo(v[k].y) : bf_lo(v[k].y); a[3] = k ? a[3] + bf_hi(v[k].y) : bf_hi(v[k].y);
          }
#pragma unroll
        for (int k = 0; k < 2; k++) {
          const float keep = (ln & 8) ? a[2+k] : a[k], send = (ln & 8) ? a[k] : a[2+k];
          a[k] = keep + __shfl_xor_sync(0xffffffffu, send, 8);
        }
#pragma unroll
        for (int k = 0; k < 2; k++) a[k] += __shfl_xor_sync(0xffffffffu, a[k], 16);
          if (!__any_sync(0xffffffffu, bad & 1) || --budget < 0) break;
        }
        const uint32_t out = pack_bf16(a[0], a[1]);
        if (ln < 16) stg_rlx32(dst, out ? out : 0x8000u);
        __syncwarp();
        if (i == 0) { RPROF(28); CPROF(6, gtime()); CPROF(4, gtime()); CPROF(5, tries); } else CPROF(7, gtime());
      }
    }
    if (warp == 1 && att) { nbar_sync<NB_O, 160>(); e_flag_add(&g_dep[E_O1 + rank * 16 + (seg >> 2)]); }
    if (n == NSTEP) break;
  }
  if (h == 0 && rank == 0 && warp < 2) g_xa[warp][lane_id()] = 0;
}
}

__global__ void __cluster_dims__(3, 1, 1) __launch_bounds__(384, 1)
rec_kernel(const __grid_constant__ rec::Maps M, const bf16* __restrict__ mem0) {
  using namespace rec;
  extern __shared__ __align__(1024) uint8_t smem[];
  const uint32_t sb = __shfl_sync(0xffffffffu, smem_u32(smem), 0);
  const int tid = threadIdx.x, wi = __shfl_sync(0xffffffffu, tid >> 5, 0);
  if ((sb & 0x3FFFF) != SMEM_BASE) __trap();
  if (wi == 0) {
    const int h = cluster_id(), rank = cluster_rank();
    for (int i = tid; i < NBAR; i += 32) mbar_init(sb + BARS + i * 8, i < 13 ? 6 : i < 19 ? 2 : 1);
    ((uint32_t*)(smem + PAD))[tid] = 0;
    fence_mbar_init(); fence_proxy_async();
    __syncwarp();
    e_expect_tx(sb + B_ST, STG); e_expect_tx(sb + B_ST + 8, STG);
    for (int i = 0; i < 2 * KR; i++) e_tma_2d(sb + (i & 1) * STG + (i >> 1) * 2048, &M.w[rank], h * DH + (i & 1) * 64, k_of_reg(i >> 1) * 16, sb + B_ST + (i & 1) * 8);
  } else if (wi == 1) {
    if (blockIdx.x < NEV / 32) { g_dep[blockIdx.x * 32 + (tid & 31)] = 0; g_claim[blockIdx.x * 32 + (tid & 31)] = 0; __threadfence(); }
    __syncwarp();
    asm volatile("griddepcontrol.launch_dependents;" ::: "memory");
  }
  cluster_arrive(); cluster_wait();
  if (wi < 8) { reg_inc<232>(); rec_math(sb, wi, M); cluster_arrive(); cluster_wait(); }
  else { reg_dec<40>(); rec_comm(sb, wi & 3, M, mem0); cluster_arrive(); cluster_wait(); }
}

namespace gm {
struct Maps { CUtensorMap ot, wo, xn, wg, wu, hl, hs, wd, out; };
constexpr int STAGES = 6, STAGE = 32768;
constexpr uint32_t SO = STAGES * STAGE, BARS = SO + 32768;
constexpr uint32_t B_FULL = BARS, B_EMPTY = BARS + 48, B_TF = BARS + 96, B_TE = BARS + 112, B_ORD = BARS + 128, B_PM = BARS + 144, B_GO = BARS + 160;
constexpr uint32_t MAIL = BARS + 176, PMAIL = BARS + 192;
constexpr uint32_t SMEM = BARS + 256;
constexpr int END = -1;

struct Tile {
  bool isO, isG, l2; int blk, col, k0, n;
  DEVI Tile(int task, int rank) {
    const int e = task >> 8, id = task & 255;
    const bool isD = e < E_G1 || e >= E_D2;
    isO = e >= E_O1 && e < E_G2; isG = !isD && !isO; l2 = e >= E_O2;
    blk = isG && l2 ? (e & 15) * 2 + rank : isD && !l2 ? e >> 1 : e & 15;
    col = isG ? (l2 ? id : id * 2 + rank) : (id & 3) * 2 + rank;
    k0 = isO ? (id >> 2) * 2048 : isG ? 0 : ((l2 ? e >> 4 : e) & 1) * 1792;
    n = isO ? 32 : isG ? 16 : 28;
  }
};

DEVI float geglu(float g, float u) {
  const float z = g * (0.7978845608028654f + 0.035677408136300125f * g * g);
  float t; asm("tanh.approx.f32 %0, %1;" : "=f"(t) : "f"(z));
  const float hg = 0.5f * g;
  return fmaf(hg, t, hg) * u;
}
struct Sched {
  int need, size;
  bool filler;
  uint4 dep, cl;
  DEVI void init(int lane) {
    const int e = lane * 4;
    const bool d = e < E_G1 || e >= E_D2, o = e >= E_O1 && e < E_G2;
    need = d ? 28 : e < E_O1 ? 64 : 128;
    size = d ? 4 : o ? 8 : e < E_O1 ? 28 : e < E_G2 + 8 ? 56 : 0;
    filler = (int)blockIdx.x < TP(5);
  }
  DEVI void scan(int lane) { cl = ldg_rlx128(g_claim + lane * 4); dep = ldg_rlx128(g_dep + lane * 4); }
  DEVI int next(int lane, int& budget) {
    while (--budget > 0) {
      int av[4], open = 0;
#pragma unroll
      for (int i = 0; i < 4; i++) { const int r = max(size - (int)(&cl.x)[i], 0); open |= r; av[i] = ((int)(&dep.x)[i] >= need ? r : 0) + (i ? av[i - 1] : 0); }
      const uint32_t mo = __ballot_sync(0xffffffffu, open);
      if (!mo) break;
      if (!filler && (mo & TP(6)) && lane >= E_O2 / 4) av[3] = 0;
      int inc = av[3], pos = 0;
      while (true) {
        const uint32_t m = __ballot_sync(0xffffffffu, inc > pos && av[3]);
        if (!m) break;
        const int l = __ffs(m) - 1, rel = pos - (inc - av[3]), i = (rel >= av[0]) + (rel >= av[1]) + (rel >= av[2]);
        int r = 0;
        if (lane == l) {
          const int tk = atomicAdd(g_claim + lane * 4 + i, 1);
          r = tk < size ? (lane * 4 + i) << 8 | tk : -1 - (inc - av[3] + (i == 0 ? av[0] : i == 1 ? av[1] : i == 2 ? av[2] : av[3]) + tk - size);
        }
        r = __shfl_sync(0xffffffffu, r, l);
        if (r >= 0) return r;
        if (pos == 0) {
#pragma unroll
          for (int o = 1; o < 32; o <<= 1) { const int v = __shfl_up_sync(0xffffffffu, inc, o); if (lane >= o) inc += v; }
        }
        pos = -1 - r;
      }
      if (pos == 0) __nanosleep(TP(7));
      scan(lane);
    }
    return END;
  }
};

DEVI void scheduler(const uint32_t sb) {
  const int lane = threadIdx.x & 31;
  int budget = SPIN_BUDGET;
  Sched sc; sc.init(lane);
#pragma unroll 1
  for (int i = 0;; i++) {
    mbar_wait(sb + B_GO, (i & 1) ^ 1, budget);
    sc.scan(lane);
    const int task = sc.next(lane, budget);
    const uint32_t r = mapa(sb, lane & 1);
    if (lane < 2) st_async32(r + PMAIL + (i & 1) * 4, task, r + B_PM + (i & 1) * 8);
    __syncwarp();
    if (task == END) break;
  }
}

DEVI void producer(const uint32_t sb, const Maps& M) {
  const int lane = threadIdx.x & 31, rank = cluster_rank();
  int budget = SPIN_BUDGET, s = 0, ph = 0;
#pragma unroll 1
  for (int i = 0;; i++) {
    e_expect_tx(sb + B_PM + (i & 1) * 8, 4);
    mbar_wait_cluster(sb + B_PM + (i & 1) * 8, (i >> 1) & 1, budget);
    const int task = budget < 0 ? END : __shfl_sync(0xffffffffu, (int)lds32v(sb + PMAIL + (i & 1) * 4), 0);
    fence_proxy_global();
    for (int z = 0; z < (task == END ? 2 : 1); z++) {
      const int g = (i + z) & 1;
      mbar_wait(sb + B_TE + g * 8, (((i + z) >> 1) & 1) ^ 1, budget);
      if (lane == 0) { sts64(sb + MAIL + g * 8, task, s | ph << 8); mbar_arrive(sb + B_TF + g * 8); }
      __syncwarp();
    }
    if (task == END) break;
    const Tile T(task, rank);
    const bool shareB = T.isG && T.l2;
    const CUtensorMap* mA = T.isO ? &M.ot : T.isG ? &M.xn : &M.hl;
    const CUtensorMap* mB0 = T.isO ? &M.wo : T.isG ? &M.wg : &M.wd;
    const CUtensorMap* mB1 = T.isG ? &M.wu : mB0;
    const int c0 = T.col * (T.isG ? 64 : 128), c1 = T.isG ? c0 : c0 + 64, row = T.blk * 128;
    const int ok = 0;
    int k = T.k0;
#pragma unroll 1
    for (int it = 0; it < T.n; it++, k += 64) {
      const uint32_t a = sb + s * STAGE, fb = sb + B_FULL + s * 8;
      mbar_wait(sb + B_EMPTY + s * 8, ph ^ 1, budget);
      e_expect_tx(fb, STAGE);
      if (shareB) {
        e_tma_2d_mc(a + 16384 + rank * 8192, rank ? mB1 : mB0, c0, k, fb);
        e_tma_2d(a, mA, k, row, fb); e_tma_2d(a + 8192, mA, k, row + 64, fb);
      } else {
        e_tma_2d_mc(a + rank * 8192, mA, T.isO ? row + rank * 64 : k, T.isO ? k + ok : row + rank * 64, fb);
        e_tma_2d(a + 16384, mB0, c0, k, fb); e_tma_2d(a + 24576, mB1, c1, k, fb);
      }
      if (it == T.n - TP(2)) e_arrive(sb + B_GO);
      if (++s == STAGES) { s = 0; ph ^= 1; }
    }
  }
}

template<int TA> DEVI void mainloop(float* d0, float* d1, uint32_t sb, int n, int s, int ph, bool lead, uint32_t ord, int& budget) {
  int prev = 0;
  const uint32_t rel = threadIdx.x & 127;
#pragma unroll 1
  for (int i = 0; i < n; i++) {
    mbar_wait(sb + B_FULL + s * 8, ph, budget);
    const uint32_t a = sb + s * STAGE;
    const uint64_t da = mkdesc(a, 16, 1024), db = mkdesc(a + 16384, 8192, 1024);
    wg_fence();
#pragma unroll
    for (int k = 0; k < 4; k++) {
      wgmma_n128<TA>(d0, da + k * (TA ? 128 : 2), db + k * 128, (i | k) != 0);
      wgmma_n128<TA>(d1, da + 512 + k * (TA ? 128 : 2), db + k * 128, (i | k) != 0);
    }
    wg_commit();
    if (i > 0) { wg_wait<1>(); p_arrive_at(sb + B_EMPTY + prev * 8, rel & 1, rel < 2); }
    prev = s;
    if (++s == STAGES) { s = 0; ph ^= 1; }
  }
  p_arrive(ord, lead);
  wg_wait<0>();
  p_arrive_at(sb + B_EMPTY + prev * 8, rel & 1, rel < 2);
}

DEVI void consumer(const uint32_t sb, const Maps& M, const int wg) {
  const int tid = threadIdx.x, lane = tid & 31, warp = (tid >> 5) & 3;
  const bool lead = (tid & 127) == 0;
  const uint32_t so = sb + SO + wg * 16384;
  int budget = SPIN_BUDGET;
  float d0[64], d1[64];
#pragma unroll 1
  for (int m = 0;; m++) {
    mbar_wait(sb + B_TF + wg * 8, m & 1, budget);
    const uint2 mail = lds64v(sb + MAIL + wg * 8);
    const int task = __shfl_sync(0xffffffffu, (int)mail.x, 0), pos = __shfl_sync(0xffffffffu, (int)mail.y, 0);
    e_arrive(sb + B_TE + wg * 8);
    if (task == END || budget < 0) break;
    const Tile T(task, cluster_rank());
    mbar_wait(sb + B_ORD + wg * 8, (m & 1) ^ wg ^ 1, budget);
    if (T.isO) mainloop<1>(d0, d1, sb, 32, pos & 255, pos >> 8, lead, sb + B_ORD + (wg ^ 1) * 8, budget);
    else mainloop<0>(d0, d1, sb, T.n, pos & 255, pos >> 8, lead, sb + B_ORD + (wg ^ 1) * 8, budget);
    const uint32_t st = so + (warp * 16 + (lane & 15)) * 128;
    if (T.isG) {
#pragma unroll
      for (int mm = 0; mm < 2; mm++) {
        const float* d = mm ? d1 : d0;
#pragma unroll
        for (int c = 0; c < 4; c++) {
          uint32_t r[4];
#pragma unroll
          for (int i = 0; i < 4; i++) r[i] = pack_bf16(geglu(d[8*c+2*i], d[32+8*c+2*i]), geglu(d[8*c+2*i+1], d[33+8*c+2*i]));
          stsm4(st + mm * 8192 + (((2 * c + (lane >> 4)) ^ (lane & 7)) << 4), r[0], r[1], r[2], r[3]);
        }
      }
      fence_proxy_async();
      nbar_sync_r(1 + wg, 128);
      if (lead) {
        tma_store_2d(&M.hs, so, T.col * 64, T.blk * 128);
        bulk_commit(); bulk_wait<0>();
        flag_add(&g_dep[T.l2 ? E_D2 + (T.col >= 28) * 16 + T.blk : E_D1 + T.blk * 2 + (T.col >= 28)]);
      }
    } else {
#pragma unroll
      for (int hf = 0; hf < 2; hf++) {
        if (hf) { if (lead) bulk_wait_read<0>(); nbar_sync_r(1 + wg, 128); }
#pragma unroll
        for (int mm = 0; mm < 2; mm++) {
          const float* d = (mm ? d1 : d0) + hf * 32;
#pragma unroll
          for (int c = 0; c < 4; c++)
            stsm4(st + mm * 8192 + (((2 * c + (lane >> 4)) ^ (lane & 7)) << 4), pack_bf16(d[8*c], d[8*c+1]), pack_bf16(d[8*c+2], d[8*c+3]),
                  pack_bf16(d[8*c+4], d[8*c+5]), pack_bf16(d[8*c+6], d[8*c+7]));
        }
        fence_proxy_async();
        nbar_sync_r(1 + wg, 128);
        if (lead) { tma_radd_2d(&M.out, so, T.col * 128 + hf * 64, T.blk * 128); bulk_commit(); }
      }
      if (lead) {
        bulk_wait<0>();
        if (T.isO || !T.l2) flag_add(&g_dep[(!T.isO ? E_LX2 : T.l2 ? E_LX1B : E_LX1A) + T.blk]);
      }
    }
    __syncwarp();
  }
}

DEVI void norm_helper(const bf16* __restrict__ x, bf16* out) {
  const int lane = threadIdx.x & 31;
  int budget = SPIN_BUDGET, tk = lane < 4 ? -1 : 1024;
#pragma unroll 1
  while (--budget > 0) {
    if (tk < 0) tk = atomicAdd(g_claim + E_LI + lane, 1);
    if (__all_sync(0xffffffffu, tk >= 1024)) break;
    const uint32_t m = __ballot_sync(0xffffffffu, tk < 1024 && (lane == 0 || ldg_acq32(g_dep + E_LI + lane * 16 + (tk >> 6)) >= 16));
    if (!m) { __nanosleep(TP(7)); continue; }
    const int ql = __ffs(m) - 1, task = __shfl_sync(0xffffffffu, tk, ql), q = E_LI + ql * 16, ev = task >> 6;
    if (lane == ql) tk = -1;
    const size_t off = (size_t)task * (DM * 4) + lane * 16;
    const char* src = (const char*)(q == E_LI ? x : out) + off;
    uint4 u[8];
#pragma unroll
    for (int i = 0; i < 8; i++) u[i] = ldg_rlx128(src + i * 512);
    if (q == E_LI) {
#pragma unroll
      for (int i = 0; i < 8; i++) stg128((char*)out + off + i * 512, u[i].x, u[i].y, u[i].z, u[i].w);
    }
    float mean[2], rs[2];
#pragma unroll
    for (int r = 0; r < 2; r++) {
      float s0 = 0, s1 = 0;
#pragma unroll
      for (int i = 0; i < 16; i++) { const uint32_t v = (&u[4*r + (i >> 2)].x)[i & 3]; s0 += bf_lo(v); s1 += bf_hi(v); }
      mean[r] = (s0 + s1) * (1.f / 32);
      s0 = s1 = 0;
#pragma unroll
      for (int i = 0; i < 16; i++) { const uint32_t v = (&u[4*r + (i >> 2)].x)[i & 3]; const float a = bf_lo(v) - mean[r], b = bf_hi(v) - mean[r]; s0 = fmaf(a, a, s0); s1 = fmaf(b, b, s1); }
      rs[r] = s0 + s1;
    }
    {
      const bool hi = lane & 16;
      float m1 = hi ? mean[1] : mean[0], q1 = hi ? rs[1] : rs[0], m2 = hi ? mean[0] : mean[1], q2 = hi ? rs[0] : rs[1], cnt = 16;
#pragma unroll
      for (int o = 16; o; o >>= 1) {
        m2 = __shfl_xor_sync(0xffffffffu, m2, o); q2 = __shfl_xor_sync(0xffffffffu, q2, o);
        const float dl = m1 - m2;
        q2 = q1 = fmaf(dl * dl, cnt, q1 + q2); m2 = m1 = 0.5f * (m1 + m2);
        cnt *= 2;
      }
      q1 = rsqrtf(q1 * (1.f / DM) + 1e-5f);
      m2 = __shfl_xor_sync(0xffffffffu, m1, 16); q2 = __shfl_xor_sync(0xffffffffu, q1, 16);
      mean[0] = hi ? m2 : m1; mean[1] = hi ? m1 : m2; rs[0] = hi ? q2 : q1; rs[1] = hi ? q1 : q2;
    }
#pragma unroll
    for (int i = 0; i < 8; i++) {
      uint32_t y[4];
#pragma unroll
      for (int c = 0; c < 4; c++) { const uint32_t v = (&u[i].x)[c]; y[c] = pack_bf16((bf_lo(v) - mean[i >> 2]) * rs[i >> 2], (bf_hi(v) - mean[i >> 2]) * rs[i >> 2]); }
      stg128((char*)g_xn + off + i * 512, y[0], y[1], y[2], y[3]);
    }
    fence_proxy_global();
    __syncwarp();
    if (lane == 0) flag_add(q == E_LI ? &g_xa[0][ev] : q == E_LX2 ? &g_xa[1][ev] : &g_dep[q == E_LX1A ? E_G1 + ev : E_G2 + (ev >> 1)]);
    __syncwarp();
  }
}
}

__global__ void __cluster_dims__(2, 1, 1) __launch_bounds__(384, 1)
gemm_kernel(const __grid_constant__ gm::Maps M, const bf16* __restrict__ x, bf16* out) {
  using namespace gm;
  extern __shared__ __align__(1024) uint8_t smem[];
  const uint32_t sb = __shfl_sync(0xffffffffu, smem_u32(smem), 0);
  const int tid = threadIdx.x, wi = __shfl_sync(0xffffffffu, tid >> 5, 0);
  if (tid < 21) mbar_init(sb + BARS + tid * 8, tid == 14 || tid == 15 ? 4 : tid >= 6 && tid < 12 ? 2 : 1);
  fence_mbar_init();
  cluster_arrive(); cluster_wait();
  if (wi < 8) { reg_inc<208>(); consumer(sb, M, wi >> 2); cluster_arrive(); cluster_wait(); }
  else {
    reg_dec<88>();
    if (wi == 8) producer(sb, M);
    else if (wi == 11 && cluster_rank() == 0) scheduler(sb);
    else {
      norm_helper(x, out);
      asm volatile("griddepcontrol.wait;" ::: "memory");
      if (wi == 9 && blockIdx.x < 64) g_h2[(NSTEP - 1) & 3][blockIdx.x * 32 + (tid & 31)] = make_uint4(0, 0, 0, 0);
    }
    __syncwarp();
    cluster_arrive(); cluster_wait();
  }
}

typedef CUresult (*PFN_encodeTiled)(CUtensorMap*, CUtensorMapDataType, cuuint32_t, void*, const cuuint64_t*, const cuuint64_t*,
                                    const cuuint32_t*, const cuuint32_t*, CUtensorMapInterleave, CUtensorMapSwizzle,
                                    CUtensorMapL2promotion, CUtensorMapFloatOOBfill);
static PFN_encodeTiled g_encode = nullptr;
static CUtensorMap make_map(const void* ptr, uint64_t rows, uint64_t cols, uint32_t box_rows) {
  CUtensorMap m;
  cuuint64_t dims[2] = {cols, rows}, strides[1] = {cols * 2};
  cuuint32_t box[2] = {64, box_rows}, es[2] = {1, 1};
  g_encode(&m, CU_TENSOR_MAP_DATA_TYPE_BFLOAT16, 2, (void*)ptr, dims, strides, box, es, CU_TENSOR_MAP_INTERLEAVE_NONE,
           CU_TENSOR_MAP_SWIZZLE_128B, CU_TENSOR_MAP_L2_PROMOTION_L2_256B, CU_TENSOR_MAP_FLOAT_OOB_FILL_NONE);
  return m;
}

static CUtensorMap make_map3(const void* ptr, uint64_t d0, uint64_t d1, uint64_t d2, uint64_t stride2) {
  CUtensorMap m;
  cuuint64_t dims[3] = {d0, d1, d2}, strides[2] = {DM * 2, stride2};
  cuuint32_t box[3] = {64, 32, 2}, es[3] = {1, 1, 1};
  g_encode(&m, CU_TENSOR_MAP_DATA_TYPE_BFLOAT16, 3, (void*)ptr, dims, strides, box, es, CU_TENSOR_MAP_INTERLEAVE_NONE,
           CU_TENSOR_MAP_SWIZZLE_128B, CU_TENSOR_MAP_L2_PROMOTION_L2_256B, CU_TENSOR_MAP_FLOAT_OOB_FILL_NONE);
  return m;
}

extern "C" void kernel_launch(void* const* d_in, const int* in_sizes, int n_in, void* d_out, int out_size) {
  const bf16* x = (const bf16*)d_in[0];
  const bf16* mem0 = (const bf16*)d_in[1];
  if (!g_encode) {
    void* p = nullptr; cudaDriverEntryPointQueryResult q;
    cudaGetDriverEntryPoint("cuTensorMapEncodeTiled", &p, cudaEnableDefault, &q);
    g_encode = (PFN_encodeTiled)p;
    cudaFuncSetAttribute(gemm_kernel, cudaFuncAttributeMaxDynamicSharedMemorySize, gm::SMEM);
    cudaFuncSetAttribute(rec_kernel, cudaFuncAttributeMaxDynamicSharedMemorySize, rec::SMEM);
  }
  bf16 *xn, *ot, *hh;
  cudaGetSymbolAddress((void**)&xn, g_xn); cudaGetSymbolAddress((void**)&ot, g_ot); cudaGetSymbolAddress((void**)&hh, g_h);
  rec::Maps R;
  for (int i = 0; i < 3; i++) R.w[i] = make_map(d_in[2 + i], DM, NH * DH, 16);
  R.wo = make_map(d_in[5], NH * DH, DM, 128);
  R.xd = make_map3(xn, DM, SEQ - LAG * 32, 2, (uint64_t)LAG * 32 * DM * 2); R.xs = make_map3(xn, 64, SEQ, DM / 64, 128);
  gm::Maps G;
  G.ot = make_map(ot, NH * DH + O_LAYER / SEQ, SEQ, 64); G.wo = make_map(d_in[5], NH * DH, DM, 64); G.xn = make_map(xn, SEQ, DM, 64);
  G.wg = make_map(d_in[8], DM, DF, 64); G.wu = make_map(d_in[9], DM, DF, 64); G.hl = make_map(hh, SEQ, DF, 64); G.hs = make_map(hh, SEQ, DF, 128);
  G.wd = make_map(d_in[10], DF, DM, 64); G.out = make_map(d_out, SEQ, DM, 128);
  rec_kernel<<<3 * NH, 384, rec::SMEM, cudaStreamPerThread>>>(R, mem0);
  cudaLaunchConfig_t cfg = {};
  cfg.gridDim = dim3(132); cfg.blockDim = dim3(384); cfg.dynamicSmemBytes = gm::SMEM; cfg.stream = cudaStreamPerThread;
  cudaLaunchAttribute at[1];
  at[0].id = cudaLaunchAttributeProgrammaticStreamSerialization; at[0].val.programmaticStreamSerializationAllowed = 1;
  cfg.attrs = at; cfg.numAttrs = 1;
  cudaLaunchKernelEx(&cfg, gemm_kernel, G, x, (bf16*)d_out);
}
```

```cpp
#include <cuda_runtime.h>
#include <cuda_bf16.h>
#include <cuda.h>
#include <stdint.h>

#define DEVI __device__ __forceinline__
typedef __nv_bfloat16 bf16;

constexpr int SEQ = 2048, DM = 1024, NH = 32, DH = 128, DF = 3584, NSEG = 64;
#define LAG 18
constexpr int NSTEP = NSEG + LAG;

#define TSS 1
#define TSD 1100
constexpr size_t O_LAYER = 0;
__device__ __align__(1024) bf16 g_xn[SEQ * DM];
__device__ __align__(1024) bf16 g_ot[SEQ * NH * DH + O_LAYER];
__device__ __align__(1024) bf16 g_h[SEQ * DF];
__device__ __align__(1024) uint2 g_h1[4][256 * 256];
__device__ __align__(1024) uint4 g_h2[4][2048];
__device__ __align__(128) uint32_t g_ts[2][32 * TSS];
enum { E_D1 = 0, E_G1 = 32, E_O1 = 48, E_O2 = 64, E_G2 = 80, E_D2 = 96,
       E_LI = 128, E_LX2 = 144, E_LX1A = 160, E_LX1B = 176, NEV = 256 };
__device__ __align__(128) int g_dep[NEV];
__device__ __align__(128) int g_claim[NEV];
__device__ __align__(128) int g_xa[2][32];

#define TUNE_DEFAULTS 1550, 2400, 5, 100, 100, 8, 0xffff, 100
constexpr int c_D[8] = {TUNE_DEFAULTS};
template<int I> struct TPV { static constexpr int v = c_D[I]; };
#define TP(i) TPV<i>::v

DEVI uint32_t smem_u32(const void* p) { return (uint32_t)__cvta_generic_to_shared(p); }
DEVI void mbar_init(uint32_t bar, uint32_t cnt) { asm volatile("mbarrier.init.shared::cta.b64 [%0], %1;" :: "r"(bar), "r"(cnt) : "memory"); }
DEVI void mbar_arrive(uint32_t bar) { asm volatile("mbarrier.arrive.shared::cta.b64 _, [%0];" :: "r"(bar) : "memory"); }
DEVI bool mbar_try(uint32_t bar, uint32_t parity) {
  uint32_t p;
  asm volatile("{.reg .pred p; mbarrier.try_wait.parity.shared::cta.b64 p, [%1], %2; selp.u32 %0, 1, 0, p;}" : "=r"(p) : "r"(bar), "r"(parity) : "memory");
  return p;
}
DEVI bool mbar_test(uint32_t bar, uint32_t parity) {
  uint32_t p;
  asm volatile("{.reg .pred p; mbarrier.test_wait.parity.shared::cta.b64 p, [%1], %2; selp.u32 %0, 1, 0, p;}" : "=r"(p) : "r"(bar), "r"(parity) : "memory");
  return p;
}
constexpr int SPIN_BUDGET = 1 << 18;
DEVI void mbar_wait(uint32_t bar, uint32_t parity, int& budget) {
  while (!mbar_try(bar, parity)) { if (--budget < 0) break; }
}
DEVI bool mbar_try_cluster(uint32_t bar, uint32_t parity) {
  uint32_t p;
  asm volatile("{.reg .pred p; mbarrier.try_wait.parity.acquire.cluster.shared::cta.b64 p, [%1], %2; selp.u32 %0, 1, 0, p;}" : "=r"(p) : "r"(bar), "r"(parity) : "memory");
  return p;
}
DEVI void mbar_wait_cluster(uint32_t bar, uint32_t parity, int& budget) {
  while (!mbar_try_cluster(bar, parity)) { if (--budget < 0) break; }
}
DEVI uint32_t mapa(uint32_t addr, uint32_t rank) { uint32_t r; asm("mapa.shared::cluster.u32 %0, %1, %2;" : "=r"(r) : "r"(addr), "r"(rank)); return r; }
DEVI void cluster_arrive() { asm volatile("barrier.cluster.arrive.release.aligned;" ::: "memory"); }
DEVI void cluster_wait() { asm volatile("barrier.cluster.wait.acquire.aligned;" ::: "memory"); }
DEVI void fence_mbar_init() { asm volatile("fence.mbarrier_init.release.cluster;" ::: "memory"); }
DEVI void fence_proxy_async() { asm volatile("fence.proxy.async.shared::cta;" ::: "memory"); }
DEVI void fence_proxy_global() { asm volatile("fence.proxy.async.global;" ::: "memory"); }
#define ELECT "{.reg .pred p; elect.sync _|p, 0xffffffff;\n @p "
DEVI void e_expect_tx(uint32_t bar, uint32_t bytes) { asm volatile(ELECT "mbarrier.arrive.expect_tx.shared::cta.b64 _, [%0], %1;}" :: "r"(bar), "r"(bytes) : "memory"); }
DEVI void e_arrive(uint32_t bar) { asm volatile(ELECT "mbarrier.arrive.shared::cta.b64 _, [%0];}" :: "r"(bar) : "memory"); }
DEVI void e_tma_2d(uint32_t dst, const CUtensorMap* m, int c0, int c1, uint32_t bar) {
  asm volatile(ELECT "cp.async.bulk.tensor.2d.shared::cluster.global.mbarrier::complete_tx::bytes [%0], [%1, {%3, %4}], [%2];}"
    :: "r"(dst), "l"(m), "r"(bar), "r"(c0), "r"(c1) : "memory");
}
DEVI void e_prefetch_2d(const CUtensorMap* m, int c0, int c1) {
  asm volatile(ELECT "cp.async.bulk.prefetch.tensor.2d.L2.global [%0, {%1, %2}];}" :: "l"(m), "r"(c0), "r"(c1) : "memory");
}
DEVI void e_prefetch_3d(const CUtensorMap* m, int c0, int c1, int c2) {
  asm volatile(ELECT "cp.async.bulk.prefetch.tensor.3d.L2.global [%0, {%1, %2, %3}];}" :: "l"(m), "r"(c0), "r"(c1), "r"(c2) : "memory");
}
DEVI void e_bulk_g2s(uint32_t dst, const void* src, uint32_t bytes, uint32_t bar) {
  asm volatile(ELECT "cp.async.bulk.shared::cluster.global.mbarrier::complete_tx::bytes [%0], [%1], %2, [%3];}" :: "r"(dst), "l"(src), "r"(bytes), "r"(bar) : "memory");
}
DEVI void e_tma_3d(uint32_t dst, const CUtensorMap* m, int c0, int c1, int c2, uint32_t bar) {
  asm volatile(ELECT "cp.async.bulk.tensor.3d.shared::cluster.global.mbarrier::complete_tx::bytes [%0], [%1, {%3, %4, %5}], [%2];}"
    :: "r"(dst), "l"(m), "r"(bar), "r"(c0), "r"(c1), "r"(c2) : "memory");
}
DEVI void e_tma_3d_mc(uint32_t dst, const CUtensorMap* m, int c0, int c1, int c2, uint32_t bar) {
  asm volatile(ELECT "cp.async.bulk.tensor.3d.shared::cluster.global.mbarrier::complete_tx::bytes.multicast::cluster [%0], [%1, {%3, %4, %5}], [%2], %6;}"
    :: "r"(dst), "l"(m), "r"(bar), "r"(c0), "r"(c1), "r"(c2), "h"((uint16_t)7) : "memory");
}
DEVI void e_tma_2d_mc(uint32_t dst, const CUtensorMap* m, int c0, int c1, uint32_t bar) {
  asm volatile(ELECT "cp.async.bulk.tensor.2d.shared::cluster.global.mbarrier::complete_tx::bytes.multicast::cluster [%0], [%1, {%3, %4}], [%2], %5;}"
    :: "r"(dst), "l"(m), "r"(bar), "r"(c0), "r"(c1), "h"((uint16_t)3) : "memory");
}
DEVI void p_arrive_at(uint32_t bar, uint32_t rank, bool c) {
  asm volatile("{.reg .pred p; .reg .b32 a; setp.ne.u32 p, %2, 0; mapa.shared::cluster.u32 a, %0, %1; @p mbarrier.arrive.shared::cluster.b64 _, [a];}"
    :: "r"(bar), "r"(rank), "r"((uint32_t)c) : "memory");
}
DEVI void p_expect_tx(uint32_t bar, uint32_t bytes, bool c) {
  asm volatile("{.reg .pred p; setp.ne.u32 p, %2, 0; @p mbarrier.arrive.expect_tx.shared::cta.b64 _, [%0], %1;}" :: "r"(bar), "r"(bytes), "r"((uint32_t)c) : "memory");
}
DEVI void p_arrive(uint32_t bar, bool c) { asm volatile("{.reg .pred p; setp.ne.u32 p, %1, 0; @p mbarrier.arrive.shared::cta.b64 _, [%0];}" :: "r"(bar), "r"((uint32_t)c) : "memory"); }
DEVI void tma_store_2d(const CUtensorMap* m, uint32_t src, int c0, int c1) {
  asm volatile("cp.async.bulk.tensor.2d.global.shared::cta.bulk_group [%0, {%2, %3}], [%1];" :: "l"(m), "r"(src), "r"(c0), "r"(c1) : "memory");
}
DEVI void tma_radd_2d(const CUtensorMap* m, uint32_t src, int c0, int c1) {
  asm volatile("cp.reduce.async.bulk.tensor.2d.global.shared::cta.add.bulk_group [%0, {%2, %3}], [%1];" :: "l"(m), "r"(src), "r"(c0), "r"(c1) : "memory");
}
DEVI void bulk_commit() { asm volatile("cp.async.bulk.commit_group;" ::: "memory"); }
template<int N> DEVI void bulk_wait_read() { asm volatile("cp.async.bulk.wait_group.read %0;" :: "n"(N) : "memory"); }
template<int N> DEVI void bulk_wait() { asm volatile("cp.async.bulk.wait_group %0;" :: "n"(N) : "memory"); }
template<int ID, int N> DEVI void nbar_sync() { asm volatile("bar.sync %0, %1;" :: "n"(ID), "n"(N) : "memory"); }
template<int ID, int N> DEVI void nbar_arrive() { asm volatile("bar.arrive %0, %1;" :: "n"(ID), "n"(N) : "memory"); }
DEVI void nbar_sync_r(int id, int n) { asm volatile("bar.sync %0, %1;" :: "r"(id), "r"(n) : "memory"); }
template<int R> DEVI void reg_inc() { asm volatile("setmaxnreg.inc.sync.aligned.u32 %0;" :: "n"(R)); }
template<int R> DEVI void reg_dec() { asm volatile("setmaxnreg.dec.sync.aligned.u32 %0;" :: "n"(R)); }
DEVI void wg_fence() { asm volatile("wgmma.fence.sync.aligned;" ::: "memory"); }
DEVI void wg_commit() { asm volatile("wgmma.commit_group.sync.aligned;" ::: "memory"); }
template<int N> DEVI void wg_wait() { asm volatile("wgmma.wait_group.sync.aligned %0;" :: "n"(N) : "memory"); }
DEVI uint64_t mkdesc(uint32_t addr, uint32_t lbo, uint32_t sbo, uint32_t sw = 1) {
  return ((uint64_t)((addr & 0x3FFFF) >> 4)) | ((uint64_t)(lbo >> 4) << 16) | ((uint64_t)(sbo >> 4) << 32) | ((uint64_t)sw << 62);
}
constexpr uint32_t SMEM_BASE = 1024;
__host__ __device__ constexpr long long CD(uint32_t off, uint32_t lbo, uint32_t sbo, uint32_t sw) {
  return (long long)(((uint64_t)((SMEM_BASE + off) >> 4)) | ((uint64_t)(lbo >> 4) << 16) | ((uint64_t)(sbo >> 4) << 32) | ((uint64_t)sw << 62));
}
DEVI uint32_t pack_bf16(float lo, float hi) { uint32_t r; asm("cvt.rn.bf16x2.f32 %0, %1, %2;" : "=r"(r) : "f"(hi), "f"(lo)); return r; }
DEVI float bf_lo(uint32_t v) { return __uint_as_float(v << 16); }
DEVI float bf_hi(uint32_t v) { return __uint_as_float(v & 0xffff0000u); }
DEVI void ldsm4t(uint32_t addr, uint32_t& r0, uint32_t& r1, uint32_t& r2, uint32_t& r3) {
  asm volatile("ldmatrix.sync.aligned.m8n8.x4.trans.shared.b16 {%0,%1,%2,%3}, [%4];" : "=r"(r0), "=r"(r1), "=r"(r2), "=r"(r3) : "r"(addr) : "memory");
}
DEVI void stsm4(uint32_t addr, uint32_t r0, uint32_t r1, uint32_t r2, uint32_t r3) {
  asm volatile("stmatrix.sync.aligned.m8n8.x4.shared.b16 [%0], {%1,%2,%3,%4};" :: "r"(addr), "r"(r0), "r"(r1), "r"(r2), "r"(r3) : "memory");
}
DEVI uint2 lds64v(uint32_t a) { uint2 v; asm volatile("ld.volatile.shared.v2.u32 {%0,%1}, [%2];" : "=r"(v.x), "=r"(v.y) : "r"(a) : "memory"); return v; }
DEVI uint32_t lds32v(uint32_t a) { uint32_t v; asm volatile("ld.volatile.shared.u32 %0, [%1];" : "=r"(v) : "r"(a) : "memory"); return v; }
DEVI uint4 lds128v(uint32_t a) { uint4 v; asm volatile("ld.volatile.shared.v4.u32 {%0,%1,%2,%3}, [%4];" : "=r"(v.x), "=r"(v.y), "=r"(v.z), "=r"(v.w) : "r"(a) : "memory"); return v; }
DEVI void cp_async16(uint32_t dst, const void* src) { asm volatile("cp.async.cg.shared.global [%0], [%1], 16;" :: "r"(dst), "l"(src) : "memory"); }
DEVI void cp_async_wait() { asm volatile("cp.async.wait_all;" ::: "memory"); }
DEVI void sts32(uint32_t a, uint32_t x) { asm volatile("st.shared.u32 [%0], %1;" :: "r"(a), "r"(x) : "memory"); }
DEVI int lane_id() { int r; asm volatile("mov.u32 %0, %%laneid;" : "=r"(r)); return r; }
DEVI void sts64(uint32_t a, uint32_t x, uint32_t y) { asm volatile("st.shared.v2.u32 [%0], {%1,%2};" :: "r"(a), "r"(x), "r"(y) : "memory"); }
DEVI void sts128(uint32_t a, uint4 v) { asm volatile("st.shared.v4.u32 [%0], {%1,%2,%3,%4};" :: "r"(a), "r"(v.x), "r"(v.y), "r"(v.z), "r"(v.w) : "memory"); }
DEVI void st_async128(uint32_t a, uint32_t x, uint32_t y, uint32_t z, uint32_t w, uint32_t bar) {
  asm volatile("st.async.weak.shared::cluster.mbarrier::complete_tx::bytes.v4.b32 [%0], {%1,%2,%3,%4}, [%5];" :: "r"(a), "r"(x), "r"(y), "r"(z), "r"(w), "r"(bar) : "memory");
}
DEVI void st_async32(uint32_t a, uint32_t x, uint32_t bar) {
  asm volatile("st.async.weak.shared::cluster.mbarrier::complete_tx::bytes.b32 [%0], %1, [%2];" :: "r"(a), "r"(x), "r"(bar) : "memory");
}
DEVI uint4 ldg_rlx128(const void* p) {
  uint4 v;
  asm volatile("ld.relaxed.gpu.global.v4.b32 {%0,%1,%2,%3}, [%4];" : "=r"(v.x), "=r"(v.y), "=r"(v.z), "=r"(v.w) : "l"(p) : "memory");
  return v;
}
DEVI int ldg_rlx32(const void* p) { int v; asm volatile("ld.relaxed.gpu.global.b32 %0, [%1];" : "=r"(v) : "l"(p) : "memory"); return v; }
DEVI int ldg_acq32(const void* p) { int v; asm volatile("ld.acquire.gpu.global.b32 %0, [%1];" : "=r"(v) : "l"(p) : "memory"); return v; }
DEVI void stg_rlx128(void* p, uint32_t x, uint32_t y, uint32_t z, uint32_t w) {
  asm volatile("st.relaxed.gpu.global.v4.b32 [%0], {%1,%2,%3,%4};" :: "l"(p), "r"(x), "r"(y), "r"(z), "r"(w) : "memory");
}
DEVI void stg128(void* p, uint32_t x, uint32_t y, uint32_t z, uint32_t w) {
  asm volatile("st.global.v4.b32 [%0], {%1,%2,%3,%4};" :: "l"(p), "r"(x), "r"(y), "r"(z), "r"(w) : "memory");
}
DEVI uint2 ldg_rlx64(const void* p) { uint2 v; asm volatile("{.reg .b64 a; ld.relaxed.gpu.global.b64 a, [%2]; mov.b64 {%0,%1}, a;}" : "=r"(v.x), "=r"(v.y) : "l"(p) : "memory"); return v; }
DEVI void stg_rlx64(void* p, uint32_t x, uint32_t y) { asm volatile("{.reg .b64 a; mov.b64 a, {%1,%2}; st.relaxed.gpu.global.b64 [%0], a;}" :: "l"(p), "r"(x), "r"(y) : "memory"); }
DEVI void stg_rlx32(void* p, uint32_t x) { asm volatile("st.relaxed.gpu.global.b32 [%0], %1;" :: "l"(p), "r"(x) : "memory"); }
DEVI void flag_add(int* p) { asm volatile("fence.proxy.async.global; red.release.gpu.global.add.s32 [%0], 1;" :: "l"(p) : "memory"); }
DEVI void e_stg_rlx32(void* p, uint32_t x) { asm volatile(ELECT "st.relaxed.gpu.global.b32 [%0], %1;}" :: "l"(p), "r"(x) : "memory"); }
DEVI void e_flag_add(int* p) { asm volatile("fence.proxy.async.global;\n" ELECT "red.release.gpu.global.add.s32 [%0], 1;}" :: "l"(p) : "memory"); }
DEVI int cluster_rank() { int r; asm volatile("mov.u32 %0, %%cluster_ctarank;" : "=r"(r)); return __shfl_sync(0xffffffffu, r, 0); }
DEVI int cluster_id() { int r; asm volatile("mov.u32 %0, %%clusterid.x;" : "=r"(r)); return __shfl_sync(0xffffffffu, r, 0); }
DEVI uint32_t clock32() { uint32_t c; asm volatile("mov.u32 %0, %%clock;" : "=r"(c)); return c; }
DEVI uint32_t gtime() { uint32_t c; asm volatile("mov.u32 %0, %%globaltimer_lo;" : "=r"(c)); return c; }
DEVI void wait_time(uint32_t t) { while (__any_sync(0xffffffffu, t - gtime() - 1 < 4000u)) {} }
DEVI void spin_until(uint32_t t0, int d) { while (__any_sync(0xffffffffu, (int)(clock32() - t0) < d)) {} }
DEVI void pin2(const void* a, const void* b) { asm volatile("{.reg .pred p; setp.eq.u64 p, %0, %1; @p st.volatile.global.u64 [%0], %1;}" :: "l"(a), "l"(b) : "memory"); }
DEVI void pin2(uint32_t a, uint32_t b) { asm volatile("{.reg .pred p; setp.eq.u32 p, %0, %1; @p st.volatile.shared.u32 [%0], %1;}" :: "r"(a), "r"(b) : "memory"); }
DEVI void p_stg_rlx64(void* p, uint32_t x, uint32_t y, bool c) {
  asm volatile("{.reg .pred p; .reg .b64 a; setp.ne.u32 p, %3, 0; mov.b64 a, {%1,%2}; @p st.relaxed.gpu.global.b64 [%0], a;}" :: "l"(p), "r"(x), "r"(y), "r"((uint32_t)c) : "memory");
}
DEVI void pin2(uint64_t a, uint64_t b) { pin2((const void*)a, (const void*)b); }
DEVI uint64_t pair(uint32_t a, uint32_t bar) { return a | (uint64_t)bar << 32; }
DEVI void st_async32(uint64_t q, uint32_t x) { st_async32((uint32_t)q, x, (uint32_t)(q >> 32)); }
DEVI void st_async128(uint64_t q, uint4 v) { st_async128((uint32_t)q, v.x, v.y, v.z, v.w, (uint32_t)(q >> 32)); }
DEVI float ex2(float x) { float r; asm("ex2.approx.ftz.f32 %0, %1;" : "=f"(r) : "f"(x)); return r; }
DEVI float rcp(float x) { float r; asm("rcp.approx.ftz.f32 %0, %1;" : "=f"(r) : "f"(x)); return r; }
DEVI uint32_t xor_or(uint32_t a, uint32_t t, uint32_t acc) { uint32_t r; asm("lop3.b32 %0, %1, %2, %3, 0xbe;" : "=r"(r) : "r"(a), "r"(t), "r"(acc)); return r; }
DEVI void stsm2(uint32_t addr, uint32_t r0, uint32_t r1) {
  asm volatile("stmatrix.sync.aligned.m8n8.x2.shared.b16 [%0], {%1,%2};" :: "r"(addr), "r"(r0), "r"(r1) : "memory");
}
DEVI uint32_t settag(uint32_t v, uint32_t tag) { return (v & ~1u) | tag; }

#define A4(c, o)  c(d[o+0]), c(d[o+1]), c(d[o+2]), c(d[o+3])
#define A8(c, o)  A4(c, o), A4(c, o+4)
#define A16(c, o) A8(c, o), A8(c, o+8)
#define A20(c, o) A16(c, o), A4(c, o+16)
#define A32(c, o) A16(c, o), A16(c, o+16)
#define RL8  "{%0,%1,%2,%3,%4,%5,%6,%7}"
#define RL16 "{%0,%1,%2,%3,%4,%5,%6,%7,%8,%9,%10,%11,%12,%13,%14,%15}"
#define RL20 "{%0,%1,%2,%3,%4,%5,%6,%7,%8,%9,%10,%11,%12,%13,%14,%15,%16,%17,%18,%19}"
#define RL32 "{%0,%1,%2,%3,%4,%5,%6,%7,%8,%9,%10,%11,%12,%13,%14,%15,%16,%17,%18,%19,%20,%21,%22,%23,%24,%25,%26,%27,%28,%29,%30,%31}"
#define RL64 "{%0,%1,%2,%3,%4,%5,%6,%7,%8,%9,%10,%11,%12,%13,%14,%15,%16,%17,%18,%19,%20,%21,%22,%23,%24,%25,%26,%27,%28,%29,%30,%31," \
  "%32,%33,%34,%35,%36,%37,%38,%39,%40,%41,%42,%43,%44,%45,%46,%47,%48,%49,%50,%51,%52,%53,%54,%55,%56,%57,%58,%59,%60,%61,%62,%63}"
#define WG_OP(shape) "wgmma.mma_async.sync.aligned." shape "k16.f32.bf16.bf16 "
#define DEF_WGMMA(N, RL, AL, i0, i1, i2, i3, i4, i5, i6)                                                                         \
  template<int SC, int TB, long long CB> DEVI void rs##N(float* d, const uint32_t* a) {                                          \
    if (SC) asm volatile("{.reg .b64 tb; mov.b64 tb, %" #i4 ";\n" WG_OP("m64n" #N) RL ", {%" #i0 ",%" #i1 ",%" #i2 ",%" #i3 "}, tb, 1, 1, 1, %" #i5 ";}" \
      : AL("+f", 0) : "r"(a[0]), "r"(a[1]), "r"(a[2]), "r"(a[3]), "n"(CB), "n"(TB));                                             \
    else asm volatile("{.reg .b64 tb; mov.b64 tb, %" #i4 ";\n" WG_OP("m64n" #N) RL ", {%" #i0 ",%" #i1 ",%" #i2 ",%" #i3 "}, tb, 0, 1, 1, %" #i5 ";}" \
      : AL("=f", 0) : "r"(a[0]), "r"(a[1]), "r"(a[2]), "r"(a[3]), "n"(CB), "n"(TB));                                             \
  }                                                                                                                              \
  template<int SC, int TA, int TB, long long CA, long long CB> DEVI void ss##N(float* d, uint32_t a) {                           \
    if (SC) asm volatile("{.reg .b64 ta, tb; .reg .b32 lo, hi; add.u32 lo, %" #i0 ", %" #i1 "; mov.b32 hi, %" #i2 "; mov.b64 ta, {lo, hi}; mov.b64 tb, %" #i3 ";\n" \
      WG_OP("m64n" #N) RL ", ta, tb, 1, 1, 1, %" #i4 ", %" #i5 ";}"                                                              \
      : AL("+f", 0) : "r"(a), "n"((int)CA), "n"((int)(CA >> 32)), "n"(CB), "n"(TA), "n"(TB));                                    \
    else asm volatile("{.reg .b64 ta, tb; .reg .b32 lo, hi; add.u32 lo, %" #i0 ", %" #i1 "; mov.b32 hi, %" #i2 "; mov.b64 ta, {lo, hi}; mov.b64 tb, %" #i3 ";\n" \
      WG_OP("m64n" #N) RL ", ta, tb, 0, 1, 1, %" #i4 ", %" #i5 ";}"                                                              \
      : AL("=f", 0) : "r"(a), "n"((int)CA), "n"((int)(CA >> 32)), "n"(CB), "n"(TA), "n"(TB));                                    \
  }
DEF_WGMMA(8, "{%0,%1,%2,%3}", A4, 4, 5, 6, 7, 8, 9, 10)
DEF_WGMMA(16, RL8, A8, 8, 9, 10, 11, 12, 13, 14)
DEF_WGMMA(32, RL16, A16, 16, 17, 18, 19, 20, 21, 22)
DEF_WGMMA(40, RL20, A20, 20, 21, 22, 23, 24, 25, 26)
DEF_WGMMA(64, RL32, A32, 32, 33, 34, 35, 36, 37, 38)
template<int TA> DEVI void wgmma_n128(float* d, uint64_t a, uint64_t b, int scale_d) {
  asm volatile("{.reg .pred p; setp.ne.b32 p, %66, 0;\n" WG_OP("m64n128") RL64 ", %64, %65, p, 1, 1, %67, 1;}"
    : A32("+f", 0), A32("+f", 32) : "l"(a), "l"(b), "r"(scale_d), "n"(TA));
}

namespace rec {
constexpr int KR = 43;
constexpr uint32_t WSZ = (64 - KR) * 2048, STG = KR * 2048;
constexpr uint32_t WS = 0;
constexpr uint32_t RING = 2 * WSZ;
constexpr uint32_t OB = RING + 3 * 8192;
constexpr uint32_t PB = OB + 4096;
constexpr uint32_t WO = RING + 32768;
constexpr uint32_t ATT = WO + 5 * 16384;
constexpr uint32_t AK = ATT + 10240, AV = ATT + 20480;
constexpr uint32_t PAD = ATT + 30720;
constexpr uint32_t BARS = PAD + 128;
constexpr uint32_t B_XE = BARS  , B_FA = BARS + 64  , B_FB = BARS + 88, B_FO = BARS + 96;
constexpr uint32_t B_ME = BARS + 104  , B_WE = BARS + 136  ;
constexpr uint32_t B_XF = BARS + 152  , B_MF = BARS + 216  , B_CP = BARS + 248  , B_WT = BARS + 280  ;
constexpr uint32_t B_AB = BARS + 296, B_OB = BARS + 304, B_ST = BARS + 312  , B_WS = BARS + 328, B_WO = BARS + 336, B_PD = BARS + 344;
constexpr int NBAR = 44;
constexpr uint32_t M0 = BARS + 384;
constexpr uint32_t SMEM = 232448;
constexpr int NB_P = 1, NB_ST = 2, NB_O = 3, NB_W0 = 4, NB_W1 = 5;
__host__ __device__ constexpr int wo_tile(int rank, int g, int i) { return i < 2 ? i * 6 + rank * 2 + g : 13 + rank - g; }
constexpr long long D_W = CD(WS, 16, 1024, 1), D_X = CD(0, 16, 1024, 1), D_M = CD(RING, 128, 256, 0), D_O = CD(OB, 128, 256, 0);
constexpr long long D_WO = CD(WO, 16, 1024, 1), D_QM = CD(ATT, 640, 0, 0), D_QT = CD(ATT + 128, 640, 64, 0), D_K = CD(AK, 640, 128, 0);
constexpr long long D_V = CD(AV, 128, 640, 0), D_P = CD(PB, 128, 768, 0);
struct Maps { CUtensorMap w[3], wo, xd, xs; };
__host__ __device__ constexpr uint32_t xslot(int s) { return s < 3 ? RING + s * 8192 : s < 5 ? WO + (s - 3) * 8192 : s < 7 ? WO + (s + 1) * 8192 : OB; }
__host__ __device__ constexpr bool k_smem(int k) { return k % 3 == 2; }
__host__ __device__ constexpr int k_idx(int k) { return k % 3 == 2 ? k / 3 : k - k / 3; }
__host__ __device__ constexpr int k_of_reg(int i) { return i + (i >> 1); }
__host__ __device__ constexpr int k_of_smem(int i) { return 3 * i + 2; }

#define RPROF(i)
#define RPROF_STEP
#define CPROF(i, v)

template<int K0, int K1> DEVI void seq_mem(float* d, const uint32_t* w, uint32_t dw) {
  if constexpr (K0 < K1) {
    constexpr long long B = D_M + K0 * 32;
    if constexpr (!k_smem(K0)) rs16<K0 != 0, 1, B>(d, w + 4 * k_idx(K0)); else ss16<1, 1, 1, D_W + k_idx(K0) * 128, B>(d, dw);
    seq_mem<K0 + 1, K1>(d, w, dw);
  }
}
template<bool DUAL, int K0, int K1> DEVI void seq_tok(float* d, const uint32_t* w, uint32_t dw) {
  if constexpr (K0 < K1) {
    constexpr long long B = D_X + (DUAL ? xslot((K0 >> 2) & 7) / 16 : xslot(K0 >> 3) / 16 + ((K0 >> 2) & 1) * 256) + (K0 & 3) * 2;
    if constexpr (DUAL) {
      if constexpr (!k_smem(K0)) rs64<K0 != 0, 0, B>(d, w + 4 * k_idx(K0)); else ss64<1, 1, 0, D_W + k_idx(K0) * 128, B>(d, dw);
    } else {
      if constexpr (!k_smem(K0)) rs32<K0 != 0, 0, B>(d, w + 4 * k_idx(K0)); else ss32<1, 1, 0, D_W + k_idx(K0) * 128, B>(d, dw);
    }
    seq_tok<DUAL, K0 + 1, K1>(d, w, dw);
  }
}
template<int T, int K0> DEVI void seq_wo(float* d, uint32_t dw) {
  if constexpr (K0 < 8) { ss16<K0 != 0, 1, 1, D_WO + T * 1024 + K0 * 128, D_O + K0 * 32>(d, dw); seq_wo<T, K0 + 1>(d, dw); }
}
template<long long Q, int K0> DEVI void seq_s(float* d) {
  if constexpr (K0 < 8) { ss40<K0 != 0, 1, 1, Q + K0 * 80, D_K + K0 * 80>(d, 0); seq_s<Q, K0 + 1>(d); }
}
template<bool DUAL, int J> DEVI void load_x(uint32_t sb, const Maps* M, int t) {
  if (DUAL) e_tma_3d_mc(sb + xslot(J & 7), &M->xd, J * 64, (t - LAG) * 32, 0, sb + B_XF + (J & 7) * 8);
  else e_tma_3d_mc(sb + xslot(J & 7), &M->xs, 0, (t < NSEG ? t : t - LAG) * 32, J * 2, sb + B_XF + (J & 7) * 8);
}
DEVI void load_x_lent(uint32_t sb, const Maps* M, int t, int j) {
  const bool dual = t >= LAG && t < NSEG;
  const uint32_t dst = sb + (j == 3 ? xslot(3) : xslot(5));
#pragma unroll
  for (int i = 0; i < 2; i++)
    e_tma_3d(dst + i * 8192, dual ? &M->xd : &M->xs, dual ? (j + i) * 64 : 0, (t < LAG ? t : t - LAG) * 32, dual ? 0 : (j + i) * 2, sb + B_XF + (j + i) * 8);
}
struct Ctx { uint32_t sb; const Maps* M; int h, rank, wi; bool lead; uint32_t par; };
#define PFN 2
#define TOKPOS 0
#define XD 2
template<bool DUAL, int J> DEVI void tok_release(const Ctx& c, int t, int& budget) {
  constexpr int NC = DUAL ? 16 : 8, S = J & 7;
  if constexpr (J + 8 < NC) {
    p_arrive_at(c.sb + B_XE + S * 8, J % 3, c.lead);
    p_expect_tx(c.sb + B_XF + S * 8, 8192, c.lead && c.wi == 0);
  } else if constexpr (S == 4 || S == 6) {
    constexpr int g = S == 4;
    p_arrive(c.sb + B_WE + g * 8, c.lead);
    if (c.wi == g * 4 + 2) {
      mbar_wait(c.sb + B_WE + g * 8, t & 1, budget);
      e_expect_tx(c.sb + B_WT + g * 8, 16384);
      e_tma_2d(c.sb + WO + (1 - g) * 49152, &c.M->wo, wo_tile(c.rank, g, 0) * 64, c.h * DH, c.sb + B_WT + g * 8);
    }
  } else if constexpr (S < 3 || S == 7) p_arrive(c.sb + B_ME + (S & 3) * 8, c.lead);
  if constexpr (J == XD - 1) {
    if (c.rank == 1 && c.wi == 5) { mbar_wait(c.sb + B_FO, t & 1, budget); load_x<DUAL, 7>(c.sb, c.M, t); }
  } else if constexpr (J >= XD && J - XD + 8 < NC) {
    constexpr int I = J - XD;
    if (c.rank == I % 3 && c.wi == (I & 1) * 4 + 1) { mbar_wait(c.sb + B_XE + I * 8, (t - LAG) & 1, budget); load_x<DUAL, I + 8>(c.sb, c.M, t); }
  }
}
template<bool DUAL, int J, class F> DEVI bool tok_pass(float* d, const uint32_t* w, uint32_t dw, Ctx& c, int t, int& budget, F after0) {
  constexpr int NC = DUAL ? 16 : 8, KC = 64 / NC;
  if constexpr (J < NC) {
    if constexpr (J > 0) mbar_wait(c.sb + B_XF + (J & 7) * 8, c.par ^ (J >> 3), budget);
    wg_fence();
    seq_tok<DUAL, J * KC, (J + 1) * KC>(d, w, dw);
    wg_commit();
    if constexpr (J > 0) { wg_wait<1>(); tok_release<DUAL, J - 1>(c, t, budget); } else after0();
    return tok_pass<DUAL, J + 1>(d, w, dw, c, t, budget, after0);
  } else {
    const bool ok = mbar_test(c.sb + B_MF, t & 1);
    wg_wait<0>();
    tok_release<DUAL, NC - 1>(c, t, budget);
    if (!DUAL) c.par ^= 1;
    return ok;
  }
}
DEVI void pack_tok(uint32_t* e, const float* d) {
#pragma unroll
  for (int i = 0; i < 8; i++) e[i] = pack_bf16(d[4 * (i & 3) + 2 * (i >> 2)], d[4 * (i & 3) + 2 * (i >> 2) + 1]);
}
DEVI void push_tok(const uint32_t* e, uint32_t sb, uint32_t o, int r) {
  const uint32_t b = mapa(sb, r);
  st_async128(b + o, e[0], e[1], e[2], e[3], b + B_AB);
}
DEVI uint32_t h1_tag(int seg) { return ((seg >> 1) & 1) ^ 1; }
DEVI uint4 pack_part(const float* c, int t) {
  return make_uint4(settag(pack_bf16(c[0], c[1]), h1_tag(t)), pack_bf16(c[2], c[3]), settag(pack_bf16(c[4], c[5]), h1_tag(t - LAG)), pack_bf16(c[6], c[7]));
}
DEVI void put_part(char* p1, char* p2, uint4 z, int t) { p_stg_rlx64(p1, z.x, z.y, t < NSEG); p_stg_rlx64(p2, z.z, z.w, t >= LAG); }

DEVI void rec_math(const uint32_t sb, const int wi, const Maps& M) {
  const int h = cluster_id(), rank = cluster_rank();
  const int warp = wi & 3, wg = wi >> 2;
  const bool lead = (threadIdx.x & 127) == 0;
  int budget = SPIN_BUDGET;
  uint32_t w[4 * KR];
  Ctx cx{sb, &M, h, rank, wi, lead, 0};
  {
    const int lane = lane_id();
    const uint32_t a = sb + wg * STG + ((lane & 7) + (lane >> 4) * 8) * 128 + (((warp * 2 + ((lane >> 3) & 1)) ^ (lane & 7)) << 4);
    mbar_wait(sb + B_ST + wg * 8, 0, budget);
#pragma unroll
    for (int k = 0; k < KR; k++) ldsm4t(a + k * 2048, w[4*k], w[4*k+1], w[4*k+2], w[4*k+3]);
    nbar_arrive<NB_ST, 384>();
    nbar_sync_r(NB_W0 + wg, 128);
    for (int i = 0; i < 5; i++) p_arrive_at(sb + B_FA + i * 8, i == 4, lead);
    mbar_wait(sb + B_WS, 0, budget);
  }
  uint4 z = make_uint4(0, 0, 0, 0);
  char *z1 = nullptr, *z2 = nullptr;
  mbar_wait(sb + B_XF, 0, budget);
#pragma unroll 1
  for (int t = 0;; t++) {
    const uint32_t dw = wg * (WSZ >> 4);
    uint32_t e[16];
    bool ok;
    auto finish = [&]() { put_part(z1, z2, z, t - 1); p_arrive_at(sb + B_FO, 1, lead); };
    if (t >= LAG && t < NSEG) {
      float d[32];
      ok = tok_pass<true, 0>(d, w, dw, cx, t, budget, finish);
      pack_tok(e + 8, d); pack_tok(e, d + 16);
    } else {
      float d[16];
      if (t > 0) finish();
      ok = tok_pass<false, 0>(d, w, dw, cx, t, budget, []() {});
      pack_tok(e, d);
#pragma unroll
      for (int i = 8; i < 16; i++) e[i] = 0;
    }
    RPROF_STEP;
    RPROF(8 + wg * 12 - 32);
    {
      float m[8];
      if (!ok) mbar_wait(sb + B_MF, t & 1, budget);
      wg_fence(); seq_mem<0, 8>(m, w, dw); wg_commit();
      const int lane = lane_id();
      {
        const uint32_t ao = ATT + rank * 10240 + wi * 1280, to = ao + 128 + (lane & 3) * 128 + (lane >> 2) * 16;
        const bool dual = t >= LAG && t < NSEG;
        RPROF(1 + wg * 12);
        push_tok(e, sb, to, t >= NSEG);
        wg_fence(); seq_mem<8, 16>(m, w, dw); wg_commit();
        push_tok(e + 4, sb, to + 640, t >= NSEG);
        mbar_wait(sb + B_MF + 8, t & 1, budget);
        wg_fence(); seq_mem<16, 32>(m, w, dw); wg_commit();
        if (dual) push_tok(e + 8, sb, to, 1);
        wg_wait<1>(); p_arrive_at(sb + B_FA, 0, lead);
        mbar_wait(sb + B_MF + 16, t & 1, budget);
        wg_fence(); seq_mem<32, 48>(m, w, dw); wg_commit();
        if (dual) push_tok(e + 12, sb, to + 640, 1);
        wg_wait<1>(); p_arrive_at(sb + B_FA + 8, 0, lead);
        const uint32_t r0 = mapa(sb, t >= NSEG), r1 = mapa(sb, 1), m0 = r0 + ao + lane * 4, m1 = r1 + ao + lane * 4;
        uint64_t q0 = pair(m0, r0 + B_AB), q1 = pair(m0 + 640, r0 + B_AB), q2 = pair(m1, r1 + B_AB), q3 = pair(m1 + 640, r1 + B_AB);
        pin2(q0, q1); pin2(q2, q3);
        mbar_wait(sb + B_MF + 24, t & 1, budget);
        wg_fence(); seq_mem<48, 64>(m, w, dw); wg_commit();
        wg_wait<1>(); p_arrive_at(sb + B_FA + 16, 0, lead);
        wg_wait<0>();
        const uint32_t a0 = pack_bf16(m[0], m[1]), a1 = pack_bf16(m[2], m[3]), a2 = pack_bf16(m[4], m[5]), a3 = pack_bf16(m[6], m[7]);
        st_async32(q0, t < NSEG ? a0 : a2); st_async32(q1, t < NSEG ? a1 : a3);
        if (dual) { st_async32(q2, a2); st_async32(q3, a3); }
        p_arrive(sb + B_PD, threadIdx.x == 0);
      }
      RPROF(2 + wg * 12);
      if (t == 0) mbar_wait(sb + B_WO, 0, budget);
      mbar_wait(sb + B_WT + wg * 8, t & 1, budget);
      const int seg = t - rank * LAG;
      constexpr float SC = 0.08838834764831845f * 1.4426950408889634f;
      if (rank < 2 && (unsigned)seg < (unsigned)NSEG) {
        float s[32];
        if (wg) {
          const uint32_t pw = sb + PB + lane * 4, o = OB + (lane >> 4) * 2048 + warp * 512 + rank * 256 + (lane & 15) * 16;
          const uint32_t r0 = mapa(sb, 0), r1 = mapa(sb, 1), r2 = mapa(sb, 2);
          uint64_t q0 = pair(r0 + o, r0 + B_OB), q1 = pair(r1 + o, r1 + B_OB), q2 = pair(r2 + o, r2 + B_OB);
          uint32_t one[4];
#pragma unroll
          for (int i = 0; i < 4; i++) one[i] = 0x3F803F80u + (pw >> 31);
          pin2(q0, q1); pin2(q2, (uint64_t)pw);
          mbar_wait_cluster(sb + B_AB, seg & 1, budget);
          fence_proxy_async();
          RPROF(3 + 12);
          wg_fence(); seq_s<D_QM, 0>(s); wg_commit();
          if (TOKPOS == 0) nbar_arrive<NB_P, 256>();
          if (warp == 1) sts32(pw + 640, 0);
          wg_wait<0>();
          float mx = fmaxf(fmaxf(fmaxf(s[0], s[1]), fmaxf(s[4], s[5])), fmaxf(fmaxf(fmaxf(s[8], s[9]), fmaxf(s[12], s[13])), fmaxf(s[16], s[17])));
          const float x1 = __shfl_xor_sync(0xffffffffu, mx, 1), x2 = __shfl_xor_sync(0xffffffffu, mx, 2), x3 = __shfl_xor_sync(0xffffffffu, mx, 3);
          const float u = (warp & 2) ? ((warp & 1) ? s[16] : s[12]) : ((warp & 1) ? s[8] : s[4]);
          const float v = (warp & 2) ? ((warp & 1) ? s[17] : s[13]) : ((warp & 1) ? s[9] : s[5]);
          const float ms = -SC * fmaxf(fmaxf(mx, x1), fmaxf(x2, x3));
          sts32(pw + 128 + warp * 128, pack_bf16(ex2(fmaf(u, SC, ms)), ex2(fmaf(v, SC, ms))));
          if (warp == 0) sts32(pw, pack_bf16(ex2(fmaf(s[0], SC, ms)), ex2(fmaf(s[1], SC, ms))));
          fence_proxy_async();
          nbar_sync<NB_W1, 128>();
          RPROF(4 + 12);
          wg_fence();
          rs8<0, 0, D_P>(s + 8, one); rs8<1, 0, D_P + 16>(s + 8, one); rs8<1, 0, D_P + 32>(s + 8, one);
          wg_commit();
          ss8<0, 0, 0, D_V, D_P>(s, 0); ss8<0, 0, 0, D_V + 320, D_P>(s + 4, 0);
          ss8<1, 0, 0, D_V + 16, D_P + 16>(s, 0); ss8<1, 0, 0, D_V + 336, D_P + 16>(s + 4, 0);
          ss8<1, 0, 0, D_V + 32, D_P + 32>(s, 0); ss8<1, 0, 0, D_V + 352, D_P + 32>(s + 4, 0);
          wg_commit();
          if (TOKPOS == 1) nbar_arrive<NB_P, 256>();
          wg_wait<1>();
          const float i0 = rcp(s[8]), i1 = rcp(s[9]);
          wg_wait<0>();
          stsm4(sb + o, pack_bf16(s[0] * i0, s[1] * i1), pack_bf16(s[2] * i0, s[3] * i1), pack_bf16(s[4] * i0, s[5] * i1), pack_bf16(s[6] * i0, s[7] * i1));
          __syncwarp();
          const uint4 y = lds128v(sb + o);
          if (t < NSTEP - 1) { st_async128(q2, y); st_async128(rank ? q0 : q1, y); st_async128(rank ? q1 : q0, y); }
          if (TOKPOS == 2) nbar_arrive<NB_P, 256>();
        } else {
          const int g = lane >> 2, lim = 8 * (g >> 1) + (g & 1) + 2 * warp - 8 * (lane & 3);
          const uint32_t pw = sb + PB + 768 + warp * 768 + lane * 16;
          char* const og = (char*)(g_ot + rank * O_LAYER) + (size_t)(h * DH + warp * 16 + (lane >> 2)) * (SEQ * 2) + seg * 64 + (lane & 3) * 16;
          pin2(pw, lim); pin2(og, nullptr);
          mbar_wait_cluster(sb + B_AB, seg & 1, budget);
          fence_proxy_async();
          nbar_sync<NB_P, 256>();
          RPROF(3);
          wg_fence(); seq_s<D_QT, 0>(s); wg_commit();
          wg_wait<0>();
#pragma unroll
          for (int i = 0; i < 8; i++) { float& v = s[4 + 4 * (i >> 1) + (i & 1)]; v = i <= lim ? v : -INFINITY; }
          float mx = fmaxf(fmaxf(fmaxf(s[0], s[1]), fmaxf(s[4], s[5])), fmaxf(fmaxf(fmaxf(s[8], s[9]), fmaxf(s[12], s[13])), fmaxf(s[16], s[17])));
          const float x1 = __shfl_xor_sync(0xffffffffu, mx, 1), x2 = __shfl_xor_sync(0xffffffffu, mx, 2), x3 = __shfl_xor_sync(0xffffffffu, mx, 3);
          const float ms = -SC * fmaxf(fmaxf(mx, x1), fmaxf(x2, x3));
#pragma unroll
          for (int i = 0; i < 10; i++) { float& v = s[4 * (i >> 1) + (i & 1)]; v = ex2(fmaf(v, SC, ms)); }
          const float sum = (((s[0] + s[1]) + (s[4] + s[5])) + ((s[8] + s[9]) + (s[12] + s[13]))) + (s[16] + s[17]);
          const float y1 = __shfl_xor_sync(0xffffffffu, sum, 1), y2 = __shfl_xor_sync(0xffffffffu, sum, 2), y3 = __shfl_xor_sync(0xffffffffu, sum, 3);
          const float inv = rcp((sum + y1) + (y2 + y3));
          stsm4(pw, pack_bf16(s[0] * inv, s[1] * inv), pack_bf16(s[4] * inv, s[5] * inv), pack_bf16(s[8] * inv, s[9] * inv), pack_bf16(s[12] * inv, s[13] * inv));
          stsm2(pw + 512, pack_bf16(s[16] * inv, s[17] * inv), 0);
          fence_proxy_async();
          nbar_sync<NB_W0, 128>();
          RPROF(4);
          wg_fence();
          ss32<0, 0, 0, D_V, D_P + 48>(s, 0); ss32<0, 0, 0, D_V + 320, D_P + 48>(s + 16, 0);
          ss32<1, 0, 0, D_V + 16, D_P + 64>(s, 0); ss32<1, 0, 0, D_V + 336, D_P + 64>(s + 16, 0);
          ss32<1, 0, 0, D_V + 32, D_P + 80>(s, 0); ss32<1, 0, 0, D_V + 352, D_P + 80>(s + 16, 0);
          wg_commit();
          wg_wait<0>();
#pragma unroll
          for (int i = 0; i < 4; i++) {
            const float* d = s + (i >> 1) * 16 + (i & 1) * 2;
            stg128(og + ((i >> 1) * 64 + (i & 1) * 8) * (SEQ * 2), pack_bf16(d[0], d[1]), pack_bf16(d[4], d[5]), pack_bf16(d[8], d[9]), pack_bf16(d[12], d[13]));
          }
          nbar_arrive<NB_O, 160>();
        }
      }
      RPROF(5 + wg * 12);
      char* const p = (char*)g_h1 + ((wo_tile(rank, wg, 0) * 4 + warp) * 4 + (lane >> 3)) * 2048 + h * 64 + (lane & 7) * 8;
      const bool three = wg == 1 || rank == 2;
      if (t < NSTEP - 1) {
        float c[24];
        const uint32_t dt = wg ? 0 : 3072;
        const int o3 = (wo_tile(rank, wg, three ? 2 : 1) - wo_tile(rank, wg, 0)) * 32768;
        char* const p1 = p + (t & 1) * sizeof(g_h1[0]);
        char* const p2 = p + (2 + ((t - LAG) & 1)) * sizeof(g_h1[0]);
        z1 = p1 + o3; z2 = p2 + o3;
        pin2(p1, p2); pin2(z1, z2);
        mbar_wait(sb + B_XF, cx.par, budget);
        mbar_wait_cluster(sb + B_OB, t & 1, budget);
        fence_proxy_async();
        RPROF(6 + wg * 12);
        wg_fence(); seq_wo<0, 0>(c, dt); wg_commit(); seq_wo<1, 0>(c + 8, dt); wg_commit();
        wg_wait<1>();
        if (warp == 2) load_x_lent(sb, &M, t + 1, wg ? 3 : 5);
        put_part(p1, p2, pack_part(c, t), t);
        if (three) {
          wg_fence(); seq_wo<2, 0>(c + 16, dt); wg_commit();
          wg_wait<1>(); put_part(p1 + 6 * 32768, p2 + 6 * 32768, pack_part(c + 8, t), t);
          wg_wait<0>(); z = pack_part(c + 16, t);
        } else { wg_wait<0>(); z = pack_part(c + 8, t); }
      } else {
        for (int i = 0; i < (three ? 3 : 2); i++) stg_rlx64(p + 3 * sizeof(g_h1[0]) + (wo_tile(rank, wg, i) - wo_tile(rank, wg, 0)) * 32768, 0, 0);
        break;
      }
      RPROF(7 + wg * 12);
    }
  }
}

DEVI void wait_xa(const int* p, int& budget) {
  while (__any_sync(0xffffffffu, ldg_acq32(p) < 64) && --budget > 0) {}
  fence_proxy_global();
}
template<bool DUAL> DEVI void first_loads(uint32_t sb, const Maps* M, int n, int h, int& budget) {
#pragma unroll
  for (int i = 0; i < PFN; i++) {
    if (DUAL) e_prefetch_3d(&M->xd, ((h + i * (16 / PFN)) & 15) * 64, (n - LAG) * 32, 0);
    else e_prefetch_3d(&M->xs, 0, (n < NSEG ? n : n - LAG) * 32, ((h + i * (8 / PFN)) & 7) * 2);
  }
  mbar_wait(sb + B_FA, n & 1, budget); load_x<DUAL, 0>(sb, M, n);
  mbar_wait(sb + B_FA + 8, n & 1, budget); load_x<DUAL, 1>(sb, M, n);
  mbar_wait(sb + B_FA + 16, n & 1, budget); load_x<DUAL, 2>(sb, M, n);
}
template<bool DUAL> DEVI void lent_loads(uint32_t sb, const Maps* M, int n, int& budget) {
  mbar_wait(sb + B_FB, n & 1, budget);
  load_x<DUAL, 3>(sb, M, n); load_x<DUAL, 4>(sb, M, n); load_x<DUAL, 5>(sb, M, n); load_x<DUAL, 6>(sb, M, n);
}
DEVI void rec_comm(const uint32_t sb, const int warp, const Maps& M, const bf16* __restrict__ mem0) {
  const int lane = threadIdx.x & 31, h = cluster_id(), rank = cluster_rank();
  int budget = SPIN_BUDGET;
  const bool two = warp == 3 || (rank == 2 && warp == 2);
  const int ntask = two ? 2 : 1, qi = two ? (warp == 3 ? rank : 3) : rank * 3 + warp;
  const int task0 = two ? h * 2 + (qi >> 1) : 64 + h * 4 + (qi >> 1);
  auto h2_word = [&](int i, int ln) {
    const int task = task0 + i * 192;
    return (char*)g_h2 + (task >> 2) * 512 + ((qi ^ i) & 1) * 256 + (task & 3) * 32 + (ln & 8) * 16 + (ln & 7) * 4;
  };
  auto first_x = [&](int t) {
    const int n = t + 1;
    p_expect_tx(sb + B_XF + (lane_id() & 7) * 8, 8192, lane_id() < 8);
    if (rank == 0) {
      if (n < NSEG && (n & 3) == 0) wait_xa(&g_xa[0][n >> 2], budget);
      if (n >= LAG && ((n - LAG) & 3) == 0) wait_xa(&g_xa[1][(n - LAG) >> 2], budget);
      if (n >= LAG && n < NSEG) first_loads<true>(sb, &M, n, h, budget); else first_loads<false>(sb, &M, n, h, budget);
    }
  };
  {
    const int task = task0 + (lane >> 4) * 192, L = (task & 3) * 8 + (lane & 7);
    if ((lane >> 4) < ntask) {
      const bf16* p = mem0 + (L & 3) * 2 * DM + (task >> 2) * 16 + (L >> 2) + (lane & 8);
      uint32_t m0 = (uint32_t)__bfloat16_as_ushort(p[0]) | (uint32_t)__bfloat16_as_ushort(p[DM]) << 16;
      m0 = m0 ? m0 : 0x8000u;
      stg_rlx32(h2_word(lane >> 4, lane), m0);
      sts32(sb + M0 + warp * 128 + lane * 4, m0);
    }
    __syncwarp();
    nbar_sync<NB_ST, 384>();
    if (warp == 2) {
      e_expect_tx(sb + B_WS, 2 * WSZ);
#pragma unroll 1
      for (int i = 0; i < 2 * (64 - KR); i++) e_tma_2d(sb + WS + (i & 1) * WSZ + (i >> 1) * 2048, &M.w[rank], h * DH + (i & 1) * 64, k_of_smem(i >> 1) * 16, sb + B_WS);
      const int nt = rank == 2 ? 6 : 5;
      e_expect_tx(sb + B_WO, (nt - 2) * 16384);
#pragma unroll 1
      for (int i = 1; i < nt; i++) if (i != 3) e_tma_2d(sb + WO + i * 16384, &M.wo, wo_tile(rank, 1 - i / 3, i % 3) * 64, h * DH, sb + B_WO);
    }
    if (warp == 3) { first_x(-1); if (rank == 0) lent_loads<false>(sb, &M, 0, budget); }
  }
  uint32_t t0 = gtime() - 4000, cpp = 0;
  const uint32_t cp = sb + B_CP + warp * 8;
#pragma unroll 1
  for (int t = 0;; t++) {
    const int n = t + 1, seg = t - rank * LAG;
    RPROF_STEP;
    const bool att = rank < 2 && (unsigned)seg < (unsigned)NSEG;
    if (warp == 3) {
      if (att) e_expect_tx(sb + B_AB, 30720);
      if (n < NSTEP) e_expect_tx(sb + B_OB, t < NSEG && t >= LAG ? 4096 : 2048);
    }
    {
      const uint32_t dst = sb + RING + warp * 8192;
      mbar_wait(sb + B_ME + warp * 8, t & 1, budget);
      wait_time(t0 + TP(1) + warp * TP(4));
      const int lane = lane_id();
      RPROF(24); CPROF(0, gtime());
      int tries = 0;
      while (true) {
        tries++;
        e_expect_tx(cp, 8192);
        e_bulk_g2s(dst, (const char*)g_h2[t & 3] + warp * 8192, 8192, cp);
        mbar_wait(cp, cpp, budget); cpp ^= 1;
        uint32_t mn = 0xffffffffu;
#pragma unroll
        for (int i = 0; i < 8; i++) mn = min(mn, lds32v(dst + i * 1024 + lane * 32 + (lane >> 2) * 4));
        if (!__any_sync(0xffffffffu, mn == 0) || --budget < 0) break;
      }
      e_arrive(sb + B_MF + warp * 8);
      RPROF(25); CPROF(1, gtime()); CPROF(2, tries);
    }
    {
      const int ln = lane_id(), i = ln >> 4;
      char* const w = h2_word(i, ln);
      if (i < ntask) {
        stg_rlx32(w + ((t + 3) & 3) * sizeof(g_h2[0]), 0);
        if (n < NSTEP && (((qi ^ i) & 1) ? t < LAG : t >= NSEG)) stg_rlx32(w + (n & 3) * sizeof(g_h2[0]), lds32v(sb + M0 + warp * 128 + ln * 4));
      }
      __syncwarp();
    }
    if (n < NSTEP) {
      const uint32_t tag = (n >> 1) & 31;
      if (warp == 3) first_x(t);
      mbar_wait(sb + B_PD, t & 1, budget);
      t0 = clock32();
      if (warp == 0 && rank == (t >= NSEG)) { mbar_wait(sb + B_AB, seg & 1, budget); e_stg_rlx32(&g_ts[t & 1][h * TSS], (gtime() & ~31u) | tag); }
      spin_until(t0, TSD);
      uint32_t v;
      do { v = ldg_rlx32(&g_ts[t & 1][lane_id() * TSS]); } while (__any_sync(0xffffffffu, (v & 31) != tag) && --budget > 0);
      const uint32_t now = __shfl_sync(0xffffffffu, v, 0);
      t0 = now + __reduce_max_sync(0xffffffffu, (int)(v - now));
      if (warp == 3) mbar_wait(sb + B_OB, t & 1, budget);
    }
    if (n < NSTEP) {
      RPROF(26); CPROF(3, t0);
#pragma unroll 1
      for (int i = 0; i < ntask; i++) {
        const int layer = (qi ^ i) & 1, sg = t - layer * LAG, task = task0 + i * 192;
        if ((unsigned)sg >= (unsigned)NSEG) continue;
        const uint32_t tag = h1_tag(sg);
        const int ln = lane_id();
        const char* const src = (const char*)g_h1[layer * 2 + (sg & 1)] + task * 2048 + ln * 8;
        char* const dst = h2_word(i, ln) + (n & 3) * sizeof(g_h2[0]);
        uint2 v[8];
        pin2(src, dst);
        wait_time(t0 + TP(0) + (task < 96 ? 0 : task < 192 ? TP(3) : 2 * TP(3)));
        int tries = 0;
        float a[4];
        while (true) {
          tries++;
#pragma unroll
          for (int k = 0; k < 8; k++) v[k] = ldg_rlx64(src + k * 256);
          uint32_t bad = 0;
#pragma unroll
          for (int k = 0; k < 8; k++) {
            bad = xor_or(v[k].x, tag, bad);
            a[0] = k ? a[0] + bf_lo(v[k].x) : bf_lo(v[k].x); a[1] = k ? a[1] + bf_hi(v[k].x) : bf_hi(v[k].x);
            a[2] = k ? a[2] + bf_lo(v[k].y) : bf_lo(v[k].y); a[3] = k ? a[3] + bf_hi(v[k].y) : bf_hi(v[k].y);
          }
#pragma unroll
        for (int k = 0; k < 2; k++) {
          const float keep = (ln & 8) ? a[2+k] : a[k], send = (ln & 8) ? a[k] : a[2+k];
          a[k] = keep + __shfl_xor_sync(0xffffffffu, send, 8);
        }
#pragma unroll
        for (int k = 0; k < 2; k++) a[k] += __shfl_xor_sync(0xffffffffu, a[k], 16);
          if (!__any_sync(0xffffffffu, bad & 1) || --budget < 0) break;
        }
        const uint32_t out = pack_bf16(a[0], a[1]);
        if (ln < 16) stg_rlx32(dst, out ? out : 0x8000u);
        __syncwarp();
        if (i == 0) { RPROF(28); CPROF(6, gtime()); CPROF(4, gtime()); CPROF(5, tries); } else CPROF(7, gtime());
      }
    }
    if (warp == 1 && att) { nbar_sync<NB_O, 160>(); e_flag_add(&g_dep[E_O1 + rank * 16 + (seg >> 2)]); }
    if (n == NSTEP) break;
  }
  if (h == 0 && rank == 0 && warp < 2) g_xa[warp][lane_id()] = 0;
}
}

__global__ void __cluster_dims__(3, 1, 1) __launch_bounds__(384, 1)
rec_kernel(const __grid_constant__ rec::Maps M, const bf16* __restrict__ mem0) {
  using namespace rec;
  extern __shared__ __align__(1024) uint8_t smem[];
  const uint32_t sb = __shfl_sync(0xffffffffu, smem_u32(smem), 0);
  const int tid = threadIdx.x, wi = __shfl_sync(0xffffffffu, tid >> 5, 0);
  if ((sb & 0x3FFFF) != SMEM_BASE) __trap();
  if (wi == 0) {
    const int h = cluster_id(), rank = cluster_rank();
    for (int i = tid; i < NBAR; i += 32) mbar_init(sb + BARS + i * 8, i < 13 ? 6 : i < 19 ? 2 : 1);
    ((uint32_t*)(smem + PAD))[tid] = 0;
    fence_mbar_init(); fence_proxy_async();
    __syncwarp();
    e_expect_tx(sb + B_ST, STG); e_expect_tx(sb + B_ST + 8, STG);
    for (int i = 0; i < 2 * KR; i++) e_tma_2d(sb + (i & 1) * STG + (i >> 1) * 2048, &M.w[rank], h * DH + (i & 1) * 64, k_of_reg(i >> 1) * 16, sb + B_ST + (i & 1) * 8);
  } else if (wi == 1) {
    if (blockIdx.x < NEV / 32) { g_dep[blockIdx.x * 32 + (tid & 31)] = 0; g_claim[blockIdx.x * 32 + (tid & 31)] = 0; __threadfence(); }
    __syncwarp();
    asm volatile("griddepcontrol.launch_dependents;" ::: "memory");
  }
  cluster_arrive(); cluster_wait();
  if (wi < 8) { reg_inc<232>(); rec_math(sb, wi, M); cluster_arrive(); cluster_wait(); }
  else { reg_dec<40>(); rec_comm(sb, wi & 3, M, mem0); cluster_arrive(); cluster_wait(); }
}

namespace gm {
struct Maps { CUtensorMap ot, wo, xn, wg, wu, hl, hs, wd, out; };
constexpr int STAGES = 6, STAGE = 32768;
constexpr uint32_t SO = STAGES * STAGE, BARS = SO + 32768;
constexpr uint32_t B_FULL = BARS, B_EMPTY = BARS + 48, B_TF = BARS + 96, B_TE = BARS + 112, B_ORD = BARS + 128, B_PM = BARS + 144, B_GO = BARS + 160;
constexpr uint32_t MAIL = BARS + 176, PMAIL = BARS + 192;
constexpr uint32_t SMEM = BARS + 256;
constexpr int END = -1;

struct Tile {
  bool isO, isG, l2; int blk, col, k0, n;
  DEVI Tile(int task, int rank) {
    const int e = task >> 8, id = task & 255;
    const bool isD = e < E_G1 || e >= E_D2;
    isO = e >= E_O1 && e < E_G2; isG = !isD && !isO; l2 = e >= E_O2;
    blk = isG && l2 ? (e & 15) * 2 + rank : isD && !l2 ? e >> 1 : e & 15;
    col = isG ? (l2 ? id : id * 2 + rank) : (id & 3) * 2 + rank;
    k0 = isO ? (id >> 2) * 2048 : isG ? 0 : ((l2 ? e >> 4 : e) & 1) * 1792;
    n = isO ? 32 : isG ? 16 : 28;
  }
};

DEVI float geglu(float g, float u) {
  const float z = g * (0.7978845608028654f + 0.035677408136300125f * g * g);
  float t; asm("tanh.approx.f32 %0, %1;" : "=f"(t) : "f"(z));
  const float hg = 0.5f * g;
  return fmaf(hg, t, hg) * u;
}
struct Sched {
  int need, size;
  bool filler;
  uint4 dep, cl;
  DEVI void init(int lane) {
    const int e = lane * 4;
    const bool d = e < E_G1 || e >= E_D2, o = e >= E_O1 && e < E_G2;
    need = d ? 28 : e < E_O1 ? 64 : 128;
    size = d ? 4 : o ? 8 : e < E_O1 ? 28 : e < E_G2 + 8 ? 56 : 0;
    filler = (int)blockIdx.x < TP(5);
  }
  DEVI void scan(int lane) { cl = ldg_rlx128(g_claim + lane * 4); dep = ldg_rlx128(g_dep + lane * 4); }
  DEVI int next(int lane, int& budget) {
    while (--budget > 0) {
      int av[4], open = 0;
#pragma unroll
      for (int i = 0; i < 4; i++) { const int r = max(size - (int)(&cl.x)[i], 0); open |= r; av[i] = ((int)(&dep.x)[i] >= need ? r : 0) + (i ? av[i - 1] : 0); }
      const uint32_t mo = __ballot_sync(0xffffffffu, open);
      if (!mo) break;
      if (!filler && (mo & TP(6)) && lane >= E_O2 / 4) av[3] = 0;
      int inc = av[3], pos = 0;
      while (true) {
        const uint32_t m = __ballot_sync(0xffffffffu, inc > pos && av[3]);
        if (!m) break;
        const int l = __ffs(m) - 1, rel = pos - (inc - av[3]), i = (rel >= av[0]) + (rel >= av[1]) + (rel >= av[2]);
        int r = 0;
        if (lane == l) {
          const int tk = atomicAdd(g_claim + lane * 4 + i, 1);
          r = tk < size ? (lane * 4 + i) << 8 | tk : -1 - (inc - av[3] + (i == 0 ? av[0] : i == 1 ? av[1] : i == 2 ? av[2] : av[3]) + tk - size);
        }
        r = __shfl_sync(0xffffffffu, r, l);
        if (r >= 0) return r;
        if (pos == 0) {
#pragma unroll
          for (int o = 1; o < 32; o <<= 1) { const int v = __shfl_up_sync(0xffffffffu, inc, o); if (lane >= o) inc += v; }
        }
        pos = -1 - r;
      }
      if (pos == 0) __nanosleep(TP(7));
      scan(lane);
    }
    return END;
  }
};

DEVI void scheduler(const uint32_t sb) {
  const int lane = threadIdx.x & 31;
  int budget = SPIN_BUDGET;
  Sched sc; sc.init(lane);
#pragma unroll 1
  for (int i = 0;; i++) {
    mbar_wait(sb + B_GO, (i & 1) ^ 1, budget);
    sc.scan(lane);
    const int task = sc.next(lane, budget);
    const uint32_t r = mapa(sb, lane & 1);
    if (lane < 2) st_async32(r + PMAIL + (i & 1) * 4, task, r + B_PM + (i & 1) * 8);
    __syncwarp();
    if (task == END) break;
  }
}

DEVI void producer(const uint32_t sb, const Maps& M) {
  const int lane = threadIdx.x & 31, rank = cluster_rank();
  int budget = SPIN_BUDGET, s = 0, ph = 0;
#pragma unroll 1
  for (int i = 0;; i++) {
    e_expect_tx(sb + B_PM + (i & 1) * 8, 4);
    mbar_wait_cluster(sb + B_PM + (i & 1) * 8, (i >> 1) & 1, budget);
    const int task = budget < 0 ? END : __shfl_sync(0xffffffffu, (int)lds32v(sb + PMAIL + (i & 1) * 4), 0);
    fence_proxy_global();
    for (int z = 0; z < (task == END ? 2 : 1); z++) {
      const int g = (i + z) & 1;
      mbar_wait(sb + B_TE + g * 8, (((i + z) >> 1) & 1) ^ 1, budget);
      if (lane == 0) { sts64(sb + MAIL + g * 8, task, s | ph << 8); mbar_arrive(sb + B_TF + g * 8); }
      __syncwarp();
    }
    if (task == END) break;
    const Tile T(task, rank);
    const bool shareB = T.isG && T.l2;
    const CUtensorMap* mA = T.isO ? &M.ot : T.isG ? &M.xn : &M.hl;
    const CUtensorMap* mB0 = T.isO ? &M.wo : T.isG ? &M.wg : &M.wd;
    const CUtensorMap* mB1 = T.isG ? &M.wu : mB0;
    const int c0 = T.col * (T.isG ? 64 : 128), c1 = T.isG ? c0 : c0 + 64, row = T.blk * 128;
    const int ok = 0;
    int k = T.k0;
#pragma unroll 1
    for (int it = 0; it < T.n; it++, k += 64) {
      const uint32_t a = sb + s * STAGE, fb = sb + B_FULL + s * 8;
      mbar_wait(sb + B_EMPTY + s * 8, ph ^ 1, budget);
      e_expect_tx(fb, STAGE);
      if (shareB) {
        e_tma_2d_mc(a + 16384 + rank * 8192, rank ? mB1 : mB0, c0, k, fb);
        e_tma_2d(a, mA, k, row, fb); e_tma_2d(a + 8192, mA, k, row + 64, fb);
      } else {
        e_tma_2d_mc(a + rank * 8192, mA, T.isO ? row + rank * 64 : k, T.isO ? k + ok : row + rank * 64, fb);
        e_tma_2d(a + 16384, mB0, c0, k, fb); e_tma_2d(a + 24576, mB1, c1, k, fb);
      }
      if (it == T.n - TP(2)) e_arrive(sb + B_GO);
      if (++s == STAGES) { s = 0; ph ^= 1; }
    }
  }
}

template<int TA> DEVI void mainloop(float* d0, float* d1, uint32_t sb, int n, int s, int ph, bool lead, uint32_t ord, int& budget) {
  int prev = 0;
  const uint32_t rel = threadIdx.x & 127;
#pragma unroll 1
  for (int i = 0; i < n; i++) {
    mbar_wait(sb + B_FULL + s * 8, ph, budget);
    const uint32_t a = sb + s * STAGE;
    const uint64_t da = mkdesc(a, 16, 1024), db = mkdesc(a + 16384, 8192, 1024);
    wg_fence();
#pragma unroll
    for (int k = 0; k < 4; k++) {
      wgmma_n128<TA>(d0, da + k * (TA ? 128 : 2), db + k * 128, (i | k) != 0);
      wgmma_n128<TA>(d1, da + 512 + k * (TA ? 128 : 2), db + k * 128, (i | k) != 0);
    }
    wg_commit();
    if (i > 0) { wg_wait<1>(); p_arrive_at(sb + B_EMPTY + prev * 8, rel & 1, rel < 2); }
    prev = s;
    if (++s == STAGES) { s = 0; ph ^= 1; }
  }
  p_arrive(ord, lead);
  wg_wait<0>();
  p_arrive_at(sb + B_EMPTY + prev * 8, rel & 1, rel < 2);
}

DEVI void consumer(const uint32_t sb, const Maps& M, const int wg) {
  const int tid = threadIdx.x, lane = tid & 31, warp = (tid >> 5) & 3;
  const bool lead = (tid & 127) == 0;
  const uint32_t so = sb + SO + wg * 16384;
  int budget = SPIN_BUDGET;
  float d0[64], d1[64];
#pragma unroll 1
  for (int m = 0;; m++) {
    mbar_wait(sb + B_TF + wg * 8, m & 1, budget);
    const uint2 mail = lds64v(sb + MAIL + wg * 8);
    const int task = __shfl_sync(0xffffffffu, (int)mail.x, 0), pos = __shfl_sync(0xffffffffu, (int)mail.y, 0);
    e_arrive(sb + B_TE + wg * 8);
    if (task == END || budget < 0) break;
    const Tile T(task, cluster_rank());
    mbar_wait(sb + B_ORD + wg * 8, (m & 1) ^ wg ^ 1, budget);
    if (T.isO) mainloop<1>(d0, d1, sb, 32, pos & 255, pos >> 8, lead, sb + B_ORD + (wg ^ 1) * 8, budget);
    else mainloop<0>(d0, d1, sb, T.n, pos & 255, pos >> 8, lead, sb + B_ORD + (wg ^ 1) * 8, budget);
    const uint32_t st = so + (warp * 16 + (lane & 15)) * 128;
    if (T.isG) {
#pragma unroll
      for (int mm = 0; mm < 2; mm++) {
        const float* d = mm ? d1 : d0;
#pragma unroll
        for (int c = 0; c < 4; c++) {
          uint32_t r[4];
#pragma unroll
          for (int i = 0; i < 4; i++) r[i] = pack_bf16(geglu(d[8*c+2*i], d[32+8*c+2*i]), geglu(d[8*c+2*i+1], d[33+8*c+2*i]));
          stsm4(st + mm * 8192 + (((2 * c + (lane >> 4)) ^ (lane & 7)) << 4), r[0], r[1], r[2], r[3]);
        }
      }
      fence_proxy_async();
      nbar_sync_r(1 + wg, 128);
      if (lead) {
        tma_store_2d(&M.hs, so, T.col * 64, T.blk * 128);
        bulk_commit(); bulk_wait<0>();
        flag_add(&g_dep[T.l2 ? E_D2 + (T.col >= 28) * 16 + T.blk : E_D1 + T.blk * 2 + (T.col >= 28)]);
      }
    } else {
#pragma unroll
      for (int hf = 0; hf < 2; hf++) {
        if (hf) { if (lead) bulk_wait_read<0>(); nbar_sync_r(1 + wg, 128); }
#pragma unroll
        for (int mm = 0; mm < 2; mm++) {
          const float* d = (mm ? d1 : d0) + hf * 32;
#pragma unroll
          for (int c = 0; c < 4; c++)
            stsm4(st + mm * 8192 + (((2 * c + (lane >> 4)) ^ (lane & 7)) << 4), pack_bf16(d[8*c], d[8*c+1]), pack_bf16(d[8*c+2], d[8*c+3]),
                  pack_bf16(d[8*c+4], d[8*c+5]), pack_bf16(d[8*c+6], d[8*c+7]));
        }
        fence_proxy_async();
        nbar_sync_r(1 + wg, 128);
        if (lead) { tma_radd_2d(&M.out, so, T.col * 128 + hf * 64, T.blk * 128); bulk_commit(); }
      }
      if (lead) {
        bulk_wait<0>();
        if (T.isO || !T.l2) flag_add(&g_dep[(!T.isO ? E_LX2 : T.l2 ? E_LX1B : E_LX1A) + T.blk]);
      }
    }
    __syncwarp();
  }
}

DEVI void norm_helper(const bf16* __restrict__ x, bf16* out) {
  const int lane = threadIdx.x & 31;
  int budget = SPIN_BUDGET, tk = lane < 4 ? -1 : 1024;
#pragma unroll 1
  while (--budget > 0) {
    if (tk < 0) tk = atomicAdd(g_claim + E_LI + lane, 1);
    if (__all_sync(0xffffffffu, tk >= 1024)) break;
    const uint32_t m = __ballot_sync(0xffffffffu, tk < 1024 && (lane == 0 || ldg_acq32(g_dep + E_LI + lane * 16 + (tk >> 6)) >= 16));
    if (!m) { __nanosleep(TP(7)); continue; }
    const int ql = __ffs(m) - 1, task = __shfl_sync(0xffffffffu, tk, ql), q = E_LI + ql * 16, ev = task >> 6;
    if (lane == ql) tk = -1;
    const size_t off = (size_t)task * (DM * 4) + lane * 16;
    const char* src = (const char*)(q == E_LI ? x : out) + off;
    uint4 u[8];
#pragma unroll
    for (int i = 0; i < 8; i++) u[i] = ldg_rlx128(src + i * 512);
    if (q == E_LI) {
#pragma unroll
      for (int i = 0; i < 8; i++) stg128((char*)out + off + i * 512, u[i].x, u[i].y, u[i].z, u[i].w);
    }
    float mean[2], rs[2];
#pragma unroll
    for (int r = 0; r < 2; r++) {
      float s0 = 0, s1 = 0;
#pragma unroll
      for (int i = 0; i < 16; i++) { const uint32_t v = (&u[4*r + (i >> 2)].x)[i & 3]; s0 += bf_lo(v); s1 += bf_hi(v); }
      mean[r] = (s0 + s1) * (1.f / 32);
      s0 = s1 = 0;
#pragma unroll
      for (int i = 0; i < 16; i++) { const uint32_t v = (&u[4*r + (i >> 2)].x)[i & 3]; const float a = bf_lo(v) - mean[r], b = bf_hi(v) - mean[r]; s0 = fmaf(a, a, s0); s1 = fmaf(b, b, s1); }
      rs[r] = s0 + s1;
    }
    {
      const bool hi = lane & 16;
      float m1 = hi ? mean[1] : mean[0], q1 = hi ? rs[1] : rs[0], m2 = hi ? mean[0] : mean[1], q2 = hi ? rs[0] : rs[1], cnt = 16;
#pragma unroll
      for (int o = 16; o; o >>= 1) {
        m2 = __shfl_xor_sync(0xffffffffu, m2, o); q2 = __shfl_xor_sync(0xffffffffu, q2, o);
        const float dl = m1 - m2;
        q2 = q1 = fmaf(dl * dl, cnt, q1 + q2); m2 = m1 = 0.5f * (m1 + m2);
        cnt *= 2;
      }
      q1 = rsqrtf(q1 * (1.f / DM) + 1e-5f);
      m2 = __shfl_xor_sync(0xffffffffu, m1, 16); q2 = __shfl_xor_sync(0xffffffffu, q1, 16);
      mean[0] = hi ? m2 : m1; mean[1] = hi ? m1 : m2; rs[0] = hi ? q2 : q1; rs[1] = hi ? q1 : q2;
    }
#pragma unroll
    for (int i = 0; i < 8; i++) {
      uint32_t y[4];
#pragma unroll
      for (int c = 0; c < 4; c++) { const uint32_t v = (&u[i].x)[c]; y[c] = pack_bf16((bf_lo(v) - mean[i >> 2]) * rs[i >> 2], (bf_hi(v) - mean[i >> 2]) * rs[i >> 2]); }
      stg128((char*)g_xn + off + i * 512, y[0], y[1], y[2], y[3]);
    }
    fence_proxy_global();
    __syncwarp();
    if (lane == 0) flag_add(q == E_LI ? &g_xa[0][ev] : q == E_LX2 ? &g_xa[1][ev] : &g_dep[q == E_LX1A ? E_G1 + ev : E_G2 + (ev >> 1)]);
    __syncwarp();
  }
}
}

__global__ void __cluster_dims__(2, 1, 1) __launch_bounds__(384, 1)
gemm_kernel(const __grid_constant__ gm::Maps M, const bf16* __restrict__ x, bf16* out) {
  using namespace gm;
  extern __shared__ __align__(1024) uint8_t smem[];
  const uint32_t sb = __shfl_sync(0xffffffffu, smem_u32(smem), 0);
  const int tid = threadIdx.x, wi = __shfl_sync(0xffffffffu, tid >> 5, 0);
  if (tid < 21) mbar_init(sb + BARS + tid * 8, tid == 14 || tid == 15 ? 4 : tid >= 6 && tid < 12 ? 2 : 1);
  fence_mbar_init();
  cluster_arrive(); cluster_wait();
  if (wi < 8) { reg_inc<208>(); consumer(sb, M, wi >> 2); cluster_arrive(); cluster_wait(); }
  else {
    reg_dec<88>();
    if (wi == 8) producer(sb, M);
    else if (wi == 11 && cluster_rank() == 0) scheduler(sb);
    else {
      norm_helper(x, out);
      asm volatile("griddepcontrol.wait;" ::: "memory");
      if (wi == 9 && blockIdx.x < 64) g_h2[(NSTEP - 1) & 3][blockIdx.x * 32 + (tid & 31)] = make_uint4(0, 0, 0, 0);
    }
    __syncwarp();
    cluster_arrive(); cluster_wait();
  }
}

typedef CUresult (*PFN_encodeTiled)(CUtensorMap*, CUtensorMapDataType, cuuint32_t, void*, const cuuint64_t*, const cuuint64_t*,
                                    const cuuint32_t*, const cuuint32_t*, CUtensorMapInterleave, CUtensorMapSwizzle,
                                    CUtensorMapL2promotion, CUtensorMapFloatOOBfill);
static PFN_encodeTiled g_encode = nullptr;
static CUtensorMap make_map(const void* ptr, uint64_t rows, uint64_t cols, uint32_t box_rows) {
  CUtensorMap m;
  cuuint64_t dims[2] = {cols, rows}, strides[1] = {cols * 2};
  cuuint32_t box[2] = {64, box_rows}, es[2] = {1, 1};
  g_encode(&m, CU_TENSOR_MAP_DATA_TYPE_BFLOAT16, 2, (void*)ptr, dims, strides, box, es, CU_TENSOR_MAP_INTERLEAVE_NONE,
           CU_TENSOR_MAP_SWIZZLE_128B, CU_TENSOR_MAP_L2_PROMOTION_L2_256B, CU_TENSOR_MAP_FLOAT_OOB_FILL_NONE);
  return m;
}

static CUtensorMap make_map3(const void* ptr, uint64_t d0, uint64_t d1, uint64_t d2, uint64_t stride2) {
  CUtensorMap m;
  cuuint64_t dims[3] = {d0, d1, d2}, strides[2] = {DM * 2, stride2};
  cuuint32_t box[3] = {64, 32, 2}, es[3] = {1, 1, 1};
  g_encode(&m, CU_TENSOR_MAP_DATA_TYPE_BFLOAT16, 3, (void*)ptr, dims, strides, box, es, CU_TENSOR_MAP_INTERLEAVE_NONE,
           CU_TENSOR_MAP_SWIZZLE_128B, CU_TENSOR_MAP_L2_PROMOTION_L2_256B, CU_TENSOR_MAP_FLOAT_OOB_FILL_NONE);
  return m;
}

extern "C" void kernel_launch(void* const* d_in, const int* in_sizes, int n_in, void* d_out, int out_size) {
  const bf16* x = (const bf16*)d_in[0];
  const bf16* mem0 = (const bf16*)d_in[1];
  if (!g_encode) {
    void* p = nullptr; cudaDriverEntryPointQueryResult q;
    cudaGetDriverEntryPoint("cuTensorMapEncodeTiled", &p, cudaEnableDefault, &q);
    g_encode = (PFN_encodeTiled)p;
    cudaFuncSetAttribute(gemm_kernel, cudaFuncAttributeMaxDynamicSharedMemorySize, gm::SMEM);
    cudaFuncSetAttribute(rec_kernel, cudaFuncAttributeMaxDynamicSharedMemorySize, rec::SMEM);
  }
  bf16 *xn, *ot, *hh;
  cudaGetSymbolAddress((void**)&xn, g_xn); cudaGetSymbolAddress((void**)&ot, g_ot); cudaGetSymbolAddress((void**)&hh, g_h);
  rec::Maps R;
  for (int i = 0; i < 3; i++) R.w[i] = make_map(d_in[2 + i], DM, NH * DH, 16);
  R.wo = make_map(d_in[5], NH * DH, DM, 128);
  R.xd = make_map3(xn, DM, SEQ - LAG * 32, 2, (uint64_t)LAG * 32 * DM * 2); R.xs = make_map3(xn, 64, SEQ, DM / 64, 128);
  gm::Maps G;
  G.ot = make_map(ot, NH * DH + O_LAYER / SEQ, SEQ, 64); G.wo = make_map(d_in[5], NH * DH, DM, 64); G.xn = make_map(xn, SEQ, DM, 64);
  G.wg = make_map(d_in[8], DM, DF, 64); G.wu = make_map(d_in[9], DM, DF, 64); G.hl = make_map(hh, SEQ, DF, 64); G.hs = make_map(hh, SEQ, DF, 128);
  G.wd = make_map(d_in[10], DF, DM, 64); G.out = make_map(d_out, SEQ, DM, 128);
  rec_kernel<<<3 * NH, 384, rec::SMEM, cudaStreamPerThread>>>(R, mem0);
  cudaLaunchConfig_t cfg = {};
  cfg.gridDim = dim3(132); cfg.blockDim = dim3(384); cfg.dynamicSmemBytes = gm::SMEM; cfg.stream = cudaStreamPerThread;
  cudaLaunchAttribute at[1];
  at[0].id = cudaLaunchAttributeProgrammaticStreamSerialization; at[0].val.programmaticStreamSerializationAllowed = 1;
  cfg.attrs = at; cfg.numAttrs = 1;
  cudaLaunchKernelEx(&cfg, gemm_kernel, G, x, (bf16*)d_out);
}
```

```cpp
#include <cuda_runtime.h>
#include <cuda_bf16.h>
#include <cuda.h>
#include <stdint.h>

#define DEVI __device__ __forceinline__
typedef __nv_bfloat16 bf16;

constexpr int SEQ = 2048, DM = 1024, NH = 32, DH = 128, DF = 3584, NSEG = 64;
#define LAG 18
constexpr int NSTEP = NSEG + LAG;

#define TSS 1
#define TSD 1100
constexpr size_t O_LAYER = 0;
__device__ __align__(1024) bf16 g_xn[SEQ * DM];
__device__ __align__(1024) bf16 g_ot[SEQ * NH * DH + O_LAYER];
__device__ __align__(1024) bf16 g_h[SEQ * DF];
__device__ __align__(1024) uint2 g_h1[4][256 * 256];
__device__ __align__(1024) uint4 g_h2[4][2048];
__device__ __align__(128) uint32_t g_ts[2][32 * TSS];
enum { E_D1 = 0, E_G1 = 32, E_O1 = 48, E_O2 = 64, E_G2 = 80, E_D2 = 96,
       E_LI = 128, E_LX2 = 144, E_LX1A = 160, E_LX1B = 176, NEV = 256 };
__device__ __align__(128) int g_dep[NEV];
__device__ __align__(128) int g_claim[NEV];
__device__ __align__(128) int g_xa[2][32];

#define TUNE_DEFAULTS 1550, 2250, 5, 100, 100, 8, 0xffff, 100
constexpr int c_D[8] = {TUNE_DEFAULTS};
template<int I> struct TPV { static constexpr int v = c_D[I]; };
#define TP(i) TPV<i>::v

DEVI uint32_t smem_u32(const void* p) { return (uint32_t)__cvta_generic_to_shared(p); }
DEVI void mbar_init(uint32_t bar, uint32_t cnt) { asm volatile("mbarrier.init.shared::cta.b64 [%0], %1;" :: "r"(bar), "r"(cnt) : "memory"); }
DEVI void mbar_arrive(uint32_t bar) { asm volatile("mbarrier.arrive.shared::cta.b64 _, [%0];" :: "r"(bar) : "memory"); }
DEVI bool mbar_try(uint32_t bar, uint32_t parity) {
  uint32_t p;
  asm volatile("{.reg .pred p; mbarrier.try_wait.parity.shared::cta.b64 p, [%1], %2; selp.u32 %0, 1, 0, p;}" : "=r"(p) : "r"(bar), "r"(parity) : "memory");
  return p;
}
DEVI bool mbar_test(uint32_t bar, uint32_t parity) {
  uint32_t p;
  asm volatile("{.reg .pred p; mbarrier.test_wait.parity.shared::cta.b64 p, [%1], %2; selp.u32 %0, 1, 0, p;}" : "=r"(p) : "r"(bar), "r"(parity) : "memory");
  return p;
}
constexpr int SPIN_BUDGET = 1 << 18;
DEVI void mbar_wait(uint32_t bar, uint32_t parity, int& budget) {
  while (!mbar_try(bar, parity)) { if (--budget < 0) break; }
}
DEVI bool mbar_try_cluster(uint32_t bar, uint32_t parity) {
  uint32_t p;
  asm volatile("{.reg .pred p; mbarrier.try_wait.parity.acquire.cluster.shared::cta.b64 p, [%1], %2; selp.u32 %0, 1, 0, p;}" : "=r"(p) : "r"(bar), "r"(parity) : "memory");
  return p;
}
DEVI void mbar_wait_cluster(uint32_t bar, uint32_t parity, int& budget) {
  while (!mbar_try_cluster(bar, parity)) { if (--budget < 0) break; }
}
DEVI uint32_t mapa(uint32_t addr, uint32_t rank) { uint32_t r; asm("mapa.shared::cluster.u32 %0, %1, %2;" : "=r"(r) : "r"(addr), "r"(rank)); return r; }
DEVI void cluster_arrive() { asm volatile("barrier.cluster.arrive.release.aligned;" ::: "memory"); }
DEVI void cluster_wait() { asm volatile("barrier.cluster.wait.acquire.aligned;" ::: "memory"); }
DEVI void fence_mbar_init() { asm volatile("fence.mbarrier_init.release.cluster;" ::: "memory"); }
DEVI void fence_proxy_async() { asm volatile("fence.proxy.async.shared::cta;" ::: "memory"); }
DEVI void fence_proxy_global() { asm volatile("fence.proxy.async.global;" ::: "memory"); }
#define ELECT "{.reg .pred p; elect.sync _|p, 0xffffffff;\n @p "
DEVI void e_expect_tx(uint32_t bar, uint32_t bytes) { asm volatile(ELECT "mbarrier.arrive.expect_tx.shared::cta.b64 _, [%0], %1;}" :: "r"(bar), "r"(bytes) : "memory"); }
DEVI void e_complete_tx(uint32_t bar, uint32_t bytes) { asm volatile("fence.acq_rel.cta;\n" ELECT "mbarrier.complete_tx.relaxed.cta.shared::cta.b64 [%0], %1;}" :: "r"(bar), "r"(bytes) : "memory"); }
DEVI void e_arrive(uint32_t bar) { asm volatile(ELECT "mbarrier.arrive.shared::cta.b64 _, [%0];}" :: "r"(bar) : "memory"); }
DEVI void e_tma_2d(uint32_t dst, const CUtensorMap* m, int c0, int c1, uint32_t bar) {
  asm volatile(ELECT "cp.async.bulk.tensor.2d.shared::cluster.global.mbarrier::complete_tx::bytes [%0], [%1, {%3, %4}], [%2];}"
    :: "r"(dst), "l"(m), "r"(bar), "r"(c0), "r"(c1) : "memory");
}
DEVI void e_prefetch_2d(const CUtensorMap* m, int c0, int c1) {
  asm volatile(ELECT "cp.async.bulk.prefetch.tensor.2d.L2.global [%0, {%1, %2}];}" :: "l"(m), "r"(c0), "r"(c1) : "memory");
}
DEVI void e_prefetch_3d(const CUtensorMap* m, int c0, int c1, int c2) {
  asm volatile(ELECT "cp.async.bulk.prefetch.tensor.3d.L2.global [%0, {%1, %2, %3}];}" :: "l"(m), "r"(c0), "r"(c1), "r"(c2) : "memory");
}
DEVI void e_bulk_g2s(uint32_t dst, const void* src, uint32_t bytes, uint32_t bar) {
  asm volatile(ELECT "cp.async.bulk.shared::cluster.global.mbarrier::complete_tx::bytes [%0], [%1], %2, [%3];}" :: "r"(dst), "l"(src), "r"(bytes), "r"(bar) : "memory");
}
DEVI void e_tma_3d(uint32_t dst, const CUtensorMap* m, int c0, int c1, int c2, uint32_t bar) {
  asm volatile(ELECT "cp.async.bulk.tensor.3d.shared::cluster.global.mbarrier::complete_tx::bytes [%0], [%1, {%3, %4, %5}], [%2];}"
    :: "r"(dst), "l"(m), "r"(bar), "r"(c0), "r"(c1), "r"(c2) : "memory");
}
DEVI void e_tma_3d_mc(uint32_t dst, const CUtensorMap* m, int c0, int c1, int c2, uint32_t bar) {
  asm volatile(ELECT "cp.async.bulk.tensor.3d.shared::cluster.global.mbarrier::complete_tx::bytes.multicast::cluster [%0], [%1, {%3, %4, %5}], [%2], %6;}"
    :: "r"(dst), "l"(m), "r"(bar), "r"(c0), "r"(c1), "r"(c2), "h"((uint16_t)7) : "memory");
}
DEVI void e_tma_2d_mc(uint32_t dst, const CUtensorMap* m, int c0, int c1, uint32_t bar) {
  asm volatile(ELECT "cp.async.bulk.tensor.2d.shared::cluster.global.mbarrier::complete_tx::bytes.multicast::cluster [%0], [%1, {%3, %4}], [%2], %5;}"
    :: "r"(dst), "l"(m), "r"(bar), "r"(c0), "r"(c1), "h"((uint16_t)3) : "memory");
}
DEVI void p_arrive_at(uint32_t bar, uint32_t rank, bool c) {
  asm volatile("{.reg .pred p; .reg .b32 a; setp.ne.u32 p, %2, 0; mapa.shared::cluster.u32 a, %0, %1; @p mbarrier.arrive.shared::cluster.b64 _, [a];}"
    :: "r"(bar), "r"(rank), "r"((uint32_t)c) : "memory");
}
DEVI void p_expect_tx(uint32_t bar, uint32_t bytes, bool c) {
  asm volatile("{.reg .pred p; setp.ne.u32 p, %2, 0; @p mbarrier.arrive.expect_tx.shared::cta.b64 _, [%0], %1;}" :: "r"(bar), "r"(bytes), "r"((uint32_t)c) : "memory");
}
DEVI void p_arrive(uint32_t bar, bool c) { asm volatile("{.reg .pred p; setp.ne.u32 p, %1, 0; @p mbarrier.arrive.shared::cta.b64 _, [%0];}" :: "r"(bar), "r"((uint32_t)c) : "memory"); }
DEVI void tma_store_2d(const CUtensorMap* m, uint32_t src, int c0, int c1) {
  asm volatile("cp.async.bulk.tensor.2d.global.shared::cta.bulk_group [%0, {%2, %3}], [%1];" :: "l"(m), "r"(src), "r"(c0), "r"(c1) : "memory");
}
DEVI void tma_radd_2d(const CUtensorMap* m, uint32_t src, int c0, int c1) {
  asm volatile("cp.reduce.async.bulk.tensor.2d.global.shared::cta.add.bulk_group [%0, {%2, %3}], [%1];" :: "l"(m), "r"(src), "r"(c0), "r"(c1) : "memory");
}
DEVI void bulk_commit() { asm volatile("cp.async.bulk.commit_group;" ::: "memory"); }
template<int N> DEVI void bulk_wait_read() { asm volatile("cp.async.bulk.wait_group.read %0;" :: "n"(N) : "memory"); }
template<int N> DEVI void bulk_wait() { asm volatile("cp.async.bulk.wait_group %0;" :: "n"(N) : "memory"); }
template<int ID, int N> DEVI void nbar_sync() { asm volatile("bar.sync %0, %1;" :: "n"(ID), "n"(N) : "memory"); }
template<int ID, int N> DEVI void nbar_arrive() { asm volatile("bar.arrive %0, %1;" :: "n"(ID), "n"(N) : "memory"); }
DEVI void nbar_sync_r(int id, int n) { asm volatile("bar.sync %0, %1;" :: "r"(id), "r"(n) : "memory"); }
template<int R> DEVI void reg_inc() { asm volatile("setmaxnreg.inc.sync.aligned.u32 %0;" :: "n"(R)); }
template<int R> DEVI void reg_dec() { asm volatile("setmaxnreg.dec.sync.aligned.u32 %0;" :: "n"(R)); }
DEVI void wg_fence() { asm volatile("wgmma.fence.sync.aligned;" ::: "memory"); }
DEVI void wg_commit() { asm volatile("wgmma.commit_group.sync.aligned;" ::: "memory"); }
template<int N> DEVI void wg_wait() { asm volatile("wgmma.wait_group.sync.aligned %0;" :: "n"(N) : "memory"); }
DEVI uint64_t mkdesc(uint32_t addr, uint32_t lbo, uint32_t sbo, uint32_t sw = 1) {
  return ((uint64_t)((addr & 0x3FFFF) >> 4)) | ((uint64_t)(lbo >> 4) << 16) | ((uint64_t)(sbo >> 4) << 32) | ((uint64_t)sw << 62);
}
constexpr uint32_t SMEM_BASE = 1024;
__host__ __device__ constexpr long long CD(uint32_t off, uint32_t lbo, uint32_t sbo, uint32_t sw) {
  return (long long)(((uint64_t)((SMEM_BASE + off) >> 4)) | ((uint64_t)(lbo >> 4) << 16) | ((uint64_t)(sbo >> 4) << 32) | ((uint64_t)sw << 62));
}
DEVI uint32_t pack_bf16(float lo, float hi) { uint32_t r; asm("cvt.rn.bf16x2.f32 %0, %1, %2;" : "=r"(r) : "f"(hi), "f"(lo)); return r; }
DEVI float bf_lo(uint32_t v) { return __uint_as_float(v << 16); }
DEVI float bf_hi(uint32_t v) { return __uint_as_float(v & 0xffff0000u); }
DEVI void ldsm4t(uint32_t addr, uint32_t& r0, uint32_t& r1, uint32_t& r2, uint32_t& r3) {
  asm volatile("ldmatrix.sync.aligned.m8n8.x4.trans.shared.b16 {%0,%1,%2,%3}, [%4];" : "=r"(r0), "=r"(r1), "=r"(r2), "=r"(r3) : "r"(addr) : "memory");
}
DEVI void stsm4(uint32_t addr, uint32_t r0, uint32_t r1, uint32_t r2, uint32_t r3) {
  asm volatile("stmatrix.sync.aligned.m8n8.x4.shared.b16 [%0], {%1,%2,%3,%4};" :: "r"(addr), "r"(r0), "r"(r1), "r"(r2), "r"(r3) : "memory");
}
DEVI uint2 lds64v(uint32_t a) { uint2 v; asm volatile("ld.volatile.shared.v2.u32 {%0,%1}, [%2];" : "=r"(v.x), "=r"(v.y) : "r"(a) : "memory"); return v; }
DEVI uint32_t lds32v(uint32_t a) { uint32_t v; asm volatile("ld.volatile.shared.u32 %0, [%1];" : "=r"(v) : "r"(a) : "memory"); return v; }
DEVI uint4 lds128v(uint32_t a) { uint4 v; asm volatile("ld.volatile.shared.v4.u32 {%0,%1,%2,%3}, [%4];" : "=r"(v.x), "=r"(v.y), "=r"(v.z), "=r"(v.w) : "r"(a) : "memory"); return v; }
DEVI void cp_async16(uint32_t dst, const void* src) { asm volatile("cp.async.cg.shared.global [%0], [%1], 16;" :: "r"(dst), "l"(src) : "memory"); }
DEVI void cp_async_wait() { asm volatile("cp.async.wait_all;" ::: "memory"); }
DEVI void sts32(uint32_t a, uint32_t x) { asm volatile("st.shared.u32 [%0], %1;" :: "r"(a), "r"(x) : "memory"); }
DEVI int lane_id() { int r; asm volatile("mov.u32 %0, %%laneid;" : "=r"(r)); return r; }
DEVI void sts64(uint32_t a, uint32_t x, uint32_t y) { asm volatile("st.shared.v2.u32 [%0], {%1,%2};" :: "r"(a), "r"(x), "r"(y) : "memory"); }
DEVI void sts128(uint32_t a, uint4 v) { asm volatile("st.shared.v4.u32 [%0], {%1,%2,%3,%4};" :: "r"(a), "r"(v.x), "r"(v.y), "r"(v.z), "r"(v.w) : "memory"); }
DEVI void st_async128(uint32_t a, uint32_t x, uint32_t y, uint32_t z, uint32_t w, uint32_t bar) {
  asm volatile("st.async.weak.shared::cluster.mbarrier::complete_tx::bytes.v4.b32 [%0], {%1,%2,%3,%4}, [%5];" :: "r"(a), "r"(x), "r"(y), "r"(z), "r"(w), "r"(bar) : "memory");
}
DEVI void st_async32(uint32_t a, uint32_t x, uint32_t bar) {
  asm volatile("st.async.weak.shared::cluster.mbarrier::complete_tx::bytes.b32 [%0], %1, [%2];" :: "r"(a), "r"(x), "r"(bar) : "memory");
}
DEVI uint4 ldg_rlx128(const void* p) {
  uint4 v;
  asm volatile("ld.relaxed.gpu.global.v4.b32 {%0,%1,%2,%3}, [%4];" : "=r"(v.x), "=r"(v.y), "=r"(v.z), "=r"(v.w) : "l"(p) : "memory");
  return v;
}
DEVI int ldg_rlx32(const void* p) { int v; asm volatile("ld.relaxed.gpu.global.b32 %0, [%1];" : "=r"(v) : "l"(p) : "memory"); return v; }
DEVI int ldg_acq32(const void* p) { int v; asm volatile("ld.acquire.gpu.global.b32 %0, [%1];" : "=r"(v) : "l"(p) : "memory"); return v; }
DEVI void stg_rlx128(void* p, uint32_t x, uint32_t y, uint32_t z, uint32_t w) {
  asm volatile("st.relaxed.gpu.global.v4.b32 [%0], {%1,%2,%3,%4};" :: "l"(p), "r"(x), "r"(y), "r"(z), "r"(w) : "memory");
}
DEVI void stg128(void* p, uint32_t x, uint32_t y, uint32_t z, uint32_t w) {
  asm volatile("st.global.v4.b32 [%0], {%1,%2,%3,%4};" :: "l"(p), "r"(x), "r"(y), "r"(z), "r"(w) : "memory");
}
DEVI uint2 ldg_rlx64(const void* p) { uint2 v; asm volatile("{.reg .b64 a; ld.relaxed.gpu.global.b64 a, [%2]; mov.b64 {%0,%1}, a;}" : "=r"(v.x), "=r"(v.y) : "l"(p) : "memory"); return v; }
DEVI void stg_rlx64(void* p, uint32_t x, uint32_t y) { asm volatile("{.reg .b64 a; mov.b64 a, {%1,%2}; st.relaxed.gpu.global.b64 [%0], a;}" :: "l"(p), "r"(x), "r"(y) : "memory"); }
DEVI void stg_rlx32(void* p, uint32_t x) { asm volatile("st.relaxed.gpu.global.b32 [%0], %1;" :: "l"(p), "r"(x) : "memory"); }
DEVI void flag_add(int* p) { asm volatile("fence.proxy.async.global; red.release.gpu.global.add.s32 [%0], 1;" :: "l"(p) : "memory"); }
DEVI void e_stg_rlx32(void* p, uint32_t x) { asm volatile(ELECT "st.relaxed.gpu.global.b32 [%0], %1;}" :: "l"(p), "r"(x) : "memory"); }
DEVI void e_flag_add(int* p) { asm volatile("fence.proxy.async.global;\n" ELECT "red.release.gpu.global.add.s32 [%0], 1;}" :: "l"(p) : "memory"); }
DEVI int cluster_rank() { int r; asm volatile("mov.u32 %0, %%cluster_ctarank;" : "=r"(r)); return __shfl_sync(0xffffffffu, r, 0); }
DEVI int cluster_id() { int r; asm volatile("mov.u32 %0, %%clusterid.x;" : "=r"(r)); return __shfl_sync(0xffffffffu, r, 0); }
DEVI uint32_t clock32() { uint32_t c; asm volatile("mov.u32 %0, %%clock;" : "=r"(c)); return c; }
DEVI uint32_t gtime() { uint32_t c; asm volatile("mov.u32 %0, %%globaltimer_lo;" : "=r"(c)); return c; }
DEVI void wait_time(uint32_t t) { while (__any_sync(0xffffffffu, t - gtime() - 1 < 4000u)) {} }
DEVI void spin_until(uint32_t t0, int d) { while (__any_sync(0xffffffffu, (int)(clock32() - t0) < d)) {} }
DEVI void pin2(const void* a, const void* b) { asm volatile("{.reg .pred p; setp.eq.u64 p, %0, %1; @p st.volatile.global.u64 [%0], %1;}" :: "l"(a), "l"(b) : "memory"); }
DEVI void pin2(uint32_t a, uint32_t b) { asm volatile("{.reg .pred p; setp.eq.u32 p, %0, %1; @p st.volatile.shared.u32 [%0], %1;}" :: "r"(a), "r"(b) : "memory"); }
DEVI void p_stg_rlx64(void* p, uint32_t x, uint32_t y, bool c) {
  asm volatile("{.reg .pred p; .reg .b64 a; setp.ne.u32 p, %3, 0; mov.b64 a, {%1,%2}; @p st.relaxed.gpu.global.b64 [%0], a;}" :: "l"(p), "r"(x), "r"(y), "r"((uint32_t)c) : "memory");
}
DEVI void pin2(uint64_t a, uint64_t b) { pin2((const void*)a, (const void*)b); }
DEVI uint64_t pair(uint32_t a, uint32_t bar) { return a | (uint64_t)bar << 32; }
DEVI void st_async32(uint64_t q, uint32_t x) { st_async32((uint32_t)q, x, (uint32_t)(q >> 32)); }
DEVI void st_async128(uint64_t q, uint4 v) { st_async128((uint32_t)q, v.x, v.y, v.z, v.w, (uint32_t)(q >> 32)); }
DEVI float ex2(float x) { float r; asm("ex2.approx.ftz.f32 %0, %1;" : "=f"(r) : "f"(x)); return r; }
DEVI float rcp(float x) { float r; asm("rcp.approx.ftz.f32 %0, %1;" : "=f"(r) : "f"(x)); return r; }
DEVI uint32_t xor_or(uint32_t a, uint32_t t, uint32_t acc) { uint32_t r; asm("lop3.b32 %0, %1, %2, %3, 0xbe;" : "=r"(r) : "r"(a), "r"(t), "r"(acc)); return r; }
DEVI void stsm2(uint32_t addr, uint32_t r0, uint32_t r1) {
  asm volatile("stmatrix.sync.aligned.m8n8.x2.shared.b16 [%0], {%1,%2};" :: "r"(addr), "r"(r0), "r"(r1) : "memory");
}
DEVI uint32_t settag(uint32_t v, uint32_t tag) { return (v & ~1u) | tag; }

#define A4(c, o)  c(d[o+0]), c(d[o+1]), c(d[o+2]), c(d[o+3])
#define A8(c, o)  A4(c, o), A4(c, o+4)
#define A16(c, o) A8(c, o), A8(c, o+8)
#define A20(c, o) A16(c, o), A4(c, o+16)
#define A32(c, o) A16(c, o), A16(c, o+16)
#define RL8  "{%0,%1,%2,%3,%4,%5,%6,%7}"
#define RL16 "{%0,%1,%2,%3,%4,%5,%6,%7,%8,%9,%10,%11,%12,%13,%14,%15}"
#define RL20 "{%0,%1,%2,%3,%4,%5,%6,%7,%8,%9,%10,%11,%12,%13,%14,%15,%16,%17,%18,%19}"
#define RL32 "{%0,%1,%2,%3,%4,%5,%6,%7,%8,%9,%10,%11,%12,%13,%14,%15,%16,%17,%18,%19,%20,%21,%22,%23,%24,%25,%26,%27,%28,%29,%30,%31}"
#define RL64 "{%0,%1,%2,%3,%4,%5,%6,%7,%8,%9,%10,%11,%12,%13,%14,%15,%16,%17,%18,%19,%20,%21,%22,%23,%24,%25,%26,%27,%28,%29,%30,%31," \
  "%32,%33,%34,%35,%36,%37,%38,%39,%40,%41,%42,%43,%44,%45,%46,%47,%48,%49,%50,%51,%52,%53,%54,%55,%56,%57,%58,%59,%60,%61,%62,%63}"
#define WG_OP(shape) "wgmma.mma_async.sync.aligned." shape "k16.f32.bf16.bf16 "
#define DEF_WGMMA(N, RL, AL, i0, i1, i2, i3, i4, i5, i6)                                                                         \
  template<int SC, int TB, long long CB> DEVI void rs##N(float* d, const uint32_t* a) {                                          \
    if (SC) asm volatile("{.reg .b64 tb; mov.b64 tb, %" #i4 ";\n" WG_OP("m64n" #N) RL ", {%" #i0 ",%" #i1 ",%" #i2 ",%" #i3 "}, tb, 1, 1, 1, %" #i5 ";}" \
      : AL("+f", 0) : "r"(a[0]), "r"(a[1]), "r"(a[2]), "r"(a[3]), "n"(CB), "n"(TB));                                             \
    else asm volatile("{.reg .b64 tb; mov.b64 tb, %" #i4 ";\n" WG_OP("m64n" #N) RL ", {%" #i0 ",%" #i1 ",%" #i2 ",%" #i3 "}, tb, 0, 1, 1, %" #i5 ";}" \
      : AL("=f", 0) : "r"(a[0]), "r"(a[1]), "r"(a[2]), "r"(a[3]), "n"(CB), "n"(TB));                                             \
  }                                                                                                                              \
  template<int SC, int TA, int TB, long long CA, long long CB> DEVI void ss##N(float* d, uint32_t a) {                           \
    if (SC) asm volatile("{.reg .b64 ta, tb; .reg .b32 lo, hi; add.u32 lo, %" #i0 ", %" #i1 "; mov.b32 hi, %" #i2 "; mov.b64 ta, {lo, hi}; mov.b64 tb, %" #i3 ";\n" \
      WG_OP("m64n" #N) RL ", ta, tb, 1, 1, 1, %" #i4 ", %" #i5 ";}"                                                              \
      : AL("+f", 0) : "r"(a), "n"((int)CA), "n"((int)(CA >> 32)), "n"(CB), "n"(TA), "n"(TB));                                    \
    else asm volatile("{.reg .b64 ta, tb; .reg .b32 lo, hi; add.u32 lo, %" #i0 ", %" #i1 "; mov.b32 hi, %" #i2 "; mov.b64 ta, {lo, hi}; mov.b64 tb, %" #i3 ";\n" \
      WG_OP("m64n" #N) RL ", ta, tb, 0, 1, 1, %" #i4 ", %" #i5 ";}"                                                              \
      : AL("=f", 0) : "r"(a), "n"((int)CA), "n"((int)(CA >> 32)), "n"(CB), "n"(TA), "n"(TB));                                    \
  }
DEF_WGMMA(8, "{%0,%1,%2,%3}", A4, 4, 5, 6, 7, 8, 9, 10)
DEF_WGMMA(16, RL8, A8, 8, 9, 10, 11, 12, 13, 14)
DEF_WGMMA(32, RL16, A16, 16, 17, 18, 19, 20, 21, 22)
DEF_WGMMA(40, RL20, A20, 20, 21, 22, 23, 24, 25, 26)
DEF_WGMMA(64, RL32, A32, 32, 33, 34, 35, 36, 37, 38)
template<int TA> DEVI void wgmma_n128(float* d, uint64_t a, uint64_t b, int scale_d) {
  asm volatile("{.reg .pred p; setp.ne.b32 p, %66, 0;\n" WG_OP("m64n128") RL64 ", %64, %65, p, 1, 1, %67, 1;}"
    : A32("+f", 0), A32("+f", 32) : "l"(a), "l"(b), "r"(scale_d), "n"(TA));
}

namespace rec {
constexpr int KR = 43;
constexpr uint32_t WSZ = (64 - KR) * 2048, STG = KR * 2048;
constexpr uint32_t WS = 0;
constexpr uint32_t RING = 2 * WSZ;
constexpr uint32_t OB = RING + 3 * 8192;
constexpr uint32_t PB = OB + 4096;
constexpr uint32_t WO = RING + 32768;
constexpr uint32_t ATT = WO + 5 * 16384;
constexpr uint32_t AK = ATT + 10240, AV = ATT + 20480;
constexpr uint32_t PAD = ATT + 30720;
constexpr uint32_t BARS = PAD + 128;
constexpr uint32_t B_XE = BARS  , B_FA = BARS + 64  , B_FB = BARS + 88, B_FO = BARS + 96;
constexpr uint32_t B_ME = BARS + 104  , B_WE = BARS + 136  ;
constexpr uint32_t B_XF = BARS + 152  , B_MF = BARS + 216  , B_CP = BARS + 248  , B_WT = BARS + 280  ;
constexpr uint32_t B_AB = BARS + 296, B_OB = BARS + 304, B_ST = BARS + 312  , B_WS = BARS + 328, B_WO = BARS + 336, B_PD = BARS + 344, B_AT = BARS + 352, B_AV = BARS + 360;
constexpr int NBAR = 46;
constexpr uint32_t M0 = BARS + 384;
constexpr uint32_t SMEM = 232448;
constexpr int NB_P = 1, NB_ST = 2, NB_O = 3, NB_W0 = 4, NB_W1 = 5;
__host__ __device__ constexpr int wo_tile(int rank, int g, int i) { return i < 2 ? i * 6 + rank * 2 + g : 13 + rank - g; }
constexpr long long D_W = CD(WS, 16, 1024, 1), D_X = CD(0, 16, 1024, 1), D_M = CD(RING, 128, 256, 0), D_O = CD(OB, 128, 256, 0);
constexpr long long D_WO = CD(WO, 16, 1024, 1), D_QM = CD(ATT, 640, 0, 0), D_QT = CD(ATT + 128, 640, 64, 0), D_K = CD(AK, 640, 128, 0);
constexpr long long D_V = CD(AV, 128, 640, 0), D_P = CD(PB, 128, 768, 0);
struct Maps { CUtensorMap w[3], wo, xd, xs; };
__host__ __device__ constexpr uint32_t xslot(int s) { return s < 3 ? RING + s * 8192 : s < 5 ? WO + (s - 3) * 8192 : s < 7 ? WO + (s + 1) * 8192 : OB; }
__host__ __device__ constexpr bool k_smem(int k) { return k % 3 == 2; }
__host__ __device__ constexpr int k_idx(int k) { return k % 3 == 2 ? k / 3 : k - k / 3; }
__host__ __device__ constexpr int k_of_reg(int i) { return i + (i >> 1); }
__host__ __device__ constexpr int k_of_smem(int i) { return 3 * i + 2; }

#define RPROF(i)
#define RPROF_STEP
#define CPROF(i, v)

template<int K0, int K1> DEVI void seq_mem(float* d, const uint32_t* w, uint32_t dw) {
  if constexpr (K0 < K1) {
    constexpr long long B = D_M + K0 * 32;
    if constexpr (!k_smem(K0)) rs16<K0 != 0, 1, B>(d, w + 4 * k_idx(K0)); else ss16<1, 1, 1, D_W + k_idx(K0) * 128, B>(d, dw);
    seq_mem<K0 + 1, K1>(d, w, dw);
  }
}
template<bool DUAL, int K0, int K1> DEVI void seq_tok(float* d, const uint32_t* w, uint32_t dw) {
  if constexpr (K0 < K1) {
    constexpr long long B = D_X + (DUAL ? xslot((K0 >> 2) & 7) / 16 : xslot(K0 >> 3) / 16 + ((K0 >> 2) & 1) * 256) + (K0 & 3) * 2;
    if constexpr (DUAL) {
      if constexpr (!k_smem(K0)) rs64<K0 != 0, 0, B>(d, w + 4 * k_idx(K0)); else ss64<1, 1, 0, D_W + k_idx(K0) * 128, B>(d, dw);
    } else {
      if constexpr (!k_smem(K0)) rs32<K0 != 0, 0, B>(d, w + 4 * k_idx(K0)); else ss32<1, 1, 0, D_W + k_idx(K0) * 128, B>(d, dw);
    }
    seq_tok<DUAL, K0 + 1, K1>(d, w, dw);
  }
}
template<int T, int K0> DEVI void seq_wo(float* d, uint32_t dw) {
  if constexpr (K0 < 8) { ss16<K0 != 0, 1, 1, D_WO + T * 1024 + K0 * 128, D_O + K0 * 32>(d, dw); seq_wo<T, K0 + 1>(d, dw); }
}
template<long long Q, int K0> DEVI void seq_s(float* d) {
  if constexpr (K0 < 8) { ss40<K0 != 0, 1, 1, Q + K0 * 80, D_K + K0 * 80>(d, 0); seq_s<Q, K0 + 1>(d); }
}
template<int K0> DEVI void seq_st(float* d) {
  if constexpr (K0 < 8) { ss32<K0 != 0, 1, 1, D_QT + K0 * 80, D_K + 8 + K0 * 80>(d, 0); seq_st<K0 + 1>(d); }
}
template<int K0> DEVI void seq_sm(float* d) {
  if constexpr (K0 < 8) { ss8<K0 != 0, 1, 1, D_QT + K0 * 80, D_K + K0 * 80>(d, 0); seq_sm<K0 + 1>(d); }
}
template<bool DUAL, int J> DEVI void load_x(uint32_t sb, const Maps* M, int t) {
  if (DUAL) e_tma_3d_mc(sb + xslot(J & 7), &M->xd, J * 64, (t - LAG) * 32, 0, sb + B_XF + (J & 7) * 8);
  else e_tma_3d_mc(sb + xslot(J & 7), &M->xs, 0, (t < NSEG ? t : t - LAG) * 32, J * 2, sb + B_XF + (J & 7) * 8);
}
DEVI void load_x_lent(uint32_t sb, const Maps* M, int t, int j) {
  const bool dual = t >= LAG && t < NSEG;
  const uint32_t dst = sb + (j == 3 ? xslot(3) : xslot(5));
#pragma unroll
  for (int i = 0; i < 2; i++)
    e_tma_3d(dst + i * 8192, dual ? &M->xd : &M->xs, dual ? (j + i) * 64 : 0, (t < LAG ? t : t - LAG) * 32, dual ? 0 : (j + i) * 2, sb + B_XF + (j + i) * 8);
}
struct Ctx { uint32_t sb; const Maps* M; int h, rank, wi; bool lead; uint32_t par; };
#define PFN 2
#define ATPOS 1
#define XD 2
template<bool DUAL, int J> DEVI void tok_release(const Ctx& c, int t, int& budget) {
  constexpr int NC = DUAL ? 16 : 8, S = J & 7;
  if constexpr (J + 8 < NC) {
    p_arrive_at(c.sb + B_XE + S * 8, J % 3, c.lead);
    p_expect_tx(c.sb + B_XF + S * 8, 8192, c.lead && c.wi == 0);
  } else if constexpr (S < 3 || S == 7) p_arrive(c.sb + B_ME + (S & 3) * 8, c.lead);
  if constexpr (J == XD - 1) {
    if (c.rank == 1 && c.wi == 5) { mbar_wait(c.sb + B_FO, t & 1, budget); load_x<DUAL, 7>(c.sb, c.M, t); }
  } else if constexpr (J >= XD && J - XD + 8 < NC) {
    constexpr int I = J - XD;
    if (c.rank == I % 3 && c.wi == (I & 1) * 4 + 1) { mbar_wait(c.sb + B_XE + I * 8, (t - LAG) & 1, budget); load_x<DUAL, I + 8>(c.sb, c.M, t); }
  }
}
template<bool DUAL, int J, class F> DEVI bool tok_pass(float* d, const uint32_t* w, uint32_t dw, Ctx& c, int t, int& budget, F after0) {
  constexpr int NC = DUAL ? 16 : 8, KC = 64 / NC;
  if constexpr (J < NC) {
    if constexpr (J > 1) mbar_wait(c.sb + B_XF + (J & 7) * 8, c.par ^ (J >> 3), budget);
    wg_fence();
    seq_tok<DUAL, J * KC, (J + 1) * KC>(d, w, dw);
    wg_commit();
    if constexpr (J == 1) after0();
    if constexpr (J > 0) { wg_wait<1>(); tok_release<DUAL, J - 1>(c, t, budget); }
    return tok_pass<DUAL, J + 1>(d, w, dw, c, t, budget, after0);
  } else {
    const bool ok = mbar_test(c.sb + B_MF, t & 1);
    wg_wait<0>();
    tok_release<DUAL, NC - 1>(c, t, budget);
    if (!DUAL) c.par ^= 1;
    return ok;
  }
}
DEVI void pack_tok(uint32_t* e, const float* d) {
#pragma unroll
  for (int i = 0; i < 8; i++) e[i] = pack_bf16(d[4 * (i & 3) + 2 * (i >> 2)], d[4 * (i & 3) + 2 * (i >> 2) + 1]);
}
DEVI void push_tok(const uint32_t* e, uint32_t sb, uint32_t o, int r) {
  const uint32_t b = mapa(sb, r);
  st_async128(b + o, e[0], e[1], e[2], e[3], b + B_AT);
}
DEVI uint32_t h1_tag(int seg) { return ((seg >> 1) & 1) ^ 1; }
DEVI uint4 pack_part(const float* c, int t) {
  return make_uint4(settag(pack_bf16(c[0], c[1]), h1_tag(t)), pack_bf16(c[2], c[3]), settag(pack_bf16(c[4], c[5]), h1_tag(t - LAG)), pack_bf16(c[6], c[7]));
}
DEVI void put_part(char* p1, char* p2, uint4 z, int t) { p_stg_rlx64(p1, z.x, z.y, t < NSEG); p_stg_rlx64(p2, z.z, z.w, t >= LAG); }

DEVI void rec_math(const uint32_t sb, const int wi, const Maps& M) {
  const int h = cluster_id(), rank = cluster_rank();
  const int warp = wi & 3, wg = wi >> 2;
  const bool lead = (threadIdx.x & 127) == 0;
  int budget = SPIN_BUDGET;
  uint32_t w[4 * KR];
  Ctx cx{sb, &M, h, rank, wi, lead, 0};
  {
    const int lane = lane_id();
    const uint32_t a = sb + wg * STG + ((lane & 7) + (lane >> 4) * 8) * 128 + (((warp * 2 + ((lane >> 3) & 1)) ^ (lane & 7)) << 4);
    mbar_wait(sb + B_ST + wg * 8, 0, budget);
#pragma unroll
    for (int k = 0; k < KR; k++) ldsm4t(a + k * 2048, w[4*k], w[4*k+1], w[4*k+2], w[4*k+3]);
    nbar_arrive<NB_ST, 384>();
    nbar_sync_r(NB_W0 + wg, 128);
    for (int i = 0; i < 5; i++) p_arrive_at(sb + B_FA + i * 8, i == 4, lead);
    mbar_wait(sb + B_WS, 0, budget);
  }
  uint4 z = make_uint4(0, 0, 0, 0);
  char *z1 = nullptr, *z2 = nullptr;
  mbar_wait(sb + B_XF, 0, budget); mbar_wait(sb + B_XF + 8, 0, budget);
#pragma unroll 1
  for (int t = 0;; t++) {
    const uint32_t dw = wg * (WSZ >> 4);
    uint32_t e[16];
    bool ok;
    auto finish = [&]() { put_part(z1, z2, z, t - 1); p_arrive_at(sb + B_FO, 1, lead); };
    if (t >= LAG && t < NSEG) {
      float d[32];
      ok = tok_pass<true, 0>(d, w, dw, cx, t, budget, finish);
      pack_tok(e + 8, d); pack_tok(e, d + 16);
    } else {
      float d[16];
      if (t > 0) finish();
      ok = tok_pass<false, 0>(d, w, dw, cx, t, budget, []() {});
      pack_tok(e, d);
#pragma unroll
      for (int i = 8; i < 16; i++) e[i] = 0;
    }
    RPROF_STEP;
    RPROF(8 + wg * 12 - 32);
    {
      float m[8];
      if (!ok) mbar_wait(sb + B_MF, t & 1, budget);
      wg_fence(); seq_mem<0, 8>(m, w, dw); wg_commit();
      const int lane = lane_id();
      const int seg = t - rank * LAG;
      const bool att = rank < 2 && (unsigned)seg < (unsigned)NSEG;
      char* const p = (char*)g_h1 + ((wo_tile(rank, wg, 0) * 4 + warp) * 4 + (lane >> 3)) * 2048 + h * 64 + (lane & 7) * 8;
      char* const p1 = p + (t & 1) * sizeof(g_h1[0]);
      char* const p2 = p + (2 + ((t - LAG) & 1)) * sizeof(g_h1[0]);
      {
        const uint32_t ao = ATT + rank * 10240 + wi * 1280, to = ao + 128 + (lane & 3) * 128 + (lane >> 2) * 16;
        const bool dual = t >= LAG && t < NSEG;
        RPROF(1 + wg * 12);
        push_tok(e, sb, to, t >= NSEG);
        wg_fence(); seq_mem<8, 16>(m, w, dw); wg_commit();
        push_tok(e + 4, sb, to + 640, t >= NSEG);
        mbar_wait(sb + B_MF + 8, t & 1, budget);
        wg_fence(); seq_mem<16, 24>(m, w, dw); wg_commit();
        if (dual) push_tok(e + 8, sb, to, 1);
        wg_fence(); seq_mem<24, 32>(m, w, dw); wg_commit();
        if (dual) push_tok(e + 12, sb, to + 640, 1);
        wg_wait<2>(); p_arrive_at(sb + B_FA, 0, lead);
        mbar_wait(sb + B_MF + 16, t & 1, budget);
        wg_fence(); seq_mem<32, 48>(m, w, dw); wg_commit();
        wg_wait<1>(); p_arrive_at(sb + B_FA + 8, 0, lead);
        const int la = dual ? rank == 0 : t >= NSEG;
        const uint32_t r0 = mapa(sb, la), r1 = mapa(sb, la ^ 1), m0 = r0 + ao + lane * 4, m1 = r1 + ao + lane * 4, ab = rank == 2 ? B_AV : B_AB;
        uint64_t q0 = pair(m0, r0 + ab), q1 = pair(m0 + 640, r0 + ab), q2 = pair(m1, r1 + ab), q3 = pair(m1 + 640, r1 + ab);
        pin2(q0, q1); pin2(q2, q3);
        mbar_wait(sb + B_MF + 24, t & 1, budget);
        wg_fence(); seq_mem<48, 64>(m, w, dw); wg_commit();
        wg_wait<1>(); p_arrive_at(sb + B_FA + 16, 0, lead);
        pin2(p1, p2);
        if (att && wg == 0) { mbar_wait_cluster(sb + B_AT, seg & 1, budget); fence_proxy_async(); }
        wg_wait<0>();
        const uint32_t a0 = pack_bf16(m[0], m[1]), a1 = pack_bf16(m[2], m[3]), a2 = pack_bf16(m[4], m[5]), a3 = pack_bf16(m[6], m[7]);
        st_async32(q0, la ? a2 : a0); st_async32(q1, la ? a3 : a1);
        if (dual) { st_async32(q2, la ? a0 : a2); st_async32(q3, la ? a1 : a3); }
        p_arrive(sb + B_PD, lead && wg == 0);
      }
      RPROF(2 + wg * 12);
      auto wo_ready = [&]() { if (t == 0) mbar_wait(sb + B_WO, 0, budget); if (t < NSTEP - 1) mbar_wait(sb + B_WT, t & 1, budget); };
      constexpr float SC = 0.08838834764831845f * 1.4426950408889634f;
      if (!att) wo_ready();
      else {
        float s[32];
        if (wg) {
          const uint32_t pw = sb + PB + lane * 4, o = OB + (lane >> 4) * 2048 + warp * 512 + rank * 256 + (lane & 15) * 16;
          const uint32_t r0 = mapa(sb, (warp & 1) ? 2 : rank ^ 1), r1 = mapa(sb, (warp & 1) ? rank ^ 1 : 2);
          uint64_t q0 = pair(r0 + o, r0 + B_OB), q1 = pair(r1 + o, r1 + B_OB);
          uint32_t one[4];
#pragma unroll
          for (int i = 0; i < 4; i++) one[i] = 0x3F803F80u + (pw >> 31);
          pin2(q0, q1); pin2(q1, (uint64_t)pw);
          wo_ready();
          mbar_wait_cluster(sb + B_AT, seg & 1, budget);
          mbar_wait_cluster(sb + B_AB, seg & 1, budget);
          fence_proxy_async();
          RPROF(3 + 12);
          wg_fence(); seq_s<D_QM, 0>(s); wg_commit();
          nbar_arrive<NB_P, 256>();
          if (warp == 1) sts32(pw + 640, 0);
          mbar_wait_cluster(sb + B_AV, seg & 1, budget);
          wg_wait<0>();
          float mx = fmaxf(fmaxf(fmaxf(s[0], s[1]), fmaxf(s[4], s[5])), fmaxf(fmaxf(fmaxf(s[8], s[9]), fmaxf(s[12], s[13])), fmaxf(s[16], s[17])));
          const float x1 = __shfl_xor_sync(0xffffffffu, mx, 1), x2 = __shfl_xor_sync(0xffffffffu, mx, 2), x3 = __shfl_xor_sync(0xffffffffu, mx, 3);
          const float u = (warp & 2) ? ((warp & 1) ? s[16] : s[12]) : ((warp & 1) ? s[8] : s[4]);
          const float v = (warp & 2) ? ((warp & 1) ? s[17] : s[13]) : ((warp & 1) ? s[9] : s[5]);
          const float ms = -SC * fmaxf(fmaxf(mx, x1), fmaxf(x2, x3));
          sts32(pw + 128 + warp * 128, pack_bf16(ex2(fmaf(u, SC, ms)), ex2(fmaf(v, SC, ms))));
          if (warp == 0) sts32(pw, pack_bf16(ex2(fmaf(s[0], SC, ms)), ex2(fmaf(s[1], SC, ms))));
          fence_proxy_async();
          nbar_sync<NB_W1, 128>();
          RPROF(4 + 12);
          wg_fence();
          rs8<0, 0, D_P>(s + 8, one); rs8<1, 0, D_P + 16>(s + 8, one); rs8<1, 0, D_P + 32>(s + 8, one);
          wg_commit();
          ss8<0, 0, 0, D_V, D_P>(s, 0); ss8<0, 0, 0, D_V + 320, D_P>(s + 4, 0);
          ss8<1, 0, 0, D_V + 16, D_P + 16>(s, 0); ss8<1, 0, 0, D_V + 336, D_P + 16>(s + 4, 0);
          ss8<1, 0, 0, D_V + 32, D_P + 32>(s, 0); ss8<1, 0, 0, D_V + 352, D_P + 32>(s + 4, 0);
          wg_commit();
          wg_wait<1>();
          const float i0 = rcp(s[8]), i1 = rcp(s[9]);
          wg_wait<0>();
          stsm4(sb + o, pack_bf16(s[0] * i0, s[1] * i1), pack_bf16(s[2] * i0, s[3] * i1), pack_bf16(s[4] * i0, s[5] * i1), pack_bf16(s[6] * i0, s[7] * i1));
          __syncwarp();
          const uint4 y = lds128v(sb + o);
          if (t < NSTEP - 1) { st_async128(q0, y); st_async128(q1, y); e_complete_tx(sb + B_OB, 512); }
        } else {
          wg_fence(); seq_st<0>(s + 4); wg_commit();
          const int g = lane >> 2, lim = 8 * (g >> 1) + (g & 1) + 2 * warp - 8 * (lane & 3);
          const uint32_t pw = sb + PB + 768 + warp * 768 + lane * 16;
          char* const og = (char*)(g_ot + rank * O_LAYER) + (size_t)(h * DH + warp * 16 + (lane >> 2)) * (SEQ * 2) + seg * 64 + (lane & 3) * 16;
          pin2(pw, lim); pin2(og, nullptr);
          wo_ready();
          nbar_sync<NB_P, 256>();
          RPROF(3);
          wg_fence(); seq_sm<0>(s); wg_commit();
          mbar_wait_cluster(sb + B_AV, seg & 1, budget);
          wg_wait<0>();
#pragma unroll
          for (int i = 0; i < 8; i++) { float& v = s[4 + 4 * (i >> 1) + (i & 1)]; v = i <= lim ? v : -INFINITY; }
          float mx = fmaxf(fmaxf(fmaxf(s[0], s[1]), fmaxf(s[4], s[5])), fmaxf(fmaxf(fmaxf(s[8], s[9]), fmaxf(s[12], s[13])), fmaxf(s[16], s[17])));
          const float x1 = __shfl_xor_sync(0xffffffffu, mx, 1), x2 = __shfl_xor_sync(0xffffffffu, mx, 2), x3 = __shfl_xor_sync(0xffffffffu, mx, 3);
          const float ms = -SC * fmaxf(fmaxf(mx, x1), fmaxf(x2, x3));
#pragma unroll
          for (int i = 0; i < 10; i++) { float& v = s[4 * (i >> 1) + (i & 1)]; v = ex2(fmaf(v, SC, ms)); }
          const float sum = (((s[0] + s[1]) + (s[4] + s[5])) + ((s[8] + s[9]) + (s[12] + s[13]))) + (s[16] + s[17]);
          const float y1 = __shfl_xor_sync(0xffffffffu, sum, 1), y2 = __shfl_xor_sync(0xffffffffu, sum, 2), y3 = __shfl_xor_sync(0xffffffffu, sum, 3);
          const float inv = rcp((sum + y1) + (y2 + y3));
          stsm4(pw, pack_bf16(s[0] * inv, s[1] * inv), pack_bf16(s[4] * inv, s[5] * inv), pack_bf16(s[8] * inv, s[9] * inv), pack_bf16(s[12] * inv, s[13] * inv));
          stsm2(pw + 512, pack_bf16(s[16] * inv, s[17] * inv), 0);
          fence_proxy_async();
          nbar_sync<NB_W0, 128>();
          RPROF(4);
          wg_fence();
          ss32<0, 0, 0, D_V, D_P + 48>(s, 0); ss32<0, 0, 0, D_V + 320, D_P + 48>(s + 16, 0);
          ss32<1, 0, 0, D_V + 16, D_P + 64>(s, 0); ss32<1, 0, 0, D_V + 336, D_P + 64>(s + 16, 0);
          ss32<1, 0, 0, D_V + 32, D_P + 80>(s, 0); ss32<1, 0, 0, D_V + 352, D_P + 80>(s + 16, 0);
          wg_commit();
          wg_wait<0>();
#pragma unroll
          for (int i = 0; i < 4; i++) {
            const float* d = s + (i >> 1) * 16 + (i & 1) * 2;
            stg128(og + ((i >> 1) * 64 + (i & 1) * 8) * (SEQ * 2), pack_bf16(d[0], d[1]), pack_bf16(d[4], d[5]), pack_bf16(d[8], d[9]), pack_bf16(d[12], d[13]));
          }
          nbar_arrive<NB_O, 160>();
        }
      }
      RPROF(5 + wg * 12);
      const bool three = wg == 1 || rank == 2;
      if (t < NSTEP - 1) {
        float c[24];
        const uint32_t dt = wg ? 0 : 3072;
        mbar_wait_cluster(sb + B_OB, t & 1, budget);
        fence_proxy_async();
        RPROF(6 + wg * 12);
        wg_fence(); seq_wo<0, 0>(c, dt); wg_commit(); seq_wo<1, 0>(c + 8, dt); wg_commit();
        mbar_wait(sb + B_XF, cx.par, budget);
        wg_wait<1>();
        if (warp == 2) load_x_lent(sb, &M, t + 1, wg ? 3 : 5);
        put_part(p1, p2, pack_part(c, t), t);
        const int o3 = (wo_tile(rank, wg, three ? 2 : 1) - wo_tile(rank, wg, 0)) * 32768;
        z1 = p1 + o3; z2 = p2 + o3;
        if (three) {
          wg_fence(); seq_wo<2, 0>(c + 16, dt); wg_commit();
          wg_wait<1>(); put_part(p1 + 6 * 32768, p2 + 6 * 32768, pack_part(c + 8, t), t);
          mbar_wait(sb + B_XF + 8, cx.par, budget);
          wg_wait<0>(); z = pack_part(c + 16, t);
        } else { mbar_wait(sb + B_XF + 8, cx.par, budget); wg_wait<0>(); z = pack_part(c + 8, t); }
      } else {
        for (int i = 0; i < (three ? 3 : 2); i++) stg_rlx64(p2 + (wo_tile(rank, wg, i) - wo_tile(rank, wg, 0)) * 32768, 0, 0);
        break;
      }
      RPROF(7 + wg * 12);
    }
  }
}

DEVI void wait_xa(const int* p, int& budget) {
  while (__any_sync(0xffffffffu, ldg_acq32(p) < 64) && --budget > 0) {}
  fence_proxy_global();
}
template<bool DUAL> DEVI void first_loads(uint32_t sb, const Maps* M, int n, int h, int& budget) {
#pragma unroll
  for (int i = 0; i < PFN; i++) {
    if (DUAL) e_prefetch_3d(&M->xd, ((h + i * (16 / PFN)) & 15) * 64, (n - LAG) * 32, 0);
    else e_prefetch_3d(&M->xs, 0, (n < NSEG ? n : n - LAG) * 32, ((h + i * (8 / PFN)) & 7) * 2);
  }
  mbar_wait(sb + B_FA, n & 1, budget); load_x<DUAL, 0>(sb, M, n);
  mbar_wait(sb + B_FA + 8, n & 1, budget); load_x<DUAL, 1>(sb, M, n);
  mbar_wait(sb + B_FA + 16, n & 1, budget); load_x<DUAL, 2>(sb, M, n);
}
template<bool DUAL> DEVI void lent_loads(uint32_t sb, const Maps* M, int n, int& budget) {
  mbar_wait(sb + B_FB, n & 1, budget);
  load_x<DUAL, 3>(sb, M, n); load_x<DUAL, 4>(sb, M, n); load_x<DUAL, 5>(sb, M, n); load_x<DUAL, 6>(sb, M, n);
}
DEVI void rec_comm(const uint32_t sb, const int warp, const Maps& M, const bf16* __restrict__ mem0) {
  const int lane = threadIdx.x & 31, h = cluster_id(), rank = cluster_rank();
  int budget = SPIN_BUDGET;
  const bool two = warp == 3 || (rank == 2 && warp == 2);
  const int ntask = two ? 2 : 1, qi = two ? (warp == 3 ? rank : 3) : rank * 3 + warp;
  const int task0 = two ? h * 2 + (qi >> 1) : 64 + h * 4 + (qi >> 1);
  auto h2_word = [&](int i, int ln) {
    const int task = task0 + i * 192;
    return (char*)g_h2 + (task >> 2) * 512 + ((qi ^ i) & 1) * 256 + (task & 3) * 32 + (ln & 8) * 16 + (ln & 7) * 4;
  };
  auto first_x = [&](int t) {
    const int n = t + 1;
    p_expect_tx(sb + B_XF + (lane_id() & 7) * 8, 8192, lane_id() < 8);
    if (rank == 0) {
      if (n < NSEG && (n & 3) == 0) wait_xa(&g_xa[0][n >> 2], budget);
      if (n >= LAG && ((n - LAG) & 3) == 0) wait_xa(&g_xa[1][(n - LAG) >> 2], budget);
      if (n >= LAG && n < NSEG) first_loads<true>(sb, &M, n, h, budget); else first_loads<false>(sb, &M, n, h, budget);
    }
  };
  {
    const int task = task0 + (lane >> 4) * 192, L = (task & 3) * 8 + (lane & 7);
    if ((lane >> 4) < ntask) {
      const bf16* p = mem0 + (L & 3) * 2 * DM + (task >> 2) * 16 + (L >> 2) + (lane & 8);
      uint32_t m0 = (uint32_t)__bfloat16_as_ushort(p[0]) | (uint32_t)__bfloat16_as_ushort(p[DM]) << 16;
      m0 = m0 ? m0 : 0x8000u;
      stg_rlx32(h2_word(lane >> 4, lane), m0);
      sts32(sb + M0 + warp * 128 + lane * 4, m0);
    }
    __syncwarp();
    nbar_sync<NB_ST, 384>();
    if (warp == 2) {
      e_expect_tx(sb + B_WS, 2 * WSZ);
#pragma unroll 1
      for (int i = 0; i < 2 * (64 - KR); i++) e_tma_2d(sb + WS + (i & 1) * WSZ + (i >> 1) * 2048, &M.w[rank], h * DH + (i & 1) * 64, k_of_smem(i >> 1) * 16, sb + B_WS);
      const int nt = rank == 2 ? 6 : 5;
      e_expect_tx(sb + B_WO, (nt - 2) * 16384);
#pragma unroll 1
      for (int i = 1; i < nt; i++) if (i != 3) e_tma_2d(sb + WO + i * 16384, &M.wo, wo_tile(rank, 1 - i / 3, i % 3) * 64, h * DH, sb + B_WO);
    }
    if (warp == 3) { first_x(-1); if (rank == 0) lent_loads<false>(sb, &M, 0, budget); }
  }
  uint32_t t0 = gtime() - 4000, cpp = 0;
  const uint32_t cp = sb + B_CP + warp * 8;
#pragma unroll 1
  for (int t = 0;; t++) {
    const int n = t + 1, seg = t - rank * LAG;
    RPROF_STEP;
    const bool att = rank < 2 && (unsigned)seg < (unsigned)NSEG;
    if (warp == 3) {
      if (att) { e_expect_tx(sb + B_AT, 24576); e_expect_tx(sb + B_AB, 4096); e_expect_tx(sb + B_AV, 2048); }
      if (n < NSTEP) e_expect_tx(sb + B_OB, t < NSEG && t >= LAG ? 4096 : 2048);
    }
    {
      const uint32_t dst = sb + RING + warp * 8192;
      mbar_wait(sb + B_ME + warp * 8, t & 1, budget);
      wait_time(t0 + TP(1) + warp * TP(4));
      const int lane = lane_id();
      RPROF(24); CPROF(0, gtime());
      int tries = 0;
      while (true) {
        tries++;
        e_expect_tx(cp, 8192);
        e_bulk_g2s(dst, (const char*)g_h2[t & 3] + warp * 8192, 8192, cp);
        mbar_wait(cp, cpp, budget); cpp ^= 1;
        uint32_t mn = 0xffffffffu;
#pragma unroll
        for (int i = 0; i < 8; i++) mn = min(mn, lds32v(dst + i * 1024 + lane * 32 + (lane >> 2) * 4));
        if (!__any_sync(0xffffffffu, mn == 0) || --budget < 0) break;
      }
      e_arrive(sb + B_MF + warp * 8);
      RPROF(25); CPROF(1, gtime()); CPROF(2, tries);
    }
    {
      const int ln = lane_id(), i = ln >> 4;
      char* const w = h2_word(i, ln);
      if (i < ntask) {
        stg_rlx32(w + ((t + 3) & 3) * sizeof(g_h2[0]), 0);
        if (n < NSTEP && (((qi ^ i) & 1) ? t < LAG : t >= NSEG)) stg_rlx32(w + (n & 3) * sizeof(g_h2[0]), lds32v(sb + M0 + warp * 128 + ln * 4));
      }
      __syncwarp();
    }
    if (n < NSTEP) {
      const uint32_t tag = (n >> 1) & 31;
      if (warp == 3) first_x(t);
      if (warp == 2) {
        mbar_wait(sb + B_ME + 24, t & 1, budget);
        e_expect_tx(sb + B_WT, 32768);
        e_tma_2d(sb + WO, &M.wo, wo_tile(rank, 1, 0) * 64, h * DH, sb + B_WT);
        e_tma_2d(sb + WO + 49152, &M.wo, wo_tile(rank, 0, 0) * 64, h * DH, sb + B_WT);
      }
      mbar_wait(sb + B_PD, t & 1, budget);
      t0 = clock32();
      if (warp == 0 && rank == (t >= NSEG)) { mbar_wait(sb + B_AB, seg & 1, budget); e_stg_rlx32(&g_ts[t & 1][h * TSS], (gtime() & ~31u) | tag); }
      spin_until(t0, TSD);
      uint32_t v;
      do { v = ldg_rlx32(&g_ts[t & 1][lane_id() * TSS]); } while (__any_sync(0xffffffffu, (v & 31) != tag) && --budget > 0);
      const uint32_t now = __shfl_sync(0xffffffffu, v, 0);
      t0 = now + __reduce_max_sync(0xffffffffu, (int)(v - now));
      if (warp == 3) mbar_wait(sb + B_OB, t & 1, budget);
    }
    if (n < NSTEP) {
      RPROF(26); CPROF(3, t0);
#pragma unroll 1
      for (int i = 0; i < ntask; i++) {
        const int layer = (qi ^ i) & 1, sg = t - layer * LAG, task = task0 + i * 192;
        if ((unsigned)sg >= (unsigned)NSEG) continue;
        const uint32_t tag = h1_tag(sg);
        const int ln = lane_id();
        const char* const src = (const char*)g_h1[layer * 2 + (sg & 1)] + task * 2048 + ln * 8;
        char* const dst = h2_word(i, ln) + (n & 3) * sizeof(g_h2[0]);
        uint2 v[8];
        pin2(src, dst);
        wait_time(t0 + TP(0) + (task < 96 ? 0 : task < 192 ? TP(3) : 2 * TP(3)));
        int tries = 0;
        float a[4];
        while (true) {
          tries++;
#pragma unroll
          for (int k = 0; k < 8; k++) v[k] = ldg_rlx64(src + k * 256);
          uint32_t bad = 0;
#pragma unroll
          for (int k = 0; k < 8; k++) {
            bad = xor_or(v[k].x, tag, bad);
            a[0] = k ? a[0] + bf_lo(v[k].x) : bf_lo(v[k].x); a[1] = k ? a[1] + bf_hi(v[k].x) : bf_hi(v[k].x);
            a[2] = k ? a[2] + bf_lo(v[k].y) : bf_lo(v[k].y); a[3] = k ? a[3] + bf_hi(v[k].y) : bf_hi(v[k].y);
          }
#pragma unroll
        for (int k = 0; k < 2; k++) {
          const float keep = (ln & 8) ? a[2+k] : a[k], send = (ln & 8) ? a[k] : a[2+k];
          a[k] = keep + __shfl_xor_sync(0xffffffffu, send, 8);
        }
#pragma unroll
        for (int k = 0; k < 2; k++) a[k] += __shfl_xor_sync(0xffffffffu, a[k], 16);
          if (!__any_sync(0xffffffffu, bad & 1) || --budget < 0) break;
        }
        const uint32_t out = pack_bf16(a[0], a[1]);
        if (ln < 16) stg_rlx32(dst, out ? out : 0x8000u);
        __syncwarp();
        if (i == 0) { RPROF(28); CPROF(6, gtime()); CPROF(4, gtime()); CPROF(5, tries); } else CPROF(7, gtime());
      }
    }
    if (warp == 1 && att) { nbar_sync<NB_O, 160>(); e_flag_add(&g_dep[E_O1 + rank * 16 + (seg >> 2)]); }
    if (n == NSTEP) break;
  }
  if (h == 0 && rank == 0 && warp < 2) g_xa[warp][lane_id()] = 0;
}
}

__global__ void __cluster_dims__(3, 1, 1) __launch_bounds__(384, 1)
rec_kernel(const __grid_constant__ rec::Maps M, const bf16* __restrict__ mem0) {
  using namespace rec;
  extern __shared__ __align__(1024) uint8_t smem[];
  const uint32_t sb = __shfl_sync(0xffffffffu, smem_u32(smem), 0);
  const int tid = threadIdx.x, wi = __shfl_sync(0xffffffffu, tid >> 5, 0);
  if ((sb & 0x3FFFF) != SMEM_BASE) __trap();
  if (wi == 0) {
    const int h = cluster_id(), rank = cluster_rank();
    for (int i = tid; i < NBAR; i += 32) mbar_init(sb + BARS + i * 8, i < 13 ? 6 : i < 19 ? 2 : 1);
    ((uint32_t*)(smem + PAD))[tid] = 0;
    fence_mbar_init(); fence_proxy_async();
    __syncwarp();
    e_expect_tx(sb + B_ST, STG); e_expect_tx(sb + B_ST + 8, STG);
    for (int i = 0; i < 2 * KR; i++) e_tma_2d(sb + (i & 1) * STG + (i >> 1) * 2048, &M.w[rank], h * DH + (i & 1) * 64, k_of_reg(i >> 1) * 16, sb + B_ST + (i & 1) * 8);
  } else if (wi == 1) {
    if (blockIdx.x < NEV / 32) { g_dep[blockIdx.x * 32 + (tid & 31)] = 0; g_claim[blockIdx.x * 32 + (tid & 31)] = 0; __threadfence(); }
    __syncwarp();
    asm volatile("griddepcontrol.launch_dependents;" ::: "memory");
  }
  cluster_arrive(); cluster_wait();
  if (wi < 8) { reg_inc<232>(); rec_math(sb, wi, M); cluster_arrive(); cluster_wait(); }
  else { reg_dec<40>(); rec_comm(sb, wi & 3, M, mem0); cluster_arrive(); cluster_wait(); }
}

namespace gm {
struct Maps { CUtensorMap ot, wo, xn, wg, wu, hl, hs, wd, out; };
constexpr int STAGES = 6, STAGE = 32768;
constexpr uint32_t SO = STAGES * STAGE, BARS = SO + 32768;
constexpr uint32_t B_FULL = BARS, B_EMPTY = BARS + 48, B_TF = BARS + 96, B_TE = BARS + 112, B_ORD = BARS + 128, B_PM = BARS + 144, B_GO = BARS + 160;
constexpr uint32_t MAIL = BARS + 176, PMAIL = BARS + 192;
constexpr uint32_t SMEM = BARS + 256;
constexpr int END = -1;

struct Tile {
  bool isO, isG, l2; int blk, col, k0, n;
  DEVI Tile(int task, int rank) {
    const int e = task >> 8, id = task & 255;
    const bool isD = e < E_G1 || e >= E_D2;
    isO = e >= E_O1 && e < E_G2; isG = !isD && !isO; l2 = e >= E_O2;
    blk = isG && l2 ? (e & 15) * 2 + rank : isD && !l2 ? e >> 1 : e & 15;
    col = isG ? (l2 ? id : id * 2 + rank) : (id & 3) * 2 + rank;
    k0 = isO ? (id >> 2) * 2048 : isG ? 0 : ((l2 ? e >> 4 : e) & 1) * 1792;
    n = isO ? 32 : isG ? 16 : 28;
  }
};

DEVI float geglu(float g, float u) {
  const float z = g * (0.7978845608028654f + 0.035677408136300125f * g * g);
  float t; asm("tanh.approx.f32 %0, %1;" : "=f"(t) : "f"(z));
  const float hg = 0.5f * g;
  return fmaf(hg, t, hg) * u;
}
struct Sched {
  int need, size;
  bool filler;
  uint4 dep, cl;
  DEVI void init(int lane) {
    const int e = lane * 4;
    const bool d = e < E_G1 || e >= E_D2, o = e >= E_O1 && e < E_G2;
    need = d ? 28 : e < E_O1 ? 64 : 128;
    size = d ? 4 : o ? 8 : e < E_O1 ? 28 : e < E_G2 + 8 ? 56 : 0;
    filler = (int)blockIdx.x < TP(5);
  }
  DEVI void scan(int lane) { cl = ldg_rlx128(g_claim + lane * 4); dep = ldg_rlx128(g_dep + lane * 4); }
  DEVI int next(int lane, int& budget) {
    while (--budget > 0) {
      int av[4], open = 0;
#pragma unroll
      for (int i = 0; i < 4; i++) { const int r = max(size - (int)(&cl.x)[i], 0); open |= r; av[i] = ((int)(&dep.x)[i] >= need ? r : 0) + (i ? av[i - 1] : 0); }
      const uint32_t mo = __ballot_sync(0xffffffffu, open);
      if (!mo) break;
      if (!filler && (mo & TP(6)) && lane >= E_O2 / 4) av[3] = 0;
      int inc = av[3], pos = 0;
      while (true) {
        const uint32_t m = __ballot_sync(0xffffffffu, inc > pos && av[3]);
        if (!m) break;
        const int l = __ffs(m) - 1, rel = pos - (inc - av[3]), i = (rel >= av[0]) + (rel >= av[1]) + (rel >= av[2]);
        int r = 0;
        if (lane == l) {
          const int tk = atomicAdd(g_claim + lane * 4 + i, 1);
          r = tk < size ? (lane * 4 + i) << 8 | tk : -1 - (inc - av[3] + (i == 0 ? av[0] : i == 1 ? av[1] : i == 2 ? av[2] : av[3]) + tk - size);
        }
        r = __shfl_sync(0xffffffffu, r, l);
        if (r >= 0) return r;
        if (pos == 0) {
#pragma unroll
          for (int o = 1; o < 32; o <<= 1) { const int v = __shfl_up_sync(0xffffffffu, inc, o); if (lane >= o) inc += v; }
        }
        pos = -1 - r;
      }
      if (pos == 0) __nanosleep(TP(7));
      scan(lane);
    }
    return END;
  }
};

DEVI void scheduler(const uint32_t sb) {
  const int lane = threadIdx.x & 31;
  int budget = SPIN_BUDGET;
  Sched sc; sc.init(lane);
#pragma unroll 1
  for (int i = 0;; i++) {
    mbar_wait(sb + B_GO, (i & 1) ^ 1, budget);
    sc.scan(lane);
    const int task = sc.next(lane, budget);
    const uint32_t r = mapa(sb, lane & 1);
    if (lane < 2) st_async32(r + PMAIL + (i & 1) * 4, task, r + B_PM + (i & 1) * 8);
    __syncwarp();
    if (task == END) break;
  }
}

DEVI void producer(const uint32_t sb, const Maps& M) {
  const int lane = threadIdx.x & 31, rank = cluster_rank();
  int budget = SPIN_BUDGET, s = 0, ph = 0;
#pragma unroll 1
  for (int i = 0;; i++) {
    e_expect_tx(sb + B_PM + (i & 1) * 8, 4);
    mbar_wait_cluster(sb + B_PM + (i & 1) * 8, (i >> 1) & 1, budget);
    const int task = budget < 0 ? END : __shfl_sync(0xffffffffu, (int)lds32v(sb + PMAIL + (i & 1) * 4), 0);
    fence_proxy_global();
    for (int z = 0; z < (task == END ? 2 : 1); z++) {
      const int g = (i + z) & 1;
      mbar_wait(sb + B_TE + g * 8, (((i + z) >> 1) & 1) ^ 1, budget);
      if (lane == 0) { sts64(sb + MAIL + g * 8, task, s | ph << 8); mbar_arrive(sb + B_TF + g * 8); }
      __syncwarp();
    }
    if (task == END) break;
    const Tile T(task, rank);
    const bool shareB = T.isG && T.l2;
    const CUtensorMap* mA = T.isO ? &M.ot : T.isG ? &M.xn : &M.hl;
    const CUtensorMap* mB0 = T.isO ? &M.wo : T.isG ? &M.wg : &M.wd;
    const CUtensorMap* mB1 = T.isG ? &M.wu : mB0;
    const int c0 = T.col * (T.isG ? 64 : 128), c1 = T.isG ? c0 : c0 + 64, row = T.blk * 128;
    const int ok = 0;
    int k = T.k0;
#pragma unroll 1
    for (int it = 0; it < T.n; it++, k += 64) {
      const uint32_t a = sb + s * STAGE, fb = sb + B_FULL + s * 8;
      mbar_wait(sb + B_EMPTY + s * 8, ph ^ 1, budget);
      e_expect_tx(fb, STAGE);
      if (shareB) {
        e_tma_2d_mc(a + 16384 + rank * 8192, rank ? mB1 : mB0, c0, k, fb);
        e_tma_2d(a, mA, k, row, fb); e_tma_2d(a + 8192, mA, k, row + 64, fb);
      } else {
        e_tma_2d_mc(a + rank * 8192, mA, T.isO ? row + rank * 64 : k, T.isO ? k + ok : row + rank * 64, fb);
        e_tma_2d(a + 16384, mB0, c0, k, fb); e_tma_2d(a + 24576, mB1, c1, k, fb);
      }
      if (it == T.n - TP(2)) e_arrive(sb + B_GO);
      if (++s == STAGES) { s = 0; ph ^= 1; }
    }
  }
}

template<int TA> DEVI void mainloop(float* d0, float* d1, uint32_t sb, int n, int s, int ph, bool lead, uint32_t ord, int& budget) {
  int prev = 0;
  const uint32_t rel = threadIdx.x & 127;
#pragma unroll 1
  for (int i = 0; i < n; i++) {
    mbar_wait(sb + B_FULL + s * 8, ph, budget);
    const uint32_t a = sb + s * STAGE;
    const uint64_t da = mkdesc(a, 16, 1024), db = mkdesc(a + 16384, 8192, 1024);
    wg_fence();
#pragma unroll
    for (int k = 0; k < 4; k++) {
      wgmma_n128<TA>(d0, da + k * (TA ? 128 : 2), db + k * 128, (i | k) != 0);
      wgmma_n128<TA>(d1, da + 512 + k * (TA ? 128 : 2), db + k * 128, (i | k) != 0);
    }
    wg_commit();
    if (i > 0) { wg_wait<1>(); p_arrive_at(sb + B_EMPTY + prev * 8, rel & 1, rel < 2); }
    prev = s;
    if (++s == STAGES) { s = 0; ph ^= 1; }
  }
  p_arrive(ord, lead);
  wg_wait<0>();
  p_arrive_at(sb + B_EMPTY + prev * 8, rel & 1, rel < 2);
}

DEVI void consumer(const uint32_t sb, const Maps& M, const int wg) {
  const int tid = threadIdx.x, lane = tid & 31, warp = (tid >> 5) & 3;
  const bool lead = (tid & 127) == 0;
  const uint32_t so = sb + SO + wg * 16384;
  int budget = SPIN_BUDGET;
  float d0[64], d1[64];
#pragma unroll 1
  for (int m = 0;; m++) {
    mbar_wait(sb + B_TF + wg * 8, m & 1, budget);
    const uint2 mail = lds64v(sb + MAIL + wg * 8);
    const int task = __shfl_sync(0xffffffffu, (int)mail.x, 0), pos = __shfl_sync(0xffffffffu, (int)mail.y, 0);
    e_arrive(sb + B_TE + wg * 8);
    if (task == END || budget < 0) break;
    const Tile T(task, cluster_rank());
    mbar_wait(sb + B_ORD + wg * 8, (m & 1) ^ wg ^ 1, budget);
    if (T.isO) mainloop<1>(d0, d1, sb, 32, pos & 255, pos >> 8, lead, sb + B_ORD + (wg ^ 1) * 8, budget);
    else mainloop<0>(d0, d1, sb, T.n, pos & 255, pos >> 8, lead, sb + B_ORD + (wg ^ 1) * 8, budget);
    const uint32_t st = so + (warp * 16 + (lane & 15)) * 128;
    if (T.isG) {
#pragma unroll
      for (int mm = 0; mm < 2; mm++) {
        const float* d = mm ? d1 : d0;
#pragma unroll
        for (int c = 0; c < 4; c++) {
          uint32_t r[4];
#pragma unroll
          for (int i = 0; i < 4; i++) r[i] = pack_bf16(geglu(d[8*c+2*i], d[32+8*c+2*i]), geglu(d[8*c+2*i+1], d[33+8*c+2*i]));
          stsm4(st + mm * 8192 + (((2 * c + (lane >> 4)) ^ (lane & 7)) << 4), r[0], r[1], r[2], r[3]);
        }
      }
      fence_proxy_async();
      nbar_sync_r(1 + wg, 128);
      if (lead) {
        tma_store_2d(&M.hs, so, T.col * 64, T.blk * 128);
        bulk_commit(); bulk_wait<0>();
        flag_add(&g_dep[T.l2 ? E_D2 + (T.col >= 28) * 16 + T.blk : E_D1 + T.blk * 2 + (T.col >= 28)]);
      }
    } else {
#pragma unroll
      for (int hf = 0; hf < 2; hf++) {
        if (hf) { if (lead) bulk_wait_read<0>(); nbar_sync_r(1 + wg, 128); }
#pragma unroll
        for (int mm = 0; mm < 2; mm++) {
          const float* d = (mm ? d1 : d0) + hf * 32;
#pragma unroll
          for (int c = 0; c < 4; c++)
            stsm4(st + mm * 8192 + (((2 * c + (lane >> 4)) ^ (lane & 7)) << 4), pack_bf16(d[8*c], d[8*c+1]), pack_bf16(d[8*c+2], d[8*c+3]),
                  pack_bf16(d[8*c+4], d[8*c+5]), pack_bf16(d[8*c+6], d[8*c+7]));
        }
        fence_proxy_async();
        nbar_sync_r(1 + wg, 128);
        if (lead) { tma_radd_2d(&M.out, so, T.col * 128 + hf * 64, T.blk * 128); bulk_commit(); }
      }
      if (lead) {
        bulk_wait<0>();
        if (T.isO || !T.l2) flag_add(&g_dep[(!T.isO ? E_LX2 : T.l2 ? E_LX1B : E_LX1A) + T.blk]);
      }
    }
    __syncwarp();
  }
}

DEVI void norm_helper(const bf16* __restrict__ x, bf16* out) {
  const int lane = threadIdx.x & 31;
  int budget = SPIN_BUDGET, tk = lane < 4 ? -1 : 1024;
#pragma unroll 1
  while (--budget > 0) {
    if (tk < 0) tk = atomicAdd(g_claim + E_LI + lane, 1);
    if (__all_sync(0xffffffffu, tk >= 1024)) break;
    const uint32_t m = __ballot_sync(0xffffffffu, tk < 1024 && (lane == 0 || ldg_acq32(g_dep + E_LI + lane * 16 + (tk >> 6)) >= 16));
    if (!m) { __nanosleep(TP(7)); continue; }
    const int ql = __ffs(m) - 1, task = __shfl_sync(0xffffffffu, tk, ql), q = E_LI + ql * 16, ev = task >> 6;
    if (lane == ql) tk = -1;
    const size_t off = (size_t)task * (DM * 4) + lane * 16;
    const char* src = (const char*)(q == E_LI ? x : out) + off;
    uint4 u[8];
#pragma unroll
    for (int i = 0; i < 8; i++) u[i] = ldg_rlx128(src + i * 512);
    if (q == E_LI) {
#pragma unroll
      for (int i = 0; i < 8; i++) stg128((char*)out + off + i * 512, u[i].x, u[i].y, u[i].z, u[i].w);
    }
    float mean[2], rs[2];
#pragma unroll
    for (int r = 0; r < 2; r++) {
      float s0 = 0, s1 = 0;
#pragma unroll
      for (int i = 0; i < 16; i++) { const uint32_t v = (&u[4*r + (i >> 2)].x)[i & 3]; s0 += bf_lo(v); s1 += bf_hi(v); }
      mean[r] = (s0 + s1) * (1.f / 32);
      s0 = s1 = 0;
#pragma unroll
      for (int i = 0; i < 16; i++) { const uint32_t v = (&u[4*r + (i >> 2)].x)[i & 3]; const float a = bf_lo(v) - mean[r], b = bf_hi(v) - mean[r]; s0 = fmaf(a, a, s0); s1 = fmaf(b, b, s1); }
      rs[r] = s0 + s1;
    }
    {
      const bool hi = lane & 16;
      float m1 = hi ? mean[1] : mean[0], q1 = hi ? rs[1] : rs[0], m2 = hi ? mean[0] : mean[1], q2 = hi ? rs[0] : rs[1], cnt = 16;
#pragma unroll
      for (int o = 16; o; o >>= 1) {
        m2 = __shfl_xor_sync(0xffffffffu, m2, o); q2 = __shfl_xor_sync(0xffffffffu, q2, o);
        const float dl = m1 - m2;
        q2 = q1 = fmaf(dl * dl, cnt, q1 + q2); m2 = m1 = 0.5f * (m1 + m2);
        cnt *= 2;
      }
      q1 = rsqrtf(q1 * (1.f / DM) + 1e-5f);
      m2 = __shfl_xor_sync(0xffffffffu, m1, 16); q2 = __shfl_xor_sync(0xffffffffu, q1, 16);
      mean[0] = hi ? m2 : m1; mean[1] = hi ? m1 : m2; rs[0] = hi ? q2 : q1; rs[1] = hi ? q1 : q2;
    }
#pragma unroll
    for (int i = 0; i < 8; i++) {
      uint32_t y[4];
#pragma unroll
      for (int c = 0; c < 4; c++) { const uint32_t v = (&u[i].x)[c]; y[c] = pack_bf16((bf_lo(v) - mean[i >> 2]) * rs[i >> 2], (bf_hi(v) - mean[i >> 2]) * rs[i >> 2]); }
      stg128((char*)g_xn + off + i * 512, y[0], y[1], y[2], y[3]);
    }
    fence_proxy_global();
    __syncwarp();
    if (lane == 0) flag_add(q == E_LI ? &g_xa[0][ev] : q == E_LX2 ? &g_xa[1][ev] : &g_dep[q == E_LX1A ? E_G1 + ev : E_G2 + (ev >> 1)]);
    __syncwarp();
  }
}
}

__global__ void __cluster_dims__(2, 1, 1) __launch_bounds__(384, 1)
gemm_kernel(const __grid_constant__ gm::Maps M, const bf16* __restrict__ x, bf16* out) {
  using namespace gm;
  extern __shared__ __align__(1024) uint8_t smem[];
  const uint32_t sb = __shfl_sync(0xffffffffu, smem_u32(smem), 0);
  const int tid = threadIdx.x, wi = __shfl_sync(0xffffffffu, tid >> 5, 0);
  if (tid < 21) mbar_init(sb + BARS + tid * 8, tid == 14 || tid == 15 ? 4 : tid >= 6 && tid < 12 ? 2 : 1);
  fence_mbar_init();
  cluster_arrive(); cluster_wait();
  if (wi < 8) { reg_inc<208>(); consumer(sb, M, wi >> 2); cluster_arrive(); cluster_wait(); }
  else {
    reg_dec<88>();
    if (wi == 8) producer(sb, M);
    else if (wi == 11 && cluster_rank() == 0) scheduler(sb);
    else {
      norm_helper(x, out);
      asm volatile("griddepcontrol.wait;" ::: "memory");
      if (wi == 9 && blockIdx.x < 64) g_h2[(NSTEP - 1) & 3][blockIdx.x * 32 + (tid & 31)] = make_uint4(0, 0, 0, 0);
    }
    __syncwarp();
    cluster_arrive(); cluster_wait();
  }
}

typedef CUresult (*PFN_encodeTiled)(CUtensorMap*, CUtensorMapDataType, cuuint32_t, void*, const cuuint64_t*, const cuuint64_t*,
                                    const cuuint32_t*, const cuuint32_t*, CUtensorMapInterleave, CUtensorMapSwizzle,
                                    CUtensorMapL2promotion, CUtensorMapFloatOOBfill);
static PFN_encodeTiled g_encode = nullptr;
static CUtensorMap make_map(const void* ptr, uint64_t rows, uint64_t cols, uint32_t box_rows) {
  CUtensorMap m;
  cuuint64_t dims[2] = {cols, rows}, strides[1] = {cols * 2};
  cuuint32_t box[2] = {64, box_rows}, es[2] = {1, 1};
  g_encode(&m, CU_TENSOR_MAP_DATA_TYPE_BFLOAT16, 2, (void*)ptr, dims, strides, box, es, CU_TENSOR_MAP_INTERLEAVE_NONE,
           CU_TENSOR_MAP_SWIZZLE_128B, CU_TENSOR_MAP_L2_PROMOTION_L2_256B, CU_TENSOR_MAP_FLOAT_OOB_FILL_NONE);
  return m;
}

static CUtensorMap make_map3(const void* ptr, uint64_t d0, uint64_t d1, uint64_t d2, uint64_t stride2) {
  CUtensorMap m;
  cuuint64_t dims[3] = {d0, d1, d2}, strides[2] = {DM * 2, stride2};
  cuuint32_t box[3] = {64, 32, 2}, es[3] = {1, 1, 1};
  g_encode(&m, CU_TENSOR_MAP_DATA_TYPE_BFLOAT16, 3, (void*)ptr, dims, strides, box, es, CU_TENSOR_MAP_INTERLEAVE_NONE,
           CU_TENSOR_MAP_SWIZZLE_128B, CU_TENSOR_MAP_L2_PROMOTION_L2_256B, CU_TENSOR_MAP_FLOAT_OOB_FILL_NONE);
  return m;
}

extern "C" void kernel_launch(void* const* d_in, const int* in_sizes, int n_in, void* d_out, int out_size) {
  const bf16* x = (const bf16*)d_in[0];
  const bf16* mem0 = (const bf16*)d_in[1];
  if (!g_encode) {
    void* p = nullptr; cudaDriverEntryPointQueryResult q;
    cudaGetDriverEntryPoint("cuTensorMapEncodeTiled", &p, cudaEnableDefault, &q);
    g_encode = (PFN_encodeTiled)p;
    cudaFuncSetAttribute(gemm_kernel, cudaFuncAttributeMaxDynamicSharedMemorySize, gm::SMEM);
    cudaFuncSetAttribute(rec_kernel, cudaFuncAttributeMaxDynamicSharedMemorySize, rec::SMEM);
  }
  bf16 *xn, *ot, *hh;
  cudaGetSymbolAddress((void**)&xn, g_xn); cudaGetSymbolAddress((void**)&ot, g_ot); cudaGetSymbolAddress((void**)&hh, g_h);
  rec::Maps R;
  for (int i = 0; i < 3; i++) R.w[i] = make_map(d_in[2 + i], DM, NH * DH, 16);
  R.wo = make_map(d_in[5], NH * DH, DM, 128);
  R.xd = make_map3(xn, DM, SEQ - LAG * 32, 2, (uint64_t)LAG * 32 * DM * 2); R.xs = make_map3(xn, 64, SEQ, DM / 64, 128);
  gm::Maps G;
  G.ot = make_map(ot, NH * DH + O_LAYER / SEQ, SEQ, 64); G.wo = make_map(d_in[5], NH * DH, DM, 64); G.xn = make_map(xn, SEQ, DM, 64);
  G.wg = make_map(d_in[8], DM, DF, 64); G.wu = make_map(d_in[9], DM, DF, 64); G.hl = make_map(hh, SEQ, DF, 64); G.hs = make_map(hh, SEQ, DF, 128);
  G.wd = make_map(d_in[10], DF, DM, 64); G.out = make_map(d_out, SEQ, DM, 128);
  rec_kernel<<<3 * NH, 384, rec::SMEM, cudaStreamPerThread>>>(R, mem0);
  cudaLaunchConfig_t cfg = {};
  cfg.gridDim = dim3(132); cfg.blockDim = dim3(384); cfg.dynamicSmemBytes = gm::SMEM; cfg.stream = cudaStreamPerThread;
  cudaLaunchAttribute at[1];
  at[0].id = cudaLaunchAttributeProgrammaticStreamSerialization; at[0].val.programmaticStreamSerializationAllowed = 1;
  cfg.attrs = at; cfg.numAttrs = 1;
  cudaLaunchKernelEx(&cfg, gemm_kernel, G, x, (bf16*)d_out);
}
```

```cpp
#include <cuda_runtime.h>
#include <cuda_bf16.h>
#include <cuda.h>
#include <stdint.h>

#define DEVI __device__ __forceinline__
typedef __nv_bfloat16 bf16;

constexpr int SEQ = 2048, DM = 1024, NH = 32, DH = 128, DF = 3584, NSEG = 64;
#define LAG 18
constexpr int NSTEP = NSEG + LAG;

#define TSS 1
#define TSD (LATE == 1 ? 1900 : 1400)
constexpr size_t O_LAYER = 0;
__device__ __align__(1024) bf16 g_xn[SEQ * DM];
__device__ __align__(1024) bf16 g_ot[SEQ * NH * DH + O_LAYER];
__device__ __align__(1024) bf16 g_h[SEQ * DF];
__device__ __align__(1024) uint2 g_h1[4][256 * 256];
__device__ __align__(1024) uint4 g_h2[4][2048];
__device__ __align__(128) uint32_t g_ts[2][32 * TSS];
enum { E_D1 = 0, E_G1 = 32, E_O1 = 48, E_O2 = 64, E_G2 = 80, E_D2 = 96,
       E_LI = 128, E_LX2 = 144, E_LX1A = 160, E_LX1B = 176, NEV = 256 };
__device__ __align__(128) int g_dep[NEV];
__device__ __align__(128) int g_claim[NEV];
__device__ __align__(128) int g_xa[2][32];

#define TUNE_DEFAULTS 1550, 2250, 5, 100, 100, 8, 0xffff, 100
constexpr int c_D[8] = {TUNE_DEFAULTS};
template<int I> struct TPV { static constexpr int v = c_D[I]; };
#define TP(i) TPV<i>::v

DEVI uint32_t smem_u32(const void* p) { return (uint32_t)__cvta_generic_to_shared(p); }
DEVI void mbar_init(uint32_t bar, uint32_t cnt) { asm volatile("mbarrier.init.shared::cta.b64 [%0], %1;" :: "r"(bar), "r"(cnt) : "memory"); }
DEVI void mbar_arrive(uint32_t bar) { asm volatile("mbarrier.arrive.shared::cta.b64 _, [%0];" :: "r"(bar) : "memory"); }
DEVI bool mbar_try(uint32_t bar, uint32_t parity) {
  uint32_t p;
  asm volatile("{.reg .pred p; mbarrier.try_wait.parity.shared::cta.b64 p, [%1], %2; selp.u32 %0, 1, 0, p;}" : "=r"(p) : "r"(bar), "r"(parity) : "memory");
  return p;
}
DEVI bool mbar_test(uint32_t bar, uint32_t parity) {
  uint32_t p;
  asm volatile("{.reg .pred p; mbarrier.test_wait.parity.shared::cta.b64 p, [%1], %2; selp.u32 %0, 1, 0, p;}" : "=r"(p) : "r"(bar), "r"(parity) : "memory");
  return p;
}
constexpr int SPIN_BUDGET = 1 << 18;
DEVI void mbar_wait(uint32_t bar, uint32_t parity, int& budget) {
  while (!mbar_try(bar, parity)) { if (--budget < 0) break; }
}
DEVI bool mbar_try_cluster(uint32_t bar, uint32_t parity) {
  uint32_t p;
  asm volatile("{.reg .pred p; mbarrier.try_wait.parity.acquire.cluster.shared::cta.b64 p, [%1], %2; selp.u32 %0, 1, 0, p;}" : "=r"(p) : "r"(bar), "r"(parity) : "memory");
  return p;
}
DEVI void mbar_wait_cluster(uint32_t bar, uint32_t parity, int& budget) {
  while (!mbar_try_cluster(bar, parity)) { if (--budget < 0) break; }
}
DEVI uint32_t mapa(uint32_t addr, uint32_t rank) { uint32_t r; asm("mapa.shared::cluster.u32 %0, %1, %2;" : "=r"(r) : "r"(addr), "r"(rank)); return r; }
DEVI void cluster_arrive() { asm volatile("barrier.cluster.arrive.release.aligned;" ::: "memory"); }
DEVI void cluster_wait() { asm volatile("barrier.cluster.wait.acquire.aligned;" ::: "memory"); }
DEVI void fence_mbar_init() { asm volatile("fence.mbarrier_init.release.cluster;" ::: "memory"); }
DEVI void fence_proxy_async() { asm volatile("fence.proxy.async.shared::cta;" ::: "memory"); }
DEVI void fence_proxy_global() { asm volatile("fence.proxy.async.global;" ::: "memory"); }
#define ELECT "{.reg .pred p; elect.sync _|p, 0xffffffff;\n @p "
DEVI void e_expect_tx(uint32_t bar, uint32_t bytes) { asm volatile(ELECT "mbarrier.arrive.expect_tx.shared::cta.b64 _, [%0], %1;}" :: "r"(bar), "r"(bytes) : "memory"); }
DEVI void e_complete_tx(uint32_t bar, uint32_t bytes) { asm volatile("fence.acq_rel.cta;\n" ELECT "mbarrier.complete_tx.relaxed.cta.shared::cta.b64 [%0], %1;}" :: "r"(bar), "r"(bytes) : "memory"); }
DEVI void e_arrive(uint32_t bar) { asm volatile(ELECT "mbarrier.arrive.shared::cta.b64 _, [%0];}" :: "r"(bar) : "memory"); }
DEVI void e_tma_2d(uint32_t dst, const CUtensorMap* m, int c0, int c1, uint32_t bar) {
  asm volatile(ELECT "cp.async.bulk.tensor.2d.shared::cluster.global.mbarrier::complete_tx::bytes [%0], [%1, {%3, %4}], [%2];}"
    :: "r"(dst), "l"(m), "r"(bar), "r"(c0), "r"(c1) : "memory");
}
DEVI void e_prefetch_2d(const CUtensorMap* m, int c0, int c1) {
  asm volatile(ELECT "cp.async.bulk.prefetch.tensor.2d.L2.global [%0, {%1, %2}];}" :: "l"(m), "r"(c0), "r"(c1) : "memory");
}
DEVI void e_prefetch_3d(const CUtensorMap* m, int c0, int c1, int c2) {
  asm volatile(ELECT "cp.async.bulk.prefetch.tensor.3d.L2.global [%0, {%1, %2, %3}];}" :: "l"(m), "r"(c0), "r"(c1), "r"(c2) : "memory");
}
DEVI void e_bulk_g2s(uint32_t dst, const void* src, uint32_t bytes, uint32_t bar) {
  asm volatile(ELECT "cp.async.bulk.shared::cluster.global.mbarrier::complete_tx::bytes [%0], [%1], %2, [%3];}" :: "r"(dst), "l"(src), "r"(bytes), "r"(bar) : "memory");
}
DEVI void e_tma_3d(uint32_t dst, const CUtensorMap* m, int c0, int c1, int c2, uint32_t bar) {
  asm volatile(ELECT "cp.async.bulk.tensor.3d.shared::cluster.global.mbarrier::complete_tx::bytes [%0], [%1, {%3, %4, %5}], [%2];}"
    :: "r"(dst), "l"(m), "r"(bar), "r"(c0), "r"(c1), "r"(c2) : "memory");
}
DEVI void e_tma_3d_mc(uint32_t dst, const CUtensorMap* m, int c0, int c1, int c2, uint32_t bar) {
  asm volatile(ELECT "cp.async.bulk.tensor.3d.shared::cluster.global.mbarrier::complete_tx::bytes.multicast::cluster [%0], [%1, {%3, %4, %5}], [%2], %6;}"
    :: "r"(dst), "l"(m), "r"(bar), "r"(c0), "r"(c1), "r"(c2), "h"((uint16_t)7) : "memory");
}
DEVI void e_tma_2d_mc(uint32_t dst, const CUtensorMap* m, int c0, int c1, uint32_t bar) {
  asm volatile(ELECT "cp.async.bulk.tensor.2d.shared::cluster.global.mbarrier::complete_tx::bytes.multicast::cluster [%0], [%1, {%3, %4}], [%2], %5;}"
    :: "r"(dst), "l"(m), "r"(bar), "r"(c0), "r"(c1), "h"((uint16_t)3) : "memory");
}
DEVI void p_arrive_at(uint32_t bar, uint32_t rank, bool c) {
  asm volatile("{.reg .pred p; .reg .b32 a; setp.ne.u32 p, %2, 0; mapa.shared::cluster.u32 a, %0, %1; @p mbarrier.arrive.shared::cluster.b64 _, [a];}"
    :: "r"(bar), "r"(rank), "r"((uint32_t)c) : "memory");
}
DEVI void p_expect_tx(uint32_t bar, uint32_t bytes, bool c) {
  asm volatile("{.reg .pred p; setp.ne.u32 p, %2, 0; @p mbarrier.arrive.expect_tx.shared::cta.b64 _, [%0], %1;}" :: "r"(bar), "r"(bytes), "r"((uint32_t)c) : "memory");
}
DEVI void p_arrive(uint32_t bar, bool c) { asm volatile("{.reg .pred p; setp.ne.u32 p, %1, 0; @p mbarrier.arrive.shared::cta.b64 _, [%0];}" :: "r"(bar), "r"((uint32_t)c) : "memory"); }
DEVI void tma_store_2d(const CUtensorMap* m, uint32_t src, int c0, int c1) {
  asm volatile("cp.async.bulk.tensor.2d.global.shared::cta.bulk_group [%0, {%2, %3}], [%1];" :: "l"(m), "r"(src), "r"(c0), "r"(c1) : "memory");
}
DEVI void tma_radd_2d(const CUtensorMap* m, uint32_t src, int c0, int c1) {
  asm volatile("cp.reduce.async.bulk.tensor.2d.global.shared::cta.add.bulk_group [%0, {%2, %3}], [%1];" :: "l"(m), "r"(src), "r"(c0), "r"(c1) : "memory");
}
DEVI void bulk_commit() { asm volatile("cp.async.bulk.commit_group;" ::: "memory"); }
template<int N> DEVI void bulk_wait_read() { asm volatile("cp.async.bulk.wait_group.read %0;" :: "n"(N) : "memory"); }
template<int N> DEVI void bulk_wait() { asm volatile("cp.async.bulk.wait_group %0;" :: "n"(N) : "memory"); }
template<int ID, int N> DEVI void nbar_sync() { asm volatile("bar.sync %0, %1;" :: "n"(ID), "n"(N) : "memory"); }
template<int ID, int N> DEVI void nbar_arrive() { asm volatile("bar.arrive %0, %1;" :: "n"(ID), "n"(N) : "memory"); }
DEVI void nbar_sync_r(int id, int n) { asm volatile("bar.sync %0, %1;" :: "r"(id), "r"(n) : "memory"); }
template<int R> DEVI void reg_inc() { asm volatile("setmaxnreg.inc.sync.aligned.u32 %0;" :: "n"(R)); }
template<int R> DEVI void reg_dec() { asm volatile("setmaxnreg.dec.sync.aligned.u32 %0;" :: "n"(R)); }
DEVI void wg_fence() { asm volatile("wgmma.fence.sync.aligned;" ::: "memory"); }
DEVI void wg_commit() { asm volatile("wgmma.commit_group.sync.aligned;" ::: "memory"); }
template<int N> DEVI void wg_wait() { asm volatile("wgmma.wait_group.sync.aligned %0;" :: "n"(N) : "memory"); }
DEVI uint64_t mkdesc(uint32_t addr, uint32_t lbo, uint32_t sbo, uint32_t sw = 1) {
  return ((uint64_t)((addr & 0x3FFFF) >> 4)) | ((uint64_t)(lbo >> 4) << 16) | ((uint64_t)(sbo >> 4) << 32) | ((uint64_t)sw << 62);
}
constexpr uint32_t SMEM_BASE = 1024;
__host__ __device__ constexpr long long CD(uint32_t off, uint32_t lbo, uint32_t sbo, uint32_t sw) {
  return (long long)(((uint64_t)((SMEM_BASE + off) >> 4)) | ((uint64_t)(lbo >> 4) << 16) | ((uint64_t)(sbo >> 4) << 32) | ((uint64_t)sw << 62));
}
DEVI uint32_t pack_bf16(float lo, float hi) { uint32_t r; asm("cvt.rn.bf16x2.f32 %0, %1, %2;" : "=r"(r) : "f"(hi), "f"(lo)); return r; }
DEVI float bf_lo(uint32_t v) { return __uint_as_float(v << 16); }
DEVI float bf_hi(uint32_t v) { return __uint_as_float(v & 0xffff0000u); }
DEVI void ldsm4t(uint32_t addr, uint32_t& r0, uint32_t& r1, uint32_t& r2, uint32_t& r3) {
  asm volatile("ldmatrix.sync.aligned.m8n8.x4.trans.shared.b16 {%0,%1,%2,%3}, [%4];" : "=r"(r0), "=r"(r1), "=r"(r2), "=r"(r3) : "r"(addr) : "memory");
}
DEVI void stsm4(uint32_t addr, uint32_t r0, uint32_t r1, uint32_t r2, uint32_t r3) {
  asm volatile("stmatrix.sync.aligned.m8n8.x4.shared.b16 [%0], {%1,%2,%3,%4};" :: "r"(addr), "r"(r0), "r"(r1), "r"(r2), "r"(r3) : "memory");
}
DEVI uint2 lds64v(uint32_t a) { uint2 v; asm volatile("ld.volatile.shared.v2.u32 {%0,%1}, [%2];" : "=r"(v.x), "=r"(v.y) : "r"(a) : "memory"); return v; }
DEVI uint32_t lds32v(uint32_t a) { uint32_t v; asm volatile("ld.volatile.shared.u32 %0, [%1];" : "=r"(v) : "r"(a) : "memory"); return v; }
DEVI uint4 lds128v(uint32_t a) { uint4 v; asm volatile("ld.volatile.shared.v4.u32 {%0,%1,%2,%3}, [%4];" : "=r"(v.x), "=r"(v.y), "=r"(v.z), "=r"(v.w) : "r"(a) : "memory"); return v; }
DEVI void cp_async16(uint32_t dst, const void* src) { asm volatile("cp.async.cg.shared.global [%0], [%1], 16;" :: "r"(dst), "l"(src) : "memory"); }
DEVI void cp_async_wait() { asm volatile("cp.async.wait_all;" ::: "memory"); }
DEVI void sts32(uint32_t a, uint32_t x) { asm volatile("st.shared.u32 [%0], %1;" :: "r"(a), "r"(x) : "memory"); }
DEVI int lane_id() { int r; asm volatile("mov.u32 %0, %%laneid;" : "=r"(r)); return r; }
DEVI void sts64(uint32_t a, uint32_t x, uint32_t y) { asm volatile("st.shared.v2.u32 [%0], {%1,%2};" :: "r"(a), "r"(x), "r"(y) : "memory"); }
DEVI void sts128(uint32_t a, uint4 v) { asm volatile("st.shared.v4.u32 [%0], {%1,%2,%3,%4};" :: "r"(a), "r"(v.x), "r"(v.y), "r"(v.z), "r"(v.w) : "memory"); }
DEVI void st_async128(uint32_t a, uint32_t x, uint32_t y, uint32_t z, uint32_t w, uint32_t bar) {
  asm volatile("st.async.weak.shared::cluster.mbarrier::complete_tx::bytes.v4.b32 [%0], {%1,%2,%3,%4}, [%5];" :: "r"(a), "r"(x), "r"(y), "r"(z), "r"(w), "r"(bar) : "memory");
}
DEVI void st_async32(uint32_t a, uint32_t x, uint32_t bar) {
  asm volatile("st.async.weak.shared::cluster.mbarrier::complete_tx::bytes.b32 [%0], %1, [%2];" :: "r"(a), "r"(x), "r"(bar) : "memory");
}
DEVI uint4 ldg_rlx128(const void* p) {
  uint4 v;
  asm volatile("ld.relaxed.gpu.global.v4.b32 {%0,%1,%2,%3}, [%4];" : "=r"(v.x), "=r"(v.y), "=r"(v.z), "=r"(v.w) : "l"(p) : "memory");
  return v;
}
DEVI int ldg_rlx32(const void* p) { int v; asm volatile("ld.relaxed.gpu.global.b32 %0, [%1];" : "=r"(v) : "l"(p) : "memory"); return v; }
DEVI int ldg_acq32(const void* p) { int v; asm volatile("ld.acquire.gpu.global.b32 %0, [%1];" : "=r"(v) : "l"(p) : "memory"); return v; }
DEVI void stg_rlx128(void* p, uint32_t x, uint32_t y, uint32_t z, uint32_t w) {
  asm volatile("st.relaxed.gpu.global.v4.b32 [%0], {%1,%2,%3,%4};" :: "l"(p), "r"(x), "r"(y), "r"(z), "r"(w) : "memory");
}
DEVI void stg128(void* p, uint32_t x, uint32_t y, uint32_t z, uint32_t w) {
  asm volatile("st.global.v4.b32 [%0], {%1,%2,%3,%4};" :: "l"(p), "r"(x), "r"(y), "r"(z), "r"(w) : "memory");
}
DEVI uint2 ldg_rlx64(const void* p) { uint2 v; asm volatile("{.reg .b64 a; ld.relaxed.gpu.global.b64 a, [%2]; mov.b64 {%0,%1}, a;}" : "=r"(v.x), "=r"(v.y) : "l"(p) : "memory"); return v; }
DEVI void stg_rlx64(void* p, uint32_t x, uint32_t y) { asm volatile("{.reg .b64 a; mov.b64 a, {%1,%2}; st.relaxed.gpu.global.b64 [%0], a;}" :: "l"(p), "r"(x), "r"(y) : "memory"); }
DEVI void stg_rlx32(void* p, uint32_t x) { asm volatile("st.relaxed.gpu.global.b32 [%0], %1;" :: "l"(p), "r"(x) : "memory"); }
DEVI void flag_add(int* p) { asm volatile("fence.proxy.async.global; red.release.gpu.global.add.s32 [%0], 1;" :: "l"(p) : "memory"); }
DEVI void e_stg_rlx32(void* p, uint32_t x) { asm volatile(ELECT "st.relaxed.gpu.global.b32 [%0], %1;}" :: "l"(p), "r"(x) : "memory"); }
DEVI void e_flag_add(int* p) { asm volatile("fence.proxy.async.global;\n" ELECT "red.release.gpu.global.add.s32 [%0], 1;}" :: "l"(p) : "memory"); }
DEVI int cluster_rank() { int r; asm volatile("mov.u32 %0, %%cluster_ctarank;" : "=r"(r)); return __shfl_sync(0xffffffffu, r, 0); }
DEVI int cluster_id() { int r; asm volatile("mov.u32 %0, %%clusterid.x;" : "=r"(r)); return __shfl_sync(0xffffffffu, r, 0); }
DEVI uint32_t clock32() { uint32_t c; asm volatile("mov.u32 %0, %%clock;" : "=r"(c)); return c; }
DEVI uint32_t gtime() { uint32_t c; asm volatile("mov.u32 %0, %%globaltimer_lo;" : "=r"(c)); return c; }
DEVI void wait_time(uint32_t t) { while (__any_sync(0xffffffffu, t - gtime() - 1 < 4000u)) {} }
DEVI void spin_until(uint32_t t0, int d) { while (__any_sync(0xffffffffu, (int)(clock32() - t0) < d)) {} }
DEVI void pin2(const void* a, const void* b) { asm volatile("{.reg .pred p; setp.eq.u64 p, %0, %1; @p st.volatile.global.u64 [%0], %1;}" :: "l"(a), "l"(b) : "memory"); }
DEVI void pin2(uint32_t a, uint32_t b) { asm volatile("{.reg .pred p; setp.eq.u32 p, %0, %1; @p st.volatile.shared.u32 [%0], %1;}" :: "r"(a), "r"(b) : "memory"); }
DEVI void p_stg_rlx64(void* p, uint32_t x, uint32_t y, bool c) {
  asm volatile("{.reg .pred p; .reg .b64 a; setp.ne.u32 p, %3, 0; mov.b64 a, {%1,%2}; @p st.relaxed.gpu.global.b64 [%0], a;}" :: "l"(p), "r"(x), "r"(y), "r"((uint32_t)c) : "memory");
}
DEVI void pin2(uint64_t a, uint64_t b) { pin2((const void*)a, (const void*)b); }
DEVI uint64_t pair(uint32_t a, uint32_t bar) { return a | (uint64_t)bar << 32; }
DEVI void st_async32(uint64_t q, uint32_t x) { st_async32((uint32_t)q, x, (uint32_t)(q >> 32)); }
DEVI void st_async128(uint64_t q, uint4 v) { st_async128((uint32_t)q, v.x, v.y, v.z, v.w, (uint32_t)(q >> 32)); }
DEVI float ex2(float x) { float r; asm("ex2.approx.ftz.f32 %0, %1;" : "=f"(r) : "f"(x)); return r; }
DEVI float rcp(float x) { float r; asm("rcp.approx.ftz.f32 %0, %1;" : "=f"(r) : "f"(x)); return r; }
DEVI uint32_t xor_or(uint32_t a, uint32_t t, uint32_t acc) { uint32_t r; asm("lop3.b32 %0, %1, %2, %3, 0xbe;" : "=r"(r) : "r"(a), "r"(t), "r"(acc)); return r; }
DEVI void stsm2(uint32_t addr, uint32_t r0, uint32_t r1) {
  asm volatile("stmatrix.sync.aligned.m8n8.x2.shared.b16 [%0], {%1,%2};" :: "r"(addr), "r"(r0), "r"(r1) : "memory");
}
DEVI uint32_t settag(uint32_t v, uint32_t tag) { return (v & ~1u) | tag; }

#define A4(c, o)  c(d[o+0]), c(d[o+1]), c(d[o+2]), c(d[o+3])
#define A8(c, o)  A4(c, o), A4(c, o+4)
#define A16(c, o) A8(c, o), A8(c, o+8)
#define A20(c, o) A16(c, o), A4(c, o+16)
#define A32(c, o) A16(c, o), A16(c, o+16)
#define RL8  "{%0,%1,%2,%3,%4,%5,%6,%7}"
#define RL16 "{%0,%1,%2,%3,%4,%5,%6,%7,%8,%9,%10,%11,%12,%13,%14,%15}"
#define RL20 "{%0,%1,%2,%3,%4,%5,%6,%7,%8,%9,%10,%11,%12,%13,%14,%15,%16,%17,%18,%19}"
#define RL32 "{%0,%1,%2,%3,%4,%5,%6,%7,%8,%9,%10,%11,%12,%13,%14,%15,%16,%17,%18,%19,%20,%21,%22,%23,%24,%25,%26,%27,%28,%29,%30,%31}"
#define RL64 "{%0,%1,%2,%3,%4,%5,%6,%7,%8,%9,%10,%11,%12,%13,%14,%15,%16,%17,%18,%19,%20,%21,%22,%23,%24,%25,%26,%27,%28,%29,%30,%31," \
  "%32,%33,%34,%35,%36,%37,%38,%39,%40,%41,%42,%43,%44,%45,%46,%47,%48,%49,%50,%51,%52,%53,%54,%55,%56,%57,%58,%59,%60,%61,%62,%63}"
#define WG_OP(shape) "wgmma.mma_async.sync.aligned." shape "k16.f32.bf16.bf16 "
#define DEF_WGMMA(N, RL, AL, i0, i1, i2, i3, i4, i5, i6)                                                                         \
  template<int SC, int TB, long long CB> DEVI void rs##N(float* d, const uint32_t* a) {                                          \
    if (SC) asm volatile("{.reg .b64 tb; mov.b64 tb, %" #i4 ";\n" WG_OP("m64n" #N) RL ", {%" #i0 ",%" #i1 ",%" #i2 ",%" #i3 "}, tb, 1, 1, 1, %" #i5 ";}" \
      : AL("+f", 0) : "r"(a[0]), "r"(a[1]), "r"(a[2]), "r"(a[3]), "n"(CB), "n"(TB));                                             \
    else asm volatile("{.reg .b64 tb; mov.b64 tb, %" #i4 ";\n" WG_OP("m64n" #N) RL ", {%" #i0 ",%" #i1 ",%" #i2 ",%" #i3 "}, tb, 0, 1, 1, %" #i5 ";}" \
      : AL("=f", 0) : "r"(a[0]), "r"(a[1]), "r"(a[2]), "r"(a[3]), "n"(CB), "n"(TB));                                             \
  }                                                                                                                              \
  template<int SC, int TA, int TB, long long CA, long long CB> DEVI void ss##N(float* d, uint32_t a) {                           \
    if (SC) asm volatile("{.reg .b64 ta, tb; .reg .b32 lo, hi; add.u32 lo, %" #i0 ", %" #i1 "; mov.b32 hi, %" #i2 "; mov.b64 ta, {lo, hi}; mov.b64 tb, %" #i3 ";\n" \
      WG_OP("m64n" #N) RL ", ta, tb, 1, 1, 1, %" #i4 ", %" #i5 ";}"                                                              \
      : AL("+f", 0) : "r"(a), "n"((int)CA), "n"((int)(CA >> 32)), "n"(CB), "n"(TA), "n"(TB));                                    \
    else asm volatile("{.reg .b64 ta, tb; .reg .b32 lo, hi; add.u32 lo, %" #i0 ", %" #i1 "; mov.b32 hi, %" #i2 "; mov.b64 ta, {lo, hi}; mov.b64 tb, %" #i3 ";\n" \
      WG_OP("m64n" #N) RL ", ta, tb, 0, 1, 1, %" #i4 ", %" #i5 ";}"                                                              \
      : AL("=f", 0) : "r"(a), "n"((int)CA), "n"((int)(CA >> 32)), "n"(CB), "n"(TA), "n"(TB));                                    \
  }
DEF_WGMMA(8, "{%0,%1,%2,%3}", A4, 4, 5, 6, 7, 8, 9, 10)
DEF_WGMMA(16, RL8, A8, 8, 9, 10, 11, 12, 13, 14)
DEF_WGMMA(32, RL16, A16, 16, 17, 18, 19, 20, 21, 22)
DEF_WGMMA(40, RL20, A20, 20, 21, 22, 23, 24, 25, 26)
DEF_WGMMA(64, RL32, A32, 32, 33, 34, 35, 36, 37, 38)
template<int TA> DEVI void wgmma_n128(float* d, uint64_t a, uint64_t b, int scale_d) {
  asm volatile("{.reg .pred p; setp.ne.b32 p, %66, 0;\n" WG_OP("m64n128") RL64 ", %64, %65, p, 1, 1, %67, 1;}"
    : A32("+f", 0), A32("+f", 32) : "l"(a), "l"(b), "r"(scale_d), "n"(TA));
}

namespace rec {
constexpr int KR = 43;
constexpr uint32_t WSZ = (64 - KR) * 2048, STG = KR * 2048;
constexpr uint32_t WS = 0;
constexpr uint32_t RING = 2 * WSZ;
constexpr uint32_t OB = RING + 3 * 8192;
constexpr uint32_t PB = OB + 4096;
constexpr uint32_t WO = RING + 32768;
constexpr uint32_t ATT = WO + 5 * 16384;
constexpr uint32_t AK = ATT + 10240, AV = ATT + 20480;
constexpr uint32_t PAD = ATT + 30720;
constexpr uint32_t BARS = PAD + 128;
constexpr uint32_t B_XE = BARS  , B_FA = BARS + 64  , B_FB = BARS + 88, B_FO = BARS + 96;
constexpr uint32_t B_ME = BARS + 104  , B_WE = BARS + 136  ;
constexpr uint32_t B_XF = BARS + 152  , B_MF = BARS + 216  , B_CP = BARS + 248  , B_WT = BARS + 280  ;
constexpr uint32_t B_AB = BARS + 296, B_OB = BARS + 304, B_ST = BARS + 312  , B_WS = BARS + 328, B_WO = BARS + 336, B_PD = BARS + 344, B_AT = BARS + 352, B_AV = BARS + 360;
constexpr int NBAR = 46;
constexpr uint32_t M0 = BARS + 384;
constexpr uint32_t SMEM = 232448;
constexpr int NB_P = 1, NB_ST = 2, NB_O = 3, NB_W0 = 4, NB_W1 = 5, NB_S = 6;
__host__ __device__ constexpr int wo_tile(int rank, int g, int i) { return i < 2 ? i * 6 + rank * 2 + g : 13 + rank - g; }
constexpr long long D_W = CD(WS, 16, 1024, 1), D_X = CD(0, 16, 1024, 1), D_M = CD(RING, 128, 256, 0), D_O = CD(OB, 128, 256, 0);
constexpr long long D_WO = CD(WO, 16, 1024, 1), D_QM = CD(ATT, 640, 0, 0), D_QT = CD(ATT + 128, 640, 64, 0), D_K = CD(AK, 640, 128, 0);
constexpr long long D_V = CD(AV, 128, 640, 0), D_P = CD(PB, 128, 768, 0);
struct Maps { CUtensorMap w[3], wo, xd, xs; };
__host__ __device__ constexpr uint32_t xslot(int s) { return s < 3 ? RING + s * 8192 : s < 5 ? WO + (s - 3) * 8192 : s < 7 ? WO + (s + 1) * 8192 : OB; }
__host__ __device__ constexpr bool k_smem(int k) { return k % 3 == 2; }
__host__ __device__ constexpr int k_idx(int k) { return k % 3 == 2 ? k / 3 : k - k / 3; }
__host__ __device__ constexpr int k_of_reg(int i) { return i + (i >> 1); }
__host__ __device__ constexpr int k_of_smem(int i) { return 3 * i + 2; }

#define RPROF(i)
#define RPROF_STEP
#define CPROF(i, v)

template<int K0, int K1> DEVI void seq_mem(float* d, const uint32_t* w, uint32_t dw) {
  if constexpr (K0 < K1) {
    constexpr long long B = D_M + K0 * 32;
    if constexpr (!k_smem(K0)) rs16<K0 != 0, 1, B>(d, w + 4 * k_idx(K0)); else ss16<1, 1, 1, D_W + k_idx(K0) * 128, B>(d, dw);
    seq_mem<K0 + 1, K1>(d, w, dw);
  }
}
template<bool DUAL, int K0, int K1> DEVI void seq_tok(float* d, const uint32_t* w, uint32_t dw) {
  if constexpr (K0 < K1) {
    constexpr long long B = D_X + (DUAL ? xslot((K0 >> 2) & 7) / 16 : xslot(K0 >> 3) / 16 + ((K0 >> 2) & 1) * 256) + (K0 & 3) * 2;
    if constexpr (DUAL) {
      if constexpr (!k_smem(K0)) rs64<K0 != 0, 0, B>(d, w + 4 * k_idx(K0)); else ss64<1, 1, 0, D_W + k_idx(K0) * 128, B>(d, dw);
    } else {
      if constexpr (!k_smem(K0)) rs32<K0 != 0, 0, B>(d, w + 4 * k_idx(K0)); else ss32<1, 1, 0, D_W + k_idx(K0) * 128, B>(d, dw);
    }
    seq_tok<DUAL, K0 + 1, K1>(d, w, dw);
  }
}
template<int T, int K0> DEVI void seq_wo(float* d, uint32_t dw) {
  if constexpr (K0 < 8) { ss16<K0 != 0, 1, 1, D_WO + T * 1024 + K0 * 128, D_O + K0 * 32>(d, dw); seq_wo<T, K0 + 1>(d, dw); }
}
template<long long Q, int K0> DEVI void seq_s(float* d) {
  if constexpr (K0 < 8) { ss40<K0 != 0, 1, 1, Q + K0 * 80, D_K + K0 * 80>(d, 0); seq_s<Q, K0 + 1>(d); }
}
template<int K0> DEVI void seq_st(float* d) {
  if constexpr (K0 < 8) { ss32<K0 != 0, 1, 1, D_QT + K0 * 80, D_K + 8 + K0 * 80>(d, 0); seq_st<K0 + 1>(d); }
}
template<int K0> DEVI void seq_sm(float* d) {
  if constexpr (K0 < 8) { ss8<K0 != 0, 1, 1, D_QT + K0 * 80, D_K + K0 * 80>(d, 0); seq_sm<K0 + 1>(d); }
}
template<bool DUAL, int J> DEVI void load_x(uint32_t sb, const Maps* M, int t) {
  if (DUAL) e_tma_3d_mc(sb + xslot(J & 7), &M->xd, J * 64, (t - LAG) * 32, 0, sb + B_XF + (J & 7) * 8);
  else e_tma_3d_mc(sb + xslot(J & 7), &M->xs, 0, (t < NSEG ? t : t - LAG) * 32, J * 2, sb + B_XF + (J & 7) * 8);
}
DEVI void load_x_lent(uint32_t sb, const Maps* M, int t, int j) {
  const bool dual = t >= LAG && t < NSEG;
  const uint32_t dst = sb + (j == 3 ? xslot(3) : xslot(5));
#pragma unroll
  for (int i = 0; i < 2; i++)
    e_tma_3d(dst + i * 8192, dual ? &M->xd : &M->xs, dual ? (j + i) * 64 : 0, (t < LAG ? t : t - LAG) * 32, dual ? 0 : (j + i) * 2, sb + B_XF + (j + i) * 8);
}
struct Ctx { uint32_t sb; const Maps* M; int h, rank, wi; bool lead; uint32_t par; };
#define PFN 2
#define SPLIT_S 0
#define LATE 1
#define XD 2
template<bool DUAL, int J> DEVI void tok_release(const Ctx& c, int t, int& budget) {
  constexpr int NC = DUAL ? 16 : 8, S = J & 7;
  if constexpr (J + 8 < NC) {
    p_arrive_at(c.sb + B_XE + S * 8, J % 3, c.lead);
    p_expect_tx(c.sb + B_XF + S * 8, 8192, c.lead && c.wi == 0);
  } else if constexpr (S < 3 || S == 7) p_arrive(c.sb + B_ME + (S & 3) * 8, c.lead);
  if constexpr (J == XD - 1) {
    if (c.rank == 1 && c.wi == 5) { mbar_wait(c.sb + B_FO, t & 1, budget); load_x<DUAL, 7>(c.sb, c.M, t); }
  } else if constexpr (J >= XD && J - XD + 8 < NC) {
    constexpr int I = J - XD;
    if (c.rank == I % 3 && c.wi == (I & 1) * 4 + 1) { mbar_wait(c.sb + B_XE + I * 8, (t - LAG) & 1, budget); load_x<DUAL, I + 8>(c.sb, c.M, t); }
  }
}
template<bool DUAL, int J, class F, class G> DEVI bool tok_pass(float* d, const uint32_t* w, uint32_t dw, Ctx& c, int t, int& budget, F after0, G setup) {
  constexpr int NC = DUAL ? 16 : 8, KC = 64 / NC;
  if constexpr (J < NC) {
    if constexpr (J > 1) mbar_wait(c.sb + B_XF + (J & 7) * 8, c.par ^ (J >> 3), budget);
    wg_fence();
    seq_tok<DUAL, J * KC, (J + 1) * KC>(d, w, dw);
    wg_commit();
    if constexpr (J == 1) after0();
    if constexpr (J >= NC - 5 && J < NC - 1) setup(J - (NC - 5));
    if constexpr (J > 0) { wg_wait<1>(); tok_release<DUAL, J - 1>(c, t, budget); }
    return tok_pass<DUAL, J + 1>(d, w, dw, c, t, budget, after0, setup);
  } else {
    const bool ok = mbar_test(c.sb + B_MF, t & 1);
    wg_wait<0>();
    tok_release<DUAL, NC - 1>(c, t, budget);
    if (!DUAL) c.par ^= 1;
    return ok;
  }
}
DEVI void pack_tok(uint32_t* e, const float* d) {
#pragma unroll
  for (int i = 0; i < 8; i++) e[i] = pack_bf16(d[4 * (i & 3) + 2 * (i >> 2)], d[4 * (i & 3) + 2 * (i >> 2) + 1]);
}
DEVI void push_tok(const uint32_t* e, uint32_t sb, uint32_t o, int r, int rank) {
  const uint32_t b = mapa(sb, r);
  st_async128(b + o, e[0], e[1], e[2], e[3], b + (rank == 2 ? B_AV : B_AT));
}
DEVI uint32_t h1_tag(int seg) { return ((seg >> 1) & 1) ^ 1; }
DEVI uint4 pack_part(const float* c, int t) {
  return make_uint4(settag(pack_bf16(c[0], c[1]), h1_tag(t)), pack_bf16(c[2], c[3]), settag(pack_bf16(c[4], c[5]), h1_tag(t - LAG)), pack_bf16(c[6], c[7]));
}
DEVI void put_part(char* p1, char* p2, uint4 z, int t) { p_stg_rlx64(p1, z.x, z.y, t < NSEG); p_stg_rlx64(p2, z.z, z.w, t >= LAG); }

DEVI void rec_math(const uint32_t sb, const int wi, const Maps& M) {
  const int h = cluster_id(), rank = cluster_rank();
  const int warp = wi & 3, wg = wi >> 2;
  const bool lead = (threadIdx.x & 127) == 0;
  int budget = SPIN_BUDGET;
  uint32_t w[4 * KR];
  Ctx cx{sb, &M, h, rank, wi, lead, 0};
  {
    const int lane = lane_id();
    const uint32_t a = sb + wg * STG + ((lane & 7) + (lane >> 4) * 8) * 128 + (((warp * 2 + ((lane >> 3) & 1)) ^ (lane & 7)) << 4);
    mbar_wait(sb + B_ST + wg * 8, 0, budget);
#pragma unroll
    for (int k = 0; k < KR; k++) ldsm4t(a + k * 2048, w[4*k], w[4*k+1], w[4*k+2], w[4*k+3]);
    nbar_arrive<NB_ST, 384>();
    nbar_sync_r(NB_W0 + wg, 128);
    for (int i = 0; i < 5; i++) p_arrive_at(sb + B_FA + i * 8, i == 4, lead);
    mbar_wait(sb + B_WS, 0, budget);
  }
  uint4 z = make_uint4(0, 0, 0, 0);
  char *z1 = nullptr, *z2 = nullptr;
  mbar_wait(sb + B_XF, 0, budget); mbar_wait(sb + B_XF + 8, 0, budget);
#pragma unroll 1
  for (int t = 0;; t++) {
    const uint32_t dw = wg * (WSZ >> 4);
    uint32_t e[16];
    bool ok;
    auto finish = [&]() { put_part(z1, z2, z, t - 1); p_arrive_at(sb + B_FO, 1, lead); };
    const int seg = t - rank * LAG;
    const bool att = rank < 2 && (unsigned)seg < (unsigned)NSEG;
    char *p1, *p2;
    uint32_t pw, oo;
    uint64_t u0, u1;
    int lane;
    auto setup = [&](int part) {
      if (part == 0) {
        lane = lane_id();
      } else if (part == 1) {
        char* const p = (char*)g_h1 + ((wo_tile(rank, wg, 0) * 4 + warp) * 4 + (lane >> 3)) * 2048 + h * 64 + (lane & 7) * 8;
        p1 = p + (t & 1) * sizeof(g_h1[0]);
        p2 = p + (2 + ((t - LAG) & 1)) * sizeof(g_h1[0]);
        pin2(p1, p2);
      } else if (part == 2) {
        oo = OB + (lane >> 4) * 2048 + warp * 512 + rank * 256 + (lane & 15) * 16;
        pw = sb + PB + (wg ? lane * 4 : 768 + warp * 768 + lane * 16);
        pin2(pw, oo);
      } else {
        if (wg) {
          const uint32_t ra = mapa(sb, (warp & 1) ? 2 : (rank ^ 1) & 1), rb = mapa(sb, (warp & 1) ? (rank ^ 1) & 1 : 2);
          u0 = pair(ra + oo, ra + B_OB); u1 = pair(rb + oo, rb + B_OB);
        } else {
          u0 = (uint64_t)((char*)(g_ot + rank * O_LAYER) + (size_t)(h * DH + warp * 16 + (lane >> 2)) * (SEQ * 2) + seg * 64 + (lane & 3) * 16);
          u1 = (uint32_t)((lane & 24) + ((lane >> 2) & 1) + 2 * warp - 8 * (lane & 3));
        }
        pin2(u0, u1);
      }
    };
    if (t >= LAG && t < NSEG) {
      float d[32];
      ok = tok_pass<true, 0>(d, w, dw, cx, t, budget, finish, setup);
      pack_tok(e + 8, d); pack_tok(e, d + 16);
    } else {
      float d[16];
      if (t > 0) finish();
      ok = tok_pass<false, 0>(d, w, dw, cx, t, budget, []() {}, setup);
      pack_tok(e, d);
#pragma unroll
      for (int i = 8; i < 16; i++) e[i] = 0;
    }
    RPROF_STEP;
    RPROF(8 + wg * 12 - 32);
    {
      float m[8];
      if (!ok) mbar_wait(sb + B_MF, t & 1, budget);
      wg_fence(); seq_mem<0, 8>(m, w, dw); wg_commit();
      {
        const uint32_t ao = ATT + rank * 10240 + wi * 1280, to = ao + 128 + (lane & 3) * 128 + (lane >> 2) * 16;
        const bool dual = t >= LAG && t < NSEG;
        const int la = dual ? rank == 0 : t >= NSEG;
        RPROF(1 + wg * 12);
        if (dual && rank == 0) {
#pragma unroll
          for (int i = 0; i < 8; i++) { const uint32_t x = e[i]; e[i] = e[8 + i]; e[8 + i] = x; }
        }
        auto piece = [&](int i) { if (i < 2 || dual) push_tok(e + 4 * i, sb, to + (i & 1) * 640, la ^ (i >> 1), rank); };
        piece(0);
        wg_fence(); seq_mem<8, 16>(m, w, dw); wg_commit();
        piece(1);
        mbar_wait(sb + B_MF + 8, t & 1, budget);
        wg_fence(); seq_mem<16, 24>(m, w, dw); wg_commit();
        piece(2);
        wg_fence(); seq_mem<24, 32>(m, w, dw); wg_commit();
        piece(3);
        mbar_wait(sb + B_MF + 16, t & 1, budget);
        wg_fence(); seq_mem<32, 48>(m, w, dw); wg_commit();
        wg_wait<1>(); p_arrive(sb + B_PD, lead && wg == 0);
        const uint32_t r0 = mapa(sb, la), r1 = mapa(sb, la ^ 1), m0 = r0 + ao + lane * 4, m1 = r1 + ao + lane * 4, ab = rank == 2 ? B_AV : B_AB;
        uint64_t q0 = pair(m0, r0 + ab), q1 = pair(m0 + 640, r0 + ab), q2 = pair(m1, r1 + ab), q3 = pair(m1 + 640, r1 + ab);
        pin2(q0, q1); pin2(q2, q3);
        mbar_wait(sb + B_MF + 24, t & 1, budget);
        wg_fence(); seq_mem<48, 64>(m, w, dw); wg_commit();
        wg_wait<1>(); p_arrive_at(sb + B_FA, 0, lead);
        if (att) { mbar_wait_cluster(sb + B_AT, seg & 1, budget); if (SPLIT_S && wg == 0) fence_proxy_async(); }
        wg_wait<0>();
        const uint32_t a0 = pack_bf16(m[0], m[1]), a1 = pack_bf16(m[2], m[3]), a2 = pack_bf16(m[4], m[5]), a3 = pack_bf16(m[6], m[7]);
        st_async32(q0, la ? a2 : a0); st_async32(q1, la ? a3 : a1);
        if (dual) { st_async32(q2, la ? a0 : a2); st_async32(q3, la ? a1 : a3); }
      }
      RPROF(2 + wg * 12);
      auto wo_ready = [&]() { if (t == 0) mbar_wait(sb + B_WO, 0, budget); if (t < NSTEP - 1) mbar_wait(sb + B_WT, t & 1, budget); };
      constexpr float SC = 0.08838834764831845f * 1.4426950408889634f;
      if (!att) wo_ready();
      else {
        float s[32];
        if (wg) {
          if (SPLIT_S) nbar_arrive<NB_S, 256>();
          uint32_t one[4];
#pragma unroll
          for (int i = 0; i < 4; i++) one[i] = 0x3F803F80u + (pw >> 31);
          mbar_wait_cluster(sb + B_AB, seg & 1, budget);
          fence_proxy_async();
          RPROF(3 + 12);
          wg_fence(); seq_s<D_QM, 0>(s); wg_commit();
          nbar_arrive<NB_P, 256>();
          if (warp == 1) sts32(pw + 640, 0);
          mbar_wait_cluster(sb + B_AV, seg & 1, budget);
          wg_wait<0>();
          float mx = fmaxf(fmaxf(fmaxf(s[0], s[1]), fmaxf(s[4], s[5])), fmaxf(fmaxf(fmaxf(s[8], s[9]), fmaxf(s[12], s[13])), fmaxf(s[16], s[17])));
          const float x1 = __shfl_xor_sync(0xffffffffu, mx, 1), x2 = __shfl_xor_sync(0xffffffffu, mx, 2), x3 = __shfl_xor_sync(0xffffffffu, mx, 3);
          const float u = (warp & 2) ? ((warp & 1) ? s[16] : s[12]) : ((warp & 1) ? s[8] : s[4]);
          const float v = (warp & 2) ? ((warp & 1) ? s[17] : s[13]) : ((warp & 1) ? s[9] : s[5]);
          const float ms = -SC * fmaxf(fmaxf(mx, x1), fmaxf(x2, x3));
          sts32(pw + 128 + warp * 128, pack_bf16(ex2(fmaf(u, SC, ms)), ex2(fmaf(v, SC, ms))));
          if (warp == 0) sts32(pw, pack_bf16(ex2(fmaf(s[0], SC, ms)), ex2(fmaf(s[1], SC, ms))));
          fence_proxy_async();
          nbar_sync<NB_W1, 128>();
          RPROF(4 + 12);
          wg_fence();
          rs8<0, 0, D_P>(s + 8, one); rs8<1, 0, D_P + 16>(s + 8, one); rs8<1, 0, D_P + 32>(s + 8, one);
          wg_commit();
          ss8<0, 0, 0, D_V, D_P>(s, 0); ss8<0, 0, 0, D_V + 320, D_P>(s + 4, 0);
          ss8<1, 0, 0, D_V + 16, D_P + 16>(s, 0); ss8<1, 0, 0, D_V + 336, D_P + 16>(s + 4, 0);
          ss8<1, 0, 0, D_V + 32, D_P + 32>(s, 0); ss8<1, 0, 0, D_V + 352, D_P + 32>(s + 4, 0);
          wg_commit();
          wg_wait<1>();
          const float i0 = rcp(s[8]), i1 = rcp(s[9]);
          wg_wait<0>();
          stsm4(sb + oo, pack_bf16(s[0] * i0, s[1] * i1), pack_bf16(s[2] * i0, s[3] * i1), pack_bf16(s[4] * i0, s[5] * i1), pack_bf16(s[6] * i0, s[7] * i1));
          __syncwarp();
          const uint4 y = lds128v(sb + oo);
          if (t < NSTEP - 1) { st_async128(u0, y); st_async128(u1, y); e_complete_tx(sb + B_OB, 512); }
          wo_ready();
        } else {
          const int lim = (int)u1;
          char* const og = (char*)u0;
          if (SPLIT_S) {
            nbar_sync<NB_S, 256>();
            wg_fence(); seq_st<0>(s + 4); wg_commit();
          }
          nbar_sync<NB_P, 256>();
          RPROF(3);
          wg_fence();
          if (SPLIT_S) seq_sm<0>(s); else seq_s<D_QT, 0>(s);
          wg_commit();
          mbar_wait_cluster(sb + B_AV, seg & 1, budget);
          wg_wait<0>();
#pragma unroll
          for (int i = 0; i < 8; i++) { float& v = s[4 + 4 * (i >> 1) + (i & 1)]; v = i <= lim ? v : -INFINITY; }
          float mx = fmaxf(fmaxf(fmaxf(s[0], s[1]), fmaxf(s[4], s[5])), fmaxf(fmaxf(fmaxf(s[8], s[9]), fmaxf(s[12], s[13])), fmaxf(s[16], s[17])));
          const float x1 = __shfl_xor_sync(0xffffffffu, mx, 1), x2 = __shfl_xor_sync(0xffffffffu, mx, 2), x3 = __shfl_xor_sync(0xffffffffu, mx, 3);
          const float ms = -SC * fmaxf(fmaxf(mx, x1), fmaxf(x2, x3));
#pragma unroll
          for (int i = 0; i < 10; i++) { float& v = s[4 * (i >> 1) + (i & 1)]; v = ex2(fmaf(v, SC, ms)); }
          const float sum = (((s[0] + s[1]) + (s[4] + s[5])) + ((s[8] + s[9]) + (s[12] + s[13]))) + (s[16] + s[17]);
          const float y1 = __shfl_xor_sync(0xffffffffu, sum, 1), y2 = __shfl_xor_sync(0xffffffffu, sum, 2), y3 = __shfl_xor_sync(0xffffffffu, sum, 3);
          const float inv = rcp((sum + y1) + (y2 + y3));
          stsm4(pw, pack_bf16(s[0] * inv, s[1] * inv), pack_bf16(s[4] * inv, s[5] * inv), pack_bf16(s[8] * inv, s[9] * inv), pack_bf16(s[12] * inv, s[13] * inv));
          stsm2(pw + 512, pack_bf16(s[16] * inv, s[17] * inv), 0);
          fence_proxy_async();
          nbar_sync<NB_W0, 128>();
          RPROF(4);
          wg_fence();
          ss32<0, 0, 0, D_V, D_P + 48>(s, 0); ss32<0, 0, 0, D_V + 320, D_P + 48>(s + 16, 0);
          ss32<1, 0, 0, D_V + 16, D_P + 64>(s, 0); ss32<1, 0, 0, D_V + 336, D_P + 64>(s + 16, 0);
          ss32<1, 0, 0, D_V + 32, D_P + 80>(s, 0); ss32<1, 0, 0, D_V + 352, D_P + 80>(s + 16, 0);
          wg_commit();
          wo_ready();
          wg_wait<0>();
#pragma unroll
          for (int i = 0; i < 4; i++) {
            const float* d = s + (i >> 1) * 16 + (i & 1) * 2;
            stg128(og + ((i >> 1) * 64 + (i & 1) * 8) * (SEQ * 2), pack_bf16(d[0], d[1]), pack_bf16(d[4], d[5]), pack_bf16(d[8], d[9]), pack_bf16(d[12], d[13]));
          }
          nbar_arrive<NB_O, 160>();
        }
      }
      RPROF(5 + wg * 12);
      const bool three = wg == 1 || rank == 2;
      if (t < NSTEP - 1) {
        float c[24];
        const uint32_t dt = wg ? 0 : 3072;
        mbar_wait_cluster(sb + B_OB, t & 1, budget);
        fence_proxy_async();
        RPROF(6 + wg * 12);
        wg_fence(); seq_wo<0, 0>(c, dt); wg_commit(); seq_wo<1, 0>(c + 8, dt); wg_commit();
        mbar_wait(sb + B_XF, cx.par, budget);
        wg_wait<1>();
        if (warp == 2) load_x_lent(sb, &M, t + 1, wg ? 3 : 5);
        put_part(p1, p2, pack_part(c, t), t);
        const int o3 = (wo_tile(rank, wg, three ? 2 : 1) - wo_tile(rank, wg, 0)) * 32768;
        z1 = p1 + o3; z2 = p2 + o3;
        if (three) {
          wg_fence(); seq_wo<2, 0>(c + 16, dt); wg_commit();
          wg_wait<1>(); put_part(p1 + 6 * 32768, p2 + 6 * 32768, pack_part(c + 8, t), t);
          mbar_wait(sb + B_XF + 8, cx.par, budget);
          wg_wait<0>(); z = pack_part(c + 16, t);
        } else { mbar_wait(sb + B_XF + 8, cx.par, budget); wg_wait<0>(); z = pack_part(c + 8, t); }
      } else {
        for (int i = 0; i < (three ? 3 : 2); i++) stg_rlx64(p2 + (wo_tile(rank, wg, i) - wo_tile(rank, wg, 0)) * 32768, 0, 0);
        break;
      }
      RPROF(7 + wg * 12);
    }
  }
}

DEVI void wait_xa(const int* p, int& budget) {
  while (__any_sync(0xffffffffu, ldg_acq32(p) < 64) && --budget > 0) {}
  fence_proxy_global();
}
template<bool DUAL> DEVI void first_loads(uint32_t sb, const Maps* M, int n, int h, int& budget) {
#pragma unroll
  for (int i = 0; i < PFN; i++) {
    if (DUAL) e_prefetch_3d(&M->xd, ((h + i * (16 / PFN)) & 15) * 64, (n - LAG) * 32, 0);
    else e_prefetch_3d(&M->xs, 0, (n < NSEG ? n : n - LAG) * 32, ((h + i * (8 / PFN)) & 7) * 2);
  }
  mbar_wait(sb + B_FA, n & 1, budget);
  load_x<DUAL, 0>(sb, M, n); load_x<DUAL, 1>(sb, M, n); load_x<DUAL, 2>(sb, M, n);
}
template<bool DUAL> DEVI void lent_loads(uint32_t sb, const Maps* M, int n, int& budget) {
  mbar_wait(sb + B_FB, n & 1, budget);
  load_x<DUAL, 3>(sb, M, n); load_x<DUAL, 4>(sb, M, n); load_x<DUAL, 5>(sb, M, n); load_x<DUAL, 6>(sb, M, n);
}
DEVI void rec_comm(const uint32_t sb, const int warp, const Maps& M, const bf16* __restrict__ mem0) {
  const int lane = threadIdx.x & 31, h = cluster_id(), rank = cluster_rank();
  int budget = SPIN_BUDGET;
  const bool two = warp == 3 || (rank == 2 && warp == 2);
  const int ntask = two ? 2 : 1, qi = two ? (warp == 3 ? rank : 3) : rank * 3 + warp;
  const int task0 = two ? h * 2 + (qi >> 1) : 64 + h * 4 + (qi >> 1);
  auto h2_word = [&](int i, int ln) {
    const int task = task0 + i * 192;
    return (char*)g_h2 + (task >> 2) * 512 + ((qi ^ i) & 1) * 256 + (task & 3) * 32 + (ln & 8) * 16 + (ln & 7) * 4;
  };
  auto first_x = [&](int t) {
    const int n = t + 1;
    p_expect_tx(sb + B_XF + (lane_id() & 7) * 8, 8192, lane_id() < 8);
    if (rank == 0) {
      if (n < NSEG && (n & 3) == 0) wait_xa(&g_xa[0][n >> 2], budget);
      if (n >= LAG && ((n - LAG) & 3) == 0) wait_xa(&g_xa[1][(n - LAG) >> 2], budget);
      if (n >= LAG && n < NSEG) first_loads<true>(sb, &M, n, h, budget); else first_loads<false>(sb, &M, n, h, budget);
    }
  };
  {
    const int task = task0 + (lane >> 4) * 192, L = (task & 3) * 8 + (lane & 7);
    if ((lane >> 4) < ntask) {
      const bf16* p = mem0 + (L & 3) * 2 * DM + (task >> 2) * 16 + (L >> 2) + (lane & 8);
      uint32_t m0 = (uint32_t)__bfloat16_as_ushort(p[0]) | (uint32_t)__bfloat16_as_ushort(p[DM]) << 16;
      m0 = m0 ? m0 : 0x8000u;
      stg_rlx32(h2_word(lane >> 4, lane), m0);
      sts32(sb + M0 + warp * 128 + lane * 4, m0);
    }
    __syncwarp();
    nbar_sync<NB_ST, 384>();
    if (warp == 2) {
      e_expect_tx(sb + B_WS, 2 * WSZ);
#pragma unroll 1
      for (int i = 0; i < 2 * (64 - KR); i++) e_tma_2d(sb + WS + (i & 1) * WSZ + (i >> 1) * 2048, &M.w[rank], h * DH + (i & 1) * 64, k_of_smem(i >> 1) * 16, sb + B_WS);
      const int nt = rank == 2 ? 6 : 5;
      e_expect_tx(sb + B_WO, (nt - 2) * 16384);
#pragma unroll 1
      for (int i = 1; i < nt; i++) if (i != 3) e_tma_2d(sb + WO + i * 16384, &M.wo, wo_tile(rank, 1 - i / 3, i % 3) * 64, h * DH, sb + B_WO);
    }
    if (warp == 3) { first_x(-1); if (rank == 0) lent_loads<false>(sb, &M, 0, budget); }
  }
  uint32_t t0 = gtime() - 4000, cpp = 0;
  const uint32_t cp = sb + B_CP + warp * 8;
#pragma unroll 1
  for (int t = 0;; t++) {
    const int n = t + 1, seg = t - rank * LAG;
    RPROF_STEP;
    const bool att = rank < 2 && (unsigned)seg < (unsigned)NSEG;
    if (warp == 3) {
      if (att) { e_expect_tx(sb + B_AT, 16384); e_expect_tx(sb + B_AB, 4096); e_expect_tx(sb + B_AV, 10240); }
      if (n < NSTEP) e_expect_tx(sb + B_OB, t < NSEG && t >= LAG ? 4096 : 2048);
    }
    {
      const uint32_t dst = sb + RING + warp * 8192;
      mbar_wait(sb + B_ME + warp * 8, t & 1, budget);
      wait_time(t0 + TP(1) + warp * TP(4));
      const int lane = lane_id();
      RPROF(24); CPROF(0, gtime());
      int tries = 0;
      while (true) {
        tries++;
        e_expect_tx(cp, 8192);
        e_bulk_g2s(dst, (const char*)g_h2[t & 3] + warp * 8192, 8192, cp);
        mbar_wait(cp, cpp, budget); cpp ^= 1;
        uint32_t mn = 0xffffffffu;
#pragma unroll
        for (int i = 0; i < 8; i++) mn = min(mn, lds32v(dst + i * 1024 + lane * 32 + (lane >> 2) * 4));
        if (!__any_sync(0xffffffffu, mn == 0) || --budget < 0) break;
      }
      e_arrive(sb + B_MF + warp * 8);
      RPROF(25); CPROF(1, gtime()); CPROF(2, tries);
    }
    {
      const int ln = lane_id(), i = ln >> 4;
      char* const w = h2_word(i, ln);
      if (i < ntask) {
        stg_rlx32(w + ((t + 3) & 3) * sizeof(g_h2[0]), 0);
        if (n < NSTEP && (((qi ^ i) & 1) ? t < LAG : t >= NSEG)) stg_rlx32(w + (n & 3) * sizeof(g_h2[0]), lds32v(sb + M0 + warp * 128 + ln * 4));
      }
      __syncwarp();
    }
    if (n < NSTEP) {
      const uint32_t tag = (n >> 1) & 31;
      mbar_wait(sb + B_PD, t & 1, budget);
      t0 = clock32();
      if (warp == 2) {
        mbar_wait(sb + B_ME + 24, t & 1, budget);
        e_expect_tx(sb + B_WT, 32768);
        e_tma_2d(sb + WO, &M.wo, wo_tile(rank, 1, 0) * 64, h * DH, sb + B_WT);
        e_tma_2d(sb + WO + 49152, &M.wo, wo_tile(rank, 0, 0) * 64, h * DH, sb + B_WT);
      }
      if (warp == 3) first_x(t);
      if (warp == 0 && rank == (t >= NSEG)) { mbar_wait(sb + B_AB, seg & 1, budget); e_stg_rlx32(&g_ts[t & 1][h * TSS], (gtime() & ~31u) | tag); }
      spin_until(t0, TSD);
      uint32_t v;
      do { v = ldg_rlx32(&g_ts[t & 1][lane_id() * TSS]); } while (__any_sync(0xffffffffu, (v & 31) != tag) && --budget > 0);
      const uint32_t now = __shfl_sync(0xffffffffu, v, 0);
      t0 = now + __reduce_max_sync(0xffffffffu, (int)(v - now));
      if (warp == 3) mbar_wait(sb + B_OB, t & 1, budget);
    }
    if (n < NSTEP) {
      RPROF(26); CPROF(3, t0);
#pragma unroll 1
      for (int i = 0; i < ntask; i++) {
        const int layer = (qi ^ i) & 1, sg = t - layer * LAG, task = task0 + i * 192;
        if ((unsigned)sg >= (unsigned)NSEG) continue;
        const uint32_t tag = h1_tag(sg);
        const int ln = lane_id();
        const char* const src = (const char*)g_h1[layer * 2 + (sg & 1)] + task * 2048 + ln * 8;
        char* const dst = h2_word(i, ln) + (n & 3) * sizeof(g_h2[0]);
        uint2 v[8];
        pin2(src, dst);
        wait_time(t0 + TP(0) + (task < 96 ? 0 : task < 192 ? TP(3) : 2 * TP(3)));
        int tries = 0;
        float a[4];
        while (true) {
          tries++;
#pragma unroll
          for (int k = 0; k < 8; k++) v[k] = ldg_rlx64(src + k * 256);
          uint32_t bad = 0;
#pragma unroll
          for (int k = 0; k < 8; k++) {
            bad = xor_or(v[k].x, tag, bad);
            a[0] = k ? a[0] + bf_lo(v[k].x) : bf_lo(v[k].x); a[1] = k ? a[1] + bf_hi(v[k].x) : bf_hi(v[k].x);
            a[2] = k ? a[2] + bf_lo(v[k].y) : bf_lo(v[k].y); a[3] = k ? a[3] + bf_hi(v[k].y) : bf_hi(v[k].y);
          }
#pragma unroll
        for (int k = 0; k < 2; k++) {
          const float keep = (ln & 8) ? a[2+k] : a[k], send = (ln & 8) ? a[k] : a[2+k];
          a[k] = keep + __shfl_xor_sync(0xffffffffu, send, 8);
        }
#pragma unroll
        for (int k = 0; k < 2; k++) a[k] += __shfl_xor_sync(0xffffffffu, a[k], 16);
          if (!__any_sync(0xffffffffu, bad & 1) || --budget < 0) break;
        }
        const uint32_t out = pack_bf16(a[0], a[1]);
        if (ln < 16) stg_rlx32(dst, out ? out : 0x8000u);
        __syncwarp();
        if (i == 0) { RPROF(28); CPROF(6, gtime()); CPROF(4, gtime()); CPROF(5, tries); } else CPROF(7, gtime());
      }
    }
    if (warp == 1 && att) { nbar_sync<NB_O, 160>(); e_flag_add(&g_dep[E_O1 + rank * 16 + (seg >> 2)]); }
    if (n == NSTEP) break;
  }
  if (h == 0 && rank == 0 && warp < 2) g_xa[warp][lane_id()] = 0;
}
}

__global__ void __cluster_dims__(3, 1, 1) __launch_bounds__(384, 1)
rec_kernel(const __grid_constant__ rec::Maps M, const bf16* __restrict__ mem0) {
  using namespace rec;
  extern __shared__ __align__(1024) uint8_t smem[];
  const uint32_t sb = __shfl_sync(0xffffffffu, smem_u32(smem), 0);
  const int tid = threadIdx.x, wi = __shfl_sync(0xffffffffu, tid >> 5, 0);
  if ((sb & 0x3FFFF) != SMEM_BASE) __trap();
  if (wi == 0) {
    const int h = cluster_id(), rank = cluster_rank();
    for (int i = tid; i < NBAR; i += 32) mbar_init(sb + BARS + i * 8, i < 13 ? 6 : i < 19 ? 2 : 1);
    ((uint32_t*)(smem + PAD))[tid] = 0;
    fence_mbar_init(); fence_proxy_async();
    __syncwarp();
    e_expect_tx(sb + B_ST, STG); e_expect_tx(sb + B_ST + 8, STG);
    for (int i = 0; i < 2 * KR; i++) e_tma_2d(sb + (i & 1) * STG + (i >> 1) * 2048, &M.w[rank], h * DH + (i & 1) * 64, k_of_reg(i >> 1) * 16, sb + B_ST + (i & 1) * 8);
  } else if (wi == 1) {
    if (blockIdx.x < NEV / 32) { g_dep[blockIdx.x * 32 + (tid & 31)] = 0; g_claim[blockIdx.x * 32 + (tid & 31)] = 0; __threadfence(); }
    __syncwarp();
    asm volatile("griddepcontrol.launch_dependents;" ::: "memory");
  }
  cluster_arrive(); cluster_wait();
  if (wi < 8) { reg_inc<232>(); rec_math(sb, wi, M); cluster_arrive(); cluster_wait(); }
  else { reg_dec<40>(); rec_comm(sb, wi & 3, M, mem0); cluster_arrive(); cluster_wait(); }
}

namespace gm {
struct Maps { CUtensorMap ot, wo, xn, wg, wu, hl, hs, wd, out; };
constexpr int STAGES = 6, STAGE = 32768;
constexpr uint32_t SO = STAGES * STAGE, BARS = SO + 32768;
constexpr uint32_t B_FULL = BARS, B_EMPTY = BARS + 48, B_TF = BARS + 96, B_TE = BARS + 112, B_ORD = BARS + 128, B_PM = BARS + 144, B_GO = BARS + 160;
constexpr uint32_t MAIL = BARS + 176, PMAIL = BARS + 192;
constexpr uint32_t SMEM = BARS + 256;
constexpr int END = -1;

struct Tile {
  bool isO, isG, l2; int blk, col, k0, n;
  DEVI Tile(int task, int rank) {
    const int e = task >> 8, id = task & 255;
    const bool isD = e < E_G1 || e >= E_D2;
    isO = e >= E_O1 && e < E_G2; isG = !isD && !isO; l2 = e >= E_O2;
    blk = isG && l2 ? (e & 15) * 2 + rank : isD && !l2 ? e >> 1 : e & 15;
    col = isG ? (l2 ? id : id * 2 + rank) : (id & 3) * 2 + rank;
    k0 = isO ? (id >> 2) * 2048 : isG ? 0 : ((l2 ? e >> 4 : e) & 1) * 1792;
    n = isO ? 32 : isG ? 16 : 28;
  }
};

DEVI float geglu(float g, float u) {
  const float z = g * (0.7978845608028654f + 0.035677408136300125f * g * g);
  float t; asm("tanh.approx.f32 %0, %1;" : "=f"(t) : "f"(z));
  const float hg = 0.5f * g;
  return fmaf(hg, t, hg) * u;
}
struct Sched {
  int need, size;
  bool filler;
  uint4 dep, cl;
  DEVI void init(int lane) {
    const int e = lane * 4;
    const bool d = e < E_G1 || e >= E_D2, o = e >= E_O1 && e < E_G2;
    need = d ? 28 : e < E_O1 ? 64 : 128;
    size = d ? 4 : o ? 8 : e < E_O1 ? 28 : e < E_G2 + 8 ? 56 : 0;
    filler = (int)blockIdx.x < TP(5);
  }
  DEVI void scan(int lane) { cl = ldg_rlx128(g_claim + lane * 4); dep = ldg_rlx128(g_dep + lane * 4); }
  DEVI int next(int lane, int& budget) {
    while (--budget > 0) {
      int av[4], open = 0;
#pragma unroll
      for (int i = 0; i < 4; i++) { const int r = max(size - (int)(&cl.x)[i], 0); open |= r; av[i] = ((int)(&dep.x)[i] >= need ? r : 0) + (i ? av[i - 1] : 0); }
      const uint32_t mo = __ballot_sync(0xffffffffu, open);
      if (!mo) break;
      if (!filler && (mo & TP(6)) && lane >= E_O2 / 4) av[3] = 0;
      int inc = av[3], pos = 0;
      while (true) {
        const uint32_t m = __ballot_sync(0xffffffffu, inc > pos && av[3]);
        if (!m) break;
        const int l = __ffs(m) - 1, rel = pos - (inc - av[3]), i = (rel >= av[0]) + (rel >= av[1]) + (rel >= av[2]);
        int r = 0;
        if (lane == l) {
          const int tk = atomicAdd(g_claim + lane * 4 + i, 1);
          r = tk < size ? (lane * 4 + i) << 8 | tk : -1 - (inc - av[3] + (i == 0 ? av[0] : i == 1 ? av[1] : i == 2 ? av[2] : av[3]) + tk - size);
        }
        r = __shfl_sync(0xffffffffu, r, l);
        if (r >= 0) return r;
        if (pos == 0) {
#pragma unroll
          for (int o = 1; o < 32; o <<= 1) { const int v = __shfl_up_sync(0xffffffffu, inc, o); if (lane >= o) inc += v; }
        }
        pos = -1 - r;
      }
      if (pos == 0) __nanosleep(TP(7));
      scan(lane);
    }
    return END;
  }
};

DEVI void scheduler(const uint32_t sb) {
  const int lane = threadIdx.x & 31;
  int budget = SPIN_BUDGET;
  Sched sc; sc.init(lane);
#pragma unroll 1
  for (int i = 0;; i++) {
    mbar_wait(sb + B_GO, (i & 1) ^ 1, budget);
    sc.scan(lane);
    const int task = sc.next(lane, budget);
    const uint32_t r = mapa(sb, lane & 1);
    if (lane < 2) st_async32(r + PMAIL + (i & 1) * 4, task, r + B_PM + (i & 1) * 8);
    __syncwarp();
    if (task == END) break;
  }
}

DEVI void producer(const uint32_t sb, const Maps& M) {
  const int lane = threadIdx.x & 31, rank = cluster_rank();
  int budget = SPIN_BUDGET, s = 0, ph = 0;
#pragma unroll 1
  for (int i = 0;; i++) {
    e_expect_tx(sb + B_PM + (i & 1) * 8, 4);
    mbar_wait_cluster(sb + B_PM + (i & 1) * 8, (i >> 1) & 1, budget);
    const int task = budget < 0 ? END : __shfl_sync(0xffffffffu, (int)lds32v(sb + PMAIL + (i & 1) * 4), 0);
    fence_proxy_global();
    for (int z = 0; z < (task == END ? 2 : 1); z++) {
      const int g = (i + z) & 1;
      mbar_wait(sb + B_TE + g * 8, (((i + z) >> 1) & 1) ^ 1, budget);
      if (lane == 0) { sts64(sb + MAIL + g * 8, task, s | ph << 8); mbar_arrive(sb + B_TF + g * 8); }
      __syncwarp();
    }
    if (task == END) break;
    const Tile T(task, rank);
    const bool shareB = T.isG && T.l2;
    const CUtensorMap* mA = T.isO ? &M.ot : T.isG ? &M.xn : &M.hl;
    const CUtensorMap* mB0 = T.isO ? &M.wo : T.isG ? &M.wg : &M.wd;
    const CUtensorMap* mB1 = T.isG ? &M.wu : mB0;
    const int c0 = T.col * (T.isG ? 64 : 128), c1 = T.isG ? c0 : c0 + 64, row = T.blk * 128;
    const int ok = 0;
    int k = T.k0;
#pragma unroll 1
    for (int it = 0; it < T.n; it++, k += 64) {
      const uint32_t a = sb + s * STAGE, fb = sb + B_FULL + s * 8;
      mbar_wait(sb + B_EMPTY + s * 8, ph ^ 1, budget);
      e_expect_tx(fb, STAGE);
      if (shareB) {
        e_tma_2d_mc(a + 16384 + rank * 8192, rank ? mB1 : mB0, c0, k, fb);
        e_tma_2d(a, mA, k, row, fb); e_tma_2d(a + 8192, mA, k, row + 64, fb);
      } else {
        e_tma_2d_mc(a + rank * 8192, mA, T.isO ? row + rank * 64 : k, T.isO ? k + ok : row + rank * 64, fb);
        e_tma_2d(a + 16384, mB0, c0, k, fb); e_tma_2d(a + 24576, mB1, c1, k, fb);
      }
      if (it == T.n - TP(2)) e_arrive(sb + B_GO);
      if (++s == STAGES) { s = 0; ph ^= 1; }
    }
  }
}

template<int TA> DEVI void mainloop(float* d0, float* d1, uint32_t sb, int n, int s, int ph, bool lead, uint32_t ord, int& budget) {
  int prev = 0;
  const uint32_t rel = threadIdx.x & 127;
#pragma unroll 1
  for (int i = 0; i < n; i++) {
    mbar_wait(sb + B_FULL + s * 8, ph, budget);
    const uint32_t a = sb + s * STAGE;
    const uint64_t da = mkdesc(a, 16, 1024), db = mkdesc(a + 16384, 8192, 1024);
    wg_fence();
#pragma unroll
    for (int k = 0; k < 4; k++) {
      wgmma_n128<TA>(d0, da + k * (TA ? 128 : 2), db + k * 128, (i | k) != 0);
      wgmma_n128<TA>(d1, da + 512 + k * (TA ? 128 : 2), db + k * 128, (i | k) != 0);
    }
    wg_commit();
    if (i > 0) { wg_wait<1>(); p_arrive_at(sb + B_EMPTY + prev * 8, rel & 1, rel < 2); }
    prev = s;
    if (++s == STAGES) { s = 0; ph ^= 1; }
  }
  p_arrive(ord, lead);
  wg_wait<0>();
  p_arrive_at(sb + B_EMPTY + prev * 8, rel & 1, rel < 2);
}

DEVI void consumer(const uint32_t sb, const Maps& M, const int wg) {
  const int tid = threadIdx.x, lane = tid & 31, warp = (tid >> 5) & 3;
  const bool lead = (tid & 127) == 0;
  const uint32_t so = sb + SO + wg * 16384;
  int budget = SPIN_BUDGET;
  float d0[64], d1[64];
#pragma unroll 1
  for (int m = 0;; m++) {
    mbar_wait(sb + B_TF + wg * 8, m & 1, budget);
    const uint2 mail = lds64v(sb + MAIL + wg * 8);
    const int task = __shfl_sync(0xffffffffu, (int)mail.x, 0), pos = __shfl_sync(0xffffffffu, (int)mail.y, 0);
    e_arrive(sb + B_TE + wg * 8);
    if (task == END || budget < 0) break;
    const Tile T(task, cluster_rank());
    mbar_wait(sb + B_ORD + wg * 8, (m & 1) ^ wg ^ 1, budget);
    if (T.isO) mainloop<1>(d0, d1, sb, 32, pos & 255, pos >> 8, lead, sb + B_ORD + (wg ^ 1) * 8, budget);
    else mainloop<0>(d0, d1, sb, T.n, pos & 255, pos >> 8, lead, sb + B_ORD + (wg ^ 1) * 8, budget);
    const uint32_t st = so + (warp * 16 + (lane & 15)) * 128;
    if (T.isG) {
#pragma unroll
      for (int mm = 0; mm < 2; mm++) {
        const float* d = mm ? d1 : d0;
#pragma unroll
        for (int c = 0; c < 4; c++) {
          uint32_t r[4];
#pragma unroll
          for (int i = 0; i < 4; i++) r[i] = pack_bf16(geglu(d[8*c+2*i], d[32+8*c+2*i]), geglu(d[8*c+2*i+1], d[33+8*c+2*i]));
          stsm4(st + mm * 8192 + (((2 * c + (lane >> 4)) ^ (lane & 7)) << 4), r[0], r[1], r[2], r[3]);
        }
      }
      fence_proxy_async();
      nbar_sync_r(1 + wg, 128);
      if (lead) {
        tma_store_2d(&M.hs, so, T.col * 64, T.blk * 128);
        bulk_commit(); bulk_wait<0>();
        flag_add(&g_dep[T.l2 ? E_D2 + (T.col >= 28) * 16 + T.blk : E_D1 + T.blk * 2 + (T.col >= 28)]);
      }
    } else {
#pragma unroll
      for (int hf = 0; hf < 2; hf++) {
        if (hf) { if (lead) bulk_wait_read<0>(); nbar_sync_r(1 + wg, 128); }
#pragma unroll
        for (int mm = 0; mm < 2; mm++) {
          const float* d = (mm ? d1 : d0) + hf * 32;
#pragma unroll
          for (int c = 0; c < 4; c++)
            stsm4(st + mm * 8192 + (((2 * c + (lane >> 4)) ^ (lane & 7)) << 4), pack_bf16(d[8*c], d[8*c+1]), pack_bf16(d[8*c+2], d[8*c+3]),
                  pack_bf16(d[8*c+4], d[8*c+5]), pack_bf16(d[8*c+6], d[8*c+7]));
        }
        fence_proxy_async();
        nbar_sync_r(1 + wg, 128);
        if (lead) { tma_radd_2d(&M.out, so, T.col * 128 + hf * 64, T.blk * 128); bulk_commit(); }
      }
      if (lead) {
        bulk_wait<0>();
        if (T.isO || !T.l2) flag_add(&g_dep[(!T.isO ? E_LX2 : T.l2 ? E_LX1B : E_LX1A) + T.blk]);
      }
    }
    __syncwarp();
  }
}

DEVI void norm_helper(const bf16* __restrict__ x, bf16* out) {
  const int lane = threadIdx.x & 31;
  int budget = SPIN_BUDGET, tk = lane < 4 ? -1 : 1024;
#pragma unroll 1
  while (--budget > 0) {
    if (tk < 0) tk = atomicAdd(g_claim + E_LI + lane, 1);
    if (__all_sync(0xffffffffu, tk >= 1024)) break;
    const uint32_t m = __ballot_sync(0xffffffffu, tk < 1024 && (lane == 0 || ldg_acq32(g_dep + E_LI + lane * 16 + (tk >> 6)) >= 16));
    if (!m) { __nanosleep(TP(7)); continue; }
    const int ql = __ffs(m) - 1, task = __shfl_sync(0xffffffffu, tk, ql), q = E_LI + ql * 16, ev = task >> 6;
    if (lane == ql) tk = -1;
    const size_t off = (size_t)task * (DM * 4) + lane * 16;
    const char* src = (const char*)(q == E_LI ? x : out) + off;
    uint4 u[8];
#pragma unroll
    for (int i = 0; i < 8; i++) u[i] = ldg_rlx128(src + i * 512);
    if (q == E_LI) {
#pragma unroll
      for (int i = 0; i < 8; i++) stg128((char*)out + off + i * 512, u[i].x, u[i].y, u[i].z, u[i].w);
    }
    float mean[2], rs[2];
#pragma unroll
    for (int r = 0; r < 2; r++) {
      float s0 = 0, s1 = 0;
#pragma unroll
      for (int i = 0; i < 16; i++) { const uint32_t v = (&u[4*r + (i >> 2)].x)[i & 3]; s0 += bf_lo(v); s1 += bf_hi(v); }
      mean[r] = (s0 + s1) * (1.f / 32);
      s0 = s1 = 0;
#pragma unroll
      for (int i = 0; i < 16; i++) { const uint32_t v = (&u[4*r + (i >> 2)].x)[i & 3]; const float a = bf_lo(v) - mean[r], b = bf_hi(v) - mean[r]; s0 = fmaf(a, a, s0); s1 = fmaf(b, b, s1); }
      rs[r] = s0 + s1;
    }
    {
      const bool hi = lane & 16;
      float m1 = hi ? mean[1] : mean[0], q1 = hi ? rs[1] : rs[0], m2 = hi ? mean[0] : mean[1], q2 = hi ? rs[0] : rs[1], cnt = 16;
#pragma unroll
      for (int o = 16; o; o >>= 1) {
        m2 = __shfl_xor_sync(0xffffffffu, m2, o); q2 = __shfl_xor_sync(0xffffffffu, q2, o);
        const float dl = m1 - m2;
        q2 = q1 = fmaf(dl * dl, cnt, q1 + q2); m2 = m1 = 0.5f * (m1 + m2);
        cnt *= 2;
      }
      q1 = rsqrtf(q1 * (1.f / DM) + 1e-5f);
      m2 = __shfl_xor_sync(0xffffffffu, m1, 16); q2 = __shfl_xor_sync(0xffffffffu, q1, 16);
      mean[0] = hi ? m2 : m1; mean[1] = hi ? m1 : m2; rs[0] = hi ? q2 : q1; rs[1] = hi ? q1 : q2;
    }
#pragma unroll
    for (int i = 0; i < 8; i++) {
      uint32_t y[4];
#pragma unroll
      for (int c = 0; c < 4; c++) { const uint32_t v = (&u[i].x)[c]; y[c] = pack_bf16((bf_lo(v) - mean[i >> 2]) * rs[i >> 2], (bf_hi(v) - mean[i >> 2]) * rs[i >> 2]); }
      stg128((char*)g_xn + off + i * 512, y[0], y[1], y[2], y[3]);
    }
    fence_proxy_global();
    __syncwarp();
    if (lane == 0) flag_add(q == E_LI ? &g_xa[0][ev] : q == E_LX2 ? &g_xa[1][ev] : &g_dep[q == E_LX1A ? E_G1 + ev : E_G2 + (ev >> 1)]);
    __syncwarp();
  }
}
}

__global__ void __cluster_dims__(2, 1, 1) __launch_bounds__(384, 1)
gemm_kernel(const __grid_constant__ gm::Maps M, const bf16* __restrict__ x, bf16* out) {
  using namespace gm;
  extern __shared__ __align__(1024) uint8_t smem[];
  const uint32_t sb = __shfl_sync(0xffffffffu, smem_u32(smem), 0);
  const int tid = threadIdx.x, wi = __shfl_sync(0xffffffffu, tid >> 5, 0);
  if (tid < 21) mbar_init(sb + BARS + tid * 8, tid == 14 || tid == 15 ? 4 : tid >= 6 && tid < 12 ? 2 : 1);
  fence_mbar_init();
  cluster_arrive(); cluster_wait();
  if (wi < 8) { reg_inc<208>(); consumer(sb, M, wi >> 2); cluster_arrive(); cluster_wait(); }
  else {
    reg_dec<88>();
    if (wi == 8) producer(sb, M);
    else if (wi == 11 && cluster_rank() == 0) scheduler(sb);
    else {
      norm_helper(x, out);
      asm volatile("griddepcontrol.wait;" ::: "memory");
      if (wi == 9 && blockIdx.x < 64) g_h2[(NSTEP - 1) & 3][blockIdx.x * 32 + (tid & 31)] = make_uint4(0, 0, 0, 0);
    }
    __syncwarp();
    cluster_arrive(); cluster_wait();
  }
}

typedef CUresult (*PFN_encodeTiled)(CUtensorMap*, CUtensorMapDataType, cuuint32_t, void*, const cuuint64_t*, const cuuint64_t*,
                                    const cuuint32_t*, const cuuint32_t*, CUtensorMapInterleave, CUtensorMapSwizzle,
                                    CUtensorMapL2promotion, CUtensorMapFloatOOBfill);
static PFN_encodeTiled g_encode = nullptr;
static CUtensorMap make_map(const void* ptr, uint64_t rows, uint64_t cols, uint32_t box_rows) {
  CUtensorMap m;
  cuuint64_t dims[2] = {cols, rows}, strides[1] = {cols * 2};
  cuuint32_t box[2] = {64, box_rows}, es[2] = {1, 1};
  g_encode(&m, CU_TENSOR_MAP_DATA_TYPE_BFLOAT16, 2, (void*)ptr, dims, strides, box, es, CU_TENSOR_MAP_INTERLEAVE_NONE,
           CU_TENSOR_MAP_SWIZZLE_128B, CU_TENSOR_MAP_L2_PROMOTION_L2_256B, CU_TENSOR_MAP_FLOAT_OOB_FILL_NONE);
  return m;
}

static CUtensorMap make_map3(const void* ptr, uint64_t d0, uint64_t d1, uint64_t d2, uint64_t stride2) {
  CUtensorMap m;
  cuuint64_t dims[3] = {d0, d1, d2}, strides[2] = {DM * 2, stride2};
  cuuint32_t box[3] = {64, 32, 2}, es[3] = {1, 1, 1};
  g_encode(&m, CU_TENSOR_MAP_DATA_TYPE_BFLOAT16, 3, (void*)ptr, dims, strides, box, es, CU_TENSOR_MAP_INTERLEAVE_NONE,
           CU_TENSOR_MAP_SWIZZLE_128B, CU_TENSOR_MAP_L2_PROMOTION_L2_256B, CU_TENSOR_MAP_FLOAT_OOB_FILL_NONE);
  return m;
}

extern "C" void kernel_launch(void* const* d_in, const int* in_sizes, int n_in, void* d_out, int out_size) {
  const bf16* x = (const bf16*)d_in[0];
  const bf16* mem0 = (const bf16*)d_in[1];
  if (!g_encode) {
    void* p = nullptr; cudaDriverEntryPointQueryResult q;
    cudaGetDriverEntryPoint("cuTensorMapEncodeTiled", &p, cudaEnableDefault, &q);
    g_encode = (PFN_encodeTiled)p;
    cudaFuncSetAttribute(gemm_kernel, cudaFuncAttributeMaxDynamicSharedMemorySize, gm::SMEM);
    cudaFuncSetAttribute(rec_kernel, cudaFuncAttributeMaxDynamicSharedMemorySize, rec::SMEM);
  }
  bf16 *xn, *ot, *hh;
  cudaGetSymbolAddress((void**)&xn, g_xn); cudaGetSymbolAddress((void**)&ot, g_ot); cudaGetSymbolAddress((void**)&hh, g_h);
  rec::Maps R;
  for (int i = 0; i < 3; i++) R.w[i] = make_map(d_in[2 + i], DM, NH * DH, 16);
  R.wo = make_map(d_in[5], NH * DH, DM, 128);
  R.xd = make_map3(xn, DM, SEQ - LAG * 32, 2, (uint64_t)LAG * 32 * DM * 2); R.xs = make_map3(xn, 64, SEQ, DM / 64, 128);
  gm::Maps G;
  G.ot = make_map(ot, NH * DH + O_LAYER / SEQ, SEQ, 64); G.wo = make_map(d_in[5], NH * DH, DM, 64); G.xn = make_map(xn, SEQ, DM, 64);
  G.wg = make_map(d_in[8], DM, DF, 64); G.wu = make_map(d_in[9], DM, DF, 64); G.hl = make_map(hh, SEQ, DF, 64); G.hs = make_map(hh, SEQ, DF, 128);
  G.wd = make_map(d_in[10], DF, DM, 64); G.out = make_map(d_out, SEQ, DM, 128);
  rec_kernel<<<3 * NH, 384, rec::SMEM, cudaStreamPerThread>>>(R, mem0);
  cudaLaunchConfig_t cfg = {};
  cfg.gridDim = dim3(132); cfg.blockDim = dim3(384); cfg.dynamicSmemBytes = gm::SMEM; cfg.stream = cudaStreamPerThread;
  cudaLaunchAttribute at[1];
  at[0].id = cudaLaunchAttributeProgrammaticStreamSerialization; at[0].val.programmaticStreamSerializationAllowed = 1;
  cfg.attrs = at; cfg.numAttrs = 1;
  cudaLaunchKernelEx(&cfg, gemm_kernel, G, x, (bf16*)d_out);
}
```

```cpp
#include <cuda_runtime.h>
#include <cuda_bf16.h>
#include <cuda.h>
#include <stdint.h>

#define DEVI __device__ __forceinline__
typedef __nv_bfloat16 bf16;

constexpr int SEQ = 2048, DM = 1024, NH = 32, DH = 128, DF = 3584, NSEG = 64;
#define LAG 18
constexpr int NSTEP = NSEG + LAG;

#define CSIZE 6
#define TSS 1
#define TSD (LATE == 1 ? 1900 : 1400)
constexpr size_t O_LAYER = 0;
__device__ __align__(1024) bf16 g_xn[SEQ * DM];
__device__ __align__(1024) bf16 g_ot[SEQ * NH * DH + O_LAYER];
__device__ __align__(1024) bf16 g_h[SEQ * DF];
__device__ __align__(1024) uint2 g_h1[4][256 * 256];
__device__ __align__(1024) uint4 g_h2[4][2048];
__device__ __align__(128) uint32_t g_ts[2][32 * TSS];
enum { E_D1 = 0, E_G1 = 32, E_O1 = 48, E_O2 = 64, E_G2 = 80, E_D2 = 96,
       E_LI = 128, E_LX2 = 144, E_LX1A = 160, E_LX1B = 176, NEV = 256 };
__device__ __align__(128) int g_dep[NEV];
__device__ __align__(128) int g_claim[NEV];
__device__ __align__(128) int g_xa[2][32];

#define TUNE_DEFAULTS 1550, 2250, 5, 100, 100, 16, 12, 100
constexpr int c_D[8] = {TUNE_DEFAULTS};
template<int I> struct TPV { static constexpr int v = c_D[I]; };
#define TP(i) TPV<i>::v

DEVI uint32_t smem_u32(const void* p) { return (uint32_t)__cvta_generic_to_shared(p); }
DEVI void mbar_init(uint32_t bar, uint32_t cnt) { asm volatile("mbarrier.init.shared::cta.b64 [%0], %1;" :: "r"(bar), "r"(cnt) : "memory"); }
DEVI void mbar_arrive(uint32_t bar) { asm volatile("mbarrier.arrive.shared::cta.b64 _, [%0];" :: "r"(bar) : "memory"); }
DEVI bool mbar_try(uint32_t bar, uint32_t parity) {
  uint32_t p;
  asm volatile("{.reg .pred p; mbarrier.try_wait.parity.shared::cta.b64 p, [%1], %2; selp.u32 %0, 1, 0, p;}" : "=r"(p) : "r"(bar), "r"(parity) : "memory");
  return p;
}
DEVI bool mbar_test(uint32_t bar, uint32_t parity) {
  uint32_t p;
  asm volatile("{.reg .pred p; mbarrier.test_wait.parity.shared::cta.b64 p, [%1], %2; selp.u32 %0, 1, 0, p;}" : "=r"(p) : "r"(bar), "r"(parity) : "memory");
  return p;
}
constexpr int SPIN_BUDGET = 1 << 18;
DEVI void mbar_wait(uint32_t bar, uint32_t parity, int& budget) {
  while (!mbar_try(bar, parity)) { if (--budget < 0) break; }
}
DEVI bool mbar_try_cluster(uint32_t bar, uint32_t parity) {
  uint32_t p;
  asm volatile("{.reg .pred p; mbarrier.try_wait.parity.acquire.cluster.shared::cta.b64 p, [%1], %2; selp.u32 %0, 1, 0, p;}" : "=r"(p) : "r"(bar), "r"(parity) : "memory");
  return p;
}
DEVI void mbar_wait_cluster(uint32_t bar, uint32_t parity, int& budget) {
  while (!mbar_try_cluster(bar, parity)) { if (--budget < 0) break; }
}
DEVI uint32_t mapa(uint32_t addr, uint32_t rank) { uint32_t r; asm("mapa.shared::cluster.u32 %0, %1, %2;" : "=r"(r) : "r"(addr), "r"(rank)); return r; }
DEVI void cluster_arrive() { asm volatile("barrier.cluster.arrive.release.aligned;" ::: "memory"); }
DEVI void cluster_wait() { asm volatile("barrier.cluster.wait.acquire.aligned;" ::: "memory"); }
DEVI void fence_mbar_init() { asm volatile("fence.mbarrier_init.release.cluster;" ::: "memory"); }
DEVI void fence_proxy_async() { asm volatile("fence.proxy.async.shared::cta;" ::: "memory"); }
DEVI void fence_proxy_global() { asm volatile("fence.proxy.async.global;" ::: "memory"); }
#define ELECT "{.reg .pred p; elect.sync _|p, 0xffffffff;\n @p "
DEVI void e_expect_tx(uint32_t bar, uint32_t bytes) { asm volatile(ELECT "mbarrier.arrive.expect_tx.shared::cta.b64 _, [%0], %1;}" :: "r"(bar), "r"(bytes) : "memory"); }
DEVI void e_complete_tx(uint32_t bar, uint32_t bytes) { asm volatile("fence.acq_rel.cta;\n" ELECT "mbarrier.complete_tx.relaxed.cta.shared::cta.b64 [%0], %1;}" :: "r"(bar), "r"(bytes) : "memory"); }
DEVI void e_arrive(uint32_t bar) { asm volatile(ELECT "mbarrier.arrive.shared::cta.b64 _, [%0];}" :: "r"(bar) : "memory"); }
DEVI void e_tma_2d(uint32_t dst, const CUtensorMap* m, int c0, int c1, uint32_t bar) {
  asm volatile(ELECT "cp.async.bulk.tensor.2d.shared::cluster.global.mbarrier::complete_tx::bytes [%0], [%1, {%3, %4}], [%2];}"
    :: "r"(dst), "l"(m), "r"(bar), "r"(c0), "r"(c1) : "memory");
}
DEVI void e_prefetch_2d(const CUtensorMap* m, int c0, int c1) {
  asm volatile(ELECT "cp.async.bulk.prefetch.tensor.2d.L2.global [%0, {%1, %2}];}" :: "l"(m), "r"(c0), "r"(c1) : "memory");
}
DEVI void e_prefetch_3d(const CUtensorMap* m, int c0, int c1, int c2) {
  asm volatile(ELECT "cp.async.bulk.prefetch.tensor.3d.L2.global [%0, {%1, %2, %3}];}" :: "l"(m), "r"(c0), "r"(c1), "r"(c2) : "memory");
}
DEVI void e_bulk_g2s(uint32_t dst, const void* src, uint32_t bytes, uint32_t bar) {
  asm volatile(ELECT "cp.async.bulk.shared::cluster.global.mbarrier::complete_tx::bytes [%0], [%1], %2, [%3];}" :: "r"(dst), "l"(src), "r"(bytes), "r"(bar) : "memory");
}
DEVI void e_tma_3d(uint32_t dst, const CUtensorMap* m, int c0, int c1, int c2, uint32_t bar) {
  asm volatile(ELECT "cp.async.bulk.tensor.3d.shared::cluster.global.mbarrier::complete_tx::bytes [%0], [%1, {%3, %4, %5}], [%2];}"
    :: "r"(dst), "l"(m), "r"(bar), "r"(c0), "r"(c1), "r"(c2) : "memory");
}
DEVI void e_tma_3d_mc(uint32_t dst, const CUtensorMap* m, int c0, int c1, int c2, uint32_t bar, int rb) {
  asm volatile(ELECT "cp.async.bulk.tensor.3d.shared::cluster.global.mbarrier::complete_tx::bytes.multicast::cluster [%0], [%1, {%3, %4, %5}], [%2], %6;}"
    :: "r"(dst), "l"(m), "r"(bar), "r"(c0), "r"(c1), "r"(c2), "h"((uint16_t)(7 << rb)) : "memory");
}
DEVI void e_tma_2d_mc(uint32_t dst, const CUtensorMap* m, int c0, int c1, uint32_t bar) {
  asm volatile(ELECT "cp.async.bulk.tensor.2d.shared::cluster.global.mbarrier::complete_tx::bytes.multicast::cluster [%0], [%1, {%3, %4}], [%2], %5;}"
    :: "r"(dst), "l"(m), "r"(bar), "r"(c0), "r"(c1), "h"((uint16_t)3) : "memory");
}
DEVI void p_arrive_at(uint32_t bar, uint32_t rank, bool c) {
  asm volatile("{.reg .pred p; .reg .b32 a; setp.ne.u32 p, %2, 0; mapa.shared::cluster.u32 a, %0, %1; @p mbarrier.arrive.shared::cluster.b64 _, [a];}"
    :: "r"(bar), "r"(rank), "r"((uint32_t)c) : "memory");
}
DEVI void p_expect_tx(uint32_t bar, uint32_t bytes, bool c) {
  asm volatile("{.reg .pred p; setp.ne.u32 p, %2, 0; @p mbarrier.arrive.expect_tx.shared::cta.b64 _, [%0], %1;}" :: "r"(bar), "r"(bytes), "r"((uint32_t)c) : "memory");
}
DEVI void p_arrive(uint32_t bar, bool c) { asm volatile("{.reg .pred p; setp.ne.u32 p, %1, 0; @p mbarrier.arrive.shared::cta.b64 _, [%0];}" :: "r"(bar), "r"((uint32_t)c) : "memory"); }
DEVI void tma_store_2d(const CUtensorMap* m, uint32_t src, int c0, int c1) {
  asm volatile("cp.async.bulk.tensor.2d.global.shared::cta.bulk_group [%0, {%2, %3}], [%1];" :: "l"(m), "r"(src), "r"(c0), "r"(c1) : "memory");
}
DEVI void tma_radd_2d(const CUtensorMap* m, uint32_t src, int c0, int c1) {
  asm volatile("cp.reduce.async.bulk.tensor.2d.global.shared::cta.add.bulk_group [%0, {%2, %3}], [%1];" :: "l"(m), "r"(src), "r"(c0), "r"(c1) : "memory");
}
DEVI void bulk_commit() { asm volatile("cp.async.bulk.commit_group;" ::: "memory"); }
template<int N> DEVI void bulk_wait_read() { asm volatile("cp.async.bulk.wait_group.read %0;" :: "n"(N) : "memory"); }
template<int N> DEVI void bulk_wait() { asm volatile("cp.async.bulk.wait_group %0;" :: "n"(N) : "memory"); }
template<int ID, int N> DEVI void nbar_sync() { asm volatile("bar.sync %0, %1;" :: "n"(ID), "n"(N) : "memory"); }
template<int ID, int N> DEVI void nbar_arrive() { asm volatile("bar.arrive %0, %1;" :: "n"(ID), "n"(N) : "memory"); }
DEVI void nbar_sync_r(int id, int n) { asm volatile("bar.sync %0, %1;" :: "r"(id), "r"(n) : "memory"); }
template<int R> DEVI void reg_inc() { asm volatile("setmaxnreg.inc.sync.aligned.u32 %0;" :: "n"(R)); }
template<int R> DEVI void reg_dec() { asm volatile("setmaxnreg.dec.sync.aligned.u32 %0;" :: "n"(R)); }
DEVI void wg_fence() { asm volatile("wgmma.fence.sync.aligned;" ::: "memory"); }
DEVI void wg_commit() { asm volatile("wgmma.commit_group.sync.aligned;" ::: "memory"); }
template<int N> DEVI void wg_wait() { asm volatile("wgmma.wait_group.sync.aligned %0;" :: "n"(N) : "memory"); }
DEVI uint64_t mkdesc(uint32_t addr, uint32_t lbo, uint32_t sbo, uint32_t sw = 1) {
  return ((uint64_t)((addr & 0x3FFFF) >> 4)) | ((uint64_t)(lbo >> 4) << 16) | ((uint64_t)(sbo >> 4) << 32) | ((uint64_t)sw << 62);
}
constexpr uint32_t SMEM_BASE = 1024;
__host__ __device__ constexpr long long CD(uint32_t off, uint32_t lbo, uint32_t sbo, uint32_t sw) {
  return (long long)(((uint64_t)((SMEM_BASE + off) >> 4)) | ((uint64_t)(lbo >> 4) << 16) | ((uint64_t)(sbo >> 4) << 32) | ((uint64_t)sw << 62));
}
DEVI uint32_t pack_bf16(float lo, float hi) { uint32_t r; asm("cvt.rn.bf16x2.f32 %0, %1, %2;" : "=r"(r) : "f"(hi), "f"(lo)); return r; }
DEVI float bf_lo(uint32_t v) { return __uint_as_float(v << 16); }
DEVI float bf_hi(uint32_t v) { return __uint_as_float(v & 0xffff0000u); }
DEVI void ldsm4t(uint32_t addr, uint32_t& r0, uint32_t& r1, uint32_t& r2, uint32_t& r3) {
  asm volatile("ldmatrix.sync.aligned.m8n8.x4.trans.shared.b16 {%0,%1,%2,%3}, [%4];" : "=r"(r0), "=r"(r1), "=r"(r2), "=r"(r3) : "r"(addr) : "memory");
}
DEVI void stsm4(uint32_t addr, uint32_t r0, uint32_t r1, uint32_t r2, uint32_t r3) {
  asm volatile("stmatrix.sync.aligned.m8n8.x4.shared.b16 [%0], {%1,%2,%3,%4};" :: "r"(addr), "r"(r0), "r"(r1), "r"(r2), "r"(r3) : "memory");
}
DEVI uint2 lds64v(uint32_t a) { uint2 v; asm volatile("ld.volatile.shared.v2.u32 {%0,%1}, [%2];" : "=r"(v.x), "=r"(v.y) : "r"(a) : "memory"); return v; }
DEVI uint32_t lds32v(uint32_t a) { uint32_t v; asm volatile("ld.volatile.shared.u32 %0, [%1];" : "=r"(v) : "r"(a) : "memory"); return v; }
DEVI uint4 lds128v(uint32_t a) { uint4 v; asm volatile("ld.volatile.shared.v4.u32 {%0,%1,%2,%3}, [%4];" : "=r"(v.x), "=r"(v.y), "=r"(v.z), "=r"(v.w) : "r"(a) : "memory"); return v; }
DEVI void cp_async16(uint32_t dst, const void* src) { asm volatile("cp.async.cg.shared.global [%0], [%1], 16;" :: "r"(dst), "l"(src) : "memory"); }
DEVI void cp_async_wait() { asm volatile("cp.async.wait_all;" ::: "memory"); }
DEVI void sts32(uint32_t a, uint32_t x) { asm volatile("st.shared.u32 [%0], %1;" :: "r"(a), "r"(x) : "memory"); }
DEVI int lane_id() { int r; asm volatile("mov.u32 %0, %%laneid;" : "=r"(r)); return r; }
DEVI void sts64(uint32_t a, uint32_t x, uint32_t y) { asm volatile("st.shared.v2.u32 [%0], {%1,%2};" :: "r"(a), "r"(x), "r"(y) : "memory"); }
DEVI void sts128(uint32_t a, uint4 v) { asm volatile("st.shared.v4.u32 [%0], {%1,%2,%3,%4};" :: "r"(a), "r"(v.x), "r"(v.y), "r"(v.z), "r"(v.w) : "memory"); }
DEVI void st_async128(uint32_t a, uint32_t x, uint32_t y, uint32_t z, uint32_t w, uint32_t bar) {
  asm volatile("st.async.weak.shared::cluster.mbarrier::complete_tx::bytes.v4.b32 [%0], {%1,%2,%3,%4}, [%5];" :: "r"(a), "r"(x), "r"(y), "r"(z), "r"(w), "r"(bar) : "memory");
}
DEVI void st_async32(uint32_t a, uint32_t x, uint32_t bar) {
  asm volatile("st.async.weak.shared::cluster.mbarrier::complete_tx::bytes.b32 [%0], %1, [%2];" :: "r"(a), "r"(x), "r"(bar) : "memory");
}
DEVI uint4 ldg_rlx128(const void* p) {
  uint4 v;
  asm volatile("ld.relaxed.gpu.global.v4.b32 {%0,%1,%2,%3}, [%4];" : "=r"(v.x), "=r"(v.y), "=r"(v.z), "=r"(v.w) : "l"(p) : "memory");
  return v;
}
DEVI int ldg_rlx32(const void* p) { int v; asm volatile("ld.relaxed.gpu.global.b32 %0, [%1];" : "=r"(v) : "l"(p) : "memory"); return v; }
DEVI int ldg_acq32(const void* p) { int v; asm volatile("ld.acquire.gpu.global.b32 %0, [%1];" : "=r"(v) : "l"(p) : "memory"); return v; }
DEVI void stg_rlx128(void* p, uint32_t x, uint32_t y, uint32_t z, uint32_t w) {
  asm volatile("st.relaxed.gpu.global.v4.b32 [%0], {%1,%2,%3,%4};" :: "l"(p), "r"(x), "r"(y), "r"(z), "r"(w) : "memory");
}
DEVI void stg128(void* p, uint32_t x, uint32_t y, uint32_t z, uint32_t w) {
  asm volatile("st.global.v4.b32 [%0], {%1,%2,%3,%4};" :: "l"(p), "r"(x), "r"(y), "r"(z), "r"(w) : "memory");
}
DEVI uint2 ldg_rlx64(const void* p) { uint2 v; asm volatile("{.reg .b64 a; ld.relaxed.gpu.global.b64 a, [%2]; mov.b64 {%0,%1}, a;}" : "=r"(v.x), "=r"(v.y) : "l"(p) : "memory"); return v; }
DEVI void stg_rlx64(void* p, uint32_t x, uint32_t y) { asm volatile("{.reg .b64 a; mov.b64 a, {%1,%2}; st.relaxed.gpu.global.b64 [%0], a;}" :: "l"(p), "r"(x), "r"(y) : "memory"); }
DEVI void stg_rlx32(void* p, uint32_t x) { asm volatile("st.relaxed.gpu.global.b32 [%0], %1;" :: "l"(p), "r"(x) : "memory"); }
DEVI void flag_add(int* p) { asm volatile("fence.proxy.async.global; red.release.gpu.global.add.s32 [%0], 1;" :: "l"(p) : "memory"); }
DEVI void e_stg_rlx32(void* p, uint32_t x) { asm volatile(ELECT "st.relaxed.gpu.global.b32 [%0], %1;}" :: "l"(p), "r"(x) : "memory"); }
DEVI void e_flag_add(int* p) { asm volatile("fence.proxy.async.global;\n" ELECT "red.release.gpu.global.add.s32 [%0], 1;}" :: "l"(p) : "memory"); }
DEVI int cluster_rank() { int r; asm volatile("mov.u32 %0, %%cluster_ctarank;" : "=r"(r)); return __shfl_sync(0xffffffffu, r, 0); }
DEVI int cta_id() { int r; asm volatile("mov.u32 %0, %%ctaid.x;" : "=r"(r)); return __shfl_sync(0xffffffffu, r, 0); }
DEVI uint32_t clock32() { uint32_t c; asm volatile("mov.u32 %0, %%clock;" : "=r"(c)); return c; }
DEVI uint32_t gtime() { uint32_t c; asm volatile("mov.u32 %0, %%globaltimer_lo;" : "=r"(c)); return c; }
DEVI void wait_time(uint32_t t) { while (__any_sync(0xffffffffu, t - gtime() - 1 < 4000u)) {} }
DEVI void spin_until(uint32_t t0, int d) { while (__any_sync(0xffffffffu, (int)(clock32() - t0) < d)) {} }
DEVI void pin2(const void* a, const void* b) { asm volatile("{.reg .pred p; setp.eq.u64 p, %0, %1; @p st.volatile.global.u64 [%0], %1;}" :: "l"(a), "l"(b) : "memory"); }
DEVI void pin2(uint32_t a, uint32_t b) { asm volatile("{.reg .pred p; setp.eq.u32 p, %0, %1; @p st.volatile.shared.u32 [%0], %1;}" :: "r"(a), "r"(b) : "memory"); }
DEVI void p_stg_rlx64(void* p, uint32_t x, uint32_t y, bool c) {
  asm volatile("{.reg .pred p; .reg .b64 a; setp.ne.u32 p, %3, 0; mov.b64 a, {%1,%2}; @p st.relaxed.gpu.global.b64 [%0], a;}" :: "l"(p), "r"(x), "r"(y), "r"((uint32_t)c) : "memory");
}
DEVI void pin2(uint64_t a, uint64_t b) { pin2((const void*)a, (const void*)b); }
DEVI uint64_t pair(uint32_t a, uint32_t bar) { return a | (uint64_t)bar << 32; }
DEVI void st_async32(uint64_t q, uint32_t x) { st_async32((uint32_t)q, x, (uint32_t)(q >> 32)); }
DEVI void st_async128(uint64_t q, uint4 v) { st_async128((uint32_t)q, v.x, v.y, v.z, v.w, (uint32_t)(q >> 32)); }
DEVI float ex2(float x) { float r; asm("ex2.approx.ftz.f32 %0, %1;" : "=f"(r) : "f"(x)); return r; }
DEVI float rcp(float x) { float r; asm("rcp.approx.ftz.f32 %0, %1;" : "=f"(r) : "f"(x)); return r; }
DEVI uint32_t xor_or(uint32_t a, uint32_t t, uint32_t acc) { uint32_t r; asm("lop3.b32 %0, %1, %2, %3, 0xbe;" : "=r"(r) : "r"(a), "r"(t), "r"(acc)); return r; }
DEVI void stsm2(uint32_t addr, uint32_t r0, uint32_t r1) {
  asm volatile("stmatrix.sync.aligned.m8n8.x2.shared.b16 [%0], {%1,%2};" :: "r"(addr), "r"(r0), "r"(r1) : "memory");
}
DEVI uint32_t settag(uint32_t v, uint32_t tag) { return (v & ~1u) | tag; }

#define A4(c, o)  c(d[o+0]), c(d[o+1]), c(d[o+2]), c(d[o+3])
#define A8(c, o)  A4(c, o), A4(c, o+4)
#define A16(c, o) A8(c, o), A8(c, o+8)
#define A20(c, o) A16(c, o), A4(c, o+16)
#define A32(c, o) A16(c, o), A16(c, o+16)
#define RL8  "{%0,%1,%2,%3,%4,%5,%6,%7}"
#define RL16 "{%0,%1,%2,%3,%4,%5,%6,%7,%8,%9,%10,%11,%12,%13,%14,%15}"
#define RL20 "{%0,%1,%2,%3,%4,%5,%6,%7,%8,%9,%10,%11,%12,%13,%14,%15,%16,%17,%18,%19}"
#define RL32 "{%0,%1,%2,%3,%4,%5,%6,%7,%8,%9,%10,%11,%12,%13,%14,%15,%16,%17,%18,%19,%20,%21,%22,%23,%24,%25,%26,%27,%28,%29,%30,%31}"
#define RL64 "{%0,%1,%2,%3,%4,%5,%6,%7,%8,%9,%10,%11,%12,%13,%14,%15,%16,%17,%18,%19,%20,%21,%22,%23,%24,%25,%26,%27,%28,%29,%30,%31," \
  "%32,%33,%34,%35,%36,%37,%38,%39,%40,%41,%42,%43,%44,%45,%46,%47,%48,%49,%50,%51,%52,%53,%54,%55,%56,%57,%58,%59,%60,%61,%62,%63}"
#define WG_OP(shape) "wgmma.mma_async.sync.aligned." shape "k16.f32.bf16.bf16 "
#define DEF_WGMMA(N, RL, AL, i0, i1, i2, i3, i4, i5, i6)                                                                         \
  template<int SC, int TB, long long CB> DEVI void rs##N(float* d, const uint32_t* a) {                                          \
    if (SC) asm volatile("{.reg .b64 tb; mov.b64 tb, %" #i4 ";\n" WG_OP("m64n" #N) RL ", {%" #i0 ",%" #i1 ",%" #i2 ",%" #i3 "}, tb, 1, 1, 1, %" #i5 ";}" \
      : AL("+f", 0) : "r"(a[0]), "r"(a[1]), "r"(a[2]), "r"(a[3]), "n"(CB), "n"(TB));                                             \
    else asm volatile("{.reg .b64 tb; mov.b64 tb, %" #i4 ";\n" WG_OP("m64n" #N) RL ", {%" #i0 ",%" #i1 ",%" #i2 ",%" #i3 "}, tb, 0, 1, 1, %" #i5 ";}" \
      : AL("=f", 0) : "r"(a[0]), "r"(a[1]), "r"(a[2]), "r"(a[3]), "n"(CB), "n"(TB));                                             \
  }                                                                                                                              \
  template<int SC, int TA, int TB, long long CA, long long CB> DEVI void ss##N(float* d, uint32_t a) {                           \
    if (SC) asm volatile("{.reg .b64 ta, tb; .reg .b32 lo, hi; add.u32 lo, %" #i0 ", %" #i1 "; mov.b32 hi, %" #i2 "; mov.b64 ta, {lo, hi}; mov.b64 tb, %" #i3 ";\n" \
      WG_OP("m64n" #N) RL ", ta, tb, 1, 1, 1, %" #i4 ", %" #i5 ";}"                                                              \
      : AL("+f", 0) : "r"(a), "n"((int)CA), "n"((int)(CA >> 32)), "n"(CB), "n"(TA), "n"(TB));                                    \
    else asm volatile("{.reg .b64 ta, tb; .reg .b32 lo, hi; add.u32 lo, %" #i0 ", %" #i1 "; mov.b32 hi, %" #i2 "; mov.b64 ta, {lo, hi}; mov.b64 tb, %" #i3 ";\n" \
      WG_OP("m64n" #N) RL ", ta, tb, 0, 1, 1, %" #i4 ", %" #i5 ";}"                                                              \
      : AL("=f", 0) : "r"(a), "n"((int)CA), "n"((int)(CA >> 32)), "n"(CB), "n"(TA), "n"(TB));                                    \
  }
DEF_WGMMA(8, "{%0,%1,%2,%3}", A4, 4, 5, 6, 7, 8, 9, 10)
DEF_WGMMA(16, RL8, A8, 8, 9, 10, 11, 12, 13, 14)
DEF_WGMMA(32, RL16, A16, 16, 17, 18, 19, 20, 21, 22)
DEF_WGMMA(40, RL20, A20, 20, 21, 22, 23, 24, 25, 26)
DEF_WGMMA(64, RL32, A32, 32, 33, 34, 35, 36, 37, 38)
template<int TA> DEVI void wgmma_n128(float* d, uint64_t a, uint64_t b, int scale_d) {
  asm volatile("{.reg .pred p; setp.ne.b32 p, %66, 0;\n" WG_OP("m64n128") RL64 ", %64, %65, p, 1, 1, %67, 1;}"
    : A32("+f", 0), A32("+f", 32) : "l"(a), "l"(b), "r"(scale_d), "n"(TA));
}

namespace rec {
constexpr int KR = 43;
constexpr uint32_t WSZ = (64 - KR) * 2048, STG = KR * 2048;
constexpr uint32_t WS = 0;
constexpr uint32_t RING = 2 * WSZ;
constexpr uint32_t OB = RING + 3 * 8192;
constexpr uint32_t PB = OB + 4096;
constexpr uint32_t WO = RING + 32768;
constexpr uint32_t ATT = WO + 5 * 16384;
constexpr uint32_t AK = ATT + 10240, AV = ATT + 20480;
constexpr uint32_t PAD = ATT + 30720;
constexpr uint32_t BARS = PAD + 128;
constexpr uint32_t B_XE = BARS  , B_FA = BARS + 64  , B_FB = BARS + 88, B_FO = BARS + 96;
constexpr uint32_t B_ME = BARS + 104  , B_WE = BARS + 136  ;
constexpr uint32_t B_XF = BARS + 152  , B_MF = BARS + 216  , B_CP = BARS + 248  , B_WT = BARS + 280  ;
constexpr uint32_t B_AB = BARS + 296, B_OB = BARS + 304, B_ST = BARS + 312  , B_WS = BARS + 328, B_WO = BARS + 336, B_PD = BARS + 344, B_AT = BARS + 352, B_AV = BARS + 360;
constexpr int NBAR = 46;
constexpr uint32_t M0 = BARS + 384;
constexpr uint32_t SMEM = 232448;
constexpr int NB_P = 1, NB_ST = 2, NB_O = 3, NB_W0 = 4, NB_W1 = 5, NB_S = 6;
__host__ __device__ constexpr int wo_tile(int rank, int g, int i) { return i < 2 ? i * 6 + rank * 2 + g : 13 + rank - g; }
constexpr long long D_W = CD(WS, 16, 1024, 1), D_X = CD(0, 16, 1024, 1), D_M = CD(RING, 128, 256, 0), D_O = CD(OB, 128, 256, 0);
constexpr long long D_WO = CD(WO, 16, 1024, 1), D_QM = CD(ATT, 640, 0, 0), D_QT = CD(ATT + 128, 640, 64, 0), D_K = CD(AK, 640, 128, 0);
constexpr long long D_V = CD(AV, 128, 640, 0), D_P = CD(PB, 128, 768, 0);
struct Maps { CUtensorMap w[3], wo, xd, xs; };
__host__ __device__ constexpr uint32_t xslot(int s) { return s < 3 ? RING + s * 8192 : s < 5 ? WO + (s - 3) * 8192 : s < 7 ? WO + (s + 1) * 8192 : OB; }
__host__ __device__ constexpr bool k_smem(int k) { return k % 3 == 2; }
__host__ __device__ constexpr int k_idx(int k) { return k % 3 == 2 ? k / 3 : k - k / 3; }
__host__ __device__ constexpr int k_of_reg(int i) { return i + (i >> 1); }
__host__ __device__ constexpr int k_of_smem(int i) { return 3 * i + 2; }

#define RPROF(i)
#define RPROF_STEP
#define CPROF(i, v)

template<int K0, int K1> DEVI void seq_mem(float* d, const uint32_t* w, uint32_t dw) {
  if constexpr (K0 < K1) {
    constexpr long long B = D_M + K0 * 32;
    if constexpr (!k_smem(K0)) rs16<K0 != 0, 1, B>(d, w + 4 * k_idx(K0)); else ss16<1, 1, 1, D_W + k_idx(K0) * 128, B>(d, dw);
    seq_mem<K0 + 1, K1>(d, w, dw);
  }
}
template<bool DUAL, int K0, int K1> DEVI void seq_tok(float* d, const uint32_t* w, uint32_t dw) {
  if constexpr (K0 < K1) {
    constexpr long long B = D_X + (DUAL ? xslot((K0 >> 2) & 7) / 16 : xslot(K0 >> 3) / 16 + ((K0 >> 2) & 1) * 256) + (K0 & 3) * 2;
    if constexpr (DUAL) {
      if constexpr (!k_smem(K0)) rs64<K0 != 0, 0, B>(d, w + 4 * k_idx(K0)); else ss64<1, 1, 0, D_W + k_idx(K0) * 128, B>(d, dw);
    } else {
      if constexpr (!k_smem(K0)) rs32<K0 != 0, 0, B>(d, w + 4 * k_idx(K0)); else ss32<1, 1, 0, D_W + k_idx(K0) * 128, B>(d, dw);
    }
    seq_tok<DUAL, K0 + 1, K1>(d, w, dw);
  }
}
template<int T, int K0> DEVI void seq_wo(float* d, uint32_t dw) {
  if constexpr (K0 < 8) { ss16<K0 != 0, 1, 1, D_WO + T * 1024 + K0 * 128, D_O + K0 * 32>(d, dw); seq_wo<T, K0 + 1>(d, dw); }
}
template<long long Q, int K0> DEVI void seq_s(float* d) {
  if constexpr (K0 < 8) { ss40<K0 != 0, 1, 1, Q + K0 * 80, D_K + K0 * 80>(d, 0); seq_s<Q, K0 + 1>(d); }
}
template<int K0> DEVI void seq_st(float* d) {
  if constexpr (K0 < 8) { ss32<K0 != 0, 1, 1, D_QT + K0 * 80, D_K + 8 + K0 * 80>(d, 0); seq_st<K0 + 1>(d); }
}
template<int K0> DEVI void seq_sm(float* d) {
  if constexpr (K0 < 8) { ss8<K0 != 0, 1, 1, D_QT + K0 * 80, D_K + K0 * 80>(d, 0); seq_sm<K0 + 1>(d); }
}
template<bool DUAL, int J> DEVI void load_x(uint32_t sb, const Maps* M, int t, int rb) {
  if (DUAL) e_tma_3d_mc(sb + xslot(J & 7), &M->xd, J * 64, (t - LAG) * 32, 0, sb + B_XF + (J & 7) * 8, rb);
  else e_tma_3d_mc(sb + xslot(J & 7), &M->xs, 0, (t < NSEG ? t : t - LAG) * 32, J * 2, sb + B_XF + (J & 7) * 8, rb);
}
DEVI void load_x_lent(uint32_t sb, const Maps* M, int t, int j) {
  const bool dual = t >= LAG && t < NSEG;
  const uint32_t dst = sb + (j == 3 ? xslot(3) : xslot(5));
#pragma unroll
  for (int i = 0; i < 2; i++)
    e_tma_3d(dst + i * 8192, dual ? &M->xd : &M->xs, dual ? (j + i) * 64 : 0, (t < LAG ? t : t - LAG) * 32, dual ? 0 : (j + i) * 2, sb + B_XF + (j + i) * 8);
}
struct Ctx { uint32_t sb; const Maps* M; int rb, rank, wi; bool lead; uint32_t par; };
#define PFN 2
#define SPLIT_S 0
#define LATE 1
#define XD 2
template<bool DUAL, int J> DEVI void tok_release(const Ctx& c, int t, int& budget) {
  constexpr int NC = DUAL ? 16 : 8, S = J & 7;
  if constexpr (J + 8 < NC) {
    p_arrive_at(c.sb + B_XE + S * 8, c.rb + J % 3, c.lead);
    p_expect_tx(c.sb + B_XF + S * 8, 8192, c.lead && c.wi == 0);
  } else if constexpr (S < 3 || S == 7) p_arrive(c.sb + B_ME + (S & 3) * 8, c.lead);
  if constexpr (J == XD - 1) {
    if (c.rank == 1 && c.wi == 5) { mbar_wait(c.sb + B_FO, t & 1, budget); load_x<DUAL, 7>(c.sb, c.M, t, c.rb); }
  } else if constexpr (J >= XD && J - XD + 8 < NC) {
    constexpr int I = J - XD;
    if (c.rank == I % 3 && c.wi == (I & 1) * 4 + 1) { mbar_wait(c.sb + B_XE + I * 8, (t - LAG) & 1, budget); load_x<DUAL, I + 8>(c.sb, c.M, t, c.rb); }
  }
}
template<bool DUAL, int J, class F, class G> DEVI bool tok_pass(float* d, const uint32_t* w, uint32_t dw, Ctx& c, int t, int& budget, F after0, G setup) {
  constexpr int NC = DUAL ? 16 : 8, KC = 64 / NC;
  if constexpr (J < NC) {
    if constexpr (J > 1) mbar_wait(c.sb + B_XF + (J & 7) * 8, c.par ^ (J >> 3), budget);
    wg_fence();
    seq_tok<DUAL, J * KC, (J + 1) * KC>(d, w, dw);
    wg_commit();
    if constexpr (J == 1) after0();
    if constexpr (J >= NC - 5 && J < NC - 1) setup(J - (NC - 5));
    if constexpr (J > 0) { wg_wait<1>(); tok_release<DUAL, J - 1>(c, t, budget); }
    return tok_pass<DUAL, J + 1>(d, w, dw, c, t, budget, after0, setup);
  } else {
    const bool ok = mbar_test(c.sb + B_MF, t & 1);
    wg_wait<0>();
    tok_release<DUAL, NC - 1>(c, t, budget);
    if (!DUAL) c.par ^= 1;
    return ok;
  }
}
DEVI void pack_tok(uint32_t* e, const float* d) {
#pragma unroll
  for (int i = 0; i < 8; i++) e[i] = pack_bf16(d[4 * (i & 3) + 2 * (i >> 2)], d[4 * (i & 3) + 2 * (i >> 2) + 1]);
}
DEVI void push_tok(const uint32_t* e, uint32_t sb, uint32_t o, int r, int rank) {
  const uint32_t b = mapa(sb, r);
  st_async128(b + o, e[0], e[1], e[2], e[3], b + (rank == 2 ? B_AV : B_AT));
}
DEVI uint32_t h1_tag(int seg) { return ((seg >> 1) & 1) ^ 1; }
DEVI uint4 pack_part(const float* c, int t) {
  return make_uint4(settag(pack_bf16(c[0], c[1]), h1_tag(t)), pack_bf16(c[2], c[3]), settag(pack_bf16(c[4], c[5]), h1_tag(t - LAG)), pack_bf16(c[6], c[7]));
}
DEVI void put_part(char* p1, char* p2, uint4 z, int t) { p_stg_rlx64(p1, z.x, z.y, t < NSEG); p_stg_rlx64(p2, z.z, z.w, t >= LAG); }

DEVI void rec_math(const uint32_t sb, const int wi, const Maps& M) {
  const int h = cta_id() / 3, rb = cluster_rank() >= 3 ? 3 : 0, rank = cluster_rank() - rb;
  const int warp = wi & 3, wg = wi >> 2;
  const bool lead = (threadIdx.x & 127) == 0;
  int budget = SPIN_BUDGET;
  uint32_t w[4 * KR];
  Ctx cx{sb, &M, rb, rank, wi, lead, 0};
  {
    const int lane = lane_id();
    const uint32_t a = sb + wg * STG + ((lane & 7) + (lane >> 4) * 8) * 128 + (((warp * 2 + ((lane >> 3) & 1)) ^ (lane & 7)) << 4);
    mbar_wait(sb + B_ST + wg * 8, 0, budget);
#pragma unroll
    for (int k = 0; k < KR; k++) ldsm4t(a + k * 2048, w[4*k], w[4*k+1], w[4*k+2], w[4*k+3]);
    nbar_arrive<NB_ST, 384>();
    nbar_sync_r(NB_W0 + wg, 128);
    for (int i = 0; i < 5; i++) p_arrive_at(sb + B_FA + i * 8, rb + (i == 4), lead);
    mbar_wait(sb + B_WS, 0, budget);
  }
  uint4 z = make_uint4(0, 0, 0, 0);
  char *z1 = nullptr, *z2 = nullptr;
  mbar_wait(sb + B_XF, 0, budget); mbar_wait(sb + B_XF + 8, 0, budget);
#pragma unroll 1
  for (int t = 0;; t++) {
    const uint32_t dw = wg * (WSZ >> 4);
    uint32_t e[16];
    bool ok;
    auto finish = [&]() { put_part(z1, z2, z, t - 1); p_arrive_at(sb + B_FO, rb + 1, lead); };
    const int seg = t - rank * LAG;
    const bool att = rank < 2 && (unsigned)seg < (unsigned)NSEG;
    char *p1, *p2;
    uint32_t pw, oo;
    uint64_t u0, u1;
    int lane;
    auto setup = [&](int part) {
      if (part == 0) {
        lane = lane_id();
      } else if (part == 1) {
        char* const p = (char*)g_h1 + ((wo_tile(rank, wg, 0) * 4 + warp) * 4 + (lane >> 3)) * 2048 + h * 64 + (lane & 7) * 8;
        p1 = p + (t & 1) * sizeof(g_h1[0]);
        p2 = p + (2 + ((t - LAG) & 1)) * sizeof(g_h1[0]);
        pin2(p1, p2);
      } else if (part == 2) {
        oo = OB + (lane >> 4) * 2048 + warp * 512 + rank * 256 + (lane & 15) * 16;
        pw = sb + PB + (wg ? lane * 4 : 768 + warp * 768 + lane * 16);
        pin2(pw, oo);
      } else {
        if (wg) {
          const uint32_t ra = mapa(sb, rb + ((warp & 1) ? 2 : (rank ^ 1) & 1)), rc = mapa(sb, rb + ((warp & 1) ? (rank ^ 1) & 1 : 2));
          u0 = pair(ra + oo, ra + B_OB); u1 = pair(rc + oo, rc + B_OB);
        } else {
          u0 = (uint64_t)((char*)(g_ot + rank * O_LAYER) + (size_t)(h * DH + warp * 16 + (lane >> 2)) * (SEQ * 2) + seg * 64 + (lane & 3) * 16);
          u1 = (uint32_t)((lane & 24) + ((lane >> 2) & 1) + 2 * warp - 8 * (lane & 3));
        }
        pin2(u0, u1);
      }
    };
    if (t >= LAG && t < NSEG) {
      float d[32];
      ok = tok_pass<true, 0>(d, w, dw, cx, t, budget, finish, setup);
      pack_tok(e + 8, d); pack_tok(e, d + 16);
    } else {
      float d[16];
      if (t > 0) finish();
      ok = tok_pass<false, 0>(d, w, dw, cx, t, budget, []() {}, setup);
      pack_tok(e, d);
#pragma unroll
      for (int i = 8; i < 16; i++) e[i] = 0;
    }
    RPROF_STEP;
    RPROF(8 + wg * 12 - 32);
    {
      float m[8];
      if (!ok) mbar_wait(sb + B_MF, t & 1, budget);
      wg_fence(); seq_mem<0, 8>(m, w, dw); wg_commit();
      {
        const uint32_t ao = ATT + rank * 10240 + wi * 1280, to = ao + 128 + (lane & 3) * 128 + (lane >> 2) * 16;
        const bool dual = t >= LAG && t < NSEG;
        const int la = dual ? rank == 0 : t >= NSEG;
        RPROF(1 + wg * 12);
        if (dual && rank == 0) {
#pragma unroll
          for (int i = 0; i < 8; i++) { const uint32_t x = e[i]; e[i] = e[8 + i]; e[8 + i] = x; }
        }
        auto piece = [&](int i) { if (i < 2 || dual) push_tok(e + 4 * i, sb, to + (i & 1) * 640, rb + (la ^ (i >> 1)), rank); };
        piece(0);
        wg_fence(); seq_mem<8, 16>(m, w, dw); wg_commit();
        piece(1);
        mbar_wait(sb + B_MF + 8, t & 1, budget);
        wg_fence(); seq_mem<16, 24>(m, w, dw); wg_commit();
        piece(2);
        wg_fence(); seq_mem<24, 32>(m, w, dw); wg_commit();
        piece(3);
        mbar_wait(sb + B_MF + 16, t & 1, budget);
        wg_fence(); seq_mem<32, 48>(m, w, dw); wg_commit();
        wg_wait<1>(); p_arrive(sb + B_PD, lead && wg == 0);
        const uint32_t r0 = mapa(sb, rb + la), r1 = mapa(sb, rb + (la ^ 1)), m0 = r0 + ao + lane * 4, m1 = r1 + ao + lane * 4, ab = rank == 2 ? B_AV : B_AB;
        uint64_t q0 = pair(m0, r0 + ab), q1 = pair(m0 + 640, r0 + ab), q2 = pair(m1, r1 + ab), q3 = pair(m1 + 640, r1 + ab);
        pin2(q0, q1); pin2(q2, q3);
        mbar_wait(sb + B_MF + 24, t & 1, budget);
        wg_fence(); seq_mem<48, 64>(m, w, dw); wg_commit();
        wg_wait<1>(); p_arrive_at(sb + B_FA, rb, lead);
        if (att) { mbar_wait_cluster(sb + B_AT, seg & 1, budget); if (SPLIT_S && wg == 0) fence_proxy_async(); }
        wg_wait<0>();
        const uint32_t a0 = pack_bf16(m[0], m[1]), a1 = pack_bf16(m[2], m[3]), a2 = pack_bf16(m[4], m[5]), a3 = pack_bf16(m[6], m[7]);
        st_async32(q0, la ? a2 : a0); st_async32(q1, la ? a3 : a1);
        if (dual) { st_async32(q2, la ? a0 : a2); st_async32(q3, la ? a1 : a3); }
      }
      RPROF(2 + wg * 12);
      auto wo_ready = [&]() { if (t == 0) mbar_wait(sb + B_WO, 0, budget); if (t < NSTEP - 1) mbar_wait(sb + B_WT, t & 1, budget); };
      constexpr float SC = 0.08838834764831845f * 1.4426950408889634f;
      if (!att) wo_ready();
      else {
        float s[32];
        if (wg) {
          if (SPLIT_S) nbar_arrive<NB_S, 256>();
          uint32_t one[4];
#pragma unroll
          for (int i = 0; i < 4; i++) one[i] = 0x3F803F80u + (pw >> 31);
          mbar_wait_cluster(sb + B_AB, seg & 1, budget);
          fence_proxy_async();
          RPROF(3 + 12);
          wg_fence(); seq_s<D_QM, 0>(s); wg_commit();
          nbar_arrive<NB_P, 256>();
          if (warp == 1) sts32(pw + 640, 0);
          mbar_wait_cluster(sb + B_AV, seg & 1, budget);
          wg_wait<0>();
          float mx = fmaxf(fmaxf(fmaxf(s[0], s[1]), fmaxf(s[4], s[5])), fmaxf(fmaxf(fmaxf(s[8], s[9]), fmaxf(s[12], s[13])), fmaxf(s[16], s[17])));
          const float x1 = __shfl_xor_sync(0xffffffffu, mx, 1), x2 = __shfl_xor_sync(0xffffffffu, mx, 2), x3 = __shfl_xor_sync(0xffffffffu, mx, 3);
          const float u = (warp & 2) ? ((warp & 1) ? s[16] : s[12]) : ((warp & 1) ? s[8] : s[4]);
          const float v = (warp & 2) ? ((warp & 1) ? s[17] : s[13]) : ((warp & 1) ? s[9] : s[5]);
          const float ms = -SC * fmaxf(fmaxf(mx, x1), fmaxf(x2, x3));
          sts32(pw + 128 + warp * 128, pack_bf16(ex2(fmaf(u, SC, ms)), ex2(fmaf(v, SC, ms))));
          if (warp == 0) sts32(pw, pack_bf16(ex2(fmaf(s[0], SC, ms)), ex2(fmaf(s[1], SC, ms))));
          fence_proxy_async();
          nbar_sync<NB_W1, 128>();
          RPROF(4 + 12);
          wg_fence();
          rs8<0, 0, D_P>(s + 8, one); rs8<1, 0, D_P + 16>(s + 8, one); rs8<1, 0, D_P + 32>(s + 8, one);
          wg_commit();
          ss8<0, 0, 0, D_V, D_P>(s, 0); ss8<0, 0, 0, D_V + 320, D_P>(s + 4, 0);
          ss8<1, 0, 0, D_V + 16, D_P + 16>(s, 0); ss8<1, 0, 0, D_V + 336, D_P + 16>(s + 4, 0);
          ss8<1, 0, 0, D_V + 32, D_P + 32>(s, 0); ss8<1, 0, 0, D_V + 352, D_P + 32>(s + 4, 0);
          wg_commit();
          wg_wait<1>();
          const float i0 = rcp(s[8]), i1 = rcp(s[9]);
          wg_wait<0>();
          stsm4(sb + oo, pack_bf16(s[0] * i0, s[1] * i1), pack_bf16(s[2] * i0, s[3] * i1), pack_bf16(s[4] * i0, s[5] * i1), pack_bf16(s[6] * i0, s[7] * i1));
          __syncwarp();
          const uint4 y = lds128v(sb + oo);
          if (t < NSTEP - 1) { st_async128(u0, y); st_async128(u1, y); e_complete_tx(sb + B_OB, 512); }
          wo_ready();
        } else {
          const int lim = (int)u1;
          char* const og = (char*)u0;
          if (SPLIT_S) {
            nbar_sync<NB_S, 256>();
            wg_fence(); seq_st<0>(s + 4); wg_commit();
          }
          nbar_sync<NB_P, 256>();
          RPROF(3);
          wg_fence();
          if (SPLIT_S) seq_sm<0>(s); else seq_s<D_QT, 0>(s);
          wg_commit();
          mbar_wait_cluster(sb + B_AV, seg & 1, budget);
          wg_wait<0>();
#pragma unroll
          for (int i = 0; i < 8; i++) { float& v = s[4 + 4 * (i >> 1) + (i & 1)]; v = i <= lim ? v : -INFINITY; }
          float mx = fmaxf(fmaxf(fmaxf(s[0], s[1]), fmaxf(s[4], s[5])), fmaxf(fmaxf(fmaxf(s[8], s[9]), fmaxf(s[12], s[13])), fmaxf(s[16], s[17])));
          const float x1 = __shfl_xor_sync(0xffffffffu, mx, 1), x2 = __shfl_xor_sync(0xffffffffu, mx, 2), x3 = __shfl_xor_sync(0xffffffffu, mx, 3);
          const float ms = -SC * fmaxf(fmaxf(mx, x1), fmaxf(x2, x3));
#pragma unroll
          for (int i = 0; i < 10; i++) { float& v = s[4 * (i >> 1) + (i & 1)]; v = ex2(fmaf(v, SC, ms)); }
          const float sum = (((s[0] + s[1]) + (s[4] + s[5])) + ((s[8] + s[9]) + (s[12] + s[13]))) + (s[16] + s[17]);
          const float y1 = __shfl_xor_sync(0xffffffffu, sum, 1), y2 = __shfl_xor_sync(0xffffffffu, sum, 2), y3 = __shfl_xor_sync(0xffffffffu, sum, 3);
          const float inv = rcp((sum + y1) + (y2 + y3));
          stsm4(pw, pack_bf16(s[0] * inv, s[1] * inv), pack_bf16(s[4] * inv, s[5] * inv), pack_bf16(s[8] * inv, s[9] * inv), pack_bf16(s[12] * inv, s[13] * inv));
          stsm2(pw + 512, pack_bf16(s[16] * inv, s[17] * inv), 0);
          fence_proxy_async();
          nbar_sync<NB_W0, 128>();
          RPROF(4);
          wg_fence();
          ss32<0, 0, 0, D_V, D_P + 48>(s, 0); ss32<0, 0, 0, D_V + 320, D_P + 48>(s + 16, 0);
          ss32<1, 0, 0, D_V + 16, D_P + 64>(s, 0); ss32<1, 0, 0, D_V + 336, D_P + 64>(s + 16, 0);
          ss32<1, 0, 0, D_V + 32, D_P + 80>(s, 0); ss32<1, 0, 0, D_V + 352, D_P + 80>(s + 16, 0);
          wg_commit();
          wo_ready();
          wg_wait<0>();
#pragma unroll
          for (int i = 0; i < 4; i++) {
            const float* d = s + (i >> 1) * 16 + (i & 1) * 2;
            stg128(og + ((i >> 1) * 64 + (i & 1) * 8) * (SEQ * 2), pack_bf16(d[0], d[1]), pack_bf16(d[4], d[5]), pack_bf16(d[8], d[9]), pack_bf16(d[12], d[13]));
          }
          nbar_arrive<NB_O, 160>();
        }
      }
      RPROF(5 + wg * 12);
      const bool three = wg == 1 || rank == 2;
      if (t < NSTEP - 1) {
        float c[24];
        const uint32_t dt = wg ? 0 : 3072;
        mbar_wait_cluster(sb + B_OB, t & 1, budget);
        fence_proxy_async();
        RPROF(6 + wg * 12);
        wg_fence(); seq_wo<0, 0>(c, dt); wg_commit(); seq_wo<1, 0>(c + 8, dt); wg_commit();
        mbar_wait(sb + B_XF, cx.par, budget);
        wg_wait<1>();
        if (warp == 2) load_x_lent(sb, &M, t + 1, wg ? 3 : 5);
        put_part(p1, p2, pack_part(c, t), t);
        const int o3 = (wo_tile(rank, wg, three ? 2 : 1) - wo_tile(rank, wg, 0)) * 32768;
        z1 = p1 + o3; z2 = p2 + o3;
        if (three) {
          wg_fence(); seq_wo<2, 0>(c + 16, dt); wg_commit();
          wg_wait<1>(); put_part(p1 + 6 * 32768, p2 + 6 * 32768, pack_part(c + 8, t), t);
          mbar_wait(sb + B_XF + 8, cx.par, budget);
          wg_wait<0>(); z = pack_part(c + 16, t);
        } else { mbar_wait(sb + B_XF + 8, cx.par, budget); wg_wait<0>(); z = pack_part(c + 8, t); }
      } else {
        for (int i = 0; i < (three ? 3 : 2); i++) stg_rlx64(p2 + (wo_tile(rank, wg, i) - wo_tile(rank, wg, 0)) * 32768, 0, 0);
        break;
      }
      RPROF(7 + wg * 12);
    }
  }
}

DEVI void wait_xa(const int* p, int& budget) {
  while (__any_sync(0xffffffffu, ldg_acq32(p) < 64) && --budget > 0) {}
  fence_proxy_global();
}
template<bool DUAL> DEVI void first_loads(uint32_t sb, const Maps* M, int n, int h, int rb, int& budget) {
#pragma unroll
  for (int i = 0; i < PFN; i++) {
    if (DUAL) e_prefetch_3d(&M->xd, ((h + i * (16 / PFN)) & 15) * 64, (n - LAG) * 32, 0);
    else e_prefetch_3d(&M->xs, 0, (n < NSEG ? n : n - LAG) * 32, ((h + i * (8 / PFN)) & 7) * 2);
  }
  mbar_wait(sb + B_FA, n & 1, budget);
  load_x<DUAL, 0>(sb, M, n, rb); load_x<DUAL, 1>(sb, M, n, rb); load_x<DUAL, 2>(sb, M, n, rb);
}
template<bool DUAL> DEVI void lent_loads(uint32_t sb, const Maps* M, int n, int rb, int& budget) {
  mbar_wait(sb + B_FB, n & 1, budget);
  load_x<DUAL, 3>(sb, M, n, rb); load_x<DUAL, 4>(sb, M, n, rb); load_x<DUAL, 5>(sb, M, n, rb); load_x<DUAL, 6>(sb, M, n, rb);
}
DEVI void rec_comm(const uint32_t sb, const int warp, const Maps& M, const bf16* __restrict__ mem0) {
  const int lane = threadIdx.x & 31, h = cta_id() / 3, rb = cluster_rank() >= 3 ? 3 : 0, rank = cluster_rank() - rb;
  int budget = SPIN_BUDGET;
  const bool two = warp == 3 || (rank == 2 && warp == 2);
  const int ntask = two ? 2 : 1, qi = two ? (warp == 3 ? rank : 3) : rank * 3 + warp;
  const int task0 = two ? h * 2 + (qi >> 1) : 64 + h * 4 + (qi >> 1);
  auto h2_word = [&](int i, int ln) {
    const int task = task0 + i * 192;
    return (char*)g_h2 + (task >> 2) * 512 + ((qi ^ i) & 1) * 256 + (task & 3) * 32 + (ln & 8) * 16 + (ln & 7) * 4;
  };
  auto first_x = [&](int t) {
    const int n = t + 1;
    p_expect_tx(sb + B_XF + (lane_id() & 7) * 8, 8192, lane_id() < 8);
    if (rank == 0) {
      if (n < NSEG && (n & 3) == 0) wait_xa(&g_xa[0][n >> 2], budget);
      if (n >= LAG && ((n - LAG) & 3) == 0) wait_xa(&g_xa[1][(n - LAG) >> 2], budget);
      if (n >= LAG && n < NSEG) first_loads<true>(sb, &M, n, h, rb, budget); else first_loads<false>(sb, &M, n, h, rb, budget);
    }
  };
  {
    const int task = task0 + (lane >> 4) * 192, L = (task & 3) * 8 + (lane & 7);
    if ((lane >> 4) < ntask) {
      const bf16* p = mem0 + (L & 3) * 2 * DM + (task >> 2) * 16 + (L >> 2) + (lane & 8);
      uint32_t m0 = (uint32_t)__bfloat16_as_ushort(p[0]) | (uint32_t)__bfloat16_as_ushort(p[DM]) << 16;
      m0 = m0 ? m0 : 0x8000u;
      stg_rlx32(h2_word(lane >> 4, lane), m0);
      sts32(sb + M0 + warp * 128 + lane * 4, m0);
    }
    __syncwarp();
    nbar_sync<NB_ST, 384>();
    if (warp == 2) {
      e_expect_tx(sb + B_WS, 2 * WSZ);
#pragma unroll 1
      for (int i = 0; i < 2 * (64 - KR); i++) e_tma_2d(sb + WS + (i & 1) * WSZ + (i >> 1) * 2048, &M.w[rank], h * DH + (i & 1) * 64, k_of_smem(i >> 1) * 16, sb + B_WS);
      const int nt = rank == 2 ? 6 : 5;
      e_expect_tx(sb + B_WO, (nt - 2) * 16384);
#pragma unroll 1
      for (int i = 1; i < nt; i++) if (i != 3) e_tma_2d(sb + WO + i * 16384, &M.wo, wo_tile(rank, 1 - i / 3, i % 3) * 64, h * DH, sb + B_WO);
    }
    if (warp == 3) { first_x(-1); if (rank == 0) lent_loads<false>(sb, &M, 0, rb, budget); }
  }
  uint32_t t0 = gtime() - 4000, cpp = 0;
  const uint32_t cp = sb + B_CP + warp * 8;
#pragma unroll 1
  for (int t = 0;; t++) {
    const int n = t + 1, seg = t - rank * LAG;
    RPROF_STEP;
    const bool att = rank < 2 && (unsigned)seg < (unsigned)NSEG;
    if (warp == 3) {
      if (att) { e_expect_tx(sb + B_AT, 16384); e_expect_tx(sb + B_AB, 4096); e_expect_tx(sb + B_AV, 10240); }
      if (n < NSTEP) e_expect_tx(sb + B_OB, t < NSEG && t >= LAG ? 4096 : 2048);
    }
    {
      const uint32_t dst = sb + RING + warp * 8192;
      mbar_wait(sb + B_ME + warp * 8, t & 1, budget);
      wait_time(t0 + TP(1) + warp * TP(4));
      const int lane = lane_id();
      RPROF(24); CPROF(0, gtime());
      int tries = 0;
      while (true) {
        tries++;
        e_expect_tx(cp, 8192);
        e_bulk_g2s(dst, (const char*)g_h2[t & 3] + warp * 8192, 8192, cp);
        mbar_wait(cp, cpp, budget); cpp ^= 1;
        uint32_t mn = 0xffffffffu;
#pragma unroll
        for (int i = 0; i < 8; i++) mn = min(mn, lds32v(dst + i * 1024 + lane * 32 + (lane >> 2) * 4));
        if (!__any_sync(0xffffffffu, mn == 0) || --budget < 0) break;
      }
      e_arrive(sb + B_MF + warp * 8);
      RPROF(25); CPROF(1, gtime()); CPROF(2, tries);
    }
    {
      const int ln = lane_id(), i = ln >> 4;
      char* const w = h2_word(i, ln);
      if (i < ntask) {
        stg_rlx32(w + ((t + 3) & 3) * sizeof(g_h2[0]), 0);
        if (n < NSTEP && (((qi ^ i) & 1) ? t < LAG : t >= NSEG)) stg_rlx32(w + (n & 3) * sizeof(g_h2[0]), lds32v(sb + M0 + warp * 128 + ln * 4));
      }
      __syncwarp();
    }
    if (n < NSTEP) {
      const uint32_t tag = (n >> 1) & 31;
      mbar_wait(sb + B_PD, t & 1, budget);
      t0 = clock32();
      if (warp == 2) {
        mbar_wait(sb + B_ME + 24, t & 1, budget);
        e_expect_tx(sb + B_WT, 32768);
        e_tma_2d(sb + WO, &M.wo, wo_tile(rank, 1, 0) * 64, h * DH, sb + B_WT);
        e_tma_2d(sb + WO + 49152, &M.wo, wo_tile(rank, 0, 0) * 64, h * DH, sb + B_WT);
      }
      if (warp == 3) first_x(t);
      if (warp == 0 && rank == (t >= NSEG)) { mbar_wait(sb + B_AB, seg & 1, budget); e_stg_rlx32(&g_ts[t & 1][h * TSS], (gtime() & ~31u) | tag); }
      spin_until(t0, TSD);
      uint32_t v;
      do { v = ldg_rlx32(&g_ts[t & 1][lane_id() * TSS]); } while (__any_sync(0xffffffffu, (v & 31) != tag) && --budget > 0);
      const uint32_t now = __shfl_sync(0xffffffffu, v, 0);
      t0 = now + __reduce_max_sync(0xffffffffu, (int)(v - now));
      if (warp == 3) mbar_wait(sb + B_OB, t & 1, budget);
    }
    if (n < NSTEP) {
      RPROF(26); CPROF(3, t0);
#pragma unroll 1
      for (int i = 0; i < ntask; i++) {
        const int layer = (qi ^ i) & 1, sg = t - layer * LAG, task = task0 + i * 192;
        if ((unsigned)sg >= (unsigned)NSEG) continue;
        const uint32_t tag = h1_tag(sg);
        const int ln = lane_id();
        const char* const src = (const char*)g_h1[layer * 2 + (sg & 1)] + task * 2048 + ln * 8;
        char* const dst = h2_word(i, ln) + (n & 3) * sizeof(g_h2[0]);
        uint2 v[8];
        pin2(src, dst);
        wait_time(t0 + TP(0) + (task < 96 ? 0 : task < 192 ? TP(3) : 2 * TP(3)));
        int tries = 0;
        float a[4];
        while (true) {
          tries++;
#pragma unroll
          for (int k = 0; k < 8; k++) v[k] = ldg_rlx64(src + k * 256);
          uint32_t bad = 0;
#pragma unroll
          for (int k = 0; k < 8; k++) {
            bad = xor_or(v[k].x, tag, bad);
            a[0] = k ? a[0] + bf_lo(v[k].x) : bf_lo(v[k].x); a[1] = k ? a[1] + bf_hi(v[k].x) : bf_hi(v[k].x);
            a[2] = k ? a[2] + bf_lo(v[k].y) : bf_lo(v[k].y); a[3] = k ? a[3] + bf_hi(v[k].y) : bf_hi(v[k].y);
          }
#pragma unroll
        for (int k = 0; k < 2; k++) {
          const float keep = (ln & 8) ? a[2+k] : a[k], send = (ln & 8) ? a[k] : a[2+k];
          a[k] = keep + __shfl_xor_sync(0xffffffffu, send, 8);
        }
#pragma unroll
        for (int k = 0; k < 2; k++) a[k] += __shfl_xor_sync(0xffffffffu, a[k], 16);
          if (!__any_sync(0xffffffffu, bad & 1) || --budget < 0) break;
        }
        const uint32_t out = pack_bf16(a[0], a[1]);
        if (ln < 16) stg_rlx32(dst, out ? out : 0x8000u);
        __syncwarp();
        if (i == 0) { RPROF(28); CPROF(6, gtime()); CPROF(4, gtime()); CPROF(5, tries); } else CPROF(7, gtime());
      }
    }
    if (warp == 1 && att) { nbar_sync<NB_O, 160>(); e_flag_add(&g_dep[E_O1 + rank * 16 + (seg >> 2)]); }
    if (n == NSTEP) break;
  }
  if (h == 0 && rank == 0 && warp < 2) g_xa[warp][lane_id()] = 0;
}
}

__global__ void __launch_bounds__(384, 1)
rec_kernel(const __grid_constant__ rec::Maps M, const bf16* __restrict__ mem0) {
  using namespace rec;
  extern __shared__ __align__(1024) uint8_t smem[];
  const uint32_t sb = __shfl_sync(0xffffffffu, smem_u32(smem), 0);
  const int tid = threadIdx.x, wi = __shfl_sync(0xffffffffu, tid >> 5, 0);
  if ((sb & 0x3FFFF) != SMEM_BASE) __trap();
  if (wi == 0) {
    const int h = cta_id() / 3, rank = cta_id() - h * 3;
    for (int i = tid; i < NBAR; i += 32) mbar_init(sb + BARS + i * 8, i < 13 ? 6 : i < 19 ? 2 : 1);
    ((uint32_t*)(smem + PAD))[tid] = 0;
    fence_mbar_init(); fence_proxy_async();
    __syncwarp();
    e_expect_tx(sb + B_ST, STG); e_expect_tx(sb + B_ST + 8, STG);
    for (int i = 0; i < 2 * KR; i++) e_tma_2d(sb + (i & 1) * STG + (i >> 1) * 2048, &M.w[rank], h * DH + (i & 1) * 64, k_of_reg(i >> 1) * 16, sb + B_ST + (i & 1) * 8);
  } else if (wi == 1) {
    if (blockIdx.x < NEV / 32) { g_dep[blockIdx.x * 32 + (tid & 31)] = 0; g_claim[blockIdx.x * 32 + (tid & 31)] = 0; __threadfence(); }
    __syncwarp();
    asm volatile("griddepcontrol.launch_dependents;" ::: "memory");
  }
  cluster_arrive(); cluster_wait();
  if (wi < 8) { reg_inc<232>(); rec_math(sb, wi, M); cluster_arrive(); cluster_wait(); }
  else { reg_dec<40>(); rec_comm(sb, wi & 3, M, mem0); cluster_arrive(); cluster_wait(); }
}

namespace gm {
struct Maps { CUtensorMap ot, wo, xn, wg, wu, hl, hs, wd, out; };
constexpr int STAGES = 6, STAGE = 32768;
constexpr uint32_t SO = STAGES * STAGE, BARS = SO + 32768;
constexpr uint32_t B_FULL = BARS, B_EMPTY = BARS + 48, B_TF = BARS + 96, B_TE = BARS + 112, B_ORD = BARS + 128, B_PM = BARS + 144, B_GO = BARS + 160;
constexpr uint32_t MAIL = BARS + 176, PMAIL = BARS + 192;
constexpr uint32_t SMEM = BARS + 256;
constexpr int END = -1;

struct Tile {
  bool isO, isG, l2; int blk, col, k0, n;
  DEVI Tile(int task, int rank) {
    const int e = task >> 8, id = task & 255;
    const bool isD = e < E_G1 || e >= E_D2;
    isO = e >= E_O1 && e < E_G2; isG = !isD && !isO; l2 = e >= E_O2;
    blk = isG && l2 ? (e & 15) * 2 + rank : isD && !l2 ? e >> 1 : e & 15;
    col = isG ? (l2 ? id : id * 2 + rank) : (id & 3) * 2 + rank;
    k0 = isO ? (id >> 2) * 2048 : isG ? 0 : ((l2 ? e >> 4 : e) & 1) * 1792;
    n = isO ? 32 : isG ? 16 : 28;
  }
};

DEVI float geglu(float g, float u) {
  const float z = g * (0.7978845608028654f + 0.035677408136300125f * g * g);
  float t; asm("tanh.approx.f32 %0, %1;" : "=f"(t) : "f"(z));
  const float hg = 0.5f * g;
  return fmaf(hg, t, hg) * u;
}
struct Sched {
  int need, size;
  bool filler;
  uint4 dep, cl;
  DEVI void init(int lane) {
    const int e = lane * 4;
    const bool d = e < E_G1 || e >= E_D2, o = e >= E_O1 && e < E_G2;
    need = d ? 28 : e < E_O1 ? 64 : 128;
    size = d ? 4 : o ? 8 : e < E_O1 ? 28 : e < E_G2 + 8 ? 56 : 0;
    filler = (int)blockIdx.x < TP(5);
  }
  DEVI void scan(int lane) { cl = ldg_rlx128(g_claim + lane * 4); dep = ldg_rlx128(g_dep + lane * 4); }
  DEVI int next(int lane, int& budget) {
    while (--budget > 0) {
      int av[4], open = 0;
#pragma unroll
      for (int i = 0; i < 4; i++) { const int r = max(size - (int)(&cl.x)[i], 0); open |= r; av[i] = ((int)(&dep.x)[i] >= need ? r : 0) + (i ? av[i - 1] : 0); }
      const uint32_t mo = __ballot_sync(0xffffffffu, open);
      if (!mo) break;
      if (filler) {
        const int x = TP(6) & 3, dx = x == 0 ? dep.x : x == 1 ? dep.y : x == 2 ? dep.z : dep.w;
        filler = !__any_sync(0xffffffffu, lane == (E_O1 + TP(6)) >> 2 && dx >= need);
      }
      if (!filler && (mo & 0xffff) && lane >= E_O2 / 4) av[3] = 0;
      int inc = av[3], pos = 0;
      while (true) {
        const uint32_t m = __ballot_sync(0xffffffffu, inc > pos && av[3]);
        if (!m) break;
        const int l = __ffs(m) - 1, rel = pos - (inc - av[3]), i = (rel >= av[0]) + (rel >= av[1]) + (rel >= av[2]);
        int r = 0;
        if (lane == l) {
          const int tk = atomicAdd(g_claim + lane * 4 + i, 1);
          r = tk < size ? (lane * 4 + i) << 8 | tk : -1 - (inc - av[3] + (i == 0 ? av[0] : i == 1 ? av[1] : i == 2 ? av[2] : av[3]) + tk - size);
        }
        r = __shfl_sync(0xffffffffu, r, l);
        if (r >= 0) return r;
        if (pos == 0) {
#pragma unroll
          for (int o = 1; o < 32; o <<= 1) { const int v = __shfl_up_sync(0xffffffffu, inc, o); if (lane >= o) inc += v; }
        }
        pos = -1 - r;
      }
      if (pos == 0) __nanosleep(TP(7));
      scan(lane);
    }
    return END;
  }
};

DEVI void scheduler(const uint32_t sb) {
  const int lane = threadIdx.x & 31;
  int budget = SPIN_BUDGET;
  Sched sc; sc.init(lane);
#pragma unroll 1
  for (int i = 0;; i++) {
    mbar_wait(sb + B_GO, (i & 1) ^ 1, budget);
    sc.scan(lane);
    const int task = sc.next(lane, budget);
    const uint32_t r = mapa(sb, lane & 1);
    if (lane < 2) st_async32(r + PMAIL + (i & 1) * 4, task, r + B_PM + (i & 1) * 8);
    __syncwarp();
    if (task == END) break;
  }
}

DEVI void producer(const uint32_t sb, const Maps& M) {
  const int lane = threadIdx.x & 31, rank = cluster_rank();
  int budget = SPIN_BUDGET, s = 0, ph = 0;
#pragma unroll 1
  for (int i = 0;; i++) {
    e_expect_tx(sb + B_PM + (i & 1) * 8, 4);
    mbar_wait_cluster(sb + B_PM + (i & 1) * 8, (i >> 1) & 1, budget);
    const int task = budget < 0 ? END : __shfl_sync(0xffffffffu, (int)lds32v(sb + PMAIL + (i & 1) * 4), 0);
    fence_proxy_global();
    for (int z = 0; z < (task == END ? 2 : 1); z++) {
      const int g = (i + z) & 1;
      mbar_wait(sb + B_TE + g * 8, (((i + z) >> 1) & 1) ^ 1, budget);
      if (lane == 0) { sts64(sb + MAIL + g * 8, task, s | ph << 8); mbar_arrive(sb + B_TF + g * 8); }
      __syncwarp();
    }
    if (task == END) break;
    const Tile T(task, rank);
    const bool shareB = T.isG && T.l2;
    const CUtensorMap* mA = T.isO ? &M.ot : T.isG ? &M.xn : &M.hl;
    const CUtensorMap* mB0 = T.isO ? &M.wo : T.isG ? &M.wg : &M.wd;
    const CUtensorMap* mB1 = T.isG ? &M.wu : mB0;
    const int c0 = T.col * (T.isG ? 64 : 128), c1 = T.isG ? c0 : c0 + 64, row = T.blk * 128;
    const int ok = 0;
    int k = T.k0;
#pragma unroll 1
    for (int it = 0; it < T.n; it++, k += 64) {
      const uint32_t a = sb + s * STAGE, fb = sb + B_FULL + s * 8;
      mbar_wait(sb + B_EMPTY + s * 8, ph ^ 1, budget);
      e_expect_tx(fb, STAGE);
      if (shareB) {
        e_tma_2d_mc(a + 16384 + rank * 8192, rank ? mB1 : mB0, c0, k, fb);
        e_tma_2d(a, mA, k, row, fb); e_tma_2d(a + 8192, mA, k, row + 64, fb);
      } else {
        e_tma_2d_mc(a + rank * 8192, mA, T.isO ? row + rank * 64 : k, T.isO ? k + ok : row + rank * 64, fb);
        e_tma_2d(a + 16384, mB0, c0, k, fb); e_tma_2d(a + 24576, mB1, c1, k, fb);
      }
      if (it == T.n - TP(2)) e_arrive(sb + B_GO);
      if (++s == STAGES) { s = 0; ph ^= 1; }
    }
  }
}

template<int TA> DEVI void mainloop(float* d0, float* d1, uint32_t sb, int n, int s, int ph, bool lead, uint32_t ord, int& budget) {
  int prev = 0;
  const uint32_t rel = threadIdx.x & 127;
#pragma unroll 1
  for (int i = 0; i < n; i++) {
    mbar_wait(sb + B_FULL + s * 8, ph, budget);
    const uint32_t a = sb + s * STAGE;
    const uint64_t da = mkdesc(a, 16, 1024), db = mkdesc(a + 16384, 8192, 1024);
    wg_fence();
#pragma unroll
    for (int k = 0; k < 4; k++) {
      wgmma_n128<TA>(d0, da + k * (TA ? 128 : 2), db + k * 128, (i | k) != 0);
      wgmma_n128<TA>(d1, da + 512 + k * (TA ? 128 : 2), db + k * 128, (i | k) != 0);
    }
    wg_commit();
    if (i > 0) { wg_wait<1>(); p_arrive_at(sb + B_EMPTY + prev * 8, rel & 1, rel < 2); }
    prev = s;
    if (++s == STAGES) { s = 0; ph ^= 1; }
  }
  p_arrive(ord, lead);
  wg_wait<0>();
  p_arrive_at(sb + B_EMPTY + prev * 8, rel & 1, rel < 2);
}

DEVI void consumer(const uint32_t sb, const Maps& M, const int wg) {
  const int tid = threadIdx.x, lane = tid & 31, warp = (tid >> 5) & 3;
  const bool lead = (tid & 127) == 0;
  const uint32_t so = sb + SO + wg * 16384;
  int budget = SPIN_BUDGET;
  float d0[64], d1[64];
#pragma unroll 1
  for (int m = 0;; m++) {
    mbar_wait(sb + B_TF + wg * 8, m & 1, budget);
    const uint2 mail = lds64v(sb + MAIL + wg * 8);
    const int task = __shfl_sync(0xffffffffu, (int)mail.x, 0), pos = __shfl_sync(0xffffffffu, (int)mail.y, 0);
    e_arrive(sb + B_TE + wg * 8);
    if (task == END || budget < 0) break;
    const Tile T(task, cluster_rank());
    mbar_wait(sb + B_ORD + wg * 8, (m & 1) ^ wg ^ 1, budget);
    if (T.isO) mainloop<1>(d0, d1, sb, 32, pos & 255, pos >> 8, lead, sb + B_ORD + (wg ^ 1) * 8, budget);
    else mainloop<0>(d0, d1, sb, T.n, pos & 255, pos >> 8, lead, sb + B_ORD + (wg ^ 1) * 8, budget);
    const uint32_t st = so + (warp * 16 + (lane & 15)) * 128;
    if (T.isG) {
#pragma unroll
      for (int mm = 0; mm < 2; mm++) {
        const float* d = mm ? d1 : d0;
#pragma unroll
        for (int c = 0; c < 4; c++) {
          uint32_t r[4];
#pragma unroll
          for (int i = 0; i < 4; i++) r[i] = pack_bf16(geglu(d[8*c+2*i], d[32+8*c+2*i]), geglu(d[8*c+2*i+1], d[33+8*c+2*i]));
          stsm4(st + mm * 8192 + (((2 * c + (lane >> 4)) ^ (lane & 7)) << 4), r[0], r[1], r[2], r[3]);
        }
      }
      fence_proxy_async();
      nbar_sync_r(1 + wg, 128);
      if (lead) {
        tma_store_2d(&M.hs, so, T.col * 64, T.blk * 128);
        bulk_commit(); bulk_wait<0>();
        flag_add(&g_dep[T.l2 ? E_D2 + (T.col >= 28) * 16 + T.blk : E_D1 + T.blk * 2 + (T.col >= 28)]);
      }
    } else {
#pragma unroll
      for (int hf = 0; hf < 2; hf++) {
        if (hf) { if (lead) bulk_wait_read<0>(); nbar_sync_r(1 + wg, 128); }
#pragma unroll
        for (int mm = 0; mm < 2; mm++) {
          const float* d = (mm ? d1 : d0) + hf * 32;
#pragma unroll
          for (int c = 0; c < 4; c++)
            stsm4(st + mm * 8192 + (((2 * c + (lane >> 4)) ^ (lane & 7)) << 4), pack_bf16(d[8*c], d[8*c+1]), pack_bf16(d[8*c+2], d[8*c+3]),
                  pack_bf16(d[8*c+4], d[8*c+5]), pack_bf16(d[8*c+6], d[8*c+7]));
        }
        fence_proxy_async();
        nbar_sync_r(1 + wg, 128);
        if (lead) { tma_radd_2d(&M.out, so, T.col * 128 + hf * 64, T.blk * 128); bulk_commit(); }
      }
      if (lead) {
        bulk_wait<0>();
        if (T.isO || !T.l2) flag_add(&g_dep[(!T.isO ? E_LX2 : T.l2 ? E_LX1B : E_LX1A) + T.blk]);
      }
    }
    __syncwarp();
  }
}

DEVI void norm_helper(const bf16* __restrict__ x, bf16* out) {
  const int lane = threadIdx.x & 31;
  int budget = SPIN_BUDGET, tk = lane < 4 ? -1 : 1024;
#pragma unroll 1
  while (--budget > 0) {
    if (tk < 0) tk = atomicAdd(g_claim + E_LI + lane, 1);
    if (__all_sync(0xffffffffu, tk >= 1024)) break;
    const uint32_t m = __ballot_sync(0xffffffffu, tk < 1024 && (lane == 0 || ldg_acq32(g_dep + E_LI + lane * 16 + (tk >> 6)) >= 16));
    if (!m) { __nanosleep(TP(7)); continue; }
    const int ql = __ffs(m) - 1, task = __shfl_sync(0xffffffffu, tk, ql), q = E_LI + ql * 16, ev = task >> 6;
    if (lane == ql) tk = -1;
    const size_t off = (size_t)task * (DM * 4) + lane * 16;
    const char* src = (const char*)(q == E_LI ? x : out) + off;
    uint4 u[8];
#pragma unroll
    for (int i = 0; i < 8; i++) u[i] = ldg_rlx128(src + i * 512);
    if (q == E_LI) {
#pragma unroll
      for (int i = 0; i < 8; i++) stg128((char*)out + off + i * 512, u[i].x, u[i].y, u[i].z, u[i].w);
    }
    float mean[2], rs[2];
#pragma unroll
    for (int r = 0; r < 2; r++) {
      float s0 = 0, s1 = 0;
#pragma unroll
      for (int i = 0; i < 16; i++) { const uint32_t v = (&u[4*r + (i >> 2)].x)[i & 3]; s0 += bf_lo(v); s1 += bf_hi(v); }
      mean[r] = (s0 + s1) * (1.f / 32);
      s0 = s1 = 0;
#pragma unroll
      for (int i = 0; i < 16; i++) { const uint32_t v = (&u[4*r + (i >> 2)].x)[i & 3]; const float a = bf_lo(v) - mean[r], b = bf_hi(v) - mean[r]; s0 = fmaf(a, a, s0); s1 = fmaf(b, b, s1); }
      rs[r] = s0 + s1;
    }
    {
      const bool hi = lane & 16;
      float m1 = hi ? mean[1] : mean[0], q1 = hi ? rs[1] : rs[0], m2 = hi ? mean[0] : mean[1], q2 = hi ? rs[0] : rs[1], cnt = 16;
#pragma unroll
      for (int o = 16; o; o >>= 1) {
        m2 = __shfl_xor_sync(0xffffffffu, m2, o); q2 = __shfl_xor_sync(0xffffffffu, q2, o);
        const float dl = m1 - m2;
        q2 = q1 = fmaf(dl * dl, cnt, q1 + q2); m2 = m1 = 0.5f * (m1 + m2);
        cnt *= 2;
      }
      q1 = rsqrtf(q1 * (1.f / DM) + 1e-5f);
      m2 = __shfl_xor_sync(0xffffffffu, m1, 16); q2 = __shfl_xor_sync(0xffffffffu, q1, 16);
      mean[0] = hi ? m2 : m1; mean[1] = hi ? m1 : m2; rs[0] = hi ? q2 : q1; rs[1] = hi ? q1 : q2;
    }
#pragma unroll
    for (int i = 0; i < 8; i++) {
      uint32_t y[4];
#pragma unroll
      for (int c = 0; c < 4; c++) { const uint32_t v = (&u[i].x)[c]; y[c] = pack_bf16((bf_lo(v) - mean[i >> 2]) * rs[i >> 2], (bf_hi(v) - mean[i >> 2]) * rs[i >> 2]); }
      stg128((char*)g_xn + off + i * 512, y[0], y[1], y[2], y[3]);
    }
    fence_proxy_global();
    __syncwarp();
    if (lane == 0) flag_add(q == E_LI ? &g_xa[0][ev] : q == E_LX2 ? &g_xa[1][ev] : &g_dep[q == E_LX1A ? E_G1 + ev : E_G2 + (ev >> 1)]);
    __syncwarp();
  }
}
}

__global__ void __cluster_dims__(2, 1, 1) __launch_bounds__(384, 1)
gemm_kernel(const __grid_constant__ gm::Maps M, const bf16* __restrict__ x, bf16* out) {
  using namespace gm;
  extern __shared__ __align__(1024) uint8_t smem[];
  const uint32_t sb = __shfl_sync(0xffffffffu, smem_u32(smem), 0);
  const int tid = threadIdx.x, wi = __shfl_sync(0xffffffffu, tid >> 5, 0);
  if (tid < 21) mbar_init(sb + BARS + tid * 8, tid == 14 || tid == 15 ? 4 : tid >= 6 && tid < 12 ? 2 : 1);
  fence_mbar_init();
  cluster_arrive(); cluster_wait();
  if (wi < 8) { reg_inc<208>(); consumer(sb, M, wi >> 2); cluster_arrive(); cluster_wait(); }
  else {
    reg_dec<88>();
    if (wi == 8) producer(sb, M);
    else if (wi == 11 && cluster_rank() == 0) scheduler(sb);
    else {
      norm_helper(x, out);
      asm volatile("griddepcontrol.wait;" ::: "memory");
      if (wi == 9 && blockIdx.x < 64) g_h2[(NSTEP - 1) & 3][blockIdx.x * 32 + (tid & 31)] = make_uint4(0, 0, 0, 0);
    }
    __syncwarp();
    cluster_arrive(); cluster_wait();
  }
}

typedef CUresult (*PFN_encodeTiled)(CUtensorMap*, CUtensorMapDataType, cuuint32_t, void*, const cuuint64_t*, const cuuint64_t*,
                                    const cuuint32_t*, const cuuint32_t*, CUtensorMapInterleave, CUtensorMapSwizzle,
                                    CUtensorMapL2promotion, CUtensorMapFloatOOBfill);
static PFN_encodeTiled g_encode = nullptr;
static CUtensorMap make_map(const void* ptr, uint64_t rows, uint64_t cols, uint32_t box_rows) {
  CUtensorMap m;
  cuuint64_t dims[2] = {cols, rows}, strides[1] = {cols * 2};
  cuuint32_t box[2] = {64, box_rows}, es[2] = {1, 1};
  g_encode(&m, CU_TENSOR_MAP_DATA_TYPE_BFLOAT16, 2, (void*)ptr, dims, strides, box, es, CU_TENSOR_MAP_INTERLEAVE_NONE,
           CU_TENSOR_MAP_SWIZZLE_128B, CU_TENSOR_MAP_L2_PROMOTION_L2_256B, CU_TENSOR_MAP_FLOAT_OOB_FILL_NONE);
  return m;
}

static CUtensorMap make_map3(const void* ptr, uint64_t d0, uint64_t d1, uint64_t d2, uint64_t stride2) {
  CUtensorMap m;
  cuuint64_t dims[3] = {d0, d1, d2}, strides[2] = {DM * 2, stride2};
  cuuint32_t box[3] = {64, 32, 2}, es[3] = {1, 1, 1};
  g_encode(&m, CU_TENSOR_MAP_DATA_TYPE_BFLOAT16, 3, (void*)ptr, dims, strides, box, es, CU_TENSOR_MAP_INTERLEAVE_NONE,
           CU_TENSOR_MAP_SWIZZLE_128B, CU_TENSOR_MAP_L2_PROMOTION_L2_256B, CU_TENSOR_MAP_FLOAT_OOB_FILL_NONE);
  return m;
}

extern "C" void kernel_launch(void* const* d_in, const int* in_sizes, int n_in, void* d_out, int out_size) {
  const bf16* x = (const bf16*)d_in[0];
  const bf16* mem0 = (const bf16*)d_in[1];
  if (!g_encode) {
    void* p = nullptr; cudaDriverEntryPointQueryResult q;
    cudaGetDriverEntryPoint("cuTensorMapEncodeTiled", &p, cudaEnableDefault, &q);
    g_encode = (PFN_encodeTiled)p;
    cudaFuncSetAttribute(gemm_kernel, cudaFuncAttributeMaxDynamicSharedMemorySize, gm::SMEM);
    cudaFuncSetAttribute(rec_kernel, cudaFuncAttributeMaxDynamicSharedMemorySize, rec::SMEM);
  }
  bf16 *xn, *ot, *hh;
  cudaGetSymbolAddress((void**)&xn, g_xn); cudaGetSymbolAddress((void**)&ot, g_ot); cudaGetSymbolAddress((void**)&hh, g_h);
  rec::Maps R;
  for (int i = 0; i < 3; i++) R.w[i] = make_map(d_in[2 + i], DM, NH * DH, 16);
  R.wo = make_map(d_in[5], NH * DH, DM, 128);
  R.xd = make_map3(xn, DM, SEQ - LAG * 32, 2, (uint64_t)LAG * 32 * DM * 2); R.xs = make_map3(xn, 64, SEQ, DM / 64, 128);
  gm::Maps G;
  G.ot = make_map(ot, NH * DH + O_LAYER / SEQ, SEQ, 64); G.wo = make_map(d_in[5], NH * DH, DM, 64); G.xn = make_map(xn, SEQ, DM, 64);
  G.wg = make_map(d_in[8], DM, DF, 64); G.wu = make_map(d_in[9], DM, DF, 64); G.hl = make_map(hh, SEQ, DF, 64); G.hs = make_map(hh, SEQ, DF, 128);
  G.wd = make_map(d_in[10], DF, DM, 64); G.out = make_map(d_out, SEQ, DM, 128);
  cudaLaunchConfig_t cfg = {};
  cudaLaunchAttribute at[1];
  cfg.attrs = at; cfg.numAttrs = 1;
  cfg.gridDim = dim3(3 * NH); cfg.blockDim = dim3(384); cfg.dynamicSmemBytes = rec::SMEM; cfg.stream = cudaStreamPerThread;
  at[0].id = cudaLaunchAttributeClusterDimension; at[0].val.clusterDim.y = at[0].val.clusterDim.z = 1;
  static int csize = 0;
  if (!csize) {
    int n = 0;
    at[0].val.clusterDim.x = 6;
    csize = cudaOccupancyMaxActiveClusters(&n, rec_kernel, &cfg) == cudaSuccess && n >= NH / 2 ? CSIZE : 3;
  }
  at[0].val.clusterDim.x = csize;
  cudaLaunchKernelEx(&cfg, rec_kernel, R, mem0);
  cfg.gridDim = dim3(132); cfg.blockDim = dim3(384); cfg.dynamicSmemBytes = gm::SMEM; cfg.stream = cudaStreamPerThread;
  at[0].id = cudaLaunchAttributeProgrammaticStreamSerialization; at[0].val.programmaticStreamSerializationAllowed = 1;
  cudaLaunchKernelEx(&cfg, gemm_kernel, G, x, (bf16*)d_out);
}
```

```cpp
#include <cuda_runtime.h>
#include <cuda_bf16.h>
#include <cuda.h>
#include <stdint.h>

#define DEVI __device__ __forceinline__
typedef __nv_bfloat16 bf16;

constexpr int SEQ = 2048, DM = 1024, NH = 32, DH = 128, DF = 3584, NSEG = 64;
#define LAG 18
constexpr int NSTEP = NSEG + LAG;

#define CSIZE 6
#define TSS 1
#define TSD 1900
constexpr size_t O_LAYER = 0;
__device__ __align__(1024) bf16 g_xn[SEQ * DM];
__device__ __align__(1024) bf16 g_ot[SEQ * NH * DH + O_LAYER];
__device__ __align__(1024) bf16 g_h[SEQ * DF];
__device__ __align__(1024) uint32_t g_xr[NSEG][DM * 4];
__device__ __align__(1024) uint2 g_h1[4][256 * 256];
__device__ __align__(1024) uint4 g_h2[4][2048];
__device__ __align__(128) uint32_t g_ts[2][32 * TSS];
enum { E_D1 = 0, E_G1 = 32, E_O1 = 48, E_O2 = 64, E_G2 = 80, E_D2 = 96,
       E_LI = 128, E_LX2 = 144, E_LX1A = 160, E_LX1B = 176, NEV = 256 };
__device__ __align__(128) int g_dep[NEV];
__device__ __align__(128) int g_claim[NEV];
__device__ __align__(128) int g_xa[2][32];

#define TUNE_DEFAULTS 1550, 2250, 5, 100, 100, 16, 12, 100
constexpr int c_D[8] = {TUNE_DEFAULTS};
template<int I> struct TPV { static constexpr int v = c_D[I]; };
#define TP(i) TPV<i>::v

DEVI uint32_t smem_u32(const void* p) { return (uint32_t)__cvta_generic_to_shared(p); }
DEVI void mbar_init(uint32_t bar, uint32_t cnt) { asm volatile("mbarrier.init.shared::cta.b64 [%0], %1;" :: "r"(bar), "r"(cnt) : "memory"); }
DEVI void mbar_arrive(uint32_t bar) { asm volatile("mbarrier.arrive.shared::cta.b64 _, [%0];" :: "r"(bar) : "memory"); }
DEVI bool mbar_try(uint32_t bar, uint32_t parity) {
  uint32_t p;
  asm volatile("{.reg .pred p; mbarrier.try_wait.parity.shared::cta.b64 p, [%1], %2; selp.u32 %0, 1, 0, p;}" : "=r"(p) : "r"(bar), "r"(parity) : "memory");
  return p;
}
DEVI bool mbar_test(uint32_t bar, uint32_t parity) {
  uint32_t p;
  asm volatile("{.reg .pred p; mbarrier.test_wait.parity.shared::cta.b64 p, [%1], %2; selp.u32 %0, 1, 0, p;}" : "=r"(p) : "r"(bar), "r"(parity) : "memory");
  return p;
}
constexpr int SPIN_BUDGET = 1 << 18;
DEVI void mbar_wait(uint32_t bar, uint32_t parity, int& budget) {
  while (!mbar_try(bar, parity)) { if (--budget < 0) break; }
}
DEVI bool mbar_try_cluster(uint32_t bar, uint32_t parity) {
  uint32_t p;
  asm volatile("{.reg .pred p; mbarrier.try_wait.parity.acquire.cluster.shared::cta.b64 p, [%1], %2; selp.u32 %0, 1, 0, p;}" : "=r"(p) : "r"(bar), "r"(parity) : "memory");
  return p;
}
DEVI void mbar_wait_cluster(uint32_t bar, uint32_t parity, int& budget) {
  while (!mbar_try_cluster(bar, parity)) { if (--budget < 0) break; }
}
DEVI uint32_t mapa(uint32_t addr, uint32_t rank) { uint32_t r; asm("mapa.shared::cluster.u32 %0, %1, %2;" : "=r"(r) : "r"(addr), "r"(rank)); return r; }
DEVI void cluster_arrive() { asm volatile("barrier.cluster.arrive.release.aligned;" ::: "memory"); }
DEVI void cluster_wait() { asm volatile("barrier.cluster.wait.acquire.aligned;" ::: "memory"); }
DEVI void fence_mbar_init() { asm volatile("fence.mbarrier_init.release.cluster;" ::: "memory"); }
DEVI void fence_proxy_async() { asm volatile("fence.proxy.async.shared::cta;" ::: "memory"); }
DEVI void fence_proxy_global() { asm volatile("fence.proxy.async.global;" ::: "memory"); }
#define ELECT "{.reg .pred p; elect.sync _|p, 0xffffffff;\n @p "
DEVI void e_expect_tx(uint32_t bar, uint32_t bytes) { asm volatile(ELECT "mbarrier.arrive.expect_tx.shared::cta.b64 _, [%0], %1;}" :: "r"(bar), "r"(bytes) : "memory"); }
DEVI void e_complete_tx(uint32_t bar, uint32_t bytes) { asm volatile("fence.acq_rel.cta;\n" ELECT "mbarrier.complete_tx.relaxed.cta.shared::cta.b64 [%0], %1;}" :: "r"(bar), "r"(bytes) : "memory"); }
DEVI void e_arrive(uint32_t bar) { asm volatile(ELECT "mbarrier.arrive.shared::cta.b64 _, [%0];}" :: "r"(bar) : "memory"); }
DEVI void e_tma_2d(uint32_t dst, const CUtensorMap* m, int c0, int c1, uint32_t bar) {
  asm volatile(ELECT "cp.async.bulk.tensor.2d.shared::cluster.global.mbarrier::complete_tx::bytes [%0], [%1, {%3, %4}], [%2];}"
    :: "r"(dst), "l"(m), "r"(bar), "r"(c0), "r"(c1) : "memory");
}
DEVI void e_prefetch_2d(const CUtensorMap* m, int c0, int c1) {
  asm volatile(ELECT "cp.async.bulk.prefetch.tensor.2d.L2.global [%0, {%1, %2}];}" :: "l"(m), "r"(c0), "r"(c1) : "memory");
}
DEVI void e_prefetch_3d(const CUtensorMap* m, int c0, int c1, int c2) {
  asm volatile(ELECT "cp.async.bulk.prefetch.tensor.3d.L2.global [%0, {%1, %2, %3}];}" :: "l"(m), "r"(c0), "r"(c1), "r"(c2) : "memory");
}
DEVI void e_bulk_g2s(uint32_t dst, const void* src, uint32_t bytes, uint32_t bar) {
  asm volatile(ELECT "cp.async.bulk.shared::cluster.global.mbarrier::complete_tx::bytes [%0], [%1], %2, [%3];}" :: "r"(dst), "l"(src), "r"(bytes), "r"(bar) : "memory");
}
DEVI void e_tma_3d(uint32_t dst, const CUtensorMap* m, int c0, int c1, int c2, uint32_t bar) {
  asm volatile(ELECT "cp.async.bulk.tensor.3d.shared::cluster.global.mbarrier::complete_tx::bytes [%0], [%1, {%3, %4, %5}], [%2];}"
    :: "r"(dst), "l"(m), "r"(bar), "r"(c0), "r"(c1), "r"(c2) : "memory");
}
DEVI void e_tma_3d_mc(uint32_t dst, const CUtensorMap* m, int c0, int c1, int c2, uint32_t bar, int rb) {
  asm volatile(ELECT "cp.async.bulk.tensor.3d.shared::cluster.global.mbarrier::complete_tx::bytes.multicast::cluster [%0], [%1, {%3, %4, %5}], [%2], %6;}"
    :: "r"(dst), "l"(m), "r"(bar), "r"(c0), "r"(c1), "r"(c2), "h"((uint16_t)(7 << rb)) : "memory");
}
DEVI void e_tma_2d_mc(uint32_t dst, const CUtensorMap* m, int c0, int c1, uint32_t bar) {
  asm volatile(ELECT "cp.async.bulk.tensor.2d.shared::cluster.global.mbarrier::complete_tx::bytes.multicast::cluster [%0], [%1, {%3, %4}], [%2], %5;}"
    :: "r"(dst), "l"(m), "r"(bar), "r"(c0), "r"(c1), "h"((uint16_t)3) : "memory");
}
DEVI void p_arrive_at(uint32_t bar, uint32_t rank, bool c) {
  asm volatile("{.reg .pred p; .reg .b32 a; setp.ne.u32 p, %2, 0; mapa.shared::cluster.u32 a, %0, %1; @p mbarrier.arrive.shared::cluster.b64 _, [a];}"
    :: "r"(bar), "r"(rank), "r"((uint32_t)c) : "memory");
}
DEVI void p_expect_tx(uint32_t bar, uint32_t bytes, bool c) {
  asm volatile("{.reg .pred p; setp.ne.u32 p, %2, 0; @p mbarrier.arrive.expect_tx.shared::cta.b64 _, [%0], %1;}" :: "r"(bar), "r"(bytes), "r"((uint32_t)c) : "memory");
}
DEVI void p_arrive(uint32_t bar, bool c) { asm volatile("{.reg .pred p; setp.ne.u32 p, %1, 0; @p mbarrier.arrive.shared::cta.b64 _, [%0];}" :: "r"(bar), "r"((uint32_t)c) : "memory"); }
DEVI void tma_store_2d(const CUtensorMap* m, uint32_t src, int c0, int c1) {
  asm volatile("cp.async.bulk.tensor.2d.global.shared::cta.bulk_group [%0, {%2, %3}], [%1];" :: "l"(m), "r"(src), "r"(c0), "r"(c1) : "memory");
}
DEVI void tma_radd_2d(const CUtensorMap* m, uint32_t src, int c0, int c1) {
  asm volatile("cp.reduce.async.bulk.tensor.2d.global.shared::cta.add.bulk_group [%0, {%2, %3}], [%1];" :: "l"(m), "r"(src), "r"(c0), "r"(c1) : "memory");
}
DEVI void bulk_commit() { asm volatile("cp.async.bulk.commit_group;" ::: "memory"); }
template<int N> DEVI void bulk_wait_read() { asm volatile("cp.async.bulk.wait_group.read %0;" :: "n"(N) : "memory"); }
template<int N> DEVI void bulk_wait() { asm volatile("cp.async.bulk.wait_group %0;" :: "n"(N) : "memory"); }
template<int ID, int N> DEVI void nbar_sync() { asm volatile("bar.sync %0, %1;" :: "n"(ID), "n"(N) : "memory"); }
template<int ID, int N> DEVI void nbar_arrive() { asm volatile("bar.arrive %0, %1;" :: "n"(ID), "n"(N) : "memory"); }
DEVI void nbar_sync_r(int id, int n) { asm volatile("bar.sync %0, %1;" :: "r"(id), "r"(n) : "memory"); }
template<int R> DEVI void reg_inc() { asm volatile("setmaxnreg.inc.sync.aligned.u32 %0;" :: "n"(R)); }
template<int R> DEVI void reg_dec() { asm volatile("setmaxnreg.dec.sync.aligned.u32 %0;" :: "n"(R)); }
DEVI void wg_fence() { asm volatile("wgmma.fence.sync.aligned;" ::: "memory"); }
DEVI void wg_commit() { asm volatile("wgmma.commit_group.sync.aligned;" ::: "memory"); }
template<int N> DEVI void wg_wait() { asm volatile("wgmma.wait_group.sync.aligned %0;" :: "n"(N) : "memory"); }
DEVI uint64_t mkdesc(uint32_t addr, uint32_t lbo, uint32_t sbo, uint32_t sw = 1) {
  return ((uint64_t)((addr & 0x3FFFF) >> 4)) | ((uint64_t)(lbo >> 4) << 16) | ((uint64_t)(sbo >> 4) << 32) | ((uint64_t)sw << 62);
}
constexpr uint32_t SMEM_BASE = 1024;
__host__ __device__ constexpr long long CD(uint32_t off, uint32_t lbo, uint32_t sbo, uint32_t sw) {
  return (long long)(((uint64_t)((SMEM_BASE + off) >> 4)) | ((uint64_t)(lbo >> 4) << 16) | ((uint64_t)(sbo >> 4) << 32) | ((uint64_t)sw << 62));
}
DEVI uint32_t pack_bf16(float lo, float hi) { uint32_t r; asm("cvt.rn.bf16x2.f32 %0, %1, %2;" : "=r"(r) : "f"(hi), "f"(lo)); return r; }
DEVI float bf_lo(uint32_t v) { return __uint_as_float(v << 16); }
DEVI float bf_hi(uint32_t v) { return __uint_as_float(v & 0xffff0000u); }
DEVI void ldsm4t(uint32_t addr, uint32_t& r0, uint32_t& r1, uint32_t& r2, uint32_t& r3) {
  asm volatile("ldmatrix.sync.aligned.m8n8.x4.trans.shared.b16 {%0,%1,%2,%3}, [%4];" : "=r"(r0), "=r"(r1), "=r"(r2), "=r"(r3) : "r"(addr) : "memory");
}
DEVI void stsm4(uint32_t addr, uint32_t r0, uint32_t r1, uint32_t r2, uint32_t r3) {
  asm volatile("stmatrix.sync.aligned.m8n8.x4.shared.b16 [%0], {%1,%2,%3,%4};" :: "r"(addr), "r"(r0), "r"(r1), "r"(r2), "r"(r3) : "memory");
}
DEVI uint2 lds64v(uint32_t a) { uint2 v; asm volatile("ld.volatile.shared.v2.u32 {%0,%1}, [%2];" : "=r"(v.x), "=r"(v.y) : "r"(a) : "memory"); return v; }
DEVI uint32_t lds32v(uint32_t a) { uint32_t v; asm volatile("ld.volatile.shared.u32 %0, [%1];" : "=r"(v) : "r"(a) : "memory"); return v; }
DEVI uint4 lds128v(uint32_t a) { uint4 v; asm volatile("ld.volatile.shared.v4.u32 {%0,%1,%2,%3}, [%4];" : "=r"(v.x), "=r"(v.y), "=r"(v.z), "=r"(v.w) : "r"(a) : "memory"); return v; }
DEVI void cp_async16(uint32_t dst, const void* src) { asm volatile("cp.async.cg.shared.global [%0], [%1], 16;" :: "r"(dst), "l"(src) : "memory"); }
DEVI void cp_async_wait() { asm volatile("cp.async.wait_all;" ::: "memory"); }
DEVI void sts32(uint32_t a, uint32_t x) { asm volatile("st.shared.u32 [%0], %1;" :: "r"(a), "r"(x) : "memory"); }
DEVI int lane_id() { int r; asm volatile("mov.u32 %0, %%laneid;" : "=r"(r)); return r; }
DEVI void sts64(uint32_t a, uint32_t x, uint32_t y) { asm volatile("st.shared.v2.u32 [%0], {%1,%2};" :: "r"(a), "r"(x), "r"(y) : "memory"); }
DEVI void sts128(uint32_t a, uint4 v) { asm volatile("st.shared.v4.u32 [%0], {%1,%2,%3,%4};" :: "r"(a), "r"(v.x), "r"(v.y), "r"(v.z), "r"(v.w) : "memory"); }
DEVI void st_async128(uint32_t a, uint32_t x, uint32_t y, uint32_t z, uint32_t w, uint32_t bar) {
  asm volatile("st.async.weak.shared::cluster.mbarrier::complete_tx::bytes.v4.b32 [%0], {%1,%2,%3,%4}, [%5];" :: "r"(a), "r"(x), "r"(y), "r"(z), "r"(w), "r"(bar) : "memory");
}
DEVI void st_async32(uint32_t a, uint32_t x, uint32_t bar) {
  asm volatile("st.async.weak.shared::cluster.mbarrier::complete_tx::bytes.b32 [%0], %1, [%2];" :: "r"(a), "r"(x), "r"(bar) : "memory");
}
DEVI uint4 ldg_rlx128(const void* p) {
  uint4 v;
  asm volatile("ld.relaxed.gpu.global.v4.b32 {%0,%1,%2,%3}, [%4];" : "=r"(v.x), "=r"(v.y), "=r"(v.z), "=r"(v.w) : "l"(p) : "memory");
  return v;
}
DEVI int ldg_rlx32(const void* p) { int v; asm volatile("ld.relaxed.gpu.global.b32 %0, [%1];" : "=r"(v) : "l"(p) : "memory"); return v; }
DEVI int ldg_acq32(const void* p) { int v; asm volatile("ld.acquire.gpu.global.b32 %0, [%1];" : "=r"(v) : "l"(p) : "memory"); return v; }
DEVI void stg_rlx128(void* p, uint32_t x, uint32_t y, uint32_t z, uint32_t w) {
  asm volatile("st.relaxed.gpu.global.v4.b32 [%0], {%1,%2,%3,%4};" :: "l"(p), "r"(x), "r"(y), "r"(z), "r"(w) : "memory");
}
DEVI void stg128(void* p, uint32_t x, uint32_t y, uint32_t z, uint32_t w) {
  asm volatile("st.global.v4.b32 [%0], {%1,%2,%3,%4};" :: "l"(p), "r"(x), "r"(y), "r"(z), "r"(w) : "memory");
}
DEVI uint2 ldg_rlx64(const void* p) { uint2 v; asm volatile("{.reg .b64 a; ld.relaxed.gpu.global.b64 a, [%2]; mov.b64 {%0,%1}, a;}" : "=r"(v.x), "=r"(v.y) : "l"(p) : "memory"); return v; }
DEVI void stg_rlx64(void* p, uint32_t x, uint32_t y) { asm volatile("{.reg .b64 a; mov.b64 a, {%1,%2}; st.relaxed.gpu.global.b64 [%0], a;}" :: "l"(p), "r"(x), "r"(y) : "memory"); }
DEVI void stg_rlx32(void* p, uint32_t x) { asm volatile("st.relaxed.gpu.global.b32 [%0], %1;" :: "l"(p), "r"(x) : "memory"); }
DEVI void flag_add(int* p) { asm volatile("fence.proxy.async.global; red.release.gpu.global.add.s32 [%0], 1;" :: "l"(p) : "memory"); }
DEVI void e_stg_rlx32(void* p, uint32_t x) { asm volatile(ELECT "st.relaxed.gpu.global.b32 [%0], %1;}" :: "l"(p), "r"(x) : "memory"); }
DEVI void e_flag_add(int* p) { asm volatile("fence.proxy.async.global;\n" ELECT "red.release.gpu.global.add.s32 [%0], 1;}" :: "l"(p) : "memory"); }
DEVI int cluster_rank() { int r; asm volatile("mov.u32 %0, %%cluster_ctarank;" : "=r"(r)); return __shfl_sync(0xffffffffu, r, 0); }
DEVI int cta_id() { int r; asm volatile("mov.u32 %0, %%ctaid.x;" : "=r"(r)); return __shfl_sync(0xffffffffu, r, 0); }
DEVI uint32_t clock32() { uint32_t c; asm volatile("mov.u32 %0, %%clock;" : "=r"(c)); return c; }
DEVI uint32_t gtime() { uint32_t c; asm volatile("mov.u32 %0, %%globaltimer_lo;" : "=r"(c)); return c; }
DEVI void wait_time(uint32_t t) { while (__any_sync(0xffffffffu, t - gtime() - 1 < 4000u)) {} }
DEVI void spin_until(uint32_t t0, int d) { while (__any_sync(0xffffffffu, (int)(clock32() - t0) < d)) {} }
DEVI void pin2(const void* a, const void* b) { asm volatile("{.reg .pred p; setp.eq.u64 p, %0, %1; @p st.volatile.global.u64 [%0], %1;}" :: "l"(a), "l"(b) : "memory"); }
DEVI void pin2(uint32_t a, uint32_t b) { asm volatile("{.reg .pred p; setp.eq.u32 p, %0, %1; @p st.volatile.shared.u32 [%0], %1;}" :: "r"(a), "r"(b) : "memory"); }
DEVI void p_stg_rlx64(void* p, uint32_t x, uint32_t y, bool c) {
  asm volatile("{.reg .pred p; .reg .b64 a; setp.ne.u32 p, %3, 0; mov.b64 a, {%1,%2}; @p st.relaxed.gpu.global.b64 [%0], a;}" :: "l"(p), "r"(x), "r"(y), "r"((uint32_t)c) : "memory");
}
DEVI void pin2(uint64_t a, uint64_t b) { pin2((const void*)a, (const void*)b); }
DEVI uint64_t pair(uint32_t a, uint32_t bar) { return a | (uint64_t)bar << 32; }
DEVI void st_async32(uint64_t q, uint32_t x) { st_async32((uint32_t)q, x, (uint32_t)(q >> 32)); }
DEVI void st_async128(uint64_t q, uint4 v) { st_async128((uint32_t)q, v.x, v.y, v.z, v.w, (uint32_t)(q >> 32)); }
DEVI float ex2(float x) { float r; asm("ex2.approx.ftz.f32 %0, %1;" : "=f"(r) : "f"(x)); return r; }
DEVI float rcp(float x) { float r; asm("rcp.approx.ftz.f32 %0, %1;" : "=f"(r) : "f"(x)); return r; }
DEVI uint32_t xor_or(uint32_t a, uint32_t t, uint32_t acc) { uint32_t r; asm("lop3.b32 %0, %1, %2, %3, 0xbe;" : "=r"(r) : "r"(a), "r"(t), "r"(acc)); return r; }
DEVI void stsm2(uint32_t addr, uint32_t r0, uint32_t r1) {
  asm volatile("stmatrix.sync.aligned.m8n8.x2.shared.b16 [%0], {%1,%2};" :: "r"(addr), "r"(r0), "r"(r1) : "memory");
}
DEVI uint32_t settag(uint32_t v, uint32_t tag) { return (v & ~1u) | tag; }

#define A4(c, o)  c(d[o+0]), c(d[o+1]), c(d[o+2]), c(d[o+3])
#define A8(c, o)  A4(c, o), A4(c, o+4)
#define A16(c, o) A8(c, o), A8(c, o+8)
#define A12(c, o) A8(c, o), A4(c, o+8)
#define A28(c, o) A16(c, o), A12(c, o+16)
#define RL12 "{%0,%1,%2,%3,%4,%5,%6,%7,%8,%9,%10,%11}"
#define RL28 "{%0,%1,%2,%3,%4,%5,%6,%7,%8,%9,%10,%11,%12,%13,%14,%15,%16,%17,%18,%19,%20,%21,%22,%23,%24,%25,%26,%27}"
#define A20(c, o) A16(c, o), A4(c, o+16)
#define A32(c, o) A16(c, o), A16(c, o+16)
#define RL8  "{%0,%1,%2,%3,%4,%5,%6,%7}"
#define RL16 "{%0,%1,%2,%3,%4,%5,%6,%7,%8,%9,%10,%11,%12,%13,%14,%15}"
#define RL20 "{%0,%1,%2,%3,%4,%5,%6,%7,%8,%9,%10,%11,%12,%13,%14,%15,%16,%17,%18,%19}"
#define RL32 "{%0,%1,%2,%3,%4,%5,%6,%7,%8,%9,%10,%11,%12,%13,%14,%15,%16,%17,%18,%19,%20,%21,%22,%23,%24,%25,%26,%27,%28,%29,%30,%31}"
#define RL64 "{%0,%1,%2,%3,%4,%5,%6,%7,%8,%9,%10,%11,%12,%13,%14,%15,%16,%17,%18,%19,%20,%21,%22,%23,%24,%25,%26,%27,%28,%29,%30,%31," \
  "%32,%33,%34,%35,%36,%37,%38,%39,%40,%41,%42,%43,%44,%45,%46,%47,%48,%49,%50,%51,%52,%53,%54,%55,%56,%57,%58,%59,%60,%61,%62,%63}"
#define WG_OP(shape) "wgmma.mma_async.sync.aligned." shape "k16.f32.bf16.bf16 "
#define DEF_WGMMA(N, RL, AL, i0, i1, i2, i3, i4, i5, i6)                                                                         \
  template<int SC, int TB, long long CB> DEVI void rs##N(float* d, const uint32_t* a) {                                          \
    if (SC) asm volatile("{.reg .b64 tb; mov.b64 tb, %" #i4 ";\n" WG_OP("m64n" #N) RL ", {%" #i0 ",%" #i1 ",%" #i2 ",%" #i3 "}, tb, 1, 1, 1, %" #i5 ";}" \
      : AL("+f", 0) : "r"(a[0]), "r"(a[1]), "r"(a[2]), "r"(a[3]), "n"(CB), "n"(TB));                                             \
    else asm volatile("{.reg .b64 tb; mov.b64 tb, %" #i4 ";\n" WG_OP("m64n" #N) RL ", {%" #i0 ",%" #i1 ",%" #i2 ",%" #i3 "}, tb, 0, 1, 1, %" #i5 ";}" \
      : AL("=f", 0) : "r"(a[0]), "r"(a[1]), "r"(a[2]), "r"(a[3]), "n"(CB), "n"(TB));                                             \
  }                                                                                                                              \
  template<int SC, int TA, int TB, long long CA, long long CB> DEVI void ss##N(float* d, uint32_t a) {                           \
    if (SC) asm volatile("{.reg .b64 ta, tb; .reg .b32 lo, hi; add.u32 lo, %" #i0 ", %" #i1 "; mov.b32 hi, %" #i2 "; mov.b64 ta, {lo, hi}; mov.b64 tb, %" #i3 ";\n" \
      WG_OP("m64n" #N) RL ", ta, tb, 1, 1, 1, %" #i4 ", %" #i5 ";}"                                                              \
      : AL("+f", 0) : "r"(a), "n"((int)CA), "n"((int)(CA >> 32)), "n"(CB), "n"(TA), "n"(TB));                                    \
    else asm volatile("{.reg .b64 ta, tb; .reg .b32 lo, hi; add.u32 lo, %" #i0 ", %" #i1 "; mov.b32 hi, %" #i2 "; mov.b64 ta, {lo, hi}; mov.b64 tb, %" #i3 ";\n" \
      WG_OP("m64n" #N) RL ", ta, tb, 0, 1, 1, %" #i4 ", %" #i5 ";}"                                                              \
      : AL("=f", 0) : "r"(a), "n"((int)CA), "n"((int)(CA >> 32)), "n"(CB), "n"(TA), "n"(TB));                                    \
  }
DEF_WGMMA(8, "{%0,%1,%2,%3}", A4, 4, 5, 6, 7, 8, 9, 10)
DEF_WGMMA(16, RL8, A8, 8, 9, 10, 11, 12, 13, 14)
DEF_WGMMA(32, RL16, A16, 16, 17, 18, 19, 20, 21, 22)
DEF_WGMMA(40, RL20, A20, 20, 21, 22, 23, 24, 25, 26)
DEF_WGMMA(24, RL12, A12, 12, 13, 14, 15, 16, 17, 18)
DEF_WGMMA(56, RL28, A28, 28, 29, 30, 31, 32, 33, 34)
template<int TA> DEVI void wgmma_n128(float* d, uint64_t a, uint64_t b, int scale_d) {
  asm volatile("{.reg .pred p; setp.ne.b32 p, %66, 0;\n" WG_OP("m64n128") RL64 ", %64, %65, p, 1, 1, %67, 1;}"
    : A32("+f", 0), A32("+f", 32) : "l"(a), "l"(b), "r"(scale_d), "n"(TA));
}

namespace rec {
constexpr int KR = 43;
constexpr uint32_t WSZ = (64 - KR) * 2048, STG = KR * 2048;
constexpr uint32_t WS = 0;
constexpr uint32_t RING = 2 * WSZ;
constexpr uint32_t OB = RING + 3 * 8192;
constexpr uint32_t PB = OB + 4096;
constexpr uint32_t WO = RING + 32768;
constexpr uint32_t ATT = WO + 5 * 16384;
constexpr uint32_t AK = ATT + 10240, AV = ATT + 20480;
constexpr uint32_t PAD = ATT + 30720;
constexpr uint32_t BARS = PAD + 128;
constexpr uint32_t B_XE = BARS  , B_FA = BARS + 64  , B_FB = BARS + 88, B_FO = BARS + 96;
constexpr uint32_t B_ME = BARS + 104  , B_WE = BARS + 136, B_PD = BARS + 144;
constexpr uint32_t B_XF = BARS + 152  , B_MF = BARS + 216  , B_CP = BARS + 248  , B_WT = BARS + 280  ;
constexpr uint32_t B_AB = BARS + 296, B_OB = BARS + 304, B_ST = BARS + 312  , B_WS = BARS + 328, B_WO = BARS + 336, B_AT = BARS + 352, B_AV = BARS + 360;
constexpr int NBAR = 46;
constexpr uint32_t M0 = BARS + 384;
constexpr uint32_t SMEM = 232448;
constexpr int NB_P = 1, NB_ST = 2, NB_O = 3, NB_W0 = 4, NB_W1 = 5;
__host__ __device__ constexpr int wo_tile(int rank, int g, int i) { return i < 2 ? i * 6 + rank * 2 + g : 13 + rank - g; }
constexpr long long D_W = CD(WS, 16, 1024, 1), D_X = CD(0, 16, 1024, 1), D_O = CD(OB, 128, 256, 0);
constexpr long long D_WO = CD(WO, 16, 1024, 1), D_QM = CD(ATT, 640, 0, 0), D_QT = CD(ATT + 128, 640, 64, 0), D_K = CD(AK, 640, 128, 0);
constexpr long long D_V = CD(AV, 128, 640, 0), D_P = CD(PB, 128, 768, 0);
struct Maps { CUtensorMap w[3], wo, xd, xs; };
__host__ __device__ constexpr uint32_t mslot(int c) { return (c ^ (c >> 1)) * 12288; }
__host__ __device__ constexpr uint32_t xslot(int s) { return s < 3 ? RING + s * 8192 : s < 5 ? WO + (s - 3) * 8192 : s < 7 ? WO + (s + 1) * 8192 : OB; }
#define KQ 0
__host__ __device__ constexpr int n_smem(int k) { return k <= KQ ? 0 : (k - KQ) * (64 - KR) / (64 - KQ); }
__host__ __device__ constexpr bool k_smem(int k) { return n_smem(k + 1) != n_smem(k); }
__host__ __device__ constexpr int k_idx(int k) { return k_smem(k) ? n_smem(k) : k - n_smem(k); }

#define RPROF(i)
#define RPROF_STEP
#define CPROF(i, v)

template<bool DUAL, int K0, int K1> DEVI void seq_mem(float* d, const uint32_t* w, uint32_t dw) {
  if constexpr (K0 < K1) {
    constexpr long long B = CD(RING, 128, DUAL ? 4096 : 8192, 0) + mslot(K0 >> 4) / 16 + (K0 & 15) * 16;
    if constexpr (DUAL) {
      if constexpr (!k_smem(K0)) rs24<K0 != 0, 1, B>(d, w + 4 * k_idx(K0)); else ss24<1, 1, 1, D_W + k_idx(K0) * 128, B>(d, dw);
    } else {
      if constexpr (!k_smem(K0)) rs16<K0 != 0, 1, B>(d, w + 4 * k_idx(K0)); else ss16<1, 1, 1, D_W + k_idx(K0) * 128, B>(d, dw);
    }
    seq_mem<DUAL, K0 + 1, K1>(d, w, dw);
  }
}
template<int N, int K0, int K1> DEVI void seq_tok(float* d, const uint32_t* w, uint32_t dw) {
  if constexpr (K0 < K1) {
    constexpr bool DUAL = N > 32;
    constexpr long long B = D_X + (DUAL ? xslot((K0 >> 2) & 7) / 16 : xslot(K0 >> 3) / 16 + ((K0 >> 2) & 1) * 256) + (K0 & 3) * 2;
    if constexpr (DUAL) {
      if constexpr (!k_smem(K0)) rs56<K0 != 0, 0, B>(d, w + 4 * k_idx(K0)); else ss56<1, 1, 0, D_W + k_idx(K0) * 128, B>(d, dw);
    } else if constexpr (N == 24) {
      if constexpr (!k_smem(K0)) rs24<K0 != 0, 0, B>(d, w + 4 * k_idx(K0)); else ss24<1, 1, 0, D_W + k_idx(K0) * 128, B>(d, dw);
    } else {
      if constexpr (!k_smem(K0)) rs32<K0 != 0, 0, B>(d, w + 4 * k_idx(K0)); else ss32<1, 1, 0, D_W + k_idx(K0) * 128, B>(d, dw);
    }
    seq_tok<N, K0 + 1, K1>(d, w, dw);
  }
}
template<int T, int K0> DEVI void seq_wo(float* d, uint32_t dw) {
  if constexpr (K0 < 8) { ss16<K0 != 0, 1, 1, D_WO + T * 1024 + K0 * 128, D_O + K0 * 32>(d, dw); seq_wo<T, K0 + 1>(d, dw); }
}
template<long long Q, int K0> DEVI void seq_s(float* d) {
  if constexpr (K0 < 8) { ss40<K0 != 0, 1, 1, Q + K0 * 80, D_K + K0 * 80>(d, 0); seq_s<Q, K0 + 1>(d); }
}
template<bool DUAL, int J> DEVI void load_x(uint32_t sb, const Maps* M, int t, int rb) {
  if (DUAL) e_tma_3d_mc(sb + xslot(J & 7), &M->xd, J * 64, (t - LAG) * 32, 0, sb + B_XF + (J & 7) * 8, rb);
  else e_tma_3d_mc(sb + xslot(J & 7), &M->xs, 0, (t < NSEG ? t : t - LAG) * 32, J * 2, sb + B_XF + (J & 7) * 8, rb);
}
DEVI void load_x_lent(uint32_t sb, const Maps* M, int t, int j) {
  const bool dual = t >= LAG && t < NSEG;
  const uint32_t dst = sb + (j == 3 ? xslot(3) : xslot(5));
#pragma unroll
  for (int i = 0; i < 2; i++)
    e_tma_3d(dst + i * 8192, dual ? &M->xd : &M->xs, dual ? (j + i) * 64 : 0, (t < LAG ? t : t - LAG) * 32, dual ? 0 : (j + i) * 2, sb + B_XF + (j + i) * 8);
}
struct True { static constexpr bool value = true; };
struct False { static constexpr bool value = false; };
struct Ctx { uint32_t sb; const Maps* M; int rb, rank, wi; bool lead; uint32_t par; };
#define PFN 2
#define XD 2
template<bool DUAL, int J> DEVI void tok_release(const Ctx& c, int t, int& budget) {
  constexpr int NC = DUAL ? 16 : 8, S = J & 7;
  if constexpr (J + 8 < NC) {
    p_arrive_at(c.sb + B_XE + S * 8, c.rb + J % 3, c.lead);
    p_expect_tx(c.sb + B_XF + S * 8, 8192, c.lead && c.wi == 0);
  } else if constexpr (S == 1 || S == 2 || S == 4 || S == 7) p_arrive(c.sb + B_ME + (S >> 1) * 8, c.lead);
  if constexpr (J == XD - 1) {
    if (c.rank == 1 && c.wi == 5) { mbar_wait(c.sb + B_FO, t & 1, budget); load_x<DUAL, 7>(c.sb, c.M, t, c.rb); }
  } else if constexpr (J >= XD && J - XD + 8 < NC) {
    constexpr int I = J - XD;
    if (c.rank == I % 3 && c.wi == (I & 1) * 4 + 1) { mbar_wait(c.sb + B_XE + I * 8, (t - LAG) & 1, budget); load_x<DUAL, I + 8>(c.sb, c.M, t, c.rb); }
  }
}
template<int N, int J, class F, class G> DEVI bool tok_pass(float* d, const uint32_t* w, uint32_t dw, Ctx& c, int t, int& budget, F after0, G setup) {
  constexpr bool DUAL = N > 32;
  constexpr int NC = DUAL ? 16 : 8, KC = 64 / NC;
  if constexpr (J < NC) {
    if constexpr (J > 1) mbar_wait(c.sb + B_XF + (J & 7) * 8, c.par ^ (J >> 3), budget);
    wg_fence();
    seq_tok<N, J * KC, (J + 1) * KC>(d, w, dw);
    wg_commit();
    if constexpr (J == 1) after0();
    if constexpr (J >= NC - 5 && J < NC - 2) setup(J - (NC - 5));
    if constexpr (J > 0) { wg_wait<1>(); tok_release<DUAL, J - 1>(c, t, budget); }
    return tok_pass<N, J + 1>(d, w, dw, c, t, budget, after0, setup);
  } else {
    const bool ok = mbar_test(c.sb + B_MF, t & 1);
    wg_wait<0>();
    tok_release<DUAL, NC - 1>(c, t, budget);
    if (!DUAL) c.par ^= 1;
    return ok;
  }
}
template<int NB> DEVI void pack_tok(uint32_t* e, const float* d) {
#pragma unroll
  for (int i = 0; i < 8; i++) if ((i & 3) < NB) e[i] = pack_bf16(d[4 * (i & 3) + 2 * (i >> 2)], d[4 * (i & 3) + 2 * (i >> 2) + 1]);
}
DEVI void push_tok(const uint32_t* e, uint32_t sb, uint32_t o, int r, int rank) {
  const uint32_t b = mapa(sb, r);
  st_async128(b + o, e[0], e[1], e[2], e[3], b + (rank == 2 ? B_AV : B_AT));
}
DEVI uint32_t h1_tag(int seg) { return ((seg >> 1) & 1) ^ 1; }
DEVI uint4 pack_part(const float* c, int t) {
  return make_uint4(settag(pack_bf16(c[0], c[1]), h1_tag(t)), pack_bf16(c[2], c[3]), settag(pack_bf16(c[4], c[5]), h1_tag(t - LAG)), pack_bf16(c[6], c[7]));
}
DEVI void put_part(char* p1, char* p2, uint4 z, int t) { p_stg_rlx64(p1, z.x, z.y, t < NSEG); p_stg_rlx64(p2, z.z, z.w, t >= LAG); }

DEVI void rec_math(const uint32_t sb, const int wi, const Maps& M) {
  const int h = cta_id() / 3, rb = cluster_rank() >= 3 ? 3 : 0, rank = cluster_rank() - rb;
  const int warp = wi & 3, wg = wi >> 2;
  const bool lead = (threadIdx.x & 127) == 0;
  int budget = SPIN_BUDGET;
  uint32_t w[4 * KR];
  Ctx cx{sb, &M, rb, rank, wi, lead, 0};
  {
    const int lane = lane_id();
    const uint32_t a = sb + wg * STG + ((lane & 7) + (lane >> 4) * 8) * 128 + (((warp * 2 + ((lane >> 3) & 1)) ^ (lane & 7)) << 4);
    mbar_wait(sb + B_ST + wg * 8, 0, budget);
#pragma unroll
    for (int k = 0; k < KR; k++) ldsm4t(a + k * 2048, w[4*k], w[4*k+1], w[4*k+2], w[4*k+3]);
    nbar_arrive<NB_ST, 384>();
    nbar_sync_r(NB_W0 + wg, 128);
    for (int i = 0; i < 5; i++) p_arrive_at(sb + B_FA + i * 8, rb + (i == 4), lead);
    mbar_wait(sb + B_WS, 0, budget);
  }
  uint4 z = make_uint4(0, 0, 0, 0);
  char *z1 = nullptr, *z2 = nullptr;
  uint32_t rt0 = 0, rt1 = 0;
  mbar_wait(sb + B_XF, 0, budget); mbar_wait(sb + B_XF + 8, 0, budget);
#pragma unroll 1
  for (int t = 0;; t++) {
    const uint32_t dw = wg * (WSZ >> 4);
    uint32_t e[16];
    bool ok;
    auto finish = [&]() { put_part(z1, z2, z, t - 1); p_arrive_at(sb + B_FO, rb + 1, lead); };
    const int seg = t - rank * LAG;
    const bool att = rank < 2 && (unsigned)seg < (unsigned)NSEG;
    char* p1;
    uint32_t pw, oo;
    uint64_t u0, u1;
    int lane;
    auto setup = [&](int part) {
      if (part == 0) {
        lane = lane_id();
      } else if (part == 1) {
        char* const p = (char*)g_h1 + ((wo_tile(rank, wg, 0) * 4 + warp) * 4 + (lane >> 3)) * 2048 + h * 64 + (lane & 7) * 8;
        p1 = p + (t & 1) * sizeof(g_h1[0]);
        pin2(p1, nullptr);
      } else if (part == 2) {
        oo = OB + (lane >> 4) * 2048 + warp * 512 + rank * 256 + (lane & 15) * 16;
        pw = sb + PB + (wg ? lane * 4 : 768 + warp * 768 + lane * 16);
        pin2(pw, oo);
      } else {
        if (wg) {
          const uint32_t ra = mapa(sb, rb + ((warp & 1) ? 2 : (rank ^ 1) & 1)), rc = mapa(sb, rb + ((warp & 1) ? (rank ^ 1) & 1 : 2));
          u0 = pair(ra + oo, ra + B_OB); u1 = pair(rc + oo, rc + B_OB);
        } else {
          u0 = (uint64_t)((char*)(g_ot + rank * O_LAYER) + (size_t)(h * DH + warp * 16 + (lane >> 2)) * (SEQ * 2) + seg * 64 + (lane & 3) * 16);
          u1 = (uint32_t)((lane & 24) + ((lane >> 2) & 1) + 2 * warp - 8 * (lane & 3));
        }
        pin2(u0, u1);
      }
    };
    RPROF_STEP;
    auto mem_pass = [&](auto dual_c) {
      constexpr bool DUAL = decltype(dual_c)::value;
      float m[DUAL ? 12 : 8];
      RPROF(8 + wg * 12 - 32);
      if (!ok) mbar_wait(sb + B_MF, t & 1, budget);
      wg_fence(); seq_mem<DUAL, 0, 8>(m, w, dw); wg_commit();
      const uint32_t ao = ATT + rank * 10240 + wi * 1280, to = ao + 128 + (lane & 3) * 128 + (lane >> 2) * 16;
      const int la = DUAL ? rank == 0 : t >= NSEG;
      RPROF(1 + wg * 12);
      if (DUAL && rank == 0) {
#pragma unroll
        for (int i = 0; i < 8; i++) { const uint32_t x = e[i]; e[i] = e[8 + i]; e[8 + i] = x; }
      }
      auto piece = [&](int i) { push_tok(e + 4 * i, sb, to + (i & 1) * 640, rb + (la ^ (i >> 1)), rank); };
      piece(0);
      wg_fence(); seq_mem<DUAL, 8, 16>(m, w, dw); wg_commit();
      piece(1);
      mbar_wait(sb + B_MF + 8, t & 1, budget);
      wg_fence(); seq_mem<DUAL, 16, 24>(m, w, dw); wg_commit();
      if (DUAL) piece(2);
      wg_fence(); seq_mem<DUAL, 24, 32>(m, w, dw); wg_commit();
      if (DUAL) piece(3);
      mbar_wait(sb + B_MF + 16, t & 1, budget);
      wg_fence(); seq_mem<DUAL, 32, 48>(m, w, dw); wg_commit();
      wg_wait<1>(); p_arrive(sb + B_PD, lead);
      const uint32_t r0 = mapa(sb, rb + la), r1 = mapa(sb, rb + (la ^ 1)), m0 = r0 + ao + lane * 4, m1 = r1 + ao + lane * 4, ab = rank == 2 ? B_AV : B_AB;
      const uint64_t q0 = pair(m0, r0 + ab), q1 = pair(m0 + 640, r0 + ab), q2 = pair(m1, r1 + ab), q3 = pair(m1 + 640, r1 + ab);
      pin2(q0, q1);
      if (DUAL) pin2(q2, q3);
      mbar_wait(sb + B_MF + 24, t & 1, budget);
      wg_fence(); seq_mem<DUAL, 48, 64>(m, w, dw); wg_commit();
      wg_wait<1>(); p_arrive_at(sb + B_FA, rb, lead);
      wg_wait<0>();
      const uint32_t a0 = pack_bf16(m[0], m[1]), a1 = pack_bf16(m[2], m[3]), a2 = pack_bf16(m[4], m[5]), a3 = pack_bf16(m[6], m[7]);
      if constexpr (DUAL) {
        st_async32(q0, la ? a2 : a0); st_async32(q1, la ? a3 : a1); st_async32(q2, la ? a0 : a2); st_async32(q3, la ? a1 : a3);
        rt0 = pack_bf16(m[8], m[9]); rt1 = pack_bf16(m[10], m[11]);
      } else { st_async32(q0, a0); st_async32(q1, a1); rt0 = a2; rt1 = a3; }
      p_arrive(sb + B_WE, lead);
    };
    if (t >= LAG && t < NSEG) {
      float d[28];
      ok = tok_pass<56, 0>(d, w, dw, cx, t, budget, finish, setup);
      pack_tok<4>(e + 8, d); pack_tok<3>(e, d + 16); e[3] = rt0; e[7] = rt1;
      mem_pass(True());
    } else {
      float d[16];
      if (t > 0) finish();
      if (t > 0 && t < LAG) {
        ok = tok_pass<24, 0>(d, w, dw, cx, t, budget, []() {}, setup);
        pack_tok<3>(e, d); e[3] = rt0; e[7] = rt1;
      } else {
        ok = tok_pass<32, 0>(d, w, dw, cx, t, budget, []() {}, setup);
        pack_tok<4>(e, d);
      }
      mem_pass(False());
    }
    {
      RPROF(2 + wg * 12);
      auto wo_ready = [&]() { if (t == 0) mbar_wait(sb + B_WO, 0, budget); if (t < NSTEP - 1) mbar_wait(sb + B_WT, t & 1, budget); };
      constexpr float SC = 0.08838834764831845f * 1.4426950408889634f;
      if (!att) wo_ready();
      else {
        float s[32];
        setup(3);
        if (wg) {
          uint32_t one[4];
#pragma unroll
          for (int i = 0; i < 4; i++) one[i] = 0x3F803F80u + (pw >> 31);
          mbar_wait_cluster(sb + B_AT, seg & 1, budget);
          mbar_wait_cluster(sb + B_AB, seg & 1, budget);
          fence_proxy_async();
          RPROF(3 + 12);
          wg_fence(); seq_s<D_QM, 0>(s); wg_commit();
          nbar_arrive<NB_P, 256>();
          if (warp == 1) sts32(pw + 640, 0);
          mbar_wait_cluster(sb + B_AV, seg & 1, budget);
          wg_wait<0>();
          float mx = fmaxf(fmaxf(fmaxf(s[0], s[1]), fmaxf(s[4], s[5])), fmaxf(fmaxf(fmaxf(s[8], s[9]), fmaxf(s[12], s[13])), fmaxf(s[16], s[17])));
          const float x1 = __shfl_xor_sync(0xffffffffu, mx, 1), x2 = __shfl_xor_sync(0xffffffffu, mx, 2), x3 = __shfl_xor_sync(0xffffffffu, mx, 3);
          const float u = (warp & 2) ? ((warp & 1) ? s[16] : s[12]) : ((warp & 1) ? s[8] : s[4]);
          const float v = (warp & 2) ? ((warp & 1) ? s[17] : s[13]) : ((warp & 1) ? s[9] : s[5]);
          const float ms = -SC * fmaxf(fmaxf(mx, x1), fmaxf(x2, x3));
          sts32(pw + 128 + warp * 128, pack_bf16(ex2(fmaf(u, SC, ms)), ex2(fmaf(v, SC, ms))));
          if (warp == 0) sts32(pw, pack_bf16(ex2(fmaf(s[0], SC, ms)), ex2(fmaf(s[1], SC, ms))));
          fence_proxy_async();
          nbar_sync<NB_W1, 128>();
          RPROF(4 + 12);
          wg_fence();
          rs8<0, 0, D_P>(s + 8, one); rs8<1, 0, D_P + 16>(s + 8, one); rs8<1, 0, D_P + 32>(s + 8, one);
          wg_commit();
          ss8<0, 0, 0, D_V, D_P>(s, 0); ss8<0, 0, 0, D_V + 320, D_P>(s + 4, 0);
          ss8<1, 0, 0, D_V + 16, D_P + 16>(s, 0); ss8<1, 0, 0, D_V + 336, D_P + 16>(s + 4, 0);
          ss8<1, 0, 0, D_V + 32, D_P + 32>(s, 0); ss8<1, 0, 0, D_V + 352, D_P + 32>(s + 4, 0);
          wg_commit();
          wg_wait<1>();
          const float i0 = rcp(s[8]), i1 = rcp(s[9]);
          wg_wait<0>();
          stsm4(sb + oo, pack_bf16(s[0] * i0, s[1] * i1), pack_bf16(s[2] * i0, s[3] * i1), pack_bf16(s[4] * i0, s[5] * i1), pack_bf16(s[6] * i0, s[7] * i1));
          __syncwarp();
          const uint4 y = lds128v(sb + oo);
          if (t < NSTEP - 1) { st_async128(u0, y); st_async128(u1, y); e_complete_tx(sb + B_OB, 512); }
          wo_ready();
        } else {
          const int lim = (int)u1;
          char* const og = (char*)u0;
          nbar_sync<NB_P, 256>();
          RPROF(3);
          wg_fence();
          seq_s<D_QT, 0>(s);
          wg_commit();
          mbar_wait_cluster(sb + B_AV, seg & 1, budget);
          wg_wait<0>();
#pragma unroll
          for (int i = 0; i < 8; i++) { float& v = s[4 + 4 * (i >> 1) + (i & 1)]; v = i <= lim ? v : -INFINITY; }
          float mx = fmaxf(fmaxf(fmaxf(s[0], s[1]), fmaxf(s[4], s[5])), fmaxf(fmaxf(fmaxf(s[8], s[9]), fmaxf(s[12], s[13])), fmaxf(s[16], s[17])));
          const float x1 = __shfl_xor_sync(0xffffffffu, mx, 1), x2 = __shfl_xor_sync(0xffffffffu, mx, 2), x3 = __shfl_xor_sync(0xffffffffu, mx, 3);
          const float ms = -SC * fmaxf(fmaxf(mx, x1), fmaxf(x2, x3));
#pragma unroll
          for (int i = 0; i < 10; i++) { float& v = s[4 * (i >> 1) + (i & 1)]; v = ex2(fmaf(v, SC, ms)); }
          const float sum = (((s[0] + s[1]) + (s[4] + s[5])) + ((s[8] + s[9]) + (s[12] + s[13]))) + (s[16] + s[17]);
          const float y1 = __shfl_xor_sync(0xffffffffu, sum, 1), y2 = __shfl_xor_sync(0xffffffffu, sum, 2), y3 = __shfl_xor_sync(0xffffffffu, sum, 3);
          const float inv = rcp((sum + y1) + (y2 + y3));
          stsm4(pw, pack_bf16(s[0] * inv, s[1] * inv), pack_bf16(s[4] * inv, s[5] * inv), pack_bf16(s[8] * inv, s[9] * inv), pack_bf16(s[12] * inv, s[13] * inv));
          stsm2(pw + 512, pack_bf16(s[16] * inv, s[17] * inv), 0);
          fence_proxy_async();
          nbar_sync<NB_W0, 128>();
          RPROF(4);
          wg_fence();
          ss32<0, 0, 0, D_V, D_P + 48>(s, 0); ss32<0, 0, 0, D_V + 320, D_P + 48>(s + 16, 0);
          ss32<1, 0, 0, D_V + 16, D_P + 64>(s, 0); ss32<1, 0, 0, D_V + 336, D_P + 64>(s + 16, 0);
          ss32<1, 0, 0, D_V + 32, D_P + 80>(s, 0); ss32<1, 0, 0, D_V + 352, D_P + 80>(s + 16, 0);
          wg_commit();
          wo_ready();
          wg_wait<0>();
#pragma unroll
          for (int i = 0; i < 4; i++) {
            const float* d = s + (i >> 1) * 16 + (i & 1) * 2;
            stg128(og + ((i >> 1) * 64 + (i & 1) * 8) * (SEQ * 2), pack_bf16(d[0], d[1]), pack_bf16(d[4], d[5]), pack_bf16(d[8], d[9]), pack_bf16(d[12], d[13]));
          }
          if ((seg & 3) == 3) nbar_arrive<NB_O, 160>();
        }
      }
      RPROF(5 + wg * 12);
      const bool three = wg == 1 || rank == 2;
      char* const p2 = p1 + (2 + ((t - LAG) & 1) - (t & 1)) * (int)sizeof(g_h1[0]);
      if (t < NSTEP - 1) {
        float c[24];
        const uint32_t dt = wg ? 0 : 3072;
        mbar_wait_cluster(sb + B_OB, t & 1, budget);
        fence_proxy_async();
        RPROF(6 + wg * 12);
        wg_fence(); seq_wo<0, 0>(c, dt); wg_commit(); seq_wo<1, 0>(c + 8, dt); wg_commit();
        mbar_wait(sb + B_XF, cx.par, budget);
        wg_wait<1>();
        if (warp == 2) load_x_lent(sb, &M, t + 1, wg ? 3 : 5);
        put_part(p1, p2, pack_part(c, t), t);
        const int o3 = (wo_tile(rank, wg, three ? 2 : 1) - wo_tile(rank, wg, 0)) * 32768;
        z1 = p1 + o3; z2 = p2 + o3;
        if (three) {
          wg_fence(); seq_wo<2, 0>(c + 16, dt); wg_commit();
          wg_wait<1>(); put_part(p1 + 6 * 32768, p2 + 6 * 32768, pack_part(c + 8, t), t);
          mbar_wait(sb + B_XF + 8, cx.par, budget);
          wg_wait<0>(); z = pack_part(c + 16, t);
        } else { mbar_wait(sb + B_XF + 8, cx.par, budget); wg_wait<0>(); z = pack_part(c + 8, t); }
      } else {
        for (int i = 0; i < (three ? 3 : 2); i++) stg_rlx64(p2 + (wo_tile(rank, wg, i) - wo_tile(rank, wg, 0)) * 32768, 0, 0);
        break;
      }
      RPROF(7 + wg * 12);
    }
  }
}

DEVI void wait_xa(const int* p, int& budget) {
  while (__any_sync(0xffffffffu, ldg_acq32(p) < 64) && --budget > 0) {}
  fence_proxy_global();
}
template<bool DUAL> DEVI void first_loads(uint32_t sb, const Maps* M, int n, int h, int rb, int& budget) {
#pragma unroll
  for (int i = 0; i < PFN; i++) {
    if (DUAL) e_prefetch_3d(&M->xd, ((h + i * (16 / PFN)) & 15) * 64, (n - LAG) * 32, 0);
    else e_prefetch_3d(&M->xs, 0, (n < NSEG ? n : n - LAG) * 32, ((h + i * (8 / PFN)) & 7) * 2);
  }
  mbar_wait(sb + B_FA, n & 1, budget);
  load_x<DUAL, 0>(sb, M, n, rb); load_x<DUAL, 1>(sb, M, n, rb); load_x<DUAL, 2>(sb, M, n, rb);
}
template<bool DUAL> DEVI void lent_loads(uint32_t sb, const Maps* M, int n, int rb, int& budget) {
  mbar_wait(sb + B_FB, n & 1, budget);
  load_x<DUAL, 3>(sb, M, n, rb); load_x<DUAL, 4>(sb, M, n, rb); load_x<DUAL, 5>(sb, M, n, rb); load_x<DUAL, 6>(sb, M, n, rb);
}
DEVI void rec_comm(const uint32_t sb, const int warp, const Maps& M, const bf16* __restrict__ mem0) {
  const int lane = threadIdx.x & 31, h = cta_id() / 3, rb = cluster_rank() >= 3 ? 3 : 0, rank = cluster_rank() - rb;
  int budget = SPIN_BUDGET;
  const bool two = warp == 3 || (rank == 2 && warp == 2);
  const int ntask = two ? 2 : 1, qi = two ? (warp == 3 ? rank : 3) : rank * 3 + warp;
  const int task0 = two ? h * 2 + (qi >> 1) : 64 + h * 4 + (qi >> 1);
  auto h2_word = [&](int i, int ln) {
    const int task = task0 + i * 192;
    return (char*)g_h2 + (task >> 6) * 8192 + ((qi ^ i) & 1) * 4096 + ((task >> 2) & 15) * 256 + (task & 3) * 32 + (ln & 8) * 16 + (ln & 7) * 4;
  };
  auto first_x = [&](int t) {
    const int n = t + 1;
    p_expect_tx(sb + B_XF + (lane_id() & 7) * 8, 8192, lane_id() < 8);
    if (rank == 0) {
      if (n >= LAG && ((n - LAG) & 3) == 0) wait_xa(&g_xa[1][(n - LAG) >> 2], budget);
      if (n >= LAG && n < NSEG) first_loads<true>(sb, &M, n, h, rb, budget); else first_loads<false>(sb, &M, n, h, rb, budget);
    }
  };
  {
    const int task = task0 + (lane >> 4) * 192, L = (task & 3) * 8 + (lane & 7);
    if ((lane >> 4) < ntask) {
      const bf16* p = mem0 + (L & 3) * 2 * DM + (task >> 2) * 16 + (L >> 2) + (lane & 8);
      uint32_t m0 = (uint32_t)__bfloat16_as_ushort(p[0]) | (uint32_t)__bfloat16_as_ushort(p[DM]) << 16;
      m0 = m0 ? m0 : 0x8000u;
      if (((qi ^ (lane >> 4)) & 1) == 0) stg_rlx32(h2_word(lane >> 4, lane), m0);
      sts32(sb + M0 + warp * 128 + lane * 4, m0);
    }
    __syncwarp();
    nbar_sync<NB_ST, 384>();
    if (warp == 2) {
      e_expect_tx(sb + B_WS, 2 * WSZ);
#pragma unroll 1
      for (int i = 0; i < 128; i++) if (k_smem(i >> 1)) e_tma_2d(sb + WS + (i & 1) * WSZ + k_idx(i >> 1) * 2048, &M.w[rank], h * DH + (i & 1) * 64, (i >> 1) * 16, sb + B_WS);
      const int nt = rank == 2 ? 6 : 5;
      e_expect_tx(sb + B_WO, (nt - 2) * 16384);
#pragma unroll 1
      for (int i = 1; i < nt; i++) if (i != 3) e_tma_2d(sb + WO + i * 16384, &M.wo, wo_tile(rank, 1 - i / 3, i % 3) * 64, h * DH, sb + B_WO);
    }
    wait_xa(&g_xa[0][0], budget);
    if (warp == 3) { first_x(-1); if (rank == 0) lent_loads<false>(sb, &M, 0, rb, budget); }
  }
  uint32_t t0 = gtime() - 4000, cpp = 0;
  const uint32_t cp = sb + B_CP + warp * 8;
#pragma unroll 1
  for (int t = 0;; t++) {
    const int n = t + 1, seg = t - rank * LAG;
    RPROF_STEP;
    const bool att = rank < 2 && (unsigned)seg < (unsigned)NSEG;
    if (warp == 3) {
      if (att) { e_expect_tx(sb + B_AT, 16384); e_expect_tx(sb + B_AB, 4096); e_expect_tx(sb + B_AV, 10240); }
      if (n < NSTEP) e_expect_tx(sb + B_OB, t < NSEG && t >= LAG ? 4096 : 2048);
    }
    {
      const bool dual = t >= LAG && t < NSEG;
      const uint32_t lo = t >= NSEG ? 4096 : 0, dst = sb + RING + mslot(warp), bytes = dual ? 8192 : 4096;
      const uint32_t chk = dst + lane_id() * 32 + (lane_id() >> 2) * 4;
      mbar_wait(sb + B_ME + warp * 8, t & 1, budget);
      uint32_t tx = bytes;
      if (n < NSEG) { e_bulk_g2s(dst + 8192, (const char*)g_xr[n] + warp * 4096, 4096, cp); tx += 4096; }
      wait_time(t0 + TP(1) + warp * TP(4));
      RPROF(24); CPROF(0, gtime());
      int tries = 0;
      while (true) {
        tries++;
        e_bulk_g2s(dst, (const char*)g_h2[t & 3] + warp * 8192 + lo, bytes, cp);
        e_expect_tx(cp, tx); tx = bytes;
        mbar_wait(cp, cpp, budget); cpp ^= 1;
        uint32_t mn = min(min(lds32v(chk), lds32v(chk + 1024)), min(lds32v(chk + 2048), lds32v(chk + 3072)));
        if (dual) mn = min(min(mn, min(lds32v(chk + 4096), lds32v(chk + 5120))), min(lds32v(chk + 6144), lds32v(chk + 7168)));
        if (!__any_sync(0xffffffffu, mn == 0) || --budget < 0) break;
      }
      e_arrive(sb + B_MF + warp * 8);
      RPROF(25); CPROF(1, gtime()); CPROF(2, tries);
      if (n + 1 < NSEG && (n & 3) == 3) wait_xa(&g_xa[0][(n + 1) >> 2], budget);
    }
    {
      const int ln = lane_id(), i = ln >> 4;
      char* const w = h2_word(i, ln);
      if (i < ntask) {
        stg_rlx32(w + ((t + 3) & 3) * sizeof(g_h2[0]), 0);
        if (n == LAG && ((qi ^ i) & 1)) stg_rlx32(w + (n & 3) * sizeof(g_h2[0]), lds32v(sb + M0 + warp * 128 + ln * 4));
      }
      __syncwarp();
    }
    if (n < NSTEP) {
      const uint32_t tag = (n >> 1) & 31;
      mbar_wait(sb + B_PD, t & 1, budget);
      t0 = clock32();
      if (warp == 2) {
        mbar_wait(sb + B_ME + 24, t & 1, budget);
        e_expect_tx(sb + B_WT, 32768);
        e_tma_2d(sb + WO + 49152, &M.wo, wo_tile(rank, 0, 0) * 64, h * DH, sb + B_WT);
        mbar_wait(sb + B_WE, t & 1, budget);
        e_tma_2d(sb + WO, &M.wo, wo_tile(rank, 1, 0) * 64, h * DH, sb + B_WT);
      }
      if (warp == 3) first_x(t);
      if (warp == 0 && rank == (t >= NSEG)) { mbar_wait(sb + B_AB, seg & 1, budget); e_stg_rlx32(&g_ts[t & 1][h * TSS], (gtime() & ~31u) | tag); }
      spin_until(t0, TSD);
      uint32_t v;
      do { v = ldg_rlx32(&g_ts[t & 1][lane_id() * TSS]); } while (__any_sync(0xffffffffu, (v & 31) != tag) && --budget > 0);
      const uint32_t now = __shfl_sync(0xffffffffu, v, 0);
      t0 = now + __reduce_max_sync(0xffffffffu, (int)(v - now));
      if (warp == 3) mbar_wait(sb + B_OB, t & 1, budget);
    }
    if (n < NSTEP) {
      RPROF(26); CPROF(3, t0);
#pragma unroll 1
      for (int i = 0; i < ntask; i++) {
        const int layer = (qi ^ i) & 1, sg = t - layer * LAG, task = task0 + i * 192;
        if ((unsigned)sg >= (unsigned)(NSEG - 1)) continue;
        const uint32_t tag = h1_tag(sg);
        const int ln = lane_id();
        const char* const src = (const char*)g_h1[layer * 2 + (sg & 1)] + task * 2048 + ln * 8;
        char* const dst = h2_word(i, ln) + (n & 3) * sizeof(g_h2[0]);
        uint2 v[8];
        pin2(src, dst);
        wait_time(t0 + TP(0) + (task < 96 ? 0 : task < 192 ? TP(3) : 2 * TP(3)));
        int tries = 0;
        float a[4];
        while (true) {
          tries++;
#pragma unroll
          for (int k = 0; k < 8; k++) v[k] = ldg_rlx64(src + k * 256);
          uint32_t bad = 0;
#pragma unroll
          for (int k = 0; k < 8; k++) {
            bad = xor_or(v[k].x, tag, bad);
            a[0] = k ? a[0] + bf_lo(v[k].x) : bf_lo(v[k].x); a[1] = k ? a[1] + bf_hi(v[k].x) : bf_hi(v[k].x);
            a[2] = k ? a[2] + bf_lo(v[k].y) : bf_lo(v[k].y); a[3] = k ? a[3] + bf_hi(v[k].y) : bf_hi(v[k].y);
          }
#pragma unroll
        for (int k = 0; k < 2; k++) {
          const float keep = (ln & 8) ? a[2+k] : a[k], send = (ln & 8) ? a[k] : a[2+k];
          a[k] = keep + __shfl_xor_sync(0xffffffffu, send, 8);
        }
#pragma unroll
        for (int k = 0; k < 2; k++) a[k] += __shfl_xor_sync(0xffffffffu, a[k], 16);
          if (!__any_sync(0xffffffffu, bad & 1) || --budget < 0) break;
        }
        const uint32_t out = pack_bf16(a[0], a[1]);
        if (ln < 16) stg_rlx32(dst, out ? out : 0x8000u);
        __syncwarp();
        if (i == 0) { RPROF(28); CPROF(6, gtime()); CPROF(4, gtime()); CPROF(5, tries); } else CPROF(7, gtime());
      }
    }
    if (warp == (t >= LAG && t < NSEG ? 2 : 1) && att && (seg & 3) == 3) { nbar_sync<NB_O, 160>(); e_flag_add(&g_dep[E_O1 + rank * 16 + (seg >> 2)]); }
    if (n == NSTEP) break;
  }
  if (h == 0 && rank == 0 && warp < 2) g_xa[warp][lane_id()] = 0;
}
}

__global__ void __launch_bounds__(384, 1)
rec_kernel(const __grid_constant__ rec::Maps M, const bf16* __restrict__ mem0) {
  using namespace rec;
  extern __shared__ __align__(1024) uint8_t smem[];
  const uint32_t sb = __shfl_sync(0xffffffffu, smem_u32(smem), 0);
  const int tid = threadIdx.x, wi = __shfl_sync(0xffffffffu, tid >> 5, 0);
  if ((sb & 0x3FFFF) != SMEM_BASE) __trap();
  if (wi == 0) {
    const int h = cta_id() / 3, rank = cta_id() - h * 3;
    for (int i = tid; i < NBAR; i += 32) mbar_init(sb + BARS + i * 8, i < 13 ? 6 : i < 19 ? 2 : 1);
    ((uint32_t*)(smem + PAD))[tid] = 0;
    fence_mbar_init(); fence_proxy_async();
    __syncwarp();
    e_expect_tx(sb + B_ST, STG); e_expect_tx(sb + B_ST + 8, STG);
#pragma unroll 1
    for (int i = 0; i < 128; i++) if (!k_smem(i >> 1)) e_tma_2d(sb + (i & 1) * STG + k_idx(i >> 1) * 2048, &M.w[rank], h * DH + (i & 1) * 64, (i >> 1) * 16, sb + B_ST + (i & 1) * 8);
  } else if (wi == 1) {
    if (blockIdx.x < NEV / 32) { g_dep[blockIdx.x * 32 + (tid & 31)] = 0; g_claim[blockIdx.x * 32 + (tid & 31)] = 0; __threadfence(); }
    __syncwarp();
    asm volatile("griddepcontrol.launch_dependents;" ::: "memory");
  }
  cluster_arrive(); cluster_wait();
  if (wi < 8) { reg_inc<232>(); rec_math(sb, wi, M); cluster_arrive(); cluster_wait(); }
  else { reg_dec<40>(); rec_comm(sb, wi & 3, M, mem0); cluster_arrive(); cluster_wait(); }
}

namespace gm {
struct Maps { CUtensorMap ot, wo, xn, wg, wu, hl, hs, wd, out; };
constexpr int STAGES = 6, STAGE = 32768;
constexpr uint32_t SO = STAGES * STAGE, BARS = SO + 32768;
constexpr uint32_t B_FULL = BARS, B_EMPTY = BARS + 48, B_TF = BARS + 96, B_TE = BARS + 112, B_ORD = BARS + 128, B_PM = BARS + 144, B_GO = BARS + 160;
constexpr uint32_t MAIL = BARS + 176, PMAIL = BARS + 192;
constexpr uint32_t SMEM = BARS + 256;
constexpr int END = -1;

struct Tile {
  bool isO, isG, l2; int blk, col, k0, n;
  DEVI Tile(int task, int rank) {
    const int e = task >> 8, id = task & 255;
    const bool isD = e < E_G1 || e >= E_D2;
    isO = e >= E_O1 && e < E_G2; isG = !isD && !isO; l2 = e >= E_O2;
    blk = isG && l2 ? (e & 15) * 2 + rank : isD && !l2 ? e >> 1 : e & 15;
    col = isG ? (l2 ? id : id * 2 + rank) : (id & 3) * 2 + rank;
    k0 = isO ? (id >> 2) * 2048 : isG ? 0 : ((l2 ? e >> 4 : e) & 1) * 1792;
    n = isO ? 32 : isG ? 16 : 28;
  }
};

DEVI float geglu(float g, float u) {
  const float z = g * (0.7978845608028654f + 0.035677408136300125f * g * g);
  float t; asm("tanh.approx.f32 %0, %1;" : "=f"(t) : "f"(z));
  const float hg = 0.5f * g;
  return fmaf(hg, t, hg) * u;
}
struct Sched {
  int need, size;
  bool filler;
  uint4 dep, cl;
  DEVI void init(int lane) {
    const int e = lane * 4;
    const bool d = e < E_G1 || e >= E_D2, o = e >= E_O1 && e < E_G2;
    need = d ? 28 : e < E_O1 ? 64 : o ? 32 : 128;
    size = d ? 4 : o ? 8 : e < E_O1 ? 28 : e < E_G2 + 8 ? 56 : 0;
    filler = (int)blockIdx.x < TP(5);
  }
  DEVI void scan(int lane) { cl = ldg_rlx128(g_claim + lane * 4); dep = ldg_rlx128(g_dep + lane * 4); }
  DEVI int next(int lane, int& budget) {
    while (--budget > 0) {
      int av[4], open = 0;
#pragma unroll
      for (int i = 0; i < 4; i++) { const int r = max(size - (int)(&cl.x)[i], 0); open |= r; av[i] = ((int)(&dep.x)[i] >= need ? r : 0) + (i ? av[i - 1] : 0); }
      const uint32_t mo = __ballot_sync(0xffffffffu, open);
      if (!mo) break;
      if (filler) {
        const int x = TP(6) & 3, dx = x == 0 ? dep.x : x == 1 ? dep.y : x == 2 ? dep.z : dep.w;
        filler = !__any_sync(0xffffffffu, lane == (E_O1 + TP(6)) >> 2 && dx >= need);
      }
      if (!filler && (mo & 0xffff) && lane >= E_O2 / 4) av[3] = 0;
      int inc = av[3], pos = 0;
      while (true) {
        const uint32_t m = __ballot_sync(0xffffffffu, inc > pos && av[3]);
        if (!m) break;
        const int l = __ffs(m) - 1, rel = pos - (inc - av[3]), i = (rel >= av[0]) + (rel >= av[1]) + (rel >= av[2]);
        int r = 0;
        if (lane == l) {
          const int tk = atomicAdd(g_claim + lane * 4 + i, 1);
          r = tk < size ? (lane * 4 + i) << 8 | tk : -1 - (inc - av[3] + (i == 0 ? av[0] : i == 1 ? av[1] : i == 2 ? av[2] : av[3]) + tk - size);
        }
        r = __shfl_sync(0xffffffffu, r, l);
        if (r >= 0) return r;
        if (pos == 0) {
#pragma unroll
          for (int o = 1; o < 32; o <<= 1) { const int v = __shfl_up_sync(0xffffffffu, inc, o); if (lane >= o) inc += v; }
        }
        pos = -1 - r;
      }
      if (pos == 0) __nanosleep(TP(7));
      scan(lane);
    }
    return END;
  }
};

DEVI void scheduler(const uint32_t sb) {
  const int lane = threadIdx.x & 31;
  int budget = SPIN_BUDGET;
  Sched sc; sc.init(lane);
#pragma unroll 1
  for (int i = 0;; i++) {
    mbar_wait(sb + B_GO, (i & 1) ^ 1, budget);
    sc.scan(lane);
    const int task = sc.next(lane, budget);
    const uint32_t r = mapa(sb, lane & 1);
    if (lane < 2) st_async32(r + PMAIL + (i & 1) * 4, task, r + B_PM + (i & 1) * 8);
    __syncwarp();
    if (task == END) break;
  }
}

DEVI void producer(const uint32_t sb, const Maps& M) {
  const int lane = threadIdx.x & 31, rank = cluster_rank();
  int budget = SPIN_BUDGET, s = 0, ph = 0;
#pragma unroll 1
  for (int i = 0;; i++) {
    e_expect_tx(sb + B_PM + (i & 1) * 8, 4);
    mbar_wait_cluster(sb + B_PM + (i & 1) * 8, (i >> 1) & 1, budget);
    const int task = budget < 0 ? END : __shfl_sync(0xffffffffu, (int)lds32v(sb + PMAIL + (i & 1) * 4), 0);
    fence_proxy_global();
    for (int z = 0; z < (task == END ? 2 : 1); z++) {
      const int g = (i + z) & 1;
      mbar_wait(sb + B_TE + g * 8, (((i + z) >> 1) & 1) ^ 1, budget);
      if (lane == 0) { sts64(sb + MAIL + g * 8, task, s | ph << 8); mbar_arrive(sb + B_TF + g * 8); }
      __syncwarp();
    }
    if (task == END) break;
    const Tile T(task, rank);
    const bool shareB = T.isG && T.l2;
    const CUtensorMap* mA = T.isO ? &M.ot : T.isG ? &M.xn : &M.hl;
    const CUtensorMap* mB0 = T.isO ? &M.wo : T.isG ? &M.wg : &M.wd;
    const CUtensorMap* mB1 = T.isG ? &M.wu : mB0;
    const int c0 = T.col * (T.isG ? 64 : 128), c1 = T.isG ? c0 : c0 + 64, row = T.blk * 128;
    const int ok = 0;
    int k = T.k0;
#pragma unroll 1
    for (int it = 0; it < T.n; it++, k += 64) {
      const uint32_t a = sb + s * STAGE, fb = sb + B_FULL + s * 8;
      mbar_wait(sb + B_EMPTY + s * 8, ph ^ 1, budget);
      e_expect_tx(fb, STAGE);
      if (shareB) {
        e_tma_2d_mc(a + 16384 + rank * 8192, rank ? mB1 : mB0, c0, k, fb);
        e_tma_2d(a, mA, k, row, fb); e_tma_2d(a + 8192, mA, k, row + 64, fb);
      } else {
        e_tma_2d_mc(a + rank * 8192, mA, T.isO ? row + rank * 64 : k, T.isO ? k + ok : row + rank * 64, fb);
        e_tma_2d(a + 16384, mB0, c0, k, fb); e_tma_2d(a + 24576, mB1, c1, k, fb);
      }
      if (it == T.n - TP(2)) e_arrive(sb + B_GO);
      if (++s == STAGES) { s = 0; ph ^= 1; }
    }
  }
}

template<int TA> DEVI void mainloop(float* d0, float* d1, uint32_t sb, int n, int s, int ph, bool lead, uint32_t ord, int& budget) {
  int prev = 0;
  const uint32_t rel = threadIdx.x & 127;
#pragma unroll 1
  for (int i = 0; i < n; i++) {
    mbar_wait(sb + B_FULL + s * 8, ph, budget);
    const uint32_t a = sb + s * STAGE;
    const uint64_t da = mkdesc(a, 16, 1024), db = mkdesc(a + 16384, 8192, 1024);
    wg_fence();
#pragma unroll
    for (int k = 0; k < 4; k++) {
      wgmma_n128<TA>(d0, da + k * (TA ? 128 : 2), db + k * 128, (i | k) != 0);
      wgmma_n128<TA>(d1, da + 512 + k * (TA ? 128 : 2), db + k * 128, (i | k) != 0);
    }
    wg_commit();
    if (i > 0) { wg_wait<1>(); p_arrive_at(sb + B_EMPTY + prev * 8, rel & 1, rel < 2); }
    prev = s;
    if (++s == STAGES) { s = 0; ph ^= 1; }
  }
  p_arrive(ord, lead);
  wg_wait<0>();
  p_arrive_at(sb + B_EMPTY + prev * 8, rel & 1, rel < 2);
}

DEVI void consumer(const uint32_t sb, const Maps& M, const int wg) {
  const int tid = threadIdx.x, lane = tid & 31, warp = (tid >> 5) & 3;
  const bool lead = (tid & 127) == 0;
  const uint32_t so = sb + SO + wg * 16384;
  int budget = SPIN_BUDGET;
  float d0[64], d1[64];
#pragma unroll 1
  for (int m = 0;; m++) {
    mbar_wait(sb + B_TF + wg * 8, m & 1, budget);
    const uint2 mail = lds64v(sb + MAIL + wg * 8);
    const int task = __shfl_sync(0xffffffffu, (int)mail.x, 0), pos = __shfl_sync(0xffffffffu, (int)mail.y, 0);
    e_arrive(sb + B_TE + wg * 8);
    if (task == END || budget < 0) break;
    const Tile T(task, cluster_rank());
    mbar_wait(sb + B_ORD + wg * 8, (m & 1) ^ wg ^ 1, budget);
    if (T.isO) mainloop<1>(d0, d1, sb, 32, pos & 255, pos >> 8, lead, sb + B_ORD + (wg ^ 1) * 8, budget);
    else mainloop<0>(d0, d1, sb, T.n, pos & 255, pos >> 8, lead, sb + B_ORD + (wg ^ 1) * 8, budget);
    const uint32_t st = so + (warp * 16 + (lane & 15)) * 128;
    if (T.isG) {
#pragma unroll
      for (int mm = 0; mm < 2; mm++) {
        const float* d = mm ? d1 : d0;
#pragma unroll
        for (int c = 0; c < 4; c++) {
          uint32_t r[4];
#pragma unroll
          for (int i = 0; i < 4; i++) r[i] = pack_bf16(geglu(d[8*c+2*i], d[32+8*c+2*i]), geglu(d[8*c+2*i+1], d[33+8*c+2*i]));
          stsm4(st + mm * 8192 + (((2 * c + (lane >> 4)) ^ (lane & 7)) << 4), r[0], r[1], r[2], r[3]);
        }
      }
      fence_proxy_async();
      nbar_sync_r(1 + wg, 128);
      if (lead) {
        tma_store_2d(&M.hs, so, T.col * 64, T.blk * 128);
        bulk_commit(); bulk_wait<0>();
        flag_add(&g_dep[T.l2 ? E_D2 + (T.col >= 28) * 16 + T.blk : E_D1 + T.blk * 2 + (T.col >= 28)]);
      }
    } else {
#pragma unroll
      for (int hf = 0; hf < 2; hf++) {
        if (hf) { if (lead) bulk_wait_read<0>(); nbar_sync_r(1 + wg, 128); }
#pragma unroll
        for (int mm = 0; mm < 2; mm++) {
          const float* d = (mm ? d1 : d0) + hf * 32;
#pragma unroll
          for (int c = 0; c < 4; c++)
            stsm4(st + mm * 8192 + (((2 * c + (lane >> 4)) ^ (lane & 7)) << 4), pack_bf16(d[8*c], d[8*c+1]), pack_bf16(d[8*c+2], d[8*c+3]),
                  pack_bf16(d[8*c+4], d[8*c+5]), pack_bf16(d[8*c+6], d[8*c+7]));
        }
        fence_proxy_async();
        nbar_sync_r(1 + wg, 128);
        if (lead) { tma_radd_2d(&M.out, so, T.col * 128 + hf * 64, T.blk * 128); bulk_commit(); }
      }
      if (lead) {
        bulk_wait<0>();
        if (T.isO || !T.l2) flag_add(&g_dep[(!T.isO ? E_LX2 : T.l2 ? E_LX1B : E_LX1A) + T.blk]);
      }
    }
    __syncwarp();
  }
}

DEVI void norm_helper(const bf16* __restrict__ x, bf16* out) {
  const int lane = threadIdx.x & 31;
  int budget = SPIN_BUDGET, tk = lane < 4 ? -1 : 1024;
#pragma unroll 1
  while (--budget > 0) {
    if (tk < 0) tk = atomicAdd(g_claim + E_LI + lane, 1);
    if (__all_sync(0xffffffffu, tk >= 1024)) break;
    const uint32_t m = __ballot_sync(0xffffffffu, tk < 1024 && (lane == 0 || ldg_acq32(g_dep + E_LI + lane * 16 + (tk >> 6)) >= 16));
    if (!m) { __nanosleep(TP(7)); continue; }
    const int ql = __ffs(m) - 1, task = __shfl_sync(0xffffffffu, tk, ql), q = E_LI + ql * 16, ev = task >> 6;
    if (lane == ql) tk = -1;
    const size_t off = (size_t)task * (DM * 4) + lane * 16;
    const char* src = (const char*)(q == E_LI ? x : out) + off;
    uint4 u[8];
#pragma unroll
    for (int i = 0; i < 8; i++) u[i] = ldg_rlx128(src + i * 512);
    if (q == E_LI) {
#pragma unroll
      for (int i = 0; i < 8; i++) stg128((char*)out + off + i * 512, u[i].x, u[i].y, u[i].z, u[i].w);
    }
    float mean[2], rs[2];
#pragma unroll
    for (int r = 0; r < 2; r++) {
      float s0 = 0, s1 = 0;
#pragma unroll
      for (int i = 0; i < 16; i++) { const uint32_t v = (&u[4*r + (i >> 2)].x)[i & 3]; s0 += bf_lo(v); s1 += bf_hi(v); }
      mean[r] = (s0 + s1) * (1.f / 32);
      s0 = s1 = 0;
#pragma unroll
      for (int i = 0; i < 16; i++) { const uint32_t v = (&u[4*r + (i >> 2)].x)[i & 3]; const float a = bf_lo(v) - mean[r], b = bf_hi(v) - mean[r]; s0 = fmaf(a, a, s0); s1 = fmaf(b, b, s1); }
      rs[r] = s0 + s1;
    }
    {
      const bool hi = lane & 16;
      float m1 = hi ? mean[1] : mean[0], q1 = hi ? rs[1] : rs[0], m2 = hi ? mean[0] : mean[1], q2 = hi ? rs[0] : rs[1], cnt = 16;
#pragma unroll
      for (int o = 16; o; o >>= 1) {
        m2 = __shfl_xor_sync(0xffffffffu, m2, o); q2 = __shfl_xor_sync(0xffffffffu, q2, o);
        const float dl = m1 - m2;
        q2 = q1 = fmaf(dl * dl, cnt, q1 + q2); m2 = m1 = 0.5f * (m1 + m2);
        cnt *= 2;
      }
      q1 = rsqrtf(q1 * (1.f / DM) + 1e-5f);
      m2 = __shfl_xor_sync(0xffffffffu, m1, 16); q2 = __shfl_xor_sync(0xffffffffu, q1, 16);
      mean[0] = hi ? m2 : m1; mean[1] = hi ? m1 : m2; rs[0] = hi ? q2 : q1; rs[1] = hi ? q1 : q2;
    }
#pragma unroll
    for (int i = 0; i < 8; i++) {
      uint32_t y[4];
#pragma unroll
      for (int c = 0; c < 4; c++) { const uint32_t v = (&u[i].x)[c]; y[c] = pack_bf16((bf_lo(v) - mean[i >> 2]) * rs[i >> 2], (bf_hi(v) - mean[i >> 2]) * rs[i >> 2]); }
      stg128((char*)g_xn + off + i * 512, y[0], y[1], y[2], y[3]);
      u[i] = make_uint4(y[0], y[1], y[2], y[3]);
    }
    if (q == E_LI && (task & 15) >= 12) {
      uint32_t* const xr = g_xr[task >> 4] + lane * 32 + (task & 3);
#pragma unroll
      for (int i = 0; i < 16; i++) {
        const uint32_t a = (&u[i >> 2].x)[i & 3], b = (&u[4 + (i >> 2)].x)[i & 3];
        xr[(i >> 2) * 1024 + (i & 3) * 8] = __byte_perm(a, b, 0x5410); xr[(i >> 2) * 1024 + (i & 3) * 8 + 4] = __byte_perm(a, b, 0x7632);
      }
    }
    fence_proxy_global();
    __syncwarp();
    if (lane == 0) flag_add(q == E_LI ? &g_xa[0][ev] : q == E_LX2 ? &g_xa[1][ev] : &g_dep[q == E_LX1A ? E_G1 + ev : E_G2 + (ev >> 1)]);
    __syncwarp();
  }
}
}

__global__ void __cluster_dims__(2, 1, 1) __launch_bounds__(384, 1)
gemm_kernel(const __grid_constant__ gm::Maps M, const bf16* __restrict__ x, bf16* out) {
  using namespace gm;
  extern __shared__ __align__(1024) uint8_t smem[];
  const uint32_t sb = __shfl_sync(0xffffffffu, smem_u32(smem), 0);
  const int tid = threadIdx.x, wi = __shfl_sync(0xffffffffu, tid >> 5, 0);
  if (tid < 21) mbar_init(sb + BARS + tid * 8, tid == 14 || tid == 15 ? 4 : tid >= 6 && tid < 12 ? 2 : 1);
  fence_mbar_init();
  cluster_arrive(); cluster_wait();
  if (wi < 8) { reg_inc<208>(); consumer(sb, M, wi >> 2); cluster_arrive(); cluster_wait(); }
  else {
    reg_dec<88>();
    if (wi == 8) producer(sb, M);
    else if (wi == 11 && cluster_rank() == 0) scheduler(sb);
    else {
      norm_helper(x, out);
      asm volatile("griddepcontrol.wait;" ::: "memory");
      if (wi == 9 && blockIdx.x < 64) g_h2[(NSTEP - 1) & 3][blockIdx.x * 32 + (tid & 31)] = make_uint4(0, 0, 0, 0);
    }
    __syncwarp();
    cluster_arrive(); cluster_wait();
  }
}

typedef CUresult (*PFN_encodeTiled)(CUtensorMap*, CUtensorMapDataType, cuuint32_t, void*, const cuuint64_t*, const cuuint64_t*,
                                    const cuuint32_t*, const cuuint32_t*, CUtensorMapInterleave, CUtensorMapSwizzle,
                                    CUtensorMapL2promotion, CUtensorMapFloatOOBfill);
static PFN_encodeTiled g_encode = nullptr;
static CUtensorMap make_map(const void* ptr, uint64_t rows, uint64_t cols, uint32_t box_rows) {
  CUtensorMap m;
  cuuint64_t dims[2] = {cols, rows}, strides[1] = {cols * 2};
  cuuint32_t box[2] = {64, box_rows}, es[2] = {1, 1};
  g_encode(&m, CU_TENSOR_MAP_DATA_TYPE_BFLOAT16, 2, (void*)ptr, dims, strides, box, es, CU_TENSOR_MAP_INTERLEAVE_NONE,
           CU_TENSOR_MAP_SWIZZLE_128B, CU_TENSOR_MAP_L2_PROMOTION_L2_256B, CU_TENSOR_MAP_FLOAT_OOB_FILL_NONE);
  return m;
}

static CUtensorMap make_map3(const void* ptr, uint64_t d0, uint64_t d1, uint64_t d2, uint64_t stride2) {
  CUtensorMap m;
  cuuint64_t dims[3] = {d0, d1, d2}, strides[2] = {DM * 2, stride2};
  cuuint32_t box[3] = {64, 32, 2}, es[3] = {1, 1, 1};
  g_encode(&m, CU_TENSOR_MAP_DATA_TYPE_BFLOAT16, 3, (void*)ptr, dims, strides, box, es, CU_TENSOR_MAP_INTERLEAVE_NONE,
           CU_TENSOR_MAP_SWIZZLE_128B, CU_TENSOR_MAP_L2_PROMOTION_L2_256B, CU_TENSOR_MAP_FLOAT_OOB_FILL_NONE);
  return m;
}

extern "C" void kernel_launch(void* const* d_in, const int* in_sizes, int n_in, void* d_out, int out_size) {
  const bf16* x = (const bf16*)d_in[0];
  const bf16* mem0 = (const bf16*)d_in[1];
  if (!g_encode) {
    void* p = nullptr; cudaDriverEntryPointQueryResult q;
    cudaGetDriverEntryPoint("cuTensorMapEncodeTiled", &p, cudaEnableDefault, &q);
    g_encode = (PFN_encodeTiled)p;
    cudaFuncSetAttribute(gemm_kernel, cudaFuncAttributeMaxDynamicSharedMemorySize, gm::SMEM);
    cudaFuncSetAttribute(rec_kernel, cudaFuncAttributeMaxDynamicSharedMemorySize, rec::SMEM);
  }
  bf16 *xn, *ot, *hh;
  cudaGetSymbolAddress((void**)&xn, g_xn); cudaGetSymbolAddress((void**)&ot, g_ot); cudaGetSymbolAddress((void**)&hh, g_h);
  rec::Maps R;
  for (int i = 0; i < 3; i++) R.w[i] = make_map(d_in[2 + i], DM, NH * DH, 16);
  R.wo = make_map(d_in[5], NH * DH, DM, 128);
  R.xd = make_map3(xn, DM, SEQ - LAG * 32, 2, (uint64_t)LAG * 32 * DM * 2); R.xs = make_map3(xn, 64, SEQ, DM / 64, 128);
  gm::Maps G;
  G.ot = make_map(ot, NH * DH + O_LAYER / SEQ, SEQ, 64); G.wo = make_map(d_in[5], NH * DH, DM, 64); G.xn = make_map(xn, SEQ, DM, 64);
  G.wg = make_map(d_in[8], DM, DF, 64); G.wu = make_map(d_in[9], DM, DF, 64); G.hl = make_map(hh, SEQ, DF, 64); G.hs = make_map(hh, SEQ, DF, 128);
  G.wd = make_map(d_in[10], DF, DM, 64); G.out = make_map(d_out, SEQ, DM, 128);
  cudaLaunchConfig_t cfg = {};
  cudaLaunchAttribute at[1];
  cfg.attrs = at; cfg.numAttrs = 1;
  cfg.gridDim = dim3(3 * NH); cfg.blockDim = dim3(384); cfg.dynamicSmemBytes = rec::SMEM; cfg.stream = cudaStreamPerThread;
  at[0].id = cudaLaunchAttributeClusterDimension; at[0].val.clusterDim.y = at[0].val.clusterDim.z = 1;
  static int csize = 0;
  if (!csize) {
    int n = 0;
    at[0].val.clusterDim.x = 6;
    csize = cudaOccupancyMaxActiveClusters(&n, rec_kernel, &cfg) == cudaSuccess && n >= NH / 2 ? CSIZE : 3;
  }
  at[0].val.clusterDim.x = csize;
  cudaLaunchKernelEx(&cfg, rec_kernel, R, mem0);
  cfg.gridDim = dim3(132); cfg.blockDim = dim3(384); cfg.dynamicSmemBytes = gm::SMEM; cfg.stream = cudaStreamPerThread;
  at[0].id = cudaLaunchAttributeProgrammaticStreamSerialization; at[0].val.programmaticStreamSerializationAllowed = 1;
  cudaLaunchKernelEx(&cfg, gemm_kernel, G, x, (bf16*)d_out);
}
```

```cpp
#include <cuda_runtime.h>
#include <cuda_bf16.h>
#include <cuda.h>
#include <stdint.h>

#define DEVI __device__ __forceinline__
typedef __nv_bfloat16 bf16;

constexpr int SEQ = 2048, DM = 1024, NH = 32, DH = 128, DF = 3584, NSEG = 64;
#define LAG 20
constexpr int NSTEP = NSEG + LAG;

#define CSIZE 6
#define TSS 1
#define TSD 1900
constexpr size_t O_LAYER = 0;
__device__ __align__(1024) bf16 g_xn[SEQ * DM];
__device__ __align__(1024) bf16 g_ot[SEQ * NH * DH + O_LAYER];
__device__ __align__(1024) bf16 g_h[SEQ * DF];
__device__ __align__(1024) uint32_t g_xr[NSEG][DM * 4];
__device__ __align__(1024) uint2 g_h1[4][256 * 256];
__device__ __align__(1024) uint4 g_h2[4][2048];
__device__ __align__(128) uint32_t g_ts[2][32 * TSS];
enum { E_D1 = 0, E_G1 = 32, E_O1 = 48, E_O2 = 64, E_G2 = 80, E_D2 = 96,
       E_LI = 128, E_LX2 = 144, E_LX1A = 160, E_LX1B = 176, NEV = 256 };
__device__ __align__(128) int g_dep[NEV];
__device__ __align__(128) int g_claim[NEV];
__device__ __align__(128) int g_xa[2][32];

#define TUNE_DEFAULTS 1550, 2250, 5, 100, 100, 36, 14, 100
constexpr int c_D[8] = {TUNE_DEFAULTS};
template<int I> struct TPV { static constexpr int v = c_D[I]; };
#define TP(i) TPV<i>::v

DEVI uint32_t smem_u32(const void* p) { return (uint32_t)__cvta_generic_to_shared(p); }
DEVI void mbar_init(uint32_t bar, uint32_t cnt) { asm volatile("mbarrier.init.shared::cta.b64 [%0], %1;" :: "r"(bar), "r"(cnt) : "memory"); }
DEVI void mbar_arrive(uint32_t bar) { asm volatile("mbarrier.arrive.shared::cta.b64 _, [%0];" :: "r"(bar) : "memory"); }
DEVI bool mbar_try(uint32_t bar, uint32_t parity) {
  uint32_t p;
  asm volatile("{.reg .pred p; mbarrier.try_wait.parity.shared::cta.b64 p, [%1], %2; selp.u32 %0, 1, 0, p;}" : "=r"(p) : "r"(bar), "r"(parity) : "memory");
  return p;
}
DEVI bool mbar_test(uint32_t bar, uint32_t parity) {
  uint32_t p;
  asm volatile("{.reg .pred p; mbarrier.test_wait.parity.shared::cta.b64 p, [%1], %2; selp.u32 %0, 1, 0, p;}" : "=r"(p) : "r"(bar), "r"(parity) : "memory");
  return p;
}
constexpr int SPIN_BUDGET = 1 << 18;
DEVI void mbar_wait(uint32_t bar, uint32_t parity, int& budget) {
  while (!mbar_try(bar, parity)) { if (--budget < 0) break; }
}
DEVI bool mbar_try_cluster(uint32_t bar, uint32_t parity) {
  uint32_t p;
  asm volatile("{.reg .pred p; mbarrier.try_wait.parity.acquire.cluster.shared::cta.b64 p, [%1], %2; selp.u32 %0, 1, 0, p;}" : "=r"(p) : "r"(bar), "r"(parity) : "memory");
  return p;
}
DEVI void mbar_wait_cluster(uint32_t bar, uint32_t parity, int& budget) {
  while (!mbar_try_cluster(bar, parity)) { if (--budget < 0) break; }
}
DEVI uint32_t mapa(uint32_t addr, uint32_t rank) { uint32_t r; asm("mapa.shared::cluster.u32 %0, %1, %2;" : "=r"(r) : "r"(addr), "r"(rank)); return r; }
DEVI void cluster_arrive() { asm volatile("barrier.cluster.arrive.release.aligned;" ::: "memory"); }
DEVI void cluster_wait() { asm volatile("barrier.cluster.wait.acquire.aligned;" ::: "memory"); }
DEVI void fence_mbar_init() { asm volatile("fence.mbarrier_init.release.cluster;" ::: "memory"); }
DEVI void fence_proxy_async() { asm volatile("fence.proxy.async.shared::cta;" ::: "memory"); }
DEVI void fence_proxy_global() { asm volatile("fence.proxy.async.global;" ::: "memory"); }
#define ELECT "{.reg .pred p; elect.sync _|p, 0xffffffff;\n @p "
DEVI void e_expect_tx(uint32_t bar, uint32_t bytes) { asm volatile(ELECT "mbarrier.arrive.expect_tx.shared::cta.b64 _, [%0], %1;}" :: "r"(bar), "r"(bytes) : "memory"); }
DEVI void e_complete_tx(uint32_t bar, uint32_t bytes) { asm volatile("fence.acq_rel.cta;\n" ELECT "mbarrier.complete_tx.relaxed.cta.shared::cta.b64 [%0], %1;}" :: "r"(bar), "r"(bytes) : "memory"); }
DEVI void e_arrive(uint32_t bar) { asm volatile(ELECT "mbarrier.arrive.shared::cta.b64 _, [%0];}" :: "r"(bar) : "memory"); }
DEVI void e_tma_2d(uint32_t dst, const CUtensorMap* m, int c0, int c1, uint32_t bar) {
  asm volatile(ELECT "cp.async.bulk.tensor.2d.shared::cluster.global.mbarrier::complete_tx::bytes [%0], [%1, {%3, %4}], [%2];}"
    :: "r"(dst), "l"(m), "r"(bar), "r"(c0), "r"(c1) : "memory");
}
DEVI void e_prefetch_2d(const CUtensorMap* m, int c0, int c1) {
  asm volatile(ELECT "cp.async.bulk.prefetch.tensor.2d.L2.global [%0, {%1, %2}];}" :: "l"(m), "r"(c0), "r"(c1) : "memory");
}
DEVI void e_prefetch_3d(const CUtensorMap* m, int c0, int c1, int c2) {
  asm volatile(ELECT "cp.async.bulk.prefetch.tensor.3d.L2.global [%0, {%1, %2, %3}];}" :: "l"(m), "r"(c0), "r"(c1), "r"(c2) : "memory");
}
DEVI void e_bulk_g2s(uint32_t dst, const void* src, uint32_t bytes, uint32_t bar) {
  asm volatile(ELECT "cp.async.bulk.shared::cluster.global.mbarrier::complete_tx::bytes [%0], [%1], %2, [%3];}" :: "r"(dst), "l"(src), "r"(bytes), "r"(bar) : "memory");
}
DEVI void e_tma_3d(uint32_t dst, const CUtensorMap* m, int c0, int c1, int c2, uint32_t bar) {
  asm volatile(ELECT "cp.async.bulk.tensor.3d.shared::cluster.global.mbarrier::complete_tx::bytes [%0], [%1, {%3, %4, %5}], [%2];}"
    :: "r"(dst), "l"(m), "r"(bar), "r"(c0), "r"(c1), "r"(c2) : "memory");
}
DEVI void e_tma_3d_mc(uint32_t dst, const CUtensorMap* m, int c0, int c1, int c2, uint32_t bar, int rb) {
  asm volatile(ELECT "cp.async.bulk.tensor.3d.shared::cluster.global.mbarrier::complete_tx::bytes.multicast::cluster [%0], [%1, {%3, %4, %5}], [%2], %6;}"
    :: "r"(dst), "l"(m), "r"(bar), "r"(c0), "r"(c1), "r"(c2), "h"((uint16_t)(7 << rb)) : "memory");
}
DEVI void e_tma_2d_mc(uint32_t dst, const CUtensorMap* m, int c0, int c1, uint32_t bar) {
  asm volatile(ELECT "cp.async.bulk.tensor.2d.shared::cluster.global.mbarrier::complete_tx::bytes.multicast::cluster [%0], [%1, {%3, %4}], [%2], %5;}"
    :: "r"(dst), "l"(m), "r"(bar), "r"(c0), "r"(c1), "h"((uint16_t)3) : "memory");
}
DEVI void p_arrive_at(uint32_t bar, uint32_t rank, bool c) {
  asm volatile("{.reg .pred p; .reg .b32 a; setp.ne.u32 p, %2, 0; mapa.shared::cluster.u32 a, %0, %1; @p mbarrier.arrive.shared::cluster.b64 _, [a];}"
    :: "r"(bar), "r"(rank), "r"((uint32_t)c) : "memory");
}
DEVI void p_expect_tx(uint32_t bar, uint32_t bytes, bool c) {
  asm volatile("{.reg .pred p; setp.ne.u32 p, %2, 0; @p mbarrier.arrive.expect_tx.shared::cta.b64 _, [%0], %1;}" :: "r"(bar), "r"(bytes), "r"((uint32_t)c) : "memory");
}
DEVI void p_arrive(uint32_t bar, bool c) { asm volatile("{.reg .pred p; setp.ne.u32 p, %1, 0; @p mbarrier.arrive.shared::cta.b64 _, [%0];}" :: "r"(bar), "r"((uint32_t)c) : "memory"); }
DEVI void tma_store_2d(const CUtensorMap* m, uint32_t src, int c0, int c1) {
  asm volatile("cp.async.bulk.tensor.2d.global.shared::cta.bulk_group [%0, {%2, %3}], [%1];" :: "l"(m), "r"(src), "r"(c0), "r"(c1) : "memory");
}
DEVI void tma_radd_2d(const CUtensorMap* m, uint32_t src, int c0, int c1) {
  asm volatile("cp.reduce.async.bulk.tensor.2d.global.shared::cta.add.bulk_group [%0, {%2, %3}], [%1];" :: "l"(m), "r"(src), "r"(c0), "r"(c1) : "memory");
}
DEVI void bulk_commit() { asm volatile("cp.async.bulk.commit_group;" ::: "memory"); }
template<int N> DEVI void bulk_wait_read() { asm volatile("cp.async.bulk.wait_group.read %0;" :: "n"(N) : "memory"); }
template<int N> DEVI void bulk_wait() { asm volatile("cp.async.bulk.wait_group %0;" :: "n"(N) : "memory"); }
template<int ID, int N> DEVI void nbar_sync() { asm volatile("bar.sync %0, %1;" :: "n"(ID), "n"(N) : "memory"); }
template<int ID, int N> DEVI void nbar_arrive() { asm volatile("bar.arrive %0, %1;" :: "n"(ID), "n"(N) : "memory"); }
DEVI void nbar_sync_r(int id, int n) { asm volatile("bar.sync %0, %1;" :: "r"(id), "r"(n) : "memory"); }
template<int R> DEVI void reg_inc() { asm volatile("setmaxnreg.inc.sync.aligned.u32 %0;" :: "n"(R)); }
template<int R> DEVI void reg_dec() { asm volatile("setmaxnreg.dec.sync.aligned.u32 %0;" :: "n"(R)); }
DEVI void wg_fence() { asm volatile("wgmma.fence.sync.aligned;" ::: "memory"); }
DEVI void wg_commit() { asm volatile("wgmma.commit_group.sync.aligned;" ::: "memory"); }
template<int N> DEVI void wg_wait() { asm volatile("wgmma.wait_group.sync.aligned %0;" :: "n"(N) : "memory"); }
DEVI uint64_t mkdesc(uint32_t addr, uint32_t lbo, uint32_t sbo, uint32_t sw = 1) {
  return ((uint64_t)((addr & 0x3FFFF) >> 4)) | ((uint64_t)(lbo >> 4) << 16) | ((uint64_t)(sbo >> 4) << 32) | ((uint64_t)sw << 62);
}
constexpr uint32_t SMEM_BASE = 1024;
__host__ __device__ constexpr long long CD(uint32_t off, uint32_t lbo, uint32_t sbo, uint32_t sw) {
  return (long long)(((uint64_t)((SMEM_BASE + off) >> 4)) | ((uint64_t)(lbo >> 4) << 16) | ((uint64_t)(sbo >> 4) << 32) | ((uint64_t)sw << 62));
}
DEVI uint32_t pack_bf16(float lo, float hi) { uint32_t r; asm("cvt.rn.bf16x2.f32 %0, %1, %2;" : "=r"(r) : "f"(hi), "f"(lo)); return r; }
DEVI float bf_lo(uint32_t v) { return __uint_as_float(v << 16); }
DEVI float bf_hi(uint32_t v) { return __uint_as_float(v & 0xffff0000u); }
DEVI void ldsm4t(uint32_t addr, uint32_t& r0, uint32_t& r1, uint32_t& r2, uint32_t& r3) {
  asm volatile("ldmatrix.sync.aligned.m8n8.x4.trans.shared.b16 {%0,%1,%2,%3}, [%4];" : "=r"(r0), "=r"(r1), "=r"(r2), "=r"(r3) : "r"(addr) : "memory");
}
DEVI void stsm4(uint32_t addr, uint32_t r0, uint32_t r1, uint32_t r2, uint32_t r3) {
  asm volatile("stmatrix.sync.aligned.m8n8.x4.shared.b16 [%0], {%1,%2,%3,%4};" :: "r"(addr), "r"(r0), "r"(r1), "r"(r2), "r"(r3) : "memory");
}
DEVI uint2 lds64v(uint32_t a) { uint2 v; asm volatile("ld.volatile.shared.v2.u32 {%0,%1}, [%2];" : "=r"(v.x), "=r"(v.y) : "r"(a) : "memory"); return v; }
DEVI uint32_t lds32v(uint32_t a) { uint32_t v; asm volatile("ld.volatile.shared.u32 %0, [%1];" : "=r"(v) : "r"(a) : "memory"); return v; }
DEVI uint4 lds128v(uint32_t a) { uint4 v; asm volatile("ld.volatile.shared.v4.u32 {%0,%1,%2,%3}, [%4];" : "=r"(v.x), "=r"(v.y), "=r"(v.z), "=r"(v.w) : "r"(a) : "memory"); return v; }
DEVI void cp_async16(uint32_t dst, const void* src) { asm volatile("cp.async.cg.shared.global [%0], [%1], 16;" :: "r"(dst), "l"(src) : "memory"); }
DEVI void cp_async_wait() { asm volatile("cp.async.wait_all;" ::: "memory"); }
DEVI void sts32(uint32_t a, uint32_t x) { asm volatile("st.shared.u32 [%0], %1;" :: "r"(a), "r"(x) : "memory"); }
DEVI int lane_id() { int r; asm volatile("mov.u32 %0, %%laneid;" : "=r"(r)); return r; }
DEVI void sts64(uint32_t a, uint32_t x, uint32_t y) { asm volatile("st.shared.v2.u32 [%0], {%1,%2};" :: "r"(a), "r"(x), "r"(y) : "memory"); }
DEVI void sts128(uint32_t a, uint4 v) { asm volatile("st.shared.v4.u32 [%0], {%1,%2,%3,%4};" :: "r"(a), "r"(v.x), "r"(v.y), "r"(v.z), "r"(v.w) : "memory"); }
DEVI void st_async128(uint32_t a, uint32_t x, uint32_t y, uint32_t z, uint32_t w, uint32_t bar) {
  asm volatile("st.async.weak.shared::cluster.mbarrier::complete_tx::bytes.v4.b32 [%0], {%1,%2,%3,%4}, [%5];" :: "r"(a), "r"(x), "r"(y), "r"(z), "r"(w), "r"(bar) : "memory");
}
DEVI void st_async32(uint32_t a, uint32_t x, uint32_t bar) {
  asm volatile("st.async.weak.shared::cluster.mbarrier::complete_tx::bytes.b32 [%0], %1, [%2];" :: "r"(a), "r"(x), "r"(bar) : "memory");
}
DEVI uint4 ldg_rlx128(const void* p) {
  uint4 v;
  asm volatile("ld.relaxed.gpu.global.v4.b32 {%0,%1,%2,%3}, [%4];" : "=r"(v.x), "=r"(v.y), "=r"(v.z), "=r"(v.w) : "l"(p) : "memory");
  return v;
}
DEVI int ldg_rlx32(const void* p) { int v; asm volatile("ld.relaxed.gpu.global.b32 %0, [%1];" : "=r"(v) : "l"(p) : "memory"); return v; }
DEVI int ldg_acq32(const void* p) { int v; asm volatile("ld.acquire.gpu.global.b32 %0, [%1];" : "=r"(v) : "l"(p) : "memory"); return v; }
DEVI void stg_rlx128(void* p, uint32_t x, uint32_t y, uint32_t z, uint32_t w) {
  asm volatile("st.relaxed.gpu.global.v4.b32 [%0], {%1,%2,%3,%4};" :: "l"(p), "r"(x), "r"(y), "r"(z), "r"(w) : "memory");
}
DEVI void stg128(void* p, uint32_t x, uint32_t y, uint32_t z, uint32_t w) {
  asm volatile("st.global.v4.b32 [%0], {%1,%2,%3,%4};" :: "l"(p), "r"(x), "r"(y), "r"(z), "r"(w) : "memory");
}
DEVI uint2 ldg_rlx64(const void* p) { uint2 v; asm volatile("{.reg .b64 a; ld.relaxed.gpu.global.b64 a, [%2]; mov.b64 {%0,%1}, a;}" : "=r"(v.x), "=r"(v.y) : "l"(p) : "memory"); return v; }
DEVI void stg_rlx64(void* p, uint32_t x, uint32_t y) { asm volatile("{.reg .b64 a; mov.b64 a, {%1,%2}; st.relaxed.gpu.global.b64 [%0], a;}" :: "l"(p), "r"(x), "r"(y) : "memory"); }
DEVI void stg_rlx32(void* p, uint32_t x) { asm volatile("st.relaxed.gpu.global.b32 [%0], %1;" :: "l"(p), "r"(x) : "memory"); }
DEVI void flag_add(int* p) { asm volatile("fence.proxy.async.global; red.release.gpu.global.add.s32 [%0], 1;" :: "l"(p) : "memory"); }
DEVI void e_stg_rlx32(void* p, uint32_t x) { asm volatile(ELECT "st.relaxed.gpu.global.b32 [%0], %1;}" :: "l"(p), "r"(x) : "memory"); }
DEVI void e_flag_add(int* p) { asm volatile("fence.proxy.async.global;\n" ELECT "red.release.gpu.global.add.s32 [%0], 1;}" :: "l"(p) : "memory"); }
DEVI int cluster_rank() { int r; asm volatile("mov.u32 %0, %%cluster_ctarank;" : "=r"(r)); return __shfl_sync(0xffffffffu, r, 0); }
DEVI int cta_id() { int r; asm volatile("mov.u32 %0, %%ctaid.x;" : "=r"(r)); return __shfl_sync(0xffffffffu, r, 0); }
DEVI uint32_t clock32() { uint32_t c; asm volatile("mov.u32 %0, %%clock;" : "=r"(c)); return c; }
DEVI uint32_t gtime() { uint32_t c; asm volatile("mov.u32 %0, %%globaltimer_lo;" : "=r"(c)); return c; }
DEVI void wait_time(uint32_t t) { while (__any_sync(0xffffffffu, t - gtime() - 1 < 4000u)) {} }
DEVI void spin_until(uint32_t t0, int d) { while (__any_sync(0xffffffffu, (int)(clock32() - t0) < d)) {} }
DEVI void pin2(const void* a, const void* b) { asm volatile("{.reg .pred p; setp.eq.u64 p, %0, %1; @p st.volatile.global.u64 [%0], %1;}" :: "l"(a), "l"(b) : "memory"); }
DEVI void pin2(uint32_t a, uint32_t b) { asm volatile("{.reg .pred p; setp.eq.u32 p, %0, %1; @p st.volatile.shared.u32 [%0], %1;}" :: "r"(a), "r"(b) : "memory"); }
DEVI void p_stg_rlx64(void* p, uint32_t x, uint32_t y, bool c) {
  asm volatile("{.reg .pred p; .reg .b64 a; setp.ne.u32 p, %3, 0; mov.b64 a, {%1,%2}; @p st.relaxed.gpu.global.b64 [%0], a;}" :: "l"(p), "r"(x), "r"(y), "r"((uint32_t)c) : "memory");
}
DEVI void pin2(uint64_t a, uint64_t b) { pin2((const void*)a, (const void*)b); }
DEVI uint64_t pair(uint32_t a, uint32_t bar) { return a | (uint64_t)bar << 32; }
DEVI void st_async32(uint64_t q, uint32_t x) { st_async32((uint32_t)q, x, (uint32_t)(q >> 32)); }
DEVI void st_async128(uint64_t q, uint4 v) { st_async128((uint32_t)q, v.x, v.y, v.z, v.w, (uint32_t)(q >> 32)); }
DEVI float ex2(float x) { float r; asm("ex2.approx.ftz.f32 %0, %1;" : "=f"(r) : "f"(x)); return r; }
DEVI float rcp(float x) { float r; asm("rcp.approx.ftz.f32 %0, %1;" : "=f"(r) : "f"(x)); return r; }
DEVI uint32_t xor_or(uint32_t a, uint32_t t, uint32_t acc) { uint32_t r; asm("lop3.b32 %0, %1, %2, %3, 0xbe;" : "=r"(r) : "r"(a), "r"(t), "r"(acc)); return r; }
DEVI void stsm2(uint32_t addr, uint32_t r0, uint32_t r1) {
  asm volatile("stmatrix.sync.aligned.m8n8.x2.shared.b16 [%0], {%1,%2};" :: "r"(addr), "r"(r0), "r"(r1) : "memory");
}
DEVI uint32_t settag(uint32_t v, uint32_t tag) { return (v & ~1u) | tag; }

#define A4(c, o)  c(d[o+0]), c(d[o+1]), c(d[o+2]), c(d[o+3])
#define A8(c, o)  A4(c, o), A4(c, o+4)
#define A16(c, o) A8(c, o), A8(c, o+8)
#define A12(c, o) A8(c, o), A4(c, o+8)
#define A28(c, o) A16(c, o), A12(c, o+16)
#define RL12 "{%0,%1,%2,%3,%4,%5,%6,%7,%8,%9,%10,%11}"
#define RL28 "{%0,%1,%2,%3,%4,%5,%6,%7,%8,%9,%10,%11,%12,%13,%14,%15,%16,%17,%18,%19,%20,%21,%22,%23,%24,%25,%26,%27}"
#define A20(c, o) A16(c, o), A4(c, o+16)
#define A32(c, o) A16(c, o), A16(c, o+16)
#define RL8  "{%0,%1,%2,%3,%4,%5,%6,%7}"
#define RL16 "{%0,%1,%2,%3,%4,%5,%6,%7,%8,%9,%10,%11,%12,%13,%14,%15}"
#define RL20 "{%0,%1,%2,%3,%4,%5,%6,%7,%8,%9,%10,%11,%12,%13,%14,%15,%16,%17,%18,%19}"
#define RL32 "{%0,%1,%2,%3,%4,%5,%6,%7,%8,%9,%10,%11,%12,%13,%14,%15,%16,%17,%18,%19,%20,%21,%22,%23,%24,%25,%26,%27,%28,%29,%30,%31}"
#define RL64 "{%0,%1,%2,%3,%4,%5,%6,%7,%8,%9,%10,%11,%12,%13,%14,%15,%16,%17,%18,%19,%20,%21,%22,%23,%24,%25,%26,%27,%28,%29,%30,%31," \
  "%32,%33,%34,%35,%36,%37,%38,%39,%40,%41,%42,%43,%44,%45,%46,%47,%48,%49,%50,%51,%52,%53,%54,%55,%56,%57,%58,%59,%60,%61,%62,%63}"
#define WG_OP(shape) "wgmma.mma_async.sync.aligned." shape "k16.f32.bf16.bf16 "
#define DEF_WGMMA(N, RL, AL, i0, i1, i2, i3, i4, i5, i6)                                                                         \
  template<int SC, int TB, long long CB> DEVI void rs##N(float* d, const uint32_t* a) {                                          \
    if (SC) asm volatile("{.reg .b64 tb; mov.b64 tb, %" #i4 ";\n" WG_OP("m64n" #N) RL ", {%" #i0 ",%" #i1 ",%" #i2 ",%" #i3 "}, tb, 1, 1, 1, %" #i5 ";}" \
      : AL("+f", 0) : "r"(a[0]), "r"(a[1]), "r"(a[2]), "r"(a[3]), "n"(CB), "n"(TB));                                             \
    else asm volatile("{.reg .b64 tb; mov.b64 tb, %" #i4 ";\n" WG_OP("m64n" #N) RL ", {%" #i0 ",%" #i1 ",%" #i2 ",%" #i3 "}, tb, 0, 1, 1, %" #i5 ";}" \
      : AL("=f", 0) : "r"(a[0]), "r"(a[1]), "r"(a[2]), "r"(a[3]), "n"(CB), "n"(TB));                                             \
  }                                                                                                                              \
  template<int SC, int TA, int TB, long long CA, long long CB> DEVI void ss##N(float* d, uint32_t a) {                           \
    if (SC) asm volatile("{.reg .b64 ta, tb; .reg .b32 lo, hi; add.u32 lo, %" #i0 ", %" #i1 "; mov.b32 hi, %" #i2 "; mov.b64 ta, {lo, hi}; mov.b64 tb, %" #i3 ";\n" \
      WG_OP("m64n" #N) RL ", ta, tb, 1, 1, 1, %" #i4 ", %" #i5 ";}"                                                              \
      : AL("+f", 0) : "r"(a), "n"((int)CA), "n"((int)(CA >> 32)), "n"(CB), "n"(TA), "n"(TB));                                    \
    else asm volatile("{.reg .b64 ta, tb; .reg .b32 lo, hi; add.u32 lo, %" #i0 ", %" #i1 "; mov.b32 hi, %" #i2 "; mov.b64 ta, {lo, hi}; mov.b64 tb, %" #i3 ";\n" \
      WG_OP("m64n" #N) RL ", ta, tb, 0, 1, 1, %" #i4 ", %" #i5 ";}"                                                              \
      : AL("=f", 0) : "r"(a), "n"((int)CA), "n"((int)(CA >> 32)), "n"(CB), "n"(TA), "n"(TB));                                    \
  }
DEF_WGMMA(8, "{%0,%1,%2,%3}", A4, 4, 5, 6, 7, 8, 9, 10)
DEF_WGMMA(16, RL8, A8, 8, 9, 10, 11, 12, 13, 14)
DEF_WGMMA(32, RL16, A16, 16, 17, 18, 19, 20, 21, 22)
DEF_WGMMA(40, RL20, A20, 20, 21, 22, 23, 24, 25, 26)
DEF_WGMMA(24, RL12, A12, 12, 13, 14, 15, 16, 17, 18)
DEF_WGMMA(56, RL28, A28, 28, 29, 30, 31, 32, 33, 34)
template<int TA> DEVI void wgmma_n128(float* d, uint64_t a, uint64_t b, int scale_d) {
  asm volatile("{.reg .pred p; setp.ne.b32 p, %66, 0;\n" WG_OP("m64n128") RL64 ", %64, %65, p, 1, 1, %67, 1;}"
    : A32("+f", 0), A32("+f", 32) : "l"(a), "l"(b), "r"(scale_d), "n"(TA));
}

namespace rec {
constexpr int KR = 43;
constexpr uint32_t WSZ = (64 - KR) * 2048, STG = KR * 2048;
constexpr uint32_t WS = 0;
constexpr uint32_t RING = 2 * WSZ;
constexpr uint32_t OB = RING + 3 * 8192;
constexpr uint32_t PB = OB + 4096;
constexpr uint32_t WO = RING + 32768;
constexpr uint32_t ATT = WO + 5 * 16384;
constexpr uint32_t AK = ATT + 10240, AV = ATT + 20480;
constexpr uint32_t PAD = ATT + 30720;
constexpr uint32_t BARS = PAD + 128;
constexpr uint32_t B_XE = BARS  , B_FA = BARS + 64  , B_FB = BARS + 88, B_FO = BARS + 96;
constexpr uint32_t B_ME = BARS + 104  , B_WE = BARS + 136, B_PD = BARS + 144;
constexpr uint32_t B_XF = BARS + 152  , B_MF = BARS + 216  , B_CP = BARS + 248  , B_WT = BARS + 280  ;
constexpr uint32_t B_AB = BARS + 296, B_OB = BARS + 304, B_ST = BARS + 312  , B_WS = BARS + 328, B_WO = BARS + 336, B_AT = BARS + 352, B_AV = BARS + 360;
constexpr int NBAR = 46;
constexpr uint32_t M0 = BARS + 384;
constexpr uint32_t SMEM = 232448;
constexpr int NB_P = 1, NB_ST = 2, NB_O = 3, NB_W0 = 4, NB_W1 = 5;
__host__ __device__ constexpr int wo_tile(int rank, int g, int i) { return i < 2 ? i * 6 + rank * 2 + g : 13 + rank - g; }
constexpr long long D_W = CD(WS, 16, 1024, 1), D_X = CD(0, 16, 1024, 1), D_O = CD(OB, 128, 256, 0);
constexpr long long D_WO = CD(WO, 16, 1024, 1), D_QM = CD(ATT, 640, 0, 0), D_QT = CD(ATT + 128, 640, 64, 0), D_K = CD(AK, 640, 128, 0);
constexpr long long D_V = CD(AV, 128, 640, 0), D_P = CD(PB, 128, 768, 0);
struct Maps { CUtensorMap w[3], wo, xd, xs; };
__host__ __device__ constexpr uint32_t mslot(int c) { return (c ^ (c >> 1)) * 12288; }
__host__ __device__ constexpr uint32_t xslot(int s) { return s < 3 ? RING + s * 8192 : s < 5 ? WO + (s - 3) * 8192 : s < 7 ? WO + (s + 1) * 8192 : OB; }
__host__ __device__ constexpr bool k_smem(int k) { return k % 3 == 2; }
__host__ __device__ constexpr int k_idx(int k) { return k % 3 == 2 ? k / 3 : k - k / 3; }
__host__ __device__ constexpr int k_of_reg(int i) { return i + (i >> 1); }
__host__ __device__ constexpr int k_of_smem(int i) { return 3 * i + 2; }

#define RPROF(i)
#define RPROF_STEP
#define CPROF(i, v)

template<bool DUAL, int K0, int K1> DEVI void seq_mem(float* d, const uint32_t* w, uint32_t dw) {
  if constexpr (K0 < K1) {
    constexpr long long B = CD(RING, 128, DUAL ? 4096 : 8192, 0) + mslot(K0 >> 4) / 16 + (K0 & 15) * 16;
    if constexpr (DUAL) {
      if constexpr (!k_smem(K0)) rs24<K0 != 0, 1, B>(d, w + 4 * k_idx(K0)); else ss24<1, 1, 1, D_W + k_idx(K0) * 128, B>(d, dw);
    } else {
      if constexpr (!k_smem(K0)) rs16<K0 != 0, 1, B>(d, w + 4 * k_idx(K0)); else ss16<1, 1, 1, D_W + k_idx(K0) * 128, B>(d, dw);
    }
    seq_mem<DUAL, K0 + 1, K1>(d, w, dw);
  }
}
template<int N, int K0, int K1> DEVI void seq_tok(float* d, const uint32_t* w, uint32_t dw) {
  if constexpr (K0 < K1) {
    constexpr bool DUAL = N > 32;
    constexpr long long B = D_X + (DUAL ? xslot((K0 >> 2) & 7) / 16 : xslot(K0 >> 3) / 16 + ((K0 >> 2) & 1) * 256) + (K0 & 3) * 2;
    if constexpr (DUAL) {
      if constexpr (!k_smem(K0)) rs56<K0 != 0, 0, B>(d, w + 4 * k_idx(K0)); else ss56<1, 1, 0, D_W + k_idx(K0) * 128, B>(d, dw);
    } else if constexpr (N == 24) {
      if constexpr (!k_smem(K0)) rs24<K0 != 0, 0, B>(d, w + 4 * k_idx(K0)); else ss24<1, 1, 0, D_W + k_idx(K0) * 128, B>(d, dw);
    } else {
      if constexpr (!k_smem(K0)) rs32<K0 != 0, 0, B>(d, w + 4 * k_idx(K0)); else ss32<1, 1, 0, D_W + k_idx(K0) * 128, B>(d, dw);
    }
    seq_tok<N, K0 + 1, K1>(d, w, dw);
  }
}
template<int T, int K0> DEVI void seq_wo(float* d, uint32_t dw) {
  if constexpr (K0 < 8) { ss16<K0 != 0, 1, 1, D_WO + T * 1024 + K0 * 128, D_O + K0 * 32>(d, dw); seq_wo<T, K0 + 1>(d, dw); }
}
template<long long Q, int K0> DEVI void seq_s(float* d) {
  if constexpr (K0 < 8) { ss40<K0 != 0, 1, 1, Q + K0 * 80, D_K + K0 * 80>(d, 0); seq_s<Q, K0 + 1>(d); }
}
template<bool DUAL, int J> DEVI void load_x(uint32_t sb, const Maps* M, int t, int rb) {
  if (DUAL) e_tma_3d_mc(sb + xslot(J & 7), &M->xd, J * 64, (t - LAG) * 32, 0, sb + B_XF + (J & 7) * 8, rb);
  else e_tma_3d_mc(sb + xslot(J & 7), &M->xs, 0, (t < NSEG ? t : t - LAG) * 32, J * 2, sb + B_XF + (J & 7) * 8, rb);
}
DEVI void load_x_lent(uint32_t sb, const Maps* M, int t, int j) {
  const bool dual = t >= LAG && t < NSEG;
  const uint32_t dst = sb + (j == 3 ? xslot(3) : xslot(5));
#pragma unroll
  for (int i = 0; i < 2; i++)
    e_tma_3d(dst + i * 8192, dual ? &M->xd : &M->xs, dual ? (j + i) * 64 : 0, (t < LAG ? t : t - LAG) * 32, dual ? 0 : (j + i) * 2, sb + B_XF + (j + i) * 8);
}
struct True { static constexpr bool value = true; };
struct False { static constexpr bool value = false; };
struct Ctx { uint32_t sb; const Maps* M; int rb, rank, wi; bool lead; uint32_t par; };
#define PFN 2
#define XD 2
template<bool DUAL, int J> DEVI void tok_release(const Ctx& c, int t, int& budget) {
  constexpr int NC = DUAL ? 16 : 8, S = J & 7;
  if constexpr (J + 8 < NC) {
    p_arrive_at(c.sb + B_XE + S * 8, c.rb + J % 3, c.lead);
    p_expect_tx(c.sb + B_XF + S * 8, 8192, c.lead && c.wi == 0);
  } else if constexpr (S == 1 || S == 2 || S == 4 || S == 7) p_arrive(c.sb + B_ME + (S >> 1) * 8, c.lead);
  if constexpr (J == XD - 1) {
    if (c.rank == 1 && c.wi == 5) { mbar_wait(c.sb + B_FO, t & 1, budget); load_x<DUAL, 7>(c.sb, c.M, t, c.rb); }
  } else if constexpr (J >= XD && J - XD + 8 < NC) {
    constexpr int I = J - XD;
    if (c.rank == I % 3 && c.wi == (I & 1) * 4 + 1) { mbar_wait(c.sb + B_XE + I * 8, (t - LAG) & 1, budget); load_x<DUAL, I + 8>(c.sb, c.M, t, c.rb); }
  }
}
template<int N, int J, class F, class G> DEVI bool tok_pass(float* d, const uint32_t* w, uint32_t dw, Ctx& c, int t, int& budget, F after0, G setup) {
  constexpr bool DUAL = N > 32;
  constexpr int NC = DUAL ? 16 : 8, KC = 64 / NC;
  if constexpr (J < NC) {
    if constexpr (J > 1) mbar_wait(c.sb + B_XF + (J & 7) * 8, c.par ^ (J >> 3), budget);
    wg_fence();
    seq_tok<N, J * KC, (J + 1) * KC>(d, w, dw);
    wg_commit();
    if constexpr (J == 1) after0();
    if constexpr (J >= NC - 5 && J < NC - 2) setup(J - (NC - 5));
    if constexpr (J > 0) { wg_wait<1>(); tok_release<DUAL, J - 1>(c, t, budget); }
    return tok_pass<N, J + 1>(d, w, dw, c, t, budget, after0, setup);
  } else {
    const bool ok = mbar_test(c.sb + B_MF, t & 1);
    wg_wait<0>();
    tok_release<DUAL, NC - 1>(c, t, budget);
    if (!DUAL) c.par ^= 1;
    return ok;
  }
}
template<int NB> DEVI void pack_tok(uint32_t* e, const float* d) {
#pragma unroll
  for (int i = 0; i < 8; i++) if ((i & 3) < NB) e[i] = pack_bf16(d[4 * (i & 3) + 2 * (i >> 2)], d[4 * (i & 3) + 2 * (i >> 2) + 1]);
}
DEVI void push_tok(const uint32_t* e, uint32_t sb, uint32_t o, int r, int rank) {
  const uint32_t b = mapa(sb, r);
  st_async128(b + o, e[0], e[1], e[2], e[3], b + (rank == 2 ? B_AV : B_AT));
}
DEVI uint32_t h1_tag(int seg) { return ((seg >> 1) & 1) ^ 1; }
DEVI uint4 pack_part(const float* c, int t) {
  return make_uint4(settag(pack_bf16(c[0], c[1]), h1_tag(t)), pack_bf16(c[2], c[3]), settag(pack_bf16(c[4], c[5]), h1_tag(t - LAG)), pack_bf16(c[6], c[7]));
}
DEVI void put_part(char* p1, char* p2, uint4 z, int t) { p_stg_rlx64(p1, z.x, z.y, t < NSEG); p_stg_rlx64(p2, z.z, z.w, t >= LAG); }

DEVI void rec_math(const uint32_t sb, const int wi, const Maps& M) {
  const int h = cta_id() / 3, rb = cluster_rank() >= 3 ? 3 : 0, rank = cluster_rank() - rb;
  const int warp = wi & 3, wg = wi >> 2;
  const bool lead = (threadIdx.x & 127) == 0;
  int budget = SPIN_BUDGET;
  uint32_t w[4 * KR];
  Ctx cx{sb, &M, rb, rank, wi, lead, 0};
  {
    const int lane = lane_id();
    const uint32_t a = sb + wg * STG + ((lane & 7) + (lane >> 4) * 8) * 128 + (((warp * 2 + ((lane >> 3) & 1)) ^ (lane & 7)) << 4);
    mbar_wait(sb + B_ST + wg * 8, 0, budget);
#pragma unroll
    for (int k = 0; k < KR; k++) ldsm4t(a + k * 2048, w[4*k], w[4*k+1], w[4*k+2], w[4*k+3]);
    nbar_arrive<NB_ST, 384>();
    nbar_sync_r(NB_W0 + wg, 128);
    for (int i = 0; i < 5; i++) p_arrive_at(sb + B_FA + i * 8, rb + (i == 4), lead);
    mbar_wait(sb + B_WS, 0, budget);
  }
  uint4 z = make_uint4(0, 0, 0, 0);
  char *z1 = nullptr, *z2 = nullptr;
  uint32_t rt0 = 0, rt1 = 0;
  mbar_wait(sb + B_XF, 0, budget); mbar_wait(sb + B_XF + 8, 0, budget);
#pragma unroll 1
  for (int t = 0;; t++) {
    const uint32_t dw = wg * (WSZ >> 4);
    uint32_t e[16];
    bool ok;
    auto finish = [&]() { put_part(z1, z2, z, t - 1); p_arrive_at(sb + B_FO, rb + 1, lead); };
    const int seg = t - rank * LAG;
    const bool att = rank < 2 && (unsigned)seg < (unsigned)NSEG;
    char* p1;
    uint32_t pw, oo;
    uint64_t u0, u1;
    int lane;
    auto setup = [&](int part) {
      if (part == 0) {
        lane = lane_id();
      } else if (part == 1) {
        char* const p = (char*)g_h1 + ((wo_tile(rank, wg, 0) * 4 + warp) * 4 + (lane >> 3)) * 2048 + h * 64 + (lane & 7) * 8;
        p1 = p + (t & 1) * sizeof(g_h1[0]);
        pin2(p1, nullptr);
      } else if (part == 2) {
        oo = OB + (lane >> 4) * 2048 + warp * 512 + rank * 256 + (lane & 15) * 16;
        pw = sb + PB + (wg ? lane * 4 : 768 + warp * 768 + lane * 16);
        pin2(pw, oo);
      } else {
        if (wg) {
          const uint32_t ra = mapa(sb, rb + ((warp & 1) ? 2 : (rank ^ 1) & 1)), rc = mapa(sb, rb + ((warp & 1) ? (rank ^ 1) & 1 : 2));
          u0 = pair(ra + oo, ra + B_OB); u1 = pair(rc + oo, rc + B_OB);
        } else {
          u0 = (uint64_t)((char*)(g_ot + rank * O_LAYER) + (size_t)(h * DH + warp * 16 + (lane >> 2)) * (SEQ * 2) + seg * 64 + (lane & 3) * 16);
          u1 = (uint32_t)((lane & 24) + ((lane >> 2) & 1) + 2 * warp - 8 * (lane & 3));
        }
        pin2(u0, u1);
      }
    };
    RPROF_STEP;
    auto mem_pass = [&](auto dual_c) {
      constexpr bool DUAL = decltype(dual_c)::value;
      float m[DUAL ? 12 : 8];
      RPROF(8 + wg * 12 - 32);
      if (!ok) mbar_wait(sb + B_MF, t & 1, budget);
      wg_fence(); seq_mem<DUAL, 0, 8>(m, w, dw); wg_commit();
      const uint32_t ao = ATT + rank * 10240 + wi * 1280, to = ao + 128 + (lane & 3) * 128 + (lane >> 2) * 16;
      const int la = DUAL ? rank == 0 : t >= NSEG;
      RPROF(1 + wg * 12);
      if (DUAL && rank == 0) {
#pragma unroll
        for (int i = 0; i < 8; i++) { const uint32_t x = e[i]; e[i] = e[8 + i]; e[8 + i] = x; }
      }
      auto piece = [&](int i) { push_tok(e + 4 * i, sb, to + (i & 1) * 640, rb + (la ^ (i >> 1)), rank); };
      piece(0);
      wg_fence(); seq_mem<DUAL, 8, 16>(m, w, dw); wg_commit();
      piece(1);
      mbar_wait(sb + B_MF + 8, t & 1, budget);
      wg_fence(); seq_mem<DUAL, 16, 24>(m, w, dw); wg_commit();
      if (DUAL) piece(2);
      wg_fence(); seq_mem<DUAL, 24, 32>(m, w, dw); wg_commit();
      if (DUAL) piece(3);
      mbar_wait(sb + B_MF + 16, t & 1, budget);
      wg_fence(); seq_mem<DUAL, 32, 48>(m, w, dw); wg_commit();
      wg_wait<1>(); p_arrive(sb + B_PD, lead);
      const uint32_t r0 = mapa(sb, rb + la), r1 = mapa(sb, rb + (la ^ 1)), m0 = r0 + ao + lane * 4, m1 = r1 + ao + lane * 4, ab = rank == 2 ? B_AV : B_AB;
      const uint64_t q0 = pair(m0, r0 + ab), q1 = pair(m0 + 640, r0 + ab), q2 = pair(m1, r1 + ab), q3 = pair(m1 + 640, r1 + ab);
      pin2(q0, q1);
      if (DUAL) pin2(q2, q3);
      mbar_wait(sb + B_MF + 24, t & 1, budget);
      wg_fence(); seq_mem<DUAL, 48, 64>(m, w, dw); wg_commit();
      wg_wait<1>(); p_arrive_at(sb + B_FA, rb, lead);
      wg_wait<0>();
      const uint32_t a0 = pack_bf16(m[0], m[1]), a1 = pack_bf16(m[2], m[3]), a2 = pack_bf16(m[4], m[5]), a3 = pack_bf16(m[6], m[7]);
      if constexpr (DUAL) {
        st_async32(q0, la ? a2 : a0); st_async32(q1, la ? a3 : a1); st_async32(q2, la ? a0 : a2); st_async32(q3, la ? a1 : a3);
        rt0 = pack_bf16(m[8], m[9]); rt1 = pack_bf16(m[10], m[11]);
      } else { st_async32(q0, a0); st_async32(q1, a1); rt0 = a2; rt1 = a3; }
      p_arrive(sb + B_WE, lead);
    };
    if (t >= LAG && t < NSEG) {
      float d[28];
      ok = tok_pass<56, 0>(d, w, dw, cx, t, budget, finish, setup);
      pack_tok<4>(e + 8, d); pack_tok<3>(e, d + 16); e[3] = rt0; e[7] = rt1;
      mem_pass(True());
    } else {
      float d[16];
      if (t > 0) finish();
      if (t > 0 && t < LAG) {
        ok = tok_pass<24, 0>(d, w, dw, cx, t, budget, []() {}, setup);
        pack_tok<3>(e, d); e[3] = rt0; e[7] = rt1;
      } else {
        ok = tok_pass<32, 0>(d, w, dw, cx, t, budget, []() {}, setup);
        pack_tok<4>(e, d);
      }
      mem_pass(False());
    }
    {
      RPROF(2 + wg * 12);
      auto wo_ready = [&]() { if (t == 0) mbar_wait(sb + B_WO, 0, budget); if (t < NSTEP - 1) mbar_wait(sb + B_WT, t & 1, budget); };
      constexpr float SC = 0.08838834764831845f * 1.4426950408889634f;
      if (!att) wo_ready();
      else {
        float s[32];
        setup(3);
        if (wg) {
          uint32_t one[4];
#pragma unroll
          for (int i = 0; i < 4; i++) one[i] = 0x3F803F80u + (pw >> 31);
          mbar_wait_cluster(sb + B_AT, seg & 1, budget);
          mbar_wait_cluster(sb + B_AB, seg & 1, budget);
          fence_proxy_async();
          RPROF(3 + 12);
          wg_fence(); seq_s<D_QM, 0>(s); wg_commit();
          nbar_arrive<NB_P, 256>();
          if (warp == 1) sts32(pw + 640, 0);
          mbar_wait_cluster(sb + B_AV, seg & 1, budget);
          wg_wait<0>();
          float mx = fmaxf(fmaxf(fmaxf(s[0], s[1]), fmaxf(s[4], s[5])), fmaxf(fmaxf(fmaxf(s[8], s[9]), fmaxf(s[12], s[13])), fmaxf(s[16], s[17])));
          const float x1 = __shfl_xor_sync(0xffffffffu, mx, 1), x2 = __shfl_xor_sync(0xffffffffu, mx, 2), x3 = __shfl_xor_sync(0xffffffffu, mx, 3);
          const float u = (warp & 2) ? ((warp & 1) ? s[16] : s[12]) : ((warp & 1) ? s[8] : s[4]);
          const float v = (warp & 2) ? ((warp & 1) ? s[17] : s[13]) : ((warp & 1) ? s[9] : s[5]);
          const float ms = -SC * fmaxf(fmaxf(mx, x1), fmaxf(x2, x3));
          sts32(pw + 128 + warp * 128, pack_bf16(ex2(fmaf(u, SC, ms)), ex2(fmaf(v, SC, ms))));
          if (warp == 0) sts32(pw, pack_bf16(ex2(fmaf(s[0], SC, ms)), ex2(fmaf(s[1], SC, ms))));
          fence_proxy_async();
          nbar_sync<NB_W1, 128>();
          RPROF(4 + 12);
          wg_fence();
          rs8<0, 0, D_P>(s + 8, one); rs8<1, 0, D_P + 16>(s + 8, one); rs8<1, 0, D_P + 32>(s + 8, one);
          wg_commit();
          ss8<0, 0, 0, D_V, D_P>(s, 0); ss8<0, 0, 0, D_V + 320, D_P>(s + 4, 0);
          ss8<1, 0, 0, D_V + 16, D_P + 16>(s, 0); ss8<1, 0, 0, D_V + 336, D_P + 16>(s + 4, 0);
          ss8<1, 0, 0, D_V + 32, D_P + 32>(s, 0); ss8<1, 0, 0, D_V + 352, D_P + 32>(s + 4, 0);
          wg_commit();
          wg_wait<1>();
          const float i0 = rcp(s[8]), i1 = rcp(s[9]);
          wg_wait<0>();
          stsm4(sb + oo, pack_bf16(s[0] * i0, s[1] * i1), pack_bf16(s[2] * i0, s[3] * i1), pack_bf16(s[4] * i0, s[5] * i1), pack_bf16(s[6] * i0, s[7] * i1));
          __syncwarp();
          const uint4 y = lds128v(sb + oo);
          if (t < NSTEP - 1) { st_async128(u0, y); st_async128(u1, y); e_complete_tx(sb + B_OB, 512); }
          wo_ready();
        } else {
          const int lim = (int)u1;
          char* const og = (char*)u0;
          nbar_sync<NB_P, 256>();
          RPROF(3);
          wg_fence();
          seq_s<D_QT, 0>(s);
          wg_commit();
          mbar_wait_cluster(sb + B_AV, seg & 1, budget);
          wg_wait<0>();
#pragma unroll
          for (int i = 0; i < 8; i++) { float& v = s[4 + 4 * (i >> 1) + (i & 1)]; v = i <= lim ? v : -INFINITY; }
          float mx = fmaxf(fmaxf(fmaxf(s[0], s[1]), fmaxf(s[4], s[5])), fmaxf(fmaxf(fmaxf(s[8], s[9]), fmaxf(s[12], s[13])), fmaxf(s[16], s[17])));
          const float x1 = __shfl_xor_sync(0xffffffffu, mx, 1), x2 = __shfl_xor_sync(0xffffffffu, mx, 2), x3 = __shfl_xor_sync(0xffffffffu, mx, 3);
          const float ms = -SC * fmaxf(fmaxf(mx, x1), fmaxf(x2, x3));
#pragma unroll
          for (int i = 0; i < 10; i++) { float& v = s[4 * (i >> 1) + (i & 1)]; v = ex2(fmaf(v, SC, ms)); }
          const float sum = (((s[0] + s[1]) + (s[4] + s[5])) + ((s[8] + s[9]) + (s[12] + s[13]))) + (s[16] + s[17]);
          const float y1 = __shfl_xor_sync(0xffffffffu, sum, 1), y2 = __shfl_xor_sync(0xffffffffu, sum, 2), y3 = __shfl_xor_sync(0xffffffffu, sum, 3);
          const float inv = rcp((sum + y1) + (y2 + y3));
          stsm4(pw, pack_bf16(s[0] * inv, s[1] * inv), pack_bf16(s[4] * inv, s[5] * inv), pack_bf16(s[8] * inv, s[9] * inv), pack_bf16(s[12] * inv, s[13] * inv));
          stsm2(pw + 512, pack_bf16(s[16] * inv, s[17] * inv), 0);
          fence_proxy_async();
          nbar_sync<NB_W0, 128>();
          RPROF(4);
          wg_fence();
          ss32<0, 0, 0, D_V, D_P + 48>(s, 0); ss32<0, 0, 0, D_V + 320, D_P + 48>(s + 16, 0);
          ss32<1, 0, 0, D_V + 16, D_P + 64>(s, 0); ss32<1, 0, 0, D_V + 336, D_P + 64>(s + 16, 0);
          ss32<1, 0, 0, D_V + 32, D_P + 80>(s, 0); ss32<1, 0, 0, D_V + 352, D_P + 80>(s + 16, 0);
          wg_commit();
          wo_ready();
          wg_wait<0>();
#pragma unroll
          for (int i = 0; i < 4; i++) {
            const float* d = s + (i >> 1) * 16 + (i & 1) * 2;
            stg128(og + ((i >> 1) * 64 + (i & 1) * 8) * (SEQ * 2), pack_bf16(d[0], d[1]), pack_bf16(d[4], d[5]), pack_bf16(d[8], d[9]), pack_bf16(d[12], d[13]));
          }
          if ((seg & 3) == 3) nbar_arrive<NB_O, 160>();
        }
      }
      RPROF(5 + wg * 12);
      const bool three = wg == 1 || rank == 2;
      char* const p2 = p1 + (2 + ((t - LAG) & 1) - (t & 1)) * (int)sizeof(g_h1[0]);
      if (t < NSTEP - 1) {
        float c[24];
        const uint32_t dt = wg ? 0 : 3072;
        mbar_wait_cluster(sb + B_OB, t & 1, budget);
        fence_proxy_async();
        RPROF(6 + wg * 12);
        wg_fence(); seq_wo<0, 0>(c, dt); wg_commit(); seq_wo<1, 0>(c + 8, dt); wg_commit();
        mbar_wait(sb + B_XF, cx.par, budget);
        wg_wait<1>();
        if (warp == 2) load_x_lent(sb, &M, t + 1, wg ? 3 : 5);
        put_part(p1, p2, pack_part(c, t), t);
        const int o3 = (wo_tile(rank, wg, three ? 2 : 1) - wo_tile(rank, wg, 0)) * 32768;
        z1 = p1 + o3; z2 = p2 + o3;
        if (three) {
          wg_fence(); seq_wo<2, 0>(c + 16, dt); wg_commit();
          wg_wait<1>(); put_part(p1 + 6 * 32768, p2 + 6 * 32768, pack_part(c + 8, t), t);
          mbar_wait(sb + B_XF + 8, cx.par, budget);
          wg_wait<0>(); z = pack_part(c + 16, t);
        } else { mbar_wait(sb + B_XF + 8, cx.par, budget); wg_wait<0>(); z = pack_part(c + 8, t); }
      } else {
        for (int i = 0; i < (three ? 3 : 2); i++) stg_rlx64(p2 + (wo_tile(rank, wg, i) - wo_tile(rank, wg, 0)) * 32768, 0, 0);
        break;
      }
      RPROF(7 + wg * 12);
    }
  }
}

DEVI void wait_xa(const int* p, int& budget) {
  while (__any_sync(0xffffffffu, ldg_acq32(p) < 64) && --budget > 0) {}
  fence_proxy_global();
}
template<bool DUAL> DEVI void first_loads(uint32_t sb, const Maps* M, int n, int h, int rb, int& budget) {
#pragma unroll
  for (int i = 0; i < PFN; i++) {
    if (DUAL) e_prefetch_3d(&M->xd, ((h + i * (16 / PFN)) & 15) * 64, (n - LAG) * 32, 0);
    else e_prefetch_3d(&M->xs, 0, (n < NSEG ? n : n - LAG) * 32, ((h + i * (8 / PFN)) & 7) * 2);
  }
  if (n + 1 < NSEG) asm volatile(ELECT "cp.async.bulk.prefetch.L2.global [%0], 2048;}" :: "l"((const char*)g_xr[n + 1] + (h & 7) * 2048) : "memory");
  mbar_wait(sb + B_FA, n & 1, budget);
  load_x<DUAL, 0>(sb, M, n, rb); load_x<DUAL, 1>(sb, M, n, rb); load_x<DUAL, 2>(sb, M, n, rb);
}
template<bool DUAL> DEVI void lent_loads(uint32_t sb, const Maps* M, int n, int rb, int& budget) {
  mbar_wait(sb + B_FB, n & 1, budget);
  load_x<DUAL, 3>(sb, M, n, rb); load_x<DUAL, 4>(sb, M, n, rb); load_x<DUAL, 5>(sb, M, n, rb); load_x<DUAL, 6>(sb, M, n, rb);
}
DEVI void rec_comm(const uint32_t sb, const int warp, const Maps& M, const bf16* __restrict__ mem0) {
  const int lane = threadIdx.x & 31, h = cta_id() / 3, rb = cluster_rank() >= 3 ? 3 : 0, rank = cluster_rank() - rb;
  int budget = SPIN_BUDGET;
  const bool two = warp == 3 || (rank == 2 && warp == 2);
  const int ntask = two ? 2 : 1, qi = two ? (warp == 3 ? rank : 3) : rank * 3 + warp;
  const int task0 = two ? h * 2 + (qi >> 1) : 64 + h * 4 + (qi >> 1);
  auto h2_word = [&](int i, int ln) {
    const int task = task0 + i * 192;
    return (char*)g_h2 + (task >> 6) * 8192 + ((qi ^ i) & 1) * 4096 + ((task >> 2) & 15) * 256 + (task & 3) * 32 + (ln & 8) * 16 + (ln & 7) * 4;
  };
  auto first_x = [&](int t) {
    const int n = t + 1;
    p_expect_tx(sb + B_XF + (lane_id() & 7) * 8, 8192, lane_id() < 8);
    if (rank == 0) {
      if (n >= LAG && ((n - LAG) & 3) == 0) wait_xa(&g_xa[1][(n - LAG) >> 2], budget);
      if (n >= LAG && n < NSEG) first_loads<true>(sb, &M, n, h, rb, budget); else first_loads<false>(sb, &M, n, h, rb, budget);
    }
  };
  {
    const int task = task0 + (lane >> 4) * 192, L = (task & 3) * 8 + (lane & 7);
    if ((lane >> 4) < ntask) {
      const bf16* p = mem0 + (L & 3) * 2 * DM + (task >> 2) * 16 + (L >> 2) + (lane & 8);
      uint32_t m0 = (uint32_t)__bfloat16_as_ushort(p[0]) | (uint32_t)__bfloat16_as_ushort(p[DM]) << 16;
      m0 = m0 ? m0 : 0x8000u;
      if (((qi ^ (lane >> 4)) & 1) == 0) stg_rlx32(h2_word(lane >> 4, lane), m0);
      sts32(sb + M0 + warp * 128 + lane * 4, m0);
    }
    __syncwarp();
    nbar_sync<NB_ST, 384>();
    if (warp == 2) {
      e_expect_tx(sb + B_WS, 2 * WSZ);
#pragma unroll 1
      for (int i = 0; i < 2 * (64 - KR); i++) e_tma_2d(sb + WS + (i & 1) * WSZ + (i >> 1) * 2048, &M.w[rank], h * DH + (i & 1) * 64, k_of_smem(i >> 1) * 16, sb + B_WS);
      const int nt = rank == 2 ? 6 : 5;
      e_expect_tx(sb + B_WO, (nt - 2) * 16384);
#pragma unroll 1
      for (int i = 1; i < nt; i++) if (i != 3) e_tma_2d(sb + WO + i * 16384, &M.wo, wo_tile(rank, 1 - i / 3, i % 3) * 64, h * DH, sb + B_WO);
    }
    wait_xa(&g_xa[0][0], budget);
    if (warp == 3) { first_x(-1); if (rank == 0) lent_loads<false>(sb, &M, 0, rb, budget); }
  }
  uint32_t t0 = gtime() - 4000, cpp = 0;
  const uint32_t cp = sb + B_CP + warp * 8;
#pragma unroll 1
  for (int t = 0;; t++) {
    const int n = t + 1, seg = t - rank * LAG;
    RPROF_STEP;
    const bool att = rank < 2 && (unsigned)seg < (unsigned)NSEG;
    if (warp == 3) {
      if (att) { e_expect_tx(sb + B_AT, 16384); e_expect_tx(sb + B_AB, 4096); e_expect_tx(sb + B_AV, 10240); }
      if (n < NSTEP) e_expect_tx(sb + B_OB, t < NSEG && t >= LAG ? 4096 : 2048);
    }
    {
      const bool dual = t >= LAG && t < NSEG;
      const uint32_t lo = t >= NSEG ? 4096 : 0, dst = sb + RING + mslot(warp), bytes = dual ? 8192 : 4096;
      const uint32_t chk = dst + lane_id() * 32 + (lane_id() >> 2) * 4;
      mbar_wait(sb + B_ME + warp * 8, t & 1, budget);
      uint32_t tx = bytes;
      if (n < NSEG) { e_bulk_g2s(dst + 8192, (const char*)g_xr[n] + warp * 4096, 4096, cp); tx += 4096; }
      wait_time(t0 + TP(1) + warp * TP(4));
      RPROF(24); CPROF(0, gtime());
      int tries = 0;
      while (true) {
        tries++;
        e_bulk_g2s(dst, (const char*)g_h2[t & 3] + warp * 8192 + lo, bytes, cp);
        e_expect_tx(cp, tx); tx = bytes;
        mbar_wait(cp, cpp, budget); cpp ^= 1;
        uint32_t mn = min(min(lds32v(chk), lds32v(chk + 1024)), min(lds32v(chk + 2048), lds32v(chk + 3072)));
        if (dual) mn = min(min(mn, min(lds32v(chk + 4096), lds32v(chk + 5120))), min(lds32v(chk + 6144), lds32v(chk + 7168)));
        if (!__any_sync(0xffffffffu, mn == 0) || --budget < 0) break;
      }
      e_arrive(sb + B_MF + warp * 8);
      RPROF(25); CPROF(1, gtime()); CPROF(2, tries);
      if (n + 1 < NSEG && (n & 3) == 3) wait_xa(&g_xa[0][(n + 1) >> 2], budget);
    }
    {
      const int ln = lane_id(), i = ln >> 4;
      char* const w = h2_word(i, ln);
      if (i < ntask) {
        stg_rlx32(w + ((t + 3) & 3) * sizeof(g_h2[0]), 0);
        if (n == LAG && ((qi ^ i) & 1)) stg_rlx32(w + (n & 3) * sizeof(g_h2[0]), lds32v(sb + M0 + warp * 128 + ln * 4));
      }
      __syncwarp();
    }
    if (n < NSTEP) {
      const uint32_t tag = (n >> 1) & 31;
      mbar_wait(sb + B_PD, t & 1, budget);
      t0 = clock32();
      if (warp == 2) {
        mbar_wait(sb + B_ME + 24, t & 1, budget);
        e_expect_tx(sb + B_WT, 32768);
        e_tma_2d(sb + WO + 49152, &M.wo, wo_tile(rank, 0, 0) * 64, h * DH, sb + B_WT);
        mbar_wait(sb + B_WE, t & 1, budget);
        e_tma_2d(sb + WO, &M.wo, wo_tile(rank, 1, 0) * 64, h * DH, sb + B_WT);
      }
      if (warp == 3) first_x(t);
      if (warp == 0 && rank == (t >= NSEG)) { mbar_wait(sb + B_AB, seg & 1, budget); e_stg_rlx32(&g_ts[t & 1][h * TSS], (gtime() & ~31u) | tag); }
      spin_until(t0, TSD);
      uint32_t v;
      do { v = ldg_rlx32(&g_ts[t & 1][lane_id() * TSS]); } while (__any_sync(0xffffffffu, (v & 31) != tag) && --budget > 0);
      const uint32_t now = __shfl_sync(0xffffffffu, v, 0);
      t0 = now + __reduce_max_sync(0xffffffffu, (int)(v - now));
      if (warp == 3) mbar_wait(sb + B_OB, t & 1, budget);
    }
    if (n < NSTEP) {
      RPROF(26); CPROF(3, t0);
#pragma unroll 1
      for (int i = 0; i < ntask; i++) {
        const int layer = (qi ^ i) & 1, sg = t - layer * LAG, task = task0 + i * 192;
        if ((unsigned)sg >= (unsigned)(NSEG - 1)) continue;
        const uint32_t tag = h1_tag(sg);
        const int ln = lane_id();
        const char* const src = (const char*)g_h1[layer * 2 + (sg & 1)] + task * 2048 + ln * 8;
        char* const dst = h2_word(i, ln) + (n & 3) * sizeof(g_h2[0]);
        uint2 v[8];
        pin2(src, dst);
        wait_time(t0 + TP(0) + (task < 96 ? 0 : task < 192 ? TP(3) : 2 * TP(3)));
        int tries = 0;
        float a[4];
        while (true) {
          tries++;
#pragma unroll
          for (int k = 0; k < 8; k++) v[k] = ldg_rlx64(src + k * 256);
          uint32_t bad = 0;
#pragma unroll
          for (int k = 0; k < 8; k++) {
            bad = xor_or(v[k].x, tag, bad);
            a[0] = k ? a[0] + bf_lo(v[k].x) : bf_lo(v[k].x); a[1] = k ? a[1] + bf_hi(v[k].x) : bf_hi(v[k].x);
            a[2] = k ? a[2] + bf_lo(v[k].y) : bf_lo(v[k].y); a[3] = k ? a[3] + bf_hi(v[k].y) : bf_hi(v[k].y);
          }
#pragma unroll
        for (int k = 0; k < 2; k++) {
          const float keep = (ln & 8) ? a[2+k] : a[k], send = (ln & 8) ? a[k] : a[2+k];
          a[k] = keep + __shfl_xor_sync(0xffffffffu, send, 8);
        }
#pragma unroll
        for (int k = 0; k < 2; k++) a[k] += __shfl_xor_sync(0xffffffffu, a[k], 16);
          if (!__any_sync(0xffffffffu, bad & 1) || --budget < 0) break;
        }
        const uint32_t out = pack_bf16(a[0], a[1]);
        if (ln < 16) stg_rlx32(dst, out ? out : 0x8000u);
        __syncwarp();
        if (i == 0) { RPROF(28); CPROF(6, gtime()); CPROF(4, gtime()); CPROF(5, tries); } else CPROF(7, gtime());
      }
    }
    if (warp == (t >= LAG && t < NSEG ? 2 : 1) && att && (seg & 3) == 3) { nbar_sync<NB_O, 160>(); e_flag_add(&g_dep[E_O1 + rank * 16 + (seg >> 2)]); }
    if (n == NSTEP) break;
  }
  if (h == 0 && rank == 0 && warp < 2) g_xa[warp][lane_id()] = 0;
}
}

__global__ void __launch_bounds__(384, 1)
rec_kernel(const __grid_constant__ rec::Maps M, const bf16* __restrict__ mem0) {
  using namespace rec;
  extern __shared__ __align__(1024) uint8_t smem[];
  const uint32_t sb = __shfl_sync(0xffffffffu, smem_u32(smem), 0);
  const int tid = threadIdx.x, wi = __shfl_sync(0xffffffffu, tid >> 5, 0);
  if ((sb & 0x3FFFF) != SMEM_BASE) __trap();
  if (wi == 0) {
    const int h = cta_id() / 3, rank = cta_id() - h * 3;
    for (int i = tid; i < NBAR; i += 32) mbar_init(sb + BARS + i * 8, i < 13 ? 6 : i < 19 ? 2 : 1);
    ((uint32_t*)(smem + PAD))[tid] = 0;
    fence_mbar_init(); fence_proxy_async();
    __syncwarp();
    e_expect_tx(sb + B_ST, STG); e_expect_tx(sb + B_ST + 8, STG);
    for (int i = 0; i < 2 * KR; i++) e_tma_2d(sb + (i & 1) * STG + (i >> 1) * 2048, &M.w[rank], h * DH + (i & 1) * 64, k_of_reg(i >> 1) * 16, sb + B_ST + (i & 1) * 8);
  } else if (wi == 1) {
    if (blockIdx.x < NEV / 32) { g_dep[blockIdx.x * 32 + (tid & 31)] = 0; g_claim[blockIdx.x * 32 + (tid & 31)] = 0; __threadfence(); }
    __syncwarp();
    asm volatile("griddepcontrol.launch_dependents;" ::: "memory");
  }
  cluster_arrive(); cluster_wait();
  if (wi < 8) { reg_inc<232>(); rec_math(sb, wi, M); cluster_arrive(); cluster_wait(); }
  else { reg_dec<40>(); rec_comm(sb, wi & 3, M, mem0); cluster_arrive(); cluster_wait(); }
}

namespace gm {
struct Maps { CUtensorMap ot, wo, xn, wg, wu, hl, hs, wd, out; };
constexpr int STAGES = 6, STAGE = 32768;
constexpr uint32_t SO = STAGES * STAGE, BARS = SO + 32768;
constexpr uint32_t B_FULL = BARS, B_EMPTY = BARS + 48, B_TF = BARS + 96, B_TE = BARS + 112, B_ORD = BARS + 128, B_PM = BARS + 144, B_GO = BARS + 160;
constexpr uint32_t MAIL = BARS + 176, PMAIL = BARS + 192;
constexpr uint32_t SMEM = BARS + 256;
constexpr int END = -1;

struct Tile {
  bool isO, isG, l2; int blk, col, k0, n;
  DEVI Tile(int task, int rank) {
    const int e = task >> 8, id = task & 255;
    const bool isD = e < E_G1 || e >= E_D2;
    isO = e >= E_O1 && e < E_G2; isG = !isD && !isO; l2 = e >= E_O2;
    blk = isG && l2 ? (e & 15) * 2 + rank : isD && !l2 ? e >> 1 : e & 15;
    col = isG ? (l2 ? id : id * 2 + rank) : (id & 3) * 2 + rank;
    k0 = isO ? (id >> 2) * 2048 : isG ? 0 : ((l2 ? e >> 4 : e) & 1) * 1792;
    n = isO ? 32 : isG ? 16 : 28;
  }
};

DEVI float geglu(float g, float u) {
  const float z = g * (0.7978845608028654f + 0.035677408136300125f * g * g);
  float t; asm("tanh.approx.f32 %0, %1;" : "=f"(t) : "f"(z));
  const float hg = 0.5f * g;
  return fmaf(hg, t, hg) * u;
}
struct Sched {
  int need, size;
  bool filler;
  uint4 dep, cl;
  DEVI void init(int lane) {
    const int e = lane * 4;
    const bool d = e < E_G1 || e >= E_D2, o = e >= E_O1 && e < E_G2;
    need = d ? 28 : e < E_O1 ? 64 : o ? 32 : 128;
    size = d ? 4 : o ? 8 : e < E_O1 ? 28 : e < E_G2 + 8 ? 56 : 0;
    filler = (int)blockIdx.x < TP(5);
  }
  DEVI void scan(int lane) { cl = ldg_rlx128(g_claim + lane * 4); dep = ldg_rlx128(g_dep + lane * 4); }
  DEVI int next(int lane, int& budget) {
    while (--budget > 0) {
      int av[4], open = 0;
#pragma unroll
      for (int i = 0; i < 4; i++) { const int r = max(size - (int)(&cl.x)[i], 0); open |= r; av[i] = ((int)(&dep.x)[i] >= need ? r : 0) + (i ? av[i - 1] : 0); }
      const uint32_t mo = __ballot_sync(0xffffffffu, open);
      if (!mo) break;
      if (filler) {
        const int x = TP(6) & 3, dx = x == 0 ? dep.x : x == 1 ? dep.y : x == 2 ? dep.z : dep.w;
        filler = !__any_sync(0xffffffffu, lane == (E_O1 + TP(6)) >> 2 && dx >= need);
      }
      if (!filler && (mo & 0xffff) && lane >= E_O2 / 4) av[3] = 0;
      int inc = av[3], pos = 0;
      while (true) {
        const uint32_t m = __ballot_sync(0xffffffffu, inc > pos && av[3]);
        if (!m) break;
        const int l = __ffs(m) - 1, rel = pos - (inc - av[3]), i = (rel >= av[0]) + (rel >= av[1]) + (rel >= av[2]);
        int r = 0;
        if (lane == l) {
          const int tk = atomicAdd(g_claim + lane * 4 + i, 1);
          r = tk < size ? (lane * 4 + i) << 8 | tk : -1 - (inc - av[3] + (i == 0 ? av[0] : i == 1 ? av[1] : i == 2 ? av[2] : av[3]) + tk - size);
        }
        r = __shfl_sync(0xffffffffu, r, l);
        if (r >= 0) return r;
        if (pos == 0) {
#pragma unroll
          for (int o = 1; o < 32; o <<= 1) { const int v = __shfl_up_sync(0xffffffffu, inc, o); if (lane >= o) inc += v; }
        }
        pos = -1 - r;
      }
      if (pos == 0) __nanosleep(TP(7));
      scan(lane);
    }
    return END;
  }
};

DEVI void scheduler(const uint32_t sb) {
  const int lane = threadIdx.x & 31;
  int budget = SPIN_BUDGET;
  Sched sc; sc.init(lane);
#pragma unroll 1
  for (int i = 0;; i++) {
    mbar_wait(sb + B_GO, (i & 1) ^ 1, budget);
    sc.scan(lane);
    const int task = sc.next(lane, budget);
    const uint32_t r = mapa(sb, lane & 1);
    if (lane < 2) st_async32(r + PMAIL + (i & 1) * 4, task, r + B_PM + (i & 1) * 8);
    __syncwarp();
    if (task == END) break;
  }
}

DEVI void producer(const uint32_t sb, const Maps& M) {
  const int lane = threadIdx.x & 31, rank = cluster_rank();
  int budget = SPIN_BUDGET, s = 0, ph = 0;
#pragma unroll 1
  for (int i = 0;; i++) {
    e_expect_tx(sb + B_PM + (i & 1) * 8, 4);
    mbar_wait_cluster(sb + B_PM + (i & 1) * 8, (i >> 1) & 1, budget);
    const int task = budget < 0 ? END : __shfl_sync(0xffffffffu, (int)lds32v(sb + PMAIL + (i & 1) * 4), 0);
    fence_proxy_global();
    for (int z = 0; z < (task == END ? 2 : 1); z++) {
      const int g = (i + z) & 1;
      mbar_wait(sb + B_TE + g * 8, (((i + z) >> 1) & 1) ^ 1, budget);
      if (lane == 0) { sts64(sb + MAIL + g * 8, task, s | ph << 8); mbar_arrive(sb + B_TF + g * 8); }
      __syncwarp();
    }
    if (task == END) break;
    const Tile T(task, rank);
    const bool shareB = T.isG && T.l2;
    const CUtensorMap* mA = T.isO ? &M.ot : T.isG ? &M.xn : &M.hl;
    const CUtensorMap* mB0 = T.isO ? &M.wo : T.isG ? &M.wg : &M.wd;
    const CUtensorMap* mB1 = T.isG ? &M.wu : mB0;
    const int c0 = T.col * (T.isG ? 64 : 128), c1 = T.isG ? c0 : c0 + 64, row = T.blk * 128;
    const int ok = 0;
    int k = T.k0;
#pragma unroll 1
    for (int it = 0; it < T.n; it++, k += 64) {
      const uint32_t a = sb + s * STAGE, fb = sb + B_FULL + s * 8;
      mbar_wait(sb + B_EMPTY + s * 8, ph ^ 1, budget);
      e_expect_tx(fb, STAGE);
      if (shareB) {
        e_tma_2d_mc(a + 16384 + rank * 8192, rank ? mB1 : mB0, c0, k, fb);
        e_tma_2d(a, mA, k, row, fb); e_tma_2d(a + 8192, mA, k, row + 64, fb);
      } else {
        e_tma_2d_mc(a + rank * 8192, mA, T.isO ? row + rank * 64 : k, T.isO ? k + ok : row + rank * 64, fb);
        e_tma_2d(a + 16384, mB0, c0, k, fb); e_tma_2d(a + 24576, mB1, c1, k, fb);
      }
      if (it == T.n - TP(2)) e_arrive(sb + B_GO);
      if (++s == STAGES) { s = 0; ph ^= 1; }
    }
  }
}

template<int TA> DEVI void mainloop(float* d0, float* d1, uint32_t sb, int n, int s, int ph, bool lead, uint32_t ord, int& budget) {
  int prev = 0;
  const uint32_t rel = threadIdx.x & 127;
#pragma unroll 1
  for (int i = 0; i < n; i++) {
    mbar_wait(sb + B_FULL + s * 8, ph, budget);
    const uint32_t a = sb + s * STAGE;
    const uint64_t da = mkdesc(a, 16, 1024), db = mkdesc(a + 16384, 8192, 1024);
    wg_fence();
#pragma unroll
    for (int k = 0; k < 4; k++) {
      wgmma_n128<TA>(d0, da + k * (TA ? 128 : 2), db + k * 128, (i | k) != 0);
      wgmma_n128<TA>(d1, da + 512 + k * (TA ? 128 : 2), db + k * 128, (i | k) != 0);
    }
    wg_commit();
    if (i > 0) { wg_wait<1>(); p_arrive_at(sb + B_EMPTY + prev * 8, rel & 1, rel < 2); }
    prev = s;
    if (++s == STAGES) { s = 0; ph ^= 1; }
  }
  p_arrive(ord, lead);
  wg_wait<0>();
  p_arrive_at(sb + B_EMPTY + prev * 8, rel & 1, rel < 2);
}

DEVI void consumer(const uint32_t sb, const Maps& M, const int wg) {
  const int tid = threadIdx.x, lane = tid & 31, warp = (tid >> 5) & 3;
  const bool lead = (tid & 127) == 0;
  const uint32_t so = sb + SO + wg * 16384;
  int budget = SPIN_BUDGET;
  float d0[64], d1[64];
#pragma unroll 1
  for (int m = 0;; m++) {
    mbar_wait(sb + B_TF + wg * 8, m & 1, budget);
    const uint2 mail = lds64v(sb + MAIL + wg * 8);
    const int task = __shfl_sync(0xffffffffu, (int)mail.x, 0), pos = __shfl_sync(0xffffffffu, (int)mail.y, 0);
    e_arrive(sb + B_TE + wg * 8);
    if (task == END || budget < 0) break;
    const Tile T(task, cluster_rank());
    mbar_wait(sb + B_ORD + wg * 8, (m & 1) ^ wg ^ 1, budget);
    if (T.isO) mainloop<1>(d0, d1, sb, 32, pos & 255, pos >> 8, lead, sb + B_ORD + (wg ^ 1) * 8, budget);
    else mainloop<0>(d0, d1, sb, T.n, pos & 255, pos >> 8, lead, sb + B_ORD + (wg ^ 1) * 8, budget);
    const uint32_t st = so + (warp * 16 + (lane & 15)) * 128;
    if (T.isG) {
#pragma unroll
      for (int mm = 0; mm < 2; mm++) {
        const float* d = mm ? d1 : d0;
#pragma unroll
        for (int c = 0; c < 4; c++) {
          uint32_t r[4];
#pragma unroll
          for (int i = 0; i < 4; i++) r[i] = pack_bf16(geglu(d[8*c+2*i], d[32+8*c+2*i]), geglu(d[8*c+2*i+1], d[33+8*c+2*i]));
          stsm4(st + mm * 8192 + (((2 * c + (lane >> 4)) ^ (lane & 7)) << 4), r[0], r[1], r[2], r[3]);
        }
      }
      fence_proxy_async();
      nbar_sync_r(1 + wg, 128);
      if (lead) {
        tma_store_2d(&M.hs, so, T.col * 64, T.blk * 128);
        bulk_commit(); bulk_wait<0>();
        flag_add(&g_dep[T.l2 ? E_D2 + (T.col >= 28) * 16 + T.blk : E_D1 + T.blk * 2 + (T.col >= 28)]);
      }
    } else {
#pragma unroll
      for (int hf = 0; hf < 2; hf++) {
        if (hf) { if (lead) bulk_wait_read<0>(); nbar_sync_r(1 + wg, 128); }
#pragma unroll
        for (int mm = 0; mm < 2; mm++) {
          const float* d = (mm ? d1 : d0) + hf * 32;
#pragma unroll
          for (int c = 0; c < 4; c++)
            stsm4(st + mm * 8192 + (((2 * c + (lane >> 4)) ^ (lane & 7)) << 4), pack_bf16(d[8*c], d[8*c+1]), pack_bf16(d[8*c+2], d[8*c+3]),
                  pack_bf16(d[8*c+4], d[8*c+5]), pack_bf16(d[8*c+6], d[8*c+7]));
        }
        fence_proxy_async();
        nbar_sync_r(1 + wg, 128);
        if (lead) { tma_radd_2d(&M.out, so, T.col * 128 + hf * 64, T.blk * 128); bulk_commit(); }
      }
      if (lead) {
        bulk_wait<0>();
        if (T.isO || !T.l2) flag_add(&g_dep[(!T.isO ? E_LX2 : T.l2 ? E_LX1B : E_LX1A) + T.blk]);
      }
    }
    __syncwarp();
  }
}

DEVI void norm_helper(const bf16* __restrict__ x, bf16* out) {
  const int lane = threadIdx.x & 31;
  int budget = SPIN_BUDGET, tk = lane < 4 ? -1 : 1024;
#pragma unroll 1
  while (--budget > 0) {
    if (tk < 0) tk = atomicAdd(g_claim + E_LI + lane, 1);
    if (__all_sync(0xffffffffu, tk >= 1024)) break;
    const uint32_t m = __ballot_sync(0xffffffffu, tk < 1024 && (lane == 0 || ldg_acq32(g_dep + E_LI + lane * 16 + (tk >> 6)) >= 16));
    if (!m) { __nanosleep(TP(7)); continue; }
    const int ql = __ffs(m) - 1, task = __shfl_sync(0xffffffffu, tk, ql), q = E_LI + ql * 16, ev = task >> 6;
    if (lane == ql) tk = -1;
    const size_t off = (size_t)task * (DM * 4) + lane * 16;
    const char* src = (const char*)(q == E_LI ? x : out) + off;
    uint4 u[8];
#pragma unroll
    for (int i = 0; i < 8; i++) u[i] = ldg_rlx128(src + i * 512);
    if (q == E_LI) {
#pragma unroll
      for (int i = 0; i < 8; i++) stg128((char*)out + off + i * 512, u[i].x, u[i].y, u[i].z, u[i].w);
    }
    float mean[2], rs[2];
#pragma unroll
    for (int r = 0; r < 2; r++) {
      float s0 = 0, s1 = 0;
#pragma unroll
      for (int i = 0; i < 16; i++) { const uint32_t v = (&u[4*r + (i >> 2)].x)[i & 3]; s0 += bf_lo(v); s1 += bf_hi(v); }
      mean[r] = (s0 + s1) * (1.f / 32);
      s0 = s1 = 0;
#pragma unroll
      for (int i = 0; i < 16; i++) { const uint32_t v = (&u[4*r + (i >> 2)].x)[i & 3]; const float a = bf_lo(v) - mean[r], b = bf_hi(v) - mean[r]; s0 = fmaf(a, a, s0); s1 = fmaf(b, b, s1); }
      rs[r] = s0 + s1;
    }
    {
      const bool hi = lane & 16;
      float m1 = hi ? mean[1] : mean[0], q1 = hi ? rs[1] : rs[0], m2 = hi ? mean[0] : mean[1], q2 = hi ? rs[0] : rs[1], cnt = 16;
#pragma unroll
      for (int o = 16; o; o >>= 1) {
        m2 = __shfl_xor_sync(0xffffffffu, m2, o); q2 = __shfl_xor_sync(0xffffffffu, q2, o);
        const float dl = m1 - m2;
        q2 = q1 = fmaf(dl * dl, cnt, q1 + q2); m2 = m1 = 0.5f * (m1 + m2);
        cnt *= 2;
      }
      q1 = rsqrtf(q1 * (1.f / DM) + 1e-5f);
      m2 = __shfl_xor_sync(0xffffffffu, m1, 16); q2 = __shfl_xor_sync(0xffffffffu, q1, 16);
      mean[0] = hi ? m2 : m1; mean[1] = hi ? m1 : m2; rs[0] = hi ? q2 : q1; rs[1] = hi ? q1 : q2;
    }
#pragma unroll
    for (int i = 0; i < 8; i++) {
      uint32_t y[4];
#pragma unroll
      for (int c = 0; c < 4; c++) { const uint32_t v = (&u[i].x)[c]; y[c] = pack_bf16((bf_lo(v) - mean[i >> 2]) * rs[i >> 2], (bf_hi(v) - mean[i >> 2]) * rs[i >> 2]); }
      stg128((char*)g_xn + off + i * 512, y[0], y[1], y[2], y[3]);
      u[i] = make_uint4(y[0], y[1], y[2], y[3]);
    }
    if (q == E_LI && (task & 15) >= 12) {
      uint32_t* const xr = g_xr[task >> 4] + lane * 32 + (task & 3);
#pragma unroll
      for (int i = 0; i < 16; i++) {
        const uint32_t a = (&u[i >> 2].x)[i & 3], b = (&u[4 + (i >> 2)].x)[i & 3];
        xr[(i >> 2) * 1024 + (i & 3) * 8] = __byte_perm(a, b, 0x5410); xr[(i >> 2) * 1024 + (i & 3) * 8 + 4] = __byte_perm(a, b, 0x7632);
      }
    }
    fence_proxy_global();
    __syncwarp();
    if (lane == 0) flag_add(q == E_LI ? &g_xa[0][ev] : q == E_LX2 ? &g_xa[1][ev] : &g_dep[q == E_LX1A ? E_G1 + ev : E_G2 + (ev >> 1)]);
    __syncwarp();
  }
}
}

__global__ void __cluster_dims__(2, 1, 1) __launch_bounds__(384, 1)
gemm_kernel(const __grid_constant__ gm::Maps M, const bf16* __restrict__ x, bf16* out) {
  using namespace gm;
  extern __shared__ __align__(1024) uint8_t smem[];
  const uint32_t sb = __shfl_sync(0xffffffffu, smem_u32(smem), 0);
  const int tid = threadIdx.x, wi = __shfl_sync(0xffffffffu, tid >> 5, 0);
  if (tid < 21) mbar_init(sb + BARS + tid * 8, tid == 14 || tid == 15 ? 4 : tid >= 6 && tid < 12 ? 2 : 1);
  fence_mbar_init();
  cluster_arrive(); cluster_wait();
  if (wi < 8) { reg_inc<208>(); consumer(sb, M, wi >> 2); cluster_arrive(); cluster_wait(); }
  else {
    reg_dec<88>();
    if (wi == 8) producer(sb, M);
    else if (wi == 11 && cluster_rank() == 0) scheduler(sb);
    else {
      norm_helper(x, out);
      asm volatile("griddepcontrol.wait;" ::: "memory");
      if (wi == 9 && blockIdx.x < 64) g_h2[(NSTEP - 1) & 3][blockIdx.x * 32 + (tid & 31)] = make_uint4(0, 0, 0, 0);
    }
    __syncwarp();
    cluster_arrive(); cluster_wait();
  }
}

typedef CUresult (*PFN_encodeTiled)(CUtensorMap*, CUtensorMapDataType, cuuint32_t, void*, const cuuint64_t*, const cuuint64_t*,
                                    const cuuint32_t*, const cuuint32_t*, CUtensorMapInterleave, CUtensorMapSwizzle,
                                    CUtensorMapL2promotion, CUtensorMapFloatOOBfill);
static PFN_encodeTiled g_encode = nullptr;
static CUtensorMap make_map(const void* ptr, uint64_t rows, uint64_t cols, uint32_t box_rows) {
  CUtensorMap m;
  cuuint64_t dims[2] = {cols, rows}, strides[1] = {cols * 2};
  cuuint32_t box[2] = {64, box_rows}, es[2] = {1, 1};
  g_encode(&m, CU_TENSOR_MAP_DATA_TYPE_BFLOAT16, 2, (void*)ptr, dims, strides, box, es, CU_TENSOR_MAP_INTERLEAVE_NONE,
           CU_TENSOR_MAP_SWIZZLE_128B, CU_TENSOR_MAP_L2_PROMOTION_L2_256B, CU_TENSOR_MAP_FLOAT_OOB_FILL_NONE);
  return m;
}

static CUtensorMap make_map3(const void* ptr, uint64_t d0, uint64_t d1, uint64_t d2, uint64_t stride2) {
  CUtensorMap m;
  cuuint64_t dims[3] = {d0, d1, d2}, strides[2] = {DM * 2, stride2};
  cuuint32_t box[3] = {64, 32, 2}, es[3] = {1, 1, 1};
  g_encode(&m, CU_TENSOR_MAP_DATA_TYPE_BFLOAT16, 3, (void*)ptr, dims, strides, box, es, CU_TENSOR_MAP_INTERLEAVE_NONE,
           CU_TENSOR_MAP_SWIZZLE_128B, CU_TENSOR_MAP_L2_PROMOTION_L2_256B, CU_TENSOR_MAP_FLOAT_OOB_FILL_NONE);
  return m;
}

extern "C" void kernel_launch(void* const* d_in, const int* in_sizes, int n_in, void* d_out, int out_size) {
  const bf16* x = (const bf16*)d_in[0];
  const bf16* mem0 = (const bf16*)d_in[1];
  if (!g_encode) {
    void* p = nullptr; cudaDriverEntryPointQueryResult q;
    cudaGetDriverEntryPoint("cuTensorMapEncodeTiled", &p, cudaEnableDefault, &q);
    g_encode = (PFN_encodeTiled)p;
    cudaFuncSetAttribute(gemm_kernel, cudaFuncAttributeMaxDynamicSharedMemorySize, gm::SMEM);
    cudaFuncSetAttribute(rec_kernel, cudaFuncAttributeMaxDynamicSharedMemorySize, rec::SMEM);
  }
  bf16 *xn, *ot, *hh;
  cudaGetSymbolAddress((void**)&xn, g_xn); cudaGetSymbolAddress((void**)&ot, g_ot); cudaGetSymbolAddress((void**)&hh, g_h);
  rec::Maps R;
  for (int i = 0; i < 3; i++) R.w[i] = make_map(d_in[2 + i], DM, NH * DH, 16);
  R.wo = make_map(d_in[5], NH * DH, DM, 128);
  R.xd = make_map3(xn, DM, SEQ - LAG * 32, 2, (uint64_t)LAG * 32 * DM * 2); R.xs = make_map3(xn, 64, SEQ, DM / 64, 128);
  gm::Maps G;
  G.ot = make_map(ot, NH * DH + O_LAYER / SEQ, SEQ, 64); G.wo = make_map(d_in[5], NH * DH, DM, 64); G.xn = make_map(xn, SEQ, DM, 64);
  G.wg = make_map(d_in[8], DM, DF, 64); G.wu = make_map(d_in[9], DM, DF, 64); G.hl = make_map(hh, SEQ, DF, 64); G.hs = make_map(hh, SEQ, DF, 128);
  G.wd = make_map(d_in[10], DF, DM, 64); G.out = make_map(d_out, SEQ, DM, 128);
  cudaLaunchConfig_t cfg = {};
  cudaLaunchAttribute at[1];
  cfg.attrs = at; cfg.numAttrs = 1;
  cfg.gridDim = dim3(3 * NH); cfg.blockDim = dim3(384); cfg.dynamicSmemBytes = rec::SMEM; cfg.stream = cudaStreamPerThread;
  at[0].id = cudaLaunchAttributeClusterDimension; at[0].val.clusterDim.y = at[0].val.clusterDim.z = 1;
  static int csize = 0;
  if (!csize) {
    int n = 0;
    at[0].val.clusterDim.x = 6;
    csize = cudaOccupancyMaxActiveClusters(&n, rec_kernel, &cfg) == cudaSuccess && n >= NH / 2 ? CSIZE : 3;
  }
  at[0].val.clusterDim.x = csize;
  cudaLaunchKernelEx(&cfg, rec_kernel, R, mem0);
  cfg.gridDim = dim3(132); cfg.blockDim = dim3(384); cfg.dynamicSmemBytes = gm::SMEM; cfg.stream = cudaStreamPerThread;
  at[0].id = cudaLaunchAttributeProgrammaticStreamSerialization; at[0].val.programmaticStreamSerializationAllowed = 1;
  cudaLaunchKernelEx(&cfg, gemm_kernel, G, x, (bf16*)d_out);
}
```

```cpp
#include <cuda_runtime.h>
#include <cuda_bf16.h>
#include <cuda.h>
#include <stdint.h>

#define DEVI __device__ __forceinline__
typedef __nv_bfloat16 bf16;

constexpr int SEQ = 2048, DM = 1024, NH = 32, DH = 128, DF = 3584, NSEG = 64;
#define LAG 20
constexpr int NSTEP = NSEG + LAG;

#define CSIZE 6
#define SLEEP 1
#define TSS 1
#define TSD 1700
constexpr size_t O_LAYER = 0;
__device__ __align__(1024) bf16 g_xn[SEQ * DM];
__device__ __align__(1024) bf16 g_ot[SEQ * NH * DH + O_LAYER];
__device__ __align__(1024) bf16 g_h[SEQ * DF];
__device__ __align__(1024) uint32_t g_xr[NSEG][DM * 4];
__device__ __align__(1024) uint2 g_h1[4][256 * 256];
__device__ __align__(1024) uint4 g_h2[4][2048];
__device__ __align__(128) uint32_t g_ts[2][32 * TSS];
enum { E_D1 = 0, E_G1 = 32, E_O1 = 48, E_O2 = 64, E_G2 = 80, E_D2 = 96,
       E_LI = 128, E_LX2 = 144, E_LX1A = 160, E_LX1B = 176, NEV = 256 };
__device__ __align__(128) int g_dep[NEV];
__device__ __align__(128) int g_claim[NEV];
__device__ __align__(128) int g_xa[2][32];

#define TUNE_DEFAULTS 1650, 2350, 6, 50, 100, 8, 14, 100, 1550, 2200, 100, 125, 1550, 2250, 200, 0
constexpr int c_D[16] = {TUNE_DEFAULTS};
template<int I> struct TPV { static constexpr int v = c_D[I]; };
#define TP(i) TPV<i>::v

DEVI uint32_t smem_u32(const void* p) { return (uint32_t)__cvta_generic_to_shared(p); }
DEVI void mbar_init(uint32_t bar, uint32_t cnt) { asm volatile("mbarrier.init.shared::cta.b64 [%0], %1;" :: "r"(bar), "r"(cnt) : "memory"); }
DEVI void mbar_arrive(uint32_t bar) { asm volatile("mbarrier.arrive.shared::cta.b64 _, [%0];" :: "r"(bar) : "memory"); }
DEVI bool mbar_try(uint32_t bar, uint32_t parity) {
  uint32_t p;
  asm volatile("{.reg .pred p; mbarrier.try_wait.parity.shared::cta.b64 p, [%1], %2; selp.u32 %0, 1, 0, p;}" : "=r"(p) : "r"(bar), "r"(parity) : "memory");
  return p;
}
DEVI bool mbar_test(uint32_t bar, uint32_t parity) {
  uint32_t p;
  asm volatile("{.reg .pred p; mbarrier.test_wait.parity.shared::cta.b64 p, [%1], %2; selp.u32 %0, 1, 0, p;}" : "=r"(p) : "r"(bar), "r"(parity) : "memory");
  return p;
}
constexpr int SPIN_BUDGET = 1 << 18;
DEVI void mbar_wait(uint32_t bar, uint32_t parity, int& budget) {
  while (!mbar_try(bar, parity)) { if (--budget < 0) break; }
}
DEVI bool mbar_try_cluster(uint32_t bar, uint32_t parity) {
  uint32_t p;
  asm volatile("{.reg .pred p; mbarrier.try_wait.parity.acquire.cluster.shared::cta.b64 p, [%1], %2; selp.u32 %0, 1, 0, p;}" : "=r"(p) : "r"(bar), "r"(parity) : "memory");
  return p;
}
DEVI void mbar_wait_cluster(uint32_t bar, uint32_t parity, int& budget) {
  while (!mbar_try_cluster(bar, parity)) { if (--budget < 0) break; }
}
DEVI uint32_t mapa(uint32_t addr, uint32_t rank) { uint32_t r; asm("mapa.shared::cluster.u32 %0, %1, %2;" : "=r"(r) : "r"(addr), "r"(rank)); return r; }
DEVI void cluster_arrive() { asm volatile("barrier.cluster.arrive.release.aligned;" ::: "memory"); }
DEVI void cluster_wait() { asm volatile("barrier.cluster.wait.acquire.aligned;" ::: "memory"); }
DEVI void fence_mbar_init() { asm volatile("fence.mbarrier_init.release.cluster;" ::: "memory"); }
DEVI void fence_proxy_async() { asm volatile("fence.proxy.async.shared::cta;" ::: "memory"); }
DEVI void fence_proxy_global() { asm volatile("fence.proxy.async.global;" ::: "memory"); }
#define ELECT "{.reg .pred p; elect.sync _|p, 0xffffffff;\n @p "
DEVI void e_expect_tx(uint32_t bar, uint32_t bytes) { asm volatile(ELECT "mbarrier.arrive.expect_tx.shared::cta.b64 _, [%0], %1;}" :: "r"(bar), "r"(bytes) : "memory"); }
DEVI void e_complete_tx(uint32_t bar, uint32_t bytes) { asm volatile("fence.acq_rel.cta;\n" ELECT "mbarrier.complete_tx.relaxed.cta.shared::cta.b64 [%0], %1;}" :: "r"(bar), "r"(bytes) : "memory"); }
DEVI void e_arrive(uint32_t bar) { asm volatile(ELECT "mbarrier.arrive.shared::cta.b64 _, [%0];}" :: "r"(bar) : "memory"); }
DEVI void e_tma_2d(uint32_t dst, const CUtensorMap* m, int c0, int c1, uint32_t bar) {
  asm volatile(ELECT "cp.async.bulk.tensor.2d.shared::cluster.global.mbarrier::complete_tx::bytes [%0], [%1, {%3, %4}], [%2];}"
    :: "r"(dst), "l"(m), "r"(bar), "r"(c0), "r"(c1) : "memory");
}
DEVI void e_prefetch_2d(const CUtensorMap* m, int c0, int c1) {
  asm volatile(ELECT "cp.async.bulk.prefetch.tensor.2d.L2.global [%0, {%1, %2}];}" :: "l"(m), "r"(c0), "r"(c1) : "memory");
}
DEVI void e_prefetch_3d(const CUtensorMap* m, int c0, int c1, int c2) {
  asm volatile(ELECT "cp.async.bulk.prefetch.tensor.3d.L2.global [%0, {%1, %2, %3}];}" :: "l"(m), "r"(c0), "r"(c1), "r"(c2) : "memory");
}
DEVI void e_bulk_g2s(uint32_t dst, const void* src, uint32_t bytes, uint32_t bar) {
  asm volatile(ELECT "cp.async.bulk.shared::cluster.global.mbarrier::complete_tx::bytes [%0], [%1], %2, [%3];}" :: "r"(dst), "l"(src), "r"(bytes), "r"(bar) : "memory");
}
DEVI void e_tma_3d(uint32_t dst, const CUtensorMap* m, int c0, int c1, int c2, uint32_t bar) {
  asm volatile(ELECT "cp.async.bulk.tensor.3d.shared::cluster.global.mbarrier::complete_tx::bytes [%0], [%1, {%3, %4, %5}], [%2];}"
    :: "r"(dst), "l"(m), "r"(bar), "r"(c0), "r"(c1), "r"(c2) : "memory");
}
DEVI void e_tma_3d_mc(uint32_t dst, const CUtensorMap* m, int c0, int c1, int c2, uint32_t bar, int rb) {
  asm volatile(ELECT "cp.async.bulk.tensor.3d.shared::cluster.global.mbarrier::complete_tx::bytes.multicast::cluster [%0], [%1, {%3, %4, %5}], [%2], %6;}"
    :: "r"(dst), "l"(m), "r"(bar), "r"(c0), "r"(c1), "r"(c2), "h"((uint16_t)(7 << rb)) : "memory");
}
DEVI void e_tma_2d_mc(uint32_t dst, const CUtensorMap* m, int c0, int c1, uint32_t bar) {
  asm volatile(ELECT "cp.async.bulk.tensor.2d.shared::cluster.global.mbarrier::complete_tx::bytes.multicast::cluster [%0], [%1, {%3, %4}], [%2], %5;}"
    :: "r"(dst), "l"(m), "r"(bar), "r"(c0), "r"(c1), "h"((uint16_t)3) : "memory");
}
DEVI void p_arrive_at(uint32_t bar, uint32_t rank, bool c) {
  asm volatile("{.reg .pred p; .reg .b32 a; setp.ne.u32 p, %2, 0; mapa.shared::cluster.u32 a, %0, %1; @p mbarrier.arrive.shared::cluster.b64 _, [a];}"
    :: "r"(bar), "r"(rank), "r"((uint32_t)c) : "memory");
}
DEVI void p_expect_tx(uint32_t bar, uint32_t bytes, bool c) {
  asm volatile("{.reg .pred p; setp.ne.u32 p, %2, 0; @p mbarrier.arrive.expect_tx.shared::cta.b64 _, [%0], %1;}" :: "r"(bar), "r"(bytes), "r"((uint32_t)c) : "memory");
}
DEVI void p_arrive(uint32_t bar, bool c) { asm volatile("{.reg .pred p; setp.ne.u32 p, %1, 0; @p mbarrier.arrive.shared::cta.b64 _, [%0];}" :: "r"(bar), "r"((uint32_t)c) : "memory"); }
DEVI void tma_store_2d(const CUtensorMap* m, uint32_t src, int c0, int c1) {
  asm volatile("cp.async.bulk.tensor.2d.global.shared::cta.bulk_group [%0, {%2, %3}], [%1];" :: "l"(m), "r"(src), "r"(c0), "r"(c1) : "memory");
}
DEVI void tma_radd_2d(const CUtensorMap* m, uint32_t src, int c0, int c1) {
  asm volatile("cp.reduce.async.bulk.tensor.2d.global.shared::cta.add.bulk_group [%0, {%2, %3}], [%1];" :: "l"(m), "r"(src), "r"(c0), "r"(c1) : "memory");
}
DEVI void bulk_commit() { asm volatile("cp.async.bulk.commit_group;" ::: "memory"); }
template<int N> DEVI void bulk_wait_read() { asm volatile("cp.async.bulk.wait_group.read %0;" :: "n"(N) : "memory"); }
template<int N> DEVI void bulk_wait() { asm volatile("cp.async.bulk.wait_group %0;" :: "n"(N) : "memory"); }
template<int ID, int N> DEVI void nbar_sync() { asm volatile("bar.sync %0, %1;" :: "n"(ID), "n"(N) : "memory"); }
template<int ID, int N> DEVI void nbar_arrive() { asm volatile("bar.arrive %0, %1;" :: "n"(ID), "n"(N) : "memory"); }
DEVI void nbar_sync_r(int id, int n) { asm volatile("bar.sync %0, %1;" :: "r"(id), "r"(n) : "memory"); }
template<int R> DEVI void reg_inc() { asm volatile("setmaxnreg.inc.sync.aligned.u32 %0;" :: "n"(R)); }
template<int R> DEVI void reg_dec() { asm volatile("setmaxnreg.dec.sync.aligned.u32 %0;" :: "n"(R)); }
DEVI void wg_fence() { asm volatile("wgmma.fence.sync.aligned;" ::: "memory"); }
DEVI void wg_commit() { asm volatile("wgmma.commit_group.sync.aligned;" ::: "memory"); }
template<int N> DEVI void wg_wait() { asm volatile("wgmma.wait_group.sync.aligned %0;" :: "n"(N) : "memory"); }
DEVI uint64_t mkdesc(uint32_t addr, uint32_t lbo, uint32_t sbo, uint32_t sw = 1) {
  return ((uint64_t)((addr & 0x3FFFF) >> 4)) | ((uint64_t)(lbo >> 4) << 16) | ((uint64_t)(sbo >> 4) << 32) | ((uint64_t)sw << 62);
}
constexpr uint32_t SMEM_BASE = 1024;
__host__ __device__ constexpr long long CD(uint32_t off, uint32_t lbo, uint32_t sbo, uint32_t sw) {
  return (long long)(((uint64_t)((SMEM_BASE + off) >> 4)) | ((uint64_t)(lbo >> 4) << 16) | ((uint64_t)(sbo >> 4) << 32) | ((uint64_t)sw << 62));
}
DEVI uint32_t pack_bf16(float lo, float hi) { uint32_t r; asm("cvt.rn.bf16x2.f32 %0, %1, %2;" : "=r"(r) : "f"(hi), "f"(lo)); return r; }
DEVI float bf_lo(uint32_t v) { return __uint_as_float(v << 16); }
DEVI float bf_hi(uint32_t v) { return __uint_as_float(v & 0xffff0000u); }
DEVI void ldsm4t(uint32_t addr, uint32_t& r0, uint32_t& r1, uint32_t& r2, uint32_t& r3) {
  asm volatile("ldmatrix.sync.aligned.m8n8.x4.trans.shared.b16 {%0,%1,%2,%3}, [%4];" : "=r"(r0), "=r"(r1), "=r"(r2), "=r"(r3) : "r"(addr) : "memory");
}
DEVI void stsm4(uint32_t addr, uint32_t r0, uint32_t r1, uint32_t r2, uint32_t r3) {
  asm volatile("stmatrix.sync.aligned.m8n8.x4.shared.b16 [%0], {%1,%2,%3,%4};" :: "r"(addr), "r"(r0), "r"(r1), "r"(r2), "r"(r3) : "memory");
}
DEVI uint2 lds64v(uint32_t a) { uint2 v; asm volatile("ld.volatile.shared.v2.u32 {%0,%1}, [%2];" : "=r"(v.x), "=r"(v.y) : "r"(a) : "memory"); return v; }
DEVI uint32_t lds32v(uint32_t a) { uint32_t v; asm volatile("ld.volatile.shared.u32 %0, [%1];" : "=r"(v) : "r"(a) : "memory"); return v; }
DEVI uint4 lds128v(uint32_t a) { uint4 v; asm volatile("ld.volatile.shared.v4.u32 {%0,%1,%2,%3}, [%4];" : "=r"(v.x), "=r"(v.y), "=r"(v.z), "=r"(v.w) : "r"(a) : "memory"); return v; }
DEVI void cp_async16(uint32_t dst, const void* src) { asm volatile("cp.async.cg.shared.global [%0], [%1], 16;" :: "r"(dst), "l"(src) : "memory"); }
DEVI void cp_async_wait() { asm volatile("cp.async.wait_all;" ::: "memory"); }
DEVI void sts32(uint32_t a, uint32_t x) { asm volatile("st.shared.u32 [%0], %1;" :: "r"(a), "r"(x) : "memory"); }
DEVI int lane_id() { int r; asm volatile("mov.u32 %0, %%laneid;" : "=r"(r)); return r; }
DEVI void sts64(uint32_t a, uint32_t x, uint32_t y) { asm volatile("st.shared.v2.u32 [%0], {%1,%2};" :: "r"(a), "r"(x), "r"(y) : "memory"); }
DEVI void sts128(uint32_t a, uint4 v) { asm volatile("st.shared.v4.u32 [%0], {%1,%2,%3,%4};" :: "r"(a), "r"(v.x), "r"(v.y), "r"(v.z), "r"(v.w) : "memory"); }
DEVI void st_async128(uint32_t a, uint32_t x, uint32_t y, uint32_t z, uint32_t w, uint32_t bar) {
  asm volatile("st.async.weak.shared::cluster.mbarrier::complete_tx::bytes.v4.b32 [%0], {%1,%2,%3,%4}, [%5];" :: "r"(a), "r"(x), "r"(y), "r"(z), "r"(w), "r"(bar) : "memory");
}
DEVI void st_async32(uint32_t a, uint32_t x, uint32_t bar) {
  asm volatile("st.async.weak.shared::cluster.mbarrier::complete_tx::bytes.b32 [%0], %1, [%2];" :: "r"(a), "r"(x), "r"(bar) : "memory");
}
DEVI uint4 ldg_rlx128(const void* p) {
  uint4 v;
  asm volatile("ld.relaxed.gpu.global.v4.b32 {%0,%1,%2,%3}, [%4];" : "=r"(v.x), "=r"(v.y), "=r"(v.z), "=r"(v.w) : "l"(p) : "memory");
  return v;
}
DEVI int ldg_rlx32(const void* p) { int v; asm volatile("ld.relaxed.gpu.global.b32 %0, [%1];" : "=r"(v) : "l"(p) : "memory"); return v; }
DEVI int ldg_acq32(const void* p) { int v; asm volatile("ld.acquire.gpu.global.b32 %0, [%1];" : "=r"(v) : "l"(p) : "memory"); return v; }
DEVI void stg_rlx128(void* p, uint32_t x, uint32_t y, uint32_t z, uint32_t w) {
  asm volatile("st.relaxed.gpu.global.v4.b32 [%0], {%1,%2,%3,%4};" :: "l"(p), "r"(x), "r"(y), "r"(z), "r"(w) : "memory");
}
DEVI void stg128(void* p, uint32_t x, uint32_t y, uint32_t z, uint32_t w) {
  asm volatile("st.global.v4.b32 [%0], {%1,%2,%3,%4};" :: "l"(p), "r"(x), "r"(y), "r"(z), "r"(w) : "memory");
}
DEVI uint2 ldg_rlx64(const void* p) { uint2 v; asm volatile("{.reg .b64 a; ld.relaxed.gpu.global.b64 a, [%2]; mov.b64 {%0,%1}, a;}" : "=r"(v.x), "=r"(v.y) : "l"(p) : "memory"); return v; }
DEVI void stg_rlx64(void* p, uint32_t x, uint32_t y) { asm volatile("{.reg .b64 a; mov.b64 a, {%1,%2}; st.relaxed.gpu.global.b64 [%0], a;}" :: "l"(p), "r"(x), "r"(y) : "memory"); }
DEVI void stg_rlx32(void* p, uint32_t x) { asm volatile("st.relaxed.gpu.global.b32 [%0], %1;" :: "l"(p), "r"(x) : "memory"); }
DEVI void flag_add(int* p) { asm volatile("fence.proxy.async.global; red.release.gpu.global.add.s32 [%0], 1;" :: "l"(p) : "memory"); }
DEVI void e_stg_rlx32(void* p, uint32_t x) { asm volatile(ELECT "st.relaxed.gpu.global.b32 [%0], %1;}" :: "l"(p), "r"(x) : "memory"); }
DEVI void e_flag_add(int* p) { asm volatile("fence.proxy.async.global;\n" ELECT "red.release.gpu.global.add.s32 [%0], 1;}" :: "l"(p) : "memory"); }
DEVI int cluster_rank() { int r; asm volatile("mov.u32 %0, %%cluster_ctarank;" : "=r"(r)); return __shfl_sync(0xffffffffu, r, 0); }
DEVI int cta_id() { int r; asm volatile("mov.u32 %0, %%ctaid.x;" : "=r"(r)); return __shfl_sync(0xffffffffu, r, 0); }
DEVI uint32_t clock32() { uint32_t c; asm volatile("mov.u32 %0, %%clock;" : "=r"(c)); return c; }
DEVI uint32_t gtime() { uint32_t c; asm volatile("mov.u32 %0, %%globaltimer_lo;" : "=r"(c)); return c; }
DEVI void wait_time(uint32_t t) {
  uint32_t r;
  while (__any_sync(0xffffffffu, (r = t - gtime() - 1) < 4000u)) {
  }
}
DEVI void spin_until(uint32_t t0, int d) {
  int r;
  while (__any_sync(0xffffffffu, (r = d - (int)(clock32() - t0)) > 0)) {
    if (r > 300) __nanosleep(r >> 2);
  }
}
DEVI void pin2(const void* a, const void* b) { asm volatile("{.reg .pred p; setp.eq.u64 p, %0, %1; @p st.volatile.global.u64 [%0], %1;}" :: "l"(a), "l"(b) : "memory"); }
DEVI void pin2(uint32_t a, uint32_t b) { asm volatile("{.reg .pred p; setp.eq.u32 p, %0, %1; @p st.volatile.shared.u32 [%0], %1;}" :: "r"(a), "r"(b) : "memory"); }
DEVI void p_stg_rlx64(void* p, uint32_t x, uint32_t y, bool c) {
  asm volatile("{.reg .pred p; .reg .b64 a; setp.ne.u32 p, %3, 0; mov.b64 a, {%1,%2}; @p st.relaxed.gpu.global.b64 [%0], a;}" :: "l"(p), "r"(x), "r"(y), "r"((uint32_t)c) : "memory");
}
DEVI void pin2(uint64_t a, uint64_t b) { pin2((const void*)a, (const void*)b); }
DEVI uint64_t pair(uint32_t a, uint32_t bar) { return a | (uint64_t)bar << 32; }
DEVI void st_async32(uint64_t q, uint32_t x) { st_async32((uint32_t)q, x, (uint32_t)(q >> 32)); }
DEVI void st_async128(uint64_t q, uint4 v) { st_async128((uint32_t)q, v.x, v.y, v.z, v.w, (uint32_t)(q >> 32)); }
DEVI float ex2(float x) { float r; asm("ex2.approx.ftz.f32 %0, %1;" : "=f"(r) : "f"(x)); return r; }
DEVI float rcp(float x) { float r; asm("rcp.approx.ftz.f32 %0, %1;" : "=f"(r) : "f"(x)); return r; }
DEVI uint32_t xor_or(uint32_t a, uint32_t t, uint32_t acc) { uint32_t r; asm("lop3.b32 %0, %1, %2, %3, 0xbe;" : "=r"(r) : "r"(a), "r"(t), "r"(acc)); return r; }
DEVI void stsm2(uint32_t addr, uint32_t r0, uint32_t r1) {
  asm volatile("stmatrix.sync.aligned.m8n8.x2.shared.b16 [%0], {%1,%2};" :: "r"(addr), "r"(r0), "r"(r1) : "memory");
}
DEVI uint32_t settag(uint32_t v, uint32_t tag) { return (v & ~1u) | tag; }

#define A4(c, o)  c(d[o+0]), c(d[o+1]), c(d[o+2]), c(d[o+3])
#define A8(c, o)  A4(c, o), A4(c, o+4)
#define A16(c, o) A8(c, o), A8(c, o+8)
#define A12(c, o) A8(c, o), A4(c, o+8)
#define A28(c, o) A16(c, o), A12(c, o+16)
#define RL12 "{%0,%1,%2,%3,%4,%5,%6,%7,%8,%9,%10,%11}"
#define RL28 "{%0,%1,%2,%3,%4,%5,%6,%7,%8,%9,%10,%11,%12,%13,%14,%15,%16,%17,%18,%19,%20,%21,%22,%23,%24,%25,%26,%27}"
#define A20(c, o) A16(c, o), A4(c, o+16)
#define A32(c, o) A16(c, o), A16(c, o+16)
#define RL8  "{%0,%1,%2,%3,%4,%5,%6,%7}"
#define RL16 "{%0,%1,%2,%3,%4,%5,%6,%7,%8,%9,%10,%11,%12,%13,%14,%15}"
#define RL20 "{%0,%1,%2,%3,%4,%5,%6,%7,%8,%9,%10,%11,%12,%13,%14,%15,%16,%17,%18,%19}"
#define RL32 "{%0,%1,%2,%3,%4,%5,%6,%7,%8,%9,%10,%11,%12,%13,%14,%15,%16,%17,%18,%19,%20,%21,%22,%23,%24,%25,%26,%27,%28,%29,%30,%31}"
#define RL64 "{%0,%1,%2,%3,%4,%5,%6,%7,%8,%9,%10,%11,%12,%13,%14,%15,%16,%17,%18,%19,%20,%21,%22,%23,%24,%25,%26,%27,%28,%29,%30,%31," \
  "%32,%33,%34,%35,%36,%37,%38,%39,%40,%41,%42,%43,%44,%45,%46,%47,%48,%49,%50,%51,%52,%53,%54,%55,%56,%57,%58,%59,%60,%61,%62,%63}"
#define WG_OP(shape) "wgmma.mma_async.sync.aligned." shape "k16.f32.bf16.bf16 "
#define DEF_WGMMA(N, RL, AL, i0, i1, i2, i3, i4, i5, i6)                                                                         \
  template<int SC, int TB, long long CB> DEVI void rs##N(float* d, const uint32_t* a) {                                          \
    if (SC) asm volatile("{.reg .b64 tb; mov.b64 tb, %" #i4 ";\n" WG_OP("m64n" #N) RL ", {%" #i0 ",%" #i1 ",%" #i2 ",%" #i3 "}, tb, 1, 1, 1, %" #i5 ";}" \
      : AL("+f", 0) : "r"(a[0]), "r"(a[1]), "r"(a[2]), "r"(a[3]), "n"(CB), "n"(TB));                                             \
    else asm volatile("{.reg .b64 tb; mov.b64 tb, %" #i4 ";\n" WG_OP("m64n" #N) RL ", {%" #i0 ",%" #i1 ",%" #i2 ",%" #i3 "}, tb, 0, 1, 1, %" #i5 ";}" \
      : AL("=f", 0) : "r"(a[0]), "r"(a[1]), "r"(a[2]), "r"(a[3]), "n"(CB), "n"(TB));                                             \
  }                                                                                                                              \
  template<int SC, int TA, int TB, long long CA, long long CB> DEVI void ss##N(float* d, uint32_t a) {                           \
    if (SC) asm volatile("{.reg .b64 ta, tb; .reg .b32 lo, hi; add.u32 lo, %" #i0 ", %" #i1 "; mov.b32 hi, %" #i2 "; mov.b64 ta, {lo, hi}; mov.b64 tb, %" #i3 ";\n" \
      WG_OP("m64n" #N) RL ", ta, tb, 1, 1, 1, %" #i4 ", %" #i5 ";}"                                                              \
      : AL("+f", 0) : "r"(a), "n"((int)CA), "n"((int)(CA >> 32)), "n"(CB), "n"(TA), "n"(TB));                                    \
    else asm volatile("{.reg .b64 ta, tb; .reg .b32 lo, hi; add.u32 lo, %" #i0 ", %" #i1 "; mov.b32 hi, %" #i2 "; mov.b64 ta, {lo, hi}; mov.b64 tb, %" #i3 ";\n" \
      WG_OP("m64n" #N) RL ", ta, tb, 0, 1, 1, %" #i4 ", %" #i5 ";}"                                                              \
      : AL("=f", 0) : "r"(a), "n"((int)CA), "n"((int)(CA >> 32)), "n"(CB), "n"(TA), "n"(TB));                                    \
  }
DEF_WGMMA(8, "{%0,%1,%2,%3}", A4, 4, 5, 6, 7, 8, 9, 10)
DEF_WGMMA(16, RL8, A8, 8, 9, 10, 11, 12, 13, 14)
DEF_WGMMA(32, RL16, A16, 16, 17, 18, 19, 20, 21, 22)
DEF_WGMMA(40, RL20, A20, 20, 21, 22, 23, 24, 25, 26)
DEF_WGMMA(24, RL12, A12, 12, 13, 14, 15, 16, 17, 18)
DEF_WGMMA(56, RL28, A28, 28, 29, 30, 31, 32, 33, 34)
template<int TA> DEVI void wgmma_n128(float* d, uint64_t a, uint64_t b, int scale_d) {
  asm volatile("{.reg .pred p; setp.ne.b32 p, %66, 0;\n" WG_OP("m64n128") RL64 ", %64, %65, p, 1, 1, %67, 1;}"
    : A32("+f", 0), A32("+f", 32) : "l"(a), "l"(b), "r"(scale_d), "n"(TA));
}

namespace rec {
constexpr int KR = 43;
constexpr uint32_t WSZ = (64 - KR) * 2048, STG = KR * 2048;
constexpr uint32_t WS = 0;
constexpr uint32_t RING = 2 * WSZ;
constexpr uint32_t OB = RING + 3 * 8192;
constexpr uint32_t PB = OB + 4096;
constexpr uint32_t WO = RING + 32768;
constexpr uint32_t ATT = WO + 5 * 16384;
constexpr uint32_t AK = ATT + 10240, AV = ATT + 20480;
constexpr uint32_t PAD = ATT + 30720;
constexpr uint32_t BARS = PAD + 128;
constexpr uint32_t B_XE = BARS  , B_FA = BARS + 64  , B_FB = BARS + 88, B_FO = BARS + 96;
constexpr uint32_t B_ME = BARS + 104  , B_WE = BARS + 136, B_PD = BARS + 144;
constexpr uint32_t B_XF = BARS + 152  , B_MF = BARS + 216  , B_CP = BARS + 248  , B_WT = BARS + 280  ;
constexpr uint32_t B_AB = BARS + 296, B_OB = BARS + 304, B_ST = BARS + 312  , B_WS = BARS + 328, B_WO = BARS + 336, B_AT = BARS + 352, B_AV = BARS + 360;
constexpr int NBAR = 46;
constexpr uint32_t M0 = BARS + 384;
constexpr uint32_t SMEM = 232448;
constexpr int NB_P = 1, NB_ST = 2, NB_O = 3, NB_W0 = 4, NB_W1 = 5;
__host__ __device__ constexpr int wo_tile(int rank, int g, int i) { return i < 2 ? i * 6 + (rank == 2 ? g : 4 - 2 * g + rank) : 13 + rank - g; }
constexpr long long D_W = CD(WS, 16, 1024, 1), D_X = CD(0, 16, 1024, 1), D_O = CD(OB, 128, 256, 0);
constexpr long long D_WO = CD(WO, 16, 1024, 1), D_QM = CD(ATT, 640, 0, 0), D_QT = CD(ATT + 128, 640, 64, 0), D_K = CD(AK, 640, 128, 0);
constexpr long long D_V = CD(AV, 128, 640, 0), D_P = CD(PB, 128, 768, 0);
struct Maps { CUtensorMap w[3], wo, xd, xs; };
__host__ __device__ constexpr uint32_t mslot(int c) { return (c ^ (c >> 1)) * 12288; }
__host__ __device__ constexpr uint32_t xslot(int s) { return s < 3 ? RING + s * 8192 : s < 5 ? WO + (s - 3) * 8192 : s < 7 ? WO + (s + 1) * 8192 : OB; }
__host__ __device__ constexpr bool k_smem(int k) { return k % 3 == 2; }
__host__ __device__ constexpr int k_idx(int k) { return k % 3 == 2 ? k / 3 : k - k / 3; }
__host__ __device__ constexpr int k_of_reg(int i) { return i + (i >> 1); }
__host__ __device__ constexpr int k_of_smem(int i) { return 3 * i + 2; }

#define RPROF(i)
#define RPROF_STEP
#define CPROF(i, v)

template<bool DUAL, int K0, int K1> DEVI void seq_mem(float* d, const uint32_t* w, uint32_t dw) {
  if constexpr (K0 < K1) {
    constexpr long long B = CD(RING, 128, DUAL ? 4096 : 8192, 0) + mslot(K0 >> 4) / 16 + (K0 & 15) * 16;
    if constexpr (DUAL) {
      if constexpr (!k_smem(K0)) rs24<K0 != 0, 1, B>(d, w + 4 * k_idx(K0)); else ss24<1, 1, 1, D_W + k_idx(K0) * 128, B>(d, dw);
    } else {
      if constexpr (!k_smem(K0)) rs16<K0 != 0, 1, B>(d, w + 4 * k_idx(K0)); else ss16<1, 1, 1, D_W + k_idx(K0) * 128, B>(d, dw);
    }
    seq_mem<DUAL, K0 + 1, K1>(d, w, dw);
  }
}
template<int N, int K0, int K1> DEVI void seq_tok(float* d, const uint32_t* w, uint32_t dw) {
  if constexpr (K0 < K1) {
    constexpr bool DUAL = N > 32;
    constexpr long long B = D_X + (DUAL ? xslot((K0 >> 2) & 7) / 16 : xslot(K0 >> 3) / 16 + ((K0 >> 2) & 1) * 256) + (K0 & 3) * 2;
    if constexpr (DUAL) {
      if constexpr (!k_smem(K0)) rs56<K0 != 0, 0, B>(d, w + 4 * k_idx(K0)); else ss56<1, 1, 0, D_W + k_idx(K0) * 128, B>(d, dw);
    } else if constexpr (N == 24) {
      if constexpr (!k_smem(K0)) rs24<K0 != 0, 0, B>(d, w + 4 * k_idx(K0)); else ss24<1, 1, 0, D_W + k_idx(K0) * 128, B>(d, dw);
    } else {
      if constexpr (!k_smem(K0)) rs32<K0 != 0, 0, B>(d, w + 4 * k_idx(K0)); else ss32<1, 1, 0, D_W + k_idx(K0) * 128, B>(d, dw);
    }
    seq_tok<N, K0 + 1, K1>(d, w, dw);
  }
}
template<int T, int K0> DEVI void seq_wo(float* d, uint32_t dw) {
  if constexpr (K0 < 8) { ss16<K0 != 0, 1, 1, D_WO + T * 1024 + K0 * 128, D_O + K0 * 32>(d, dw); seq_wo<T, K0 + 1>(d, dw); }
}
template<long long Q, int K0> DEVI void seq_s(float* d) {
  if constexpr (K0 < 8) { ss40<K0 != 0, 1, 1, Q + K0 * 80, D_K + K0 * 80>(d, 0); seq_s<Q, K0 + 1>(d); }
}
template<bool DUAL, int J> DEVI void load_x(uint32_t sb, const Maps* M, int t, int rb) {
  if (DUAL) e_tma_3d_mc(sb + xslot(J & 7), &M->xd, J * 64, (t - LAG) * 32, 0, sb + B_XF + (J & 7) * 8, rb);
  else e_tma_3d_mc(sb + xslot(J & 7), &M->xs, 0, (t < NSEG ? t : t - LAG) * 32, J * 2, sb + B_XF + (J & 7) * 8, rb);
}
DEVI void load_x_lent(uint32_t sb, const Maps* M, int t, int j) {
  const bool dual = t >= LAG && t < NSEG;
  const uint32_t dst = sb + (j == 3 ? xslot(3) : xslot(5));
#pragma unroll
  for (int i = 0; i < 2; i++)
    e_tma_3d(dst + i * 8192, dual ? &M->xd : &M->xs, dual ? (j + i) * 64 : 0, (t < LAG ? t : t - LAG) * 32, dual ? 0 : (j + i) * 2, sb + B_XF + (j + i) * 8);
}
struct True { static constexpr bool value = true; };
struct False { static constexpr bool value = false; };
struct Ctx { uint32_t sb; const Maps* M; int rb, rank, wi; bool lead; uint32_t par; };
#define PFN 2
#define XD 2
template<bool DUAL, int J> DEVI void tok_release(const Ctx& c, int t, int& budget) {
  constexpr int NC = DUAL ? 16 : 8, S = J & 7;
  if constexpr (J + 8 < NC) {
    p_arrive_at(c.sb + B_XE + S * 8, c.rb + J % 3, c.lead);
    p_expect_tx(c.sb + B_XF + S * 8, 8192, c.lead && c.wi == 0);
  } else if constexpr (S == 1 || S == 2 || S == 4 || S == 7) p_arrive(c.sb + B_ME + (S >> 1) * 8, c.lead);
  if constexpr (J == XD - 1) {
    if (c.rank == 1 && c.wi == 5) { mbar_wait(c.sb + B_FO, t & 1, budget); load_x<DUAL, 7>(c.sb, c.M, t, c.rb); }
  } else if constexpr (J >= XD && J - XD + 8 < NC) {
    constexpr int I = J - XD;
    if (c.rank == I % 3 && c.wi == (I & 1) * 4 + 1) { mbar_wait(c.sb + B_XE + I * 8, (t - LAG) & 1, budget); load_x<DUAL, I + 8>(c.sb, c.M, t, c.rb); }
  }
}
template<int N, int J, class F, class G> DEVI bool tok_pass(float* d, const uint32_t* w, uint32_t dw, Ctx& c, int t, int& budget, F after0, G setup) {
  constexpr bool DUAL = N > 32;
  constexpr int NC = DUAL ? 16 : 8, KC = 64 / NC;
  if constexpr (J < NC) {
    if constexpr (J > 1) mbar_wait(c.sb + B_XF + (J & 7) * 8, c.par ^ (J >> 3), budget);
    wg_fence();
    seq_tok<N, J * KC, (J + 1) * KC>(d, w, dw);
    wg_commit();
    if constexpr (J == 1) after0();
    if constexpr (J >= NC - 5 && J < NC - 2) setup(J - (NC - 5));
    if constexpr (J > 0) { wg_wait<1>(); tok_release<DUAL, J - 1>(c, t, budget); }
    return tok_pass<N, J + 1>(d, w, dw, c, t, budget, after0, setup);
  } else {
    const bool ok = mbar_test(c.sb + B_MF, t & 1);
    wg_wait<0>();
    tok_release<DUAL, NC - 1>(c, t, budget);
    if (!DUAL) c.par ^= 1;
    return ok;
  }
}
template<int NB> DEVI void pack_tok(uint32_t* e, const float* d) {
#pragma unroll
  for (int i = 0; i < 8; i++) if ((i & 3) < NB) e[i] = pack_bf16(d[4 * (i & 3) + 2 * (i >> 2)], d[4 * (i & 3) + 2 * (i >> 2) + 1]);
}
DEVI void push_tok(const uint32_t* e, uint32_t sb, uint32_t o, int r, int rank) {
  const uint32_t b = mapa(sb, r);
  st_async128(b + o, e[0], e[1], e[2], e[3], b + (rank == 2 ? B_AV : B_AT));
}
DEVI uint32_t h1_tag(int seg) { return ((seg >> 1) & 1) ^ 1; }
DEVI uint4 pack_part(const float* c, int t) {
  return make_uint4(settag(pack_bf16(c[0], c[1]), h1_tag(t)), pack_bf16(c[2], c[3]), settag(pack_bf16(c[4], c[5]), h1_tag(t - LAG)), pack_bf16(c[6], c[7]));
}
DEVI void put_part(char* p1, char* p2, uint4 z, int t) { p_stg_rlx64(p1, z.x, z.y, t < NSEG); p_stg_rlx64(p2, z.z, z.w, t >= LAG); }

DEVI void rec_math(const uint32_t sb, const int wi, const Maps& M) {
  const int h = cta_id() / 3, rb = cluster_rank() >= 3 ? 3 : 0, rank = cluster_rank() - rb;
  const int warp = wi & 3, wg = wi >> 2;
  const bool lead = (threadIdx.x & 127) == 0;
  int budget = SPIN_BUDGET;
  uint32_t w[4 * KR];
  Ctx cx{sb, &M, rb, rank, wi, lead, 0};
  {
    const int lane = lane_id();
    const uint32_t a = sb + wg * STG + ((lane & 7) + (lane >> 4) * 8) * 128 + (((warp * 2 + ((lane >> 3) & 1)) ^ (lane & 7)) << 4);
    for (int i = 0; i < (wg == 1 || rank == 2 ? 12 : 8); i++)
      stg_rlx64((char*)g_h1[i & 3] + ((wo_tile(rank, wg, i >> 2) * 4 + warp) * 4 + (lane >> 3)) * 2048 + h * 64 + (lane & 7) * 8, 0, 0);
    mbar_wait(sb + B_ST + wg * 8, 0, budget);
#pragma unroll
    for (int k = 0; k < KR; k++) ldsm4t(a + k * 2048, w[4*k], w[4*k+1], w[4*k+2], w[4*k+3]);
    nbar_arrive<NB_ST, 384>();
    nbar_sync_r(NB_W0 + wg, 128);
    for (int i = 0; i < 5; i++) p_arrive_at(sb + B_FA + i * 8, rb + (i == 4), lead);
    mbar_wait(sb + B_WS, 0, budget);
  }
  uint4 z = make_uint4(0, 0, 0, 0);
  char *z1 = nullptr, *z2 = nullptr;
  uint32_t rt0 = 0, rt1 = 0;
  mbar_wait(sb + B_XF, 0, budget); mbar_wait(sb + B_XF + 8, 0, budget);
#pragma unroll 1
  for (int t = 0;; t++) {
    const uint32_t dw = wg * (WSZ >> 4);
    uint32_t e[16];
    bool ok;
    auto finish = [&]() { put_part(z1, z2, z, t - 1); p_arrive_at(sb + B_FO, rb + 1, lead); };
    const int seg = t - rank * LAG;
    const bool att = rank < 2 && (unsigned)seg < (unsigned)NSEG;
    char* p1;
    uint32_t pw, oo;
    uint64_t u0, u1;
    int lane;
    auto setup = [&](int part) {
      if (part == 0) {
        lane = lane_id();
      } else if (part == 1) {
        char* const p = (char*)g_h1 + ((wo_tile(rank, wg, 0) * 4 + warp) * 4 + (lane >> 3)) * 2048 + h * 64 + (lane & 7) * 8;
        p1 = p + (t & 1) * sizeof(g_h1[0]);
        pin2(p1, nullptr);
      } else if (part == 2) {
        oo = OB + (lane >> 4) * 2048 + warp * 512 + rank * 256 + (lane & 15) * 16;
        pw = sb + PB + (wg ? lane * 4 : 768 + warp * 768 + lane * 16);
        pin2(pw, oo);
      } else {
        if (wg) {
          const uint32_t ra = mapa(sb, rb + ((warp & 1) ? 2 : (rank ^ 1) & 1)), rc = mapa(sb, rb + ((warp & 1) ? (rank ^ 1) & 1 : 2));
          u0 = pair(ra + oo, ra + B_OB); u1 = pair(rc + oo, rc + B_OB);
        } else {
          u0 = (uint64_t)((char*)(g_ot + rank * O_LAYER) + (size_t)(h * DH + warp * 16 + (lane >> 2)) * (SEQ * 2) + seg * 64 + (lane & 3) * 16);
          u1 = (uint32_t)((lane & 24) + ((lane >> 2) & 1) + 2 * warp - 8 * (lane & 3));
        }
        pin2(u0, u1);
      }
    };
    RPROF_STEP;
    auto mem_pass = [&](auto dual_c) {
      constexpr bool DUAL = decltype(dual_c)::value;
      float m[DUAL ? 12 : 8];
      RPROF(8 + wg * 12 - 32);
      if (!ok) mbar_wait(sb + B_MF, t & 1, budget);
      wg_fence(); seq_mem<DUAL, 0, 8>(m, w, dw); wg_commit();
      const uint32_t ao = ATT + rank * 10240 + wi * 1280, to = ao + 128 + (lane & 3) * 128 + (lane >> 2) * 16;
      const int la = DUAL ? rank == 0 : t >= NSEG;
      RPROF(1 + wg * 12);
      if (DUAL && rank == 0) {
#pragma unroll
        for (int i = 0; i < 8; i++) { const uint32_t x = e[i]; e[i] = e[8 + i]; e[8 + i] = x; }
      }
      auto piece = [&](int i) { push_tok(e + 4 * i, sb, to + (i & 1) * 640, rb + (la ^ (i >> 1)), rank); };
      piece(0);
      wg_fence(); seq_mem<DUAL, 8, 16>(m, w, dw); wg_commit();
      piece(1);
      mbar_wait(sb + B_MF + 8, t & 1, budget);
      wg_fence(); seq_mem<DUAL, 16, 24>(m, w, dw); wg_commit();
      if (DUAL) piece(2);
      wg_fence(); seq_mem<DUAL, 24, 32>(m, w, dw); wg_commit();
      if (DUAL) piece(3);
      mbar_wait(sb + B_MF + 16, t & 1, budget);
      wg_fence(); seq_mem<DUAL, 32, 48>(m, w, dw); wg_commit();
      wg_wait<1>(); p_arrive(sb + B_PD, lead);
      const uint32_t r0 = mapa(sb, rb + la), r1 = mapa(sb, rb + (la ^ 1)), m0 = r0 + ao + lane * 4, m1 = r1 + ao + lane * 4, ab = rank == 2 ? B_AV : B_AB;
      const uint64_t q0 = pair(m0, r0 + ab), q1 = pair(m0 + 640, r0 + ab), q2 = pair(m1, r1 + ab), q3 = pair(m1 + 640, r1 + ab);
      pin2(q0, q1);
      if (DUAL) pin2(q2, q3);
      mbar_wait(sb + B_MF + 24, t & 1, budget);
      wg_fence(); seq_mem<DUAL, 48, 64>(m, w, dw); wg_commit();
      wg_wait<1>(); p_arrive_at(sb + B_FA, rb, lead);
      wg_wait<0>();
      const uint32_t a0 = pack_bf16(m[0], m[1]), a1 = pack_bf16(m[2], m[3]), a2 = pack_bf16(m[4], m[5]), a3 = pack_bf16(m[6], m[7]);
      if constexpr (DUAL) {
        st_async32(q0, la ? a2 : a0); st_async32(q1, la ? a3 : a1); st_async32(q2, la ? a0 : a2); st_async32(q3, la ? a1 : a3);
        rt0 = pack_bf16(m[8], m[9]); rt1 = pack_bf16(m[10], m[11]);
      } else { st_async32(q0, a0); st_async32(q1, a1); rt0 = a2; rt1 = a3; }
      p_arrive(sb + B_WE, lead);
    };
    if (t >= LAG && t < NSEG) {
      float d[28];
      ok = tok_pass<56, 0>(d, w, dw, cx, t, budget, finish, setup);
      pack_tok<4>(e + 8, d); pack_tok<3>(e, d + 16); e[3] = rt0; e[7] = rt1;
      mem_pass(True());
    } else {
      float d[16];
      if (t > 0) finish();
      if (t > 0 && t < LAG) {
        ok = tok_pass<24, 0>(d, w, dw, cx, t, budget, []() {}, setup);
        pack_tok<3>(e, d); e[3] = rt0; e[7] = rt1;
      } else {
        ok = tok_pass<32, 0>(d, w, dw, cx, t, budget, []() {}, setup);
        pack_tok<4>(e, d);
      }
      mem_pass(False());
    }
    {
      RPROF(2 + wg * 12);
      auto wo_ready = [&]() { if (t == 0) mbar_wait(sb + B_WO, 0, budget); if (t < NSTEP - 1) mbar_wait(sb + B_WT, t & 1, budget); };
      constexpr float SC = 0.08838834764831845f * 1.4426950408889634f;
      if (!att) wo_ready();
      else {
        float s[32];
        setup(3);
        if (wg) {
          uint32_t one[4];
#pragma unroll
          for (int i = 0; i < 4; i++) one[i] = 0x3F803F80u + (pw >> 31);
          mbar_wait_cluster(sb + B_AT, seg & 1, budget);
          mbar_wait_cluster(sb + B_AB, seg & 1, budget);
          fence_proxy_async();
          RPROF(3 + 12);
          wg_fence(); seq_s<D_QM, 0>(s); wg_commit();
          nbar_arrive<NB_P, 256>();
          if (warp == 1) sts32(pw + 640, 0);
          mbar_wait_cluster(sb + B_AV, seg & 1, budget);
          wg_wait<0>();
          float mx = fmaxf(fmaxf(fmaxf(s[0], s[1]), fmaxf(s[4], s[5])), fmaxf(fmaxf(fmaxf(s[8], s[9]), fmaxf(s[12], s[13])), fmaxf(s[16], s[17])));
          const float x1 = __shfl_xor_sync(0xffffffffu, mx, 1), x2 = __shfl_xor_sync(0xffffffffu, mx, 2), x3 = __shfl_xor_sync(0xffffffffu, mx, 3);
          const float u = (warp & 2) ? ((warp & 1) ? s[16] : s[12]) : ((warp & 1) ? s[8] : s[4]);
          const float v = (warp & 2) ? ((warp & 1) ? s[17] : s[13]) : ((warp & 1) ? s[9] : s[5]);
          const float ms = -SC * fmaxf(fmaxf(mx, x1), fmaxf(x2, x3));
          sts32(pw + 128 + warp * 128, pack_bf16(ex2(fmaf(u, SC, ms)), ex2(fmaf(v, SC, ms))));
          if (warp == 0) sts32(pw, pack_bf16(ex2(fmaf(s[0], SC, ms)), ex2(fmaf(s[1], SC, ms))));
          fence_proxy_async();
          nbar_sync<NB_W1, 128>();
          RPROF(4 + 12);
          wg_fence();
          rs8<0, 0, D_P>(s + 8, one); rs8<1, 0, D_P + 16>(s + 8, one); rs8<1, 0, D_P + 32>(s + 8, one);
          wg_commit();
          ss8<0, 0, 0, D_V, D_P>(s, 0); ss8<0, 0, 0, D_V + 320, D_P>(s + 4, 0);
          ss8<1, 0, 0, D_V + 16, D_P + 16>(s, 0); ss8<1, 0, 0, D_V + 336, D_P + 16>(s + 4, 0);
          ss8<1, 0, 0, D_V + 32, D_P + 32>(s, 0); ss8<1, 0, 0, D_V + 352, D_P + 32>(s + 4, 0);
          wg_commit();
          wg_wait<1>();
          const float i0 = rcp(s[8]), i1 = rcp(s[9]);
          wg_wait<0>();
          stsm4(sb + oo, pack_bf16(s[0] * i0, s[1] * i1), pack_bf16(s[2] * i0, s[3] * i1), pack_bf16(s[4] * i0, s[5] * i1), pack_bf16(s[6] * i0, s[7] * i1));
          __syncwarp();
          const uint4 y = lds128v(sb + oo);
          if (t < NSTEP - 1) { st_async128(u0, y); st_async128(u1, y); e_complete_tx(sb + B_OB, 512); }
          wo_ready();
        } else {
          const int lim = (int)u1;
          char* const og = (char*)u0;
          nbar_sync<NB_P, 256>();
          RPROF(3);
          wg_fence();
          seq_s<D_QT, 0>(s);
          wg_commit();
          mbar_wait_cluster(sb + B_AV, seg & 1, budget);
          wg_wait<0>();
#pragma unroll
          for (int i = 0; i < 8; i++) { float& v = s[4 + 4 * (i >> 1) + (i & 1)]; v = i <= lim ? v : -INFINITY; }
          float mx = fmaxf(fmaxf(fmaxf(s[0], s[1]), fmaxf(s[4], s[5])), fmaxf(fmaxf(fmaxf(s[8], s[9]), fmaxf(s[12], s[13])), fmaxf(s[16], s[17])));
          const float x1 = __shfl_xor_sync(0xffffffffu, mx, 1), x2 = __shfl_xor_sync(0xffffffffu, mx, 2), x3 = __shfl_xor_sync(0xffffffffu, mx, 3);
          const float ms = -SC * fmaxf(fmaxf(mx, x1), fmaxf(x2, x3));
#pragma unroll
          for (int i = 0; i < 10; i++) { float& v = s[4 * (i >> 1) + (i & 1)]; v = ex2(fmaf(v, SC, ms)); }
          const float sum = (((s[0] + s[1]) + (s[4] + s[5])) + ((s[8] + s[9]) + (s[12] + s[13]))) + (s[16] + s[17]);
          const float y1 = __shfl_xor_sync(0xffffffffu, sum, 1), y2 = __shfl_xor_sync(0xffffffffu, sum, 2), y3 = __shfl_xor_sync(0xffffffffu, sum, 3);
          const float inv = rcp((sum + y1) + (y2 + y3));
          stsm4(pw, pack_bf16(s[0] * inv, s[1] * inv), pack_bf16(s[4] * inv, s[5] * inv), pack_bf16(s[8] * inv, s[9] * inv), pack_bf16(s[12] * inv, s[13] * inv));
          stsm2(pw + 512, pack_bf16(s[16] * inv, s[17] * inv), 0);
          fence_proxy_async();
          nbar_sync<NB_W0, 128>();
          RPROF(4);
          wg_fence();
          ss32<0, 0, 0, D_V, D_P + 48>(s, 0); ss32<0, 0, 0, D_V + 320, D_P + 48>(s + 16, 0);
          ss32<1, 0, 0, D_V + 16, D_P + 64>(s, 0); ss32<1, 0, 0, D_V + 336, D_P + 64>(s + 16, 0);
          ss32<1, 0, 0, D_V + 32, D_P + 80>(s, 0); ss32<1, 0, 0, D_V + 352, D_P + 80>(s + 16, 0);
          wg_commit();
          wo_ready();
          wg_wait<0>();
#pragma unroll
          for (int i = 0; i < 4; i++) {
            const float* d = s + (i >> 1) * 16 + (i & 1) * 2;
            stg128(og + ((i >> 1) * 64 + (i & 1) * 8) * (SEQ * 2), pack_bf16(d[0], d[1]), pack_bf16(d[4], d[5]), pack_bf16(d[8], d[9]), pack_bf16(d[12], d[13]));
          }
          if ((seg & 3) == 3) nbar_arrive<NB_O, 160>();
        }
      }
      RPROF(5 + wg * 12);
      const bool three = wg == 1 || rank == 2;
      char* const p2 = p1 + (2 + ((t - LAG) & 1) - (t & 1)) * (int)sizeof(g_h1[0]);
      if (t < NSTEP - 1) {
        float c[24];
        const uint32_t dt = wg ? 0 : 3072;
        mbar_wait_cluster(sb + B_OB, t & 1, budget);
        fence_proxy_async();
        RPROF(6 + wg * 12);
        wg_fence(); seq_wo<0, 0>(c, dt); wg_commit(); seq_wo<1, 0>(c + 8, dt); wg_commit();
        mbar_wait(sb + B_XF, cx.par, budget);
        wg_wait<1>();
        if (warp == 2) load_x_lent(sb, &M, t + 1, wg ? 3 : 5);
        put_part(p1, p2, pack_part(c, t), t);
        const int o3 = (wo_tile(rank, wg, three ? 2 : 1) - wo_tile(rank, wg, 0)) * 32768;
        z1 = p1 + o3; z2 = p2 + o3;
        if (three) {
          wg_fence(); seq_wo<2, 0>(c + 16, dt); wg_commit();
          wg_wait<1>(); put_part(p1 + 6 * 32768, p2 + 6 * 32768, pack_part(c + 8, t), t);
          mbar_wait(sb + B_XF + 8, cx.par, budget);
          wg_wait<0>(); z = pack_part(c + 16, t);
        } else { mbar_wait(sb + B_XF + 8, cx.par, budget); wg_wait<0>(); z = pack_part(c + 8, t); }
      } else break;
      RPROF(7 + wg * 12);
    }
  }
}

DEVI void wait_xa(const int* p, int& budget) {
  while (__any_sync(0xffffffffu, ldg_acq32(p) < 64) && --budget > 0) {}
  fence_proxy_global();
}
template<bool DUAL> DEVI void first_loads(uint32_t sb, const Maps* M, int n, int h, int rb, int& budget) {
#pragma unroll
  for (int i = 0; i < PFN; i++) {
    if (DUAL) e_prefetch_3d(&M->xd, ((h + i * (16 / PFN)) & 15) * 64, (n - LAG) * 32, 0);
    else e_prefetch_3d(&M->xs, 0, (n < NSEG ? n : n - LAG) * 32, ((h + i * (8 / PFN)) & 7) * 2);
  }
  if (n + 1 < NSEG) asm volatile(ELECT "cp.async.bulk.prefetch.L2.global [%0], 2048;}" :: "l"((const char*)g_xr[n + 1] + (h & 7) * 2048) : "memory");
  mbar_wait(sb + B_FA, n & 1, budget);
  load_x<DUAL, 0>(sb, M, n, rb); load_x<DUAL, 1>(sb, M, n, rb); load_x<DUAL, 2>(sb, M, n, rb);
}
template<bool DUAL> DEVI void lent_loads(uint32_t sb, const Maps* M, int n, int rb, int& budget) {
  mbar_wait(sb + B_FB, n & 1, budget);
  load_x<DUAL, 3>(sb, M, n, rb); load_x<DUAL, 4>(sb, M, n, rb); load_x<DUAL, 5>(sb, M, n, rb); load_x<DUAL, 6>(sb, M, n, rb);
}
DEVI void rec_comm(const uint32_t sb, const int warp, const Maps& M, const bf16* __restrict__ mem0) {
  const int lane = threadIdx.x & 31, h = cta_id() / 3, rb = cluster_rank() >= 3 ? 3 : 0, rank = cluster_rank() - rb;
  int budget = SPIN_BUDGET;
  const bool two = warp == 3 || (rank == 2 && warp == 2);
  const int ntask = two ? 2 : 1, qi = two ? (warp == 3 ? rank : 3) : rank * 3 + warp;
  const int task0 = two ? h * 2 + (qi >> 1) : 64 + h * 4 + (qi >> 1);
  auto h2_word = [&](int i, int ln) {
    const int task = task0 + i * 192;
    return (char*)g_h2 + (task >> 6) * 8192 + ((qi ^ i) & 1) * 4096 + ((task >> 2) & 15) * 256 + (task & 3) * 32 + (ln & 8) * 16 + (ln & 7) * 4;
  };
  auto first_x = [&](int t) {
    const int n = t + 1;
    p_expect_tx(sb + B_XF + (lane_id() & 7) * 8, 8192, lane_id() < 8);
    if (rank == 0) {
      if (n >= LAG && ((n - LAG) & 3) == 0) wait_xa(&g_xa[1][(n - LAG) >> 2], budget);
      if (n >= LAG && n < NSEG) first_loads<true>(sb, &M, n, h, rb, budget); else first_loads<false>(sb, &M, n, h, rb, budget);
    }
  };
  {
    const int task = task0 + (lane >> 4) * 192, L = (task & 3) * 8 + (lane & 7);
    if ((lane >> 4) < ntask) {
      const bf16* p = mem0 + (L & 3) * 2 * DM + (task >> 2) * 16 + (L >> 2) + (lane & 8);
      uint32_t m0 = (uint32_t)__bfloat16_as_ushort(p[0]) | (uint32_t)__bfloat16_as_ushort(p[DM]) << 16;
      m0 = m0 ? m0 : 0x8000u;
      stg_rlx32(h2_word(lane >> 4, lane), ((qi ^ (lane >> 4)) & 1) ? 0 : m0);
      for (int i = 1; i < 4; i++) stg_rlx32(h2_word(lane >> 4, lane) + i * sizeof(g_h2[0]), 0);
      sts32(sb + M0 + warp * 128 + lane * 4, m0);
    }
    __syncwarp();
    nbar_sync<NB_ST, 384>();
    if (warp == 2) {
      e_expect_tx(sb + B_WS, 2 * WSZ);
#pragma unroll 1
      for (int i = 0; i < 2 * (64 - KR); i++) e_tma_2d(sb + WS + (i & 1) * WSZ + (i >> 1) * 2048, &M.w[rank], h * DH + (i & 1) * 64, k_of_smem(i >> 1) * 16, sb + B_WS);
      const int nt = rank == 2 ? 6 : 5;
      e_expect_tx(sb + B_WO, (nt - 2) * 16384);
#pragma unroll 1
      for (int i = 1; i < nt; i++) if (i != 3) e_tma_2d(sb + WO + i * 16384, &M.wo, wo_tile(rank, 1 - i / 3, i % 3) * 64, h * DH, sb + B_WO);
    }
    wait_xa(&g_xa[0][0], budget);
    if (warp == 3) { first_x(-1); if (rank == 0) lent_loads<false>(sb, &M, 0, rb, budget); }
  }
  uint32_t t0 = gtime() - 4000, cpp = 0;
  const uint32_t cp = sb + B_CP + warp * 8;
#pragma unroll 1
  for (int t = 0;; t++) {
    const int n = t + 1, seg = t - rank * LAG;
    RPROF_STEP;
    const bool att = rank < 2 && (unsigned)seg < (unsigned)NSEG;
    if (warp == 3) {
      if (att) { e_expect_tx(sb + B_AT, 16384); e_expect_tx(sb + B_AB, 4096); e_expect_tx(sb + B_AV, 10240); }
      if (n < NSTEP) e_expect_tx(sb + B_OB, t < NSEG && t >= LAG ? 4096 : 2048);
    }
    {
      const bool dual = t >= LAG && t < NSEG;
      const int ck = warp ^ (warp < 2 && !dual && (rank & 1) == (t >= NSEG));
      const uint32_t lo = t >= NSEG ? 4096 : 0, dst = sb + RING + mslot(ck), bytes = dual ? 8192 : 4096;
      const uint32_t chk = dst + lane_id() * 32 + (lane_id() >> 2) * 4;
      mbar_wait(sb + B_ME + ck * 8, t & 1, budget);
      uint32_t tx = bytes;
      if (n < NSEG) { e_bulk_g2s(dst + 8192, (const char*)g_xr[n] + ck * 4096, 4096, cp); tx += 4096; }
      wait_time(t0 + (t <= LAG ? TP(9) + ck * TP(11) : t <= NSEG ? TP(1) + ck * TP(4) : TP(13) + ck * TP(11)));
      RPROF(24); CPROF(0, gtime());
      int tries = 0;
      while (true) {
        tries++;
        e_bulk_g2s(dst, (const char*)g_h2[t & 3] + ck * 8192 + lo, bytes, cp);
        e_expect_tx(cp, tx); tx = bytes;
        mbar_wait(cp, cpp, budget); cpp ^= 1;
        uint32_t mn = min(min(lds32v(chk), lds32v(chk + 1024)), min(lds32v(chk + 2048), lds32v(chk + 3072)));
        if (dual) mn = min(min(mn, min(lds32v(chk + 4096), lds32v(chk + 5120))), min(lds32v(chk + 6144), lds32v(chk + 7168)));
        if (!__any_sync(0xffffffffu, mn == 0) || --budget < 0) break;
      }
      e_arrive(sb + B_MF + ck * 8);
      RPROF(25); CPROF(1, gtime()); CPROF(2, tries);
      if (n + 1 < NSEG && (n & 3) == 3) wait_xa(&g_xa[0][(n + 1) >> 2], budget);
    }
    {
      const int ln = lane_id(), i = ln >> 4;
      char* const w = h2_word(i, ln);
      if (i < ntask) {
        stg_rlx32(w + ((t + 3) & 3) * sizeof(g_h2[0]), 0);
        if (n == LAG && ((qi ^ i) & 1)) stg_rlx32(w + (n & 3) * sizeof(g_h2[0]), lds32v(sb + M0 + warp * 128 + ln * 4));
      }
      __syncwarp();
    }
    if (n < NSTEP) {
      const uint32_t tag = (n >> 1) & 31;
      mbar_wait(sb + B_PD, t & 1, budget);
      t0 = clock32();
      if (warp == 2) {
        mbar_wait(sb + B_ME + 24, t & 1, budget);
        e_expect_tx(sb + B_WT, 32768);
        e_tma_2d(sb + WO + 49152, &M.wo, wo_tile(rank, 0, 0) * 64, h * DH, sb + B_WT);
        mbar_wait(sb + B_WE, t & 1, budget);
        e_tma_2d(sb + WO, &M.wo, wo_tile(rank, 1, 0) * 64, h * DH, sb + B_WT);
      }
      if (warp == 3) first_x(t);
      if (warp == 0 && rank == (t >= NSEG)) { mbar_wait(sb + B_AB, seg & 1, budget); e_stg_rlx32(&g_ts[t & 1][h * TSS], (gtime() & ~31u) | tag); }
      spin_until(t0, TSD);
      uint32_t v;
      do { v = ldg_rlx32(&g_ts[t & 1][lane_id() * TSS]); } while (__any_sync(0xffffffffu, (v & 31) != tag) && --budget > 0);
      const uint32_t now = __shfl_sync(0xffffffffu, v, 0);
      t0 = now + __reduce_max_sync(0xffffffffu, (int)(v - now));
      if (warp == 3) mbar_wait(sb + B_OB, t & 1, budget);
    }
    if (n < NSTEP) {
      RPROF(26); CPROF(3, t0);
#pragma unroll 1
      for (int i = 0; i < ntask; i++) {
        const int layer = (qi ^ i) & 1, sg = t - layer * LAG, task = task0 + i * 192;
        if ((unsigned)sg >= (unsigned)(NSEG - 1)) continue;
        const uint32_t tag = h1_tag(sg);
        const int ln = lane_id();
        const char* const src = (const char*)g_h1[layer * 2 + (sg & 1)] + task * 2048 + ln * 8;
        char* const dst = h2_word(i, ln) + (n & 3) * sizeof(g_h2[0]);
        uint2 v[8];
        pin2(src, dst);
        const int wave = task < 64 ? 0 : task < 192 ? 1 : 2;
        wait_time(t0 + (t < LAG ? TP(8) : t < NSEG ? TP(0) : TP(12)) + (wave == 0 ? -TP(10) : wave == 1 ? 0 : TP(3)));
        int tries = 0;
        float a[4];
        while (true) {
          tries++;
#pragma unroll
          for (int k = 0; k < 8; k++) v[k] = ldg_rlx64(src + k * 256);
          uint32_t bad = 0;
#pragma unroll
          for (int k = 0; k < 8; k++) {
            bad = xor_or(v[k].x, tag, bad);
            a[0] = k ? a[0] + bf_lo(v[k].x) : bf_lo(v[k].x); a[1] = k ? a[1] + bf_hi(v[k].x) : bf_hi(v[k].x);
            a[2] = k ? a[2] + bf_lo(v[k].y) : bf_lo(v[k].y); a[3] = k ? a[3] + bf_hi(v[k].y) : bf_hi(v[k].y);
          }
#pragma unroll
        for (int k = 0; k < 2; k++) {
          const float keep = (ln & 8) ? a[2+k] : a[k], send = (ln & 8) ? a[k] : a[2+k];
          a[k] = keep + __shfl_xor_sync(0xffffffffu, send, 8);
        }
#pragma unroll
        for (int k = 0; k < 2; k++) a[k] += __shfl_xor_sync(0xffffffffu, a[k], 16);
          if (!__any_sync(0xffffffffu, bad & 1) || --budget < 0) break;
        }
        const uint32_t out = pack_bf16(a[0], a[1]);
        if (ln < 16) stg_rlx32(dst, out ? out : 0x8000u);
        __syncwarp();
        if (i == 0) { RPROF(28); CPROF(6, gtime()); CPROF(4, gtime()); CPROF(5, tries); } else CPROF(7, gtime());
      }
    }
    if (warp == (t >= LAG && t < NSEG ? 2 : 1) && att && (seg & 3) == 3) {
      nbar_sync<NB_O, 160>(); e_flag_add(&g_dep[E_O1 + rank * 16 + (seg >> 2)]); }
    if (n == NSTEP) break;
  }
  if (h == 0 && rank == 0 && warp < 2) g_xa[warp][lane_id()] = 0;
}
}

__global__ void __launch_bounds__(384, 1)
rec_kernel(const __grid_constant__ rec::Maps M, const bf16* __restrict__ mem0) {
  using namespace rec;
  extern __shared__ __align__(1024) uint8_t smem[];
  const uint32_t sb = __shfl_sync(0xffffffffu, smem_u32(smem), 0);
  const int tid = threadIdx.x, wi = __shfl_sync(0xffffffffu, tid >> 5, 0);
  if ((sb & 0x3FFFF) != SMEM_BASE) __trap();
  if (wi == 0) {
    const int h = cta_id() / 3, rank = cta_id() - h * 3;
    for (int i = tid; i < NBAR; i += 32) mbar_init(sb + BARS + i * 8, i < 13 ? 6 : i < 19 ? 2 : 1);
    ((uint32_t*)(smem + PAD))[tid] = 0;
    fence_mbar_init(); fence_proxy_async();
    __syncwarp();
    e_expect_tx(sb + B_ST, STG); e_expect_tx(sb + B_ST + 8, STG);
    for (int i = 0; i < 2 * KR; i++) e_tma_2d(sb + (i & 1) * STG + (i >> 1) * 2048, &M.w[rank], h * DH + (i & 1) * 64, k_of_reg(i >> 1) * 16, sb + B_ST + (i & 1) * 8);
  } else if (wi == 1) {
    if (blockIdx.x < NEV / 32) { g_dep[blockIdx.x * 32 + (tid & 31)] = 0; g_claim[blockIdx.x * 32 + (tid & 31)] = 0; __threadfence(); }
    __syncwarp();
    asm volatile("griddepcontrol.launch_dependents;" ::: "memory");
  }
  cluster_arrive(); cluster_wait();
  if (wi < 8) { reg_inc<232>(); rec_math(sb, wi, M); cluster_arrive(); cluster_wait(); }
  else { reg_dec<40>(); rec_comm(sb, wi & 3, M, mem0); cluster_arrive(); cluster_wait(); }
}

namespace gm {
struct Maps { CUtensorMap ot, wo, xn, wg, wu, hl, hs, wd, out; };
constexpr int STAGES = 6, STAGE = 32768;
constexpr uint32_t SO = STAGES * STAGE, BARS = SO + 32768;
constexpr uint32_t B_FULL = BARS, B_EMPTY = BARS + 48, B_TF = BARS + 96, B_TE = BARS + 112, B_ORD = BARS + 128, B_PM = BARS + 144, B_GO = BARS + 160;
constexpr uint32_t MAIL = BARS + 176, PMAIL = BARS + 192;
constexpr uint32_t SMEM = BARS + 256;
constexpr int END = -1;
#define GT gtime
#define PRIO 1
#define SO1 2
#define SO2 2
#define SD1 2
#define SD2 2

struct Tile {
  bool isO, isG, l2; int blk, col, k0, n;
  DEVI Tile(int task, int rank) {
    const int e = task >> 8, id = task & 255;
    const bool isD = e < E_G1 || e >= E_D2;
    isO = e >= E_O1 && e < E_G2; isG = !isD && !isO; l2 = e >= E_O2;
    blk = isG && l2 ? (e & 15) * 2 + rank : isD && !l2 ? e >> 1 : e & 15;
    col = isG ? (l2 ? id : id * 2 + rank) : (id & 3) * 2 + rank;
    n = isO ? 64 / (l2 ? SO2 : SO1) : isG ? 16 : 56 / (l2 ? SD2 : SD1);
    k0 = isG ? 0 : (id >> 2) * n * 64 + (isO ? 0 : ((l2 ? e >> 4 : e) & 1) * 1792);
  }
};

DEVI float geglu(float g, float u) {
  const float z = g * (0.7978845608028654f + 0.035677408136300125f * g * g);
  float t; asm("tanh.approx.f32 %0, %1;" : "=f"(t) : "f"(z));
  const float hg = 0.5f * g;
  return fmaf(hg, t, hg) * u;
}
struct Sched {
  int need, size, e;
  bool filler;
  uint4 dep, cl;
  DEVI void init(int lane) {
    e = (lane < 4 ? lane + 12 : lane < 16 ? lane - 4 : lane) * 4;
    const bool d = e < E_G1 || e >= E_D2, o = e >= E_O1 && e < E_G2;
    need = d ? 28 : e < E_O1 ? 64 : o ? 32 : 128;
    size = d ? 2 * (e < E_G1 ? SD1 : SD2) : o ? 4 * (e < E_O2 ? SO1 : SO2) : e < E_O1 ? 28 : e < E_G2 + 8 ? 56 : 0;
    filler = (int)blockIdx.x >= TP(5);
  }
  DEVI void scan(int lane) { cl = ldg_rlx128(g_claim + e); dep = ldg_rlx128(g_dep + e); }
  DEVI int next(int lane, int& budget) {
    while (--budget > 0) {
      int av[4], open = 0;
#pragma unroll
      for (int i = 0; i < 4; i++) { const int r = max(size - (int)(&cl.x)[i], 0); open |= r; av[i] = ((int)(&dep.x)[i] >= need ? r : 0) + (i ? av[i - 1] : 0); }
      const uint32_t mo = __ballot_sync(0xffffffffu, open);
      if (!mo) break;
      if (filler) {
        const int x = TP(6) & 3, dx = x == 0 ? dep.x : x == 1 ? dep.y : x == 2 ? dep.z : dep.w;
        filler = !__any_sync(0xffffffffu, e == ((E_O1 + TP(6)) & ~3) && dx >= need);
      }
      if (!filler && (mo & 0xffff) && lane >= E_O2 / 4) av[3] = 0;
      int inc = av[3], pos = 0;
      while (true) {
        const uint32_t m = __ballot_sync(0xffffffffu, inc > pos && av[3]);
        if (!m) break;
        const int l = __ffs(m) - 1, rel = pos - (inc - av[3]), i = (rel >= av[0]) + (rel >= av[1]) + (rel >= av[2]);
        int r = 0;
        if (lane == l) {
          const int tk = atomicAdd(g_claim + e + i, 1);
          r = tk < size ? (e + i) << 8 | tk : -1 - (inc - av[3] + (i == 0 ? av[0] : i == 1 ? av[1] : i == 2 ? av[2] : av[3]) + tk - size);
        }
        r = __shfl_sync(0xffffffffu, r, l);
        if (r >= 0) return r;
        if (pos == 0) {
#pragma unroll
          for (int o = 1; o < 32; o <<= 1) { const int v = __shfl_up_sync(0xffffffffu, inc, o); if (lane >= o) inc += v; }
        }
        pos = -1 - r;
      }
      if (pos == 0) __nanosleep(TP(7));
      scan(lane);
    }
    return END;
  }
};

DEVI void scheduler(const uint32_t sb) {
  const int lane = threadIdx.x & 31;
  int budget = SPIN_BUDGET;
  Sched sc; sc.init(lane);
#pragma unroll 1
  for (int i = 0;; i++) {
    mbar_wait(sb + B_GO, (i & 1) ^ 1, budget);
    sc.scan(lane);
    const int task = sc.next(lane, budget);
    const uint32_t r = mapa(sb, lane & 1);
    if (lane < 2) st_async32(r + PMAIL + (i & 1) * 4, task, r + B_PM + (i & 1) * 8);
    __syncwarp();
    if (task == END) break;
  }
}

DEVI void producer(const uint32_t sb, const Maps& M) {
  const int lane = threadIdx.x & 31, rank = cluster_rank();
  int budget = SPIN_BUDGET, s = 0, ph = 0;
#pragma unroll 1
  for (int i = 0;; i++) {
    e_expect_tx(sb + B_PM + (i & 1) * 8, 4);
    mbar_wait_cluster(sb + B_PM + (i & 1) * 8, (i >> 1) & 1, budget);
    const int task = budget < 0 ? END : __shfl_sync(0xffffffffu, (int)lds32v(sb + PMAIL + (i & 1) * 4), 0);
    fence_proxy_global();
    for (int z = 0; z < (task == END ? 2 : 1); z++) {
      const int g = (i + z) & 1;
      mbar_wait(sb + B_TE + g * 8, (((i + z) >> 1) & 1) ^ 1, budget);
      if (lane == 0) { sts64(sb + MAIL + g * 8, task, s | ph << 8); mbar_arrive(sb + B_TF + g * 8); }
      __syncwarp();
    }
    if (task == END) break;
    const Tile T(task, rank);
    const bool shareB = T.isG && T.l2;
    const CUtensorMap* mA = T.isO ? &M.ot : T.isG ? &M.xn : &M.hl;
    const CUtensorMap* mB0 = T.isO ? &M.wo : T.isG ? &M.wg : &M.wd;
    const CUtensorMap* mB1 = T.isG ? &M.wu : mB0;
    const int c0 = T.col * (T.isG ? 64 : 128), c1 = T.isG ? c0 : c0 + 64, row = T.blk * 128;
    const int ok = 0;
    int k = T.k0;
#pragma unroll 1
    for (int it = 0; it < T.n; it++, k += 64) {
      const uint32_t a = sb + s * STAGE, fb = sb + B_FULL + s * 8;
      mbar_wait(sb + B_EMPTY + s * 8, ph ^ 1, budget);
      e_expect_tx(fb, STAGE);
      if (shareB) {
        e_tma_2d_mc(a + 16384 + rank * 8192, rank ? mB1 : mB0, c0, k, fb);
        e_tma_2d(a, mA, k, row, fb); e_tma_2d(a + 8192, mA, k, row + 64, fb);
      } else {
        e_tma_2d_mc(a + rank * 8192, mA, T.isO ? row + rank * 64 : k, T.isO ? k + ok : row + rank * 64, fb);
        e_tma_2d(a + 16384, mB0, c0, k, fb); e_tma_2d(a + 24576, mB1, c1, k, fb);
      }
      if (it == T.n - TP(2)) e_arrive(sb + B_GO);
      if (++s == STAGES) { s = 0; ph ^= 1; }
    }
  }
}

template<int TA> DEVI void mainloop(float* d0, float* d1, uint32_t sb, int n, int s, int ph, bool lead, uint32_t ord, int& budget) {
  int prev = 0;
  const uint32_t rel = threadIdx.x & 127;
#pragma unroll 1
  for (int i = 0; i < n; i++) {
    mbar_wait(sb + B_FULL + s * 8, ph, budget);
    const uint32_t a = sb + s * STAGE;
    const uint64_t da = mkdesc(a, 16, 1024), db = mkdesc(a + 16384, 8192, 1024);
    wg_fence();
#pragma unroll
    for (int k = 0; k < 4; k++) {
      wgmma_n128<TA>(d0, da + k * (TA ? 128 : 2), db + k * 128, (i | k) != 0);
      wgmma_n128<TA>(d1, da + 512 + k * (TA ? 128 : 2), db + k * 128, (i | k) != 0);
    }
    wg_commit();
    if (i > 0) { wg_wait<1>(); p_arrive_at(sb + B_EMPTY + prev * 8, rel & 1, rel < 2); }
    prev = s;
    if (++s == STAGES) { s = 0; ph ^= 1; }
  }
  p_arrive(ord, lead);
  wg_wait<0>();
  p_arrive_at(sb + B_EMPTY + prev * 8, rel & 1, rel < 2);
}

DEVI void consumer(const uint32_t sb, const Maps& M, const int wg) {
  const int tid = threadIdx.x, lane = tid & 31, warp = (tid >> 5) & 3;
  const bool lead = (tid & 127) == 0;
  const uint32_t so = sb + SO + wg * 16384;
  int budget = SPIN_BUDGET;
  float d0[64], d1[64];
#pragma unroll 1
  for (int m = 0;; m++) {
    mbar_wait(sb + B_TF + wg * 8, m & 1, budget);
    const uint2 mail = lds64v(sb + MAIL + wg * 8);
    const int task = __shfl_sync(0xffffffffu, (int)mail.x, 0), pos = __shfl_sync(0xffffffffu, (int)mail.y, 0);
    e_arrive(sb + B_TE + wg * 8);
    if (task == END || budget < 0) break;
    const Tile T(task, cluster_rank());
    mbar_wait(sb + B_ORD + wg * 8, (m & 1) ^ wg ^ 1, budget);
    if (T.isO) mainloop<1>(d0, d1, sb, T.n, pos & 255, pos >> 8, lead, sb + B_ORD + (wg ^ 1) * 8, budget);
    else mainloop<0>(d0, d1, sb, T.n, pos & 255, pos >> 8, lead, sb + B_ORD + (wg ^ 1) * 8, budget);
    const uint32_t st = so + (warp * 16 + (lane & 15)) * 128;
    if (T.isG) {
      int* const fl = &g_dep[T.l2 ? E_D2 + (T.col >= 28) * 16 + T.blk : E_D1 + T.blk * 2 + (T.col >= 28)];
#pragma unroll
      for (int mm = 0; mm < 2; mm++) {
        const float* d = mm ? d1 : d0;
#pragma unroll
        for (int c = 0; c < 4; c++) {
          uint32_t r[4];
#pragma unroll
          for (int i = 0; i < 4; i++) r[i] = pack_bf16(geglu(d[8*c+2*i], d[32+8*c+2*i]), geglu(d[8*c+2*i+1], d[33+8*c+2*i]));
          stsm4(st + mm * 8192 + (((2 * c + (lane >> 4)) ^ (lane & 7)) << 4), r[0], r[1], r[2], r[3]);
        }
      }
      fence_proxy_async();
      nbar_sync_r(1 + wg, 128);
      if (lead) {
        tma_store_2d(&M.hs, so, T.col * 64, T.blk * 128);
        bulk_commit();
        bulk_wait<0>();
        flag_add(fl);
      }
    } else {
#pragma unroll
      for (int hf = 0; hf < 2; hf++) {
        if (hf) { if (lead) bulk_wait_read<0>(); nbar_sync_r(1 + wg, 128); }
#pragma unroll
        for (int mm = 0; mm < 2; mm++) {
          const float* d = (mm ? d1 : d0) + hf * 32;
#pragma unroll
          for (int c = 0; c < 4; c++)
            stsm4(st + mm * 8192 + (((2 * c + (lane >> 4)) ^ (lane & 7)) << 4), pack_bf16(d[8*c], d[8*c+1]), pack_bf16(d[8*c+2], d[8*c+3]),
                  pack_bf16(d[8*c+4], d[8*c+5]), pack_bf16(d[8*c+6], d[8*c+7]));
        }
        fence_proxy_async();
        nbar_sync_r(1 + wg, 128);
        if (lead) { tma_radd_2d(&M.out, so, T.col * 128 + hf * 64, T.blk * 128); bulk_commit(); }
      }
      if (lead) {
        bulk_wait<0>();
        if (T.isO || !T.l2) flag_add(&g_dep[(!T.isO ? E_LX2 : T.l2 ? E_LX1B : E_LX1A) + T.blk]);
      }
    }
    __syncwarp();
  }
}

DEVI void norm_helper(const bf16* __restrict__ x, bf16* out) {
  const int lane = threadIdx.x & 31;
  int budget = SPIN_BUDGET, tk = lane < 4 ? -1 : 1024;
#pragma unroll 1
  while (--budget > 0) {
    if (tk < 0) tk = atomicAdd(g_claim + E_LI + lane, 1);
    if (__all_sync(0xffffffffu, tk >= 1024)) break;
    const uint32_t m = __ballot_sync(0xffffffffu, tk < 1024 && (lane == 0 || ldg_acq32(g_dep + E_LI + lane * 16 + (tk >> 6)) >= 8 * (lane == 1 ? SD1 : lane == 2 ? SO1 : SO2)));
    if (!m) { __nanosleep(TP(7)); continue; }
    const int ql = __ffs(m) - 1, task = __shfl_sync(0xffffffffu, tk, ql), q = E_LI + ql * 16, ev = task >> 6;
    if (lane == ql) tk = -1;
    const size_t off = (size_t)task * (DM * 4) + lane * 16;
    const char* src = (const char*)(q == E_LI ? x : out) + off;
    uint4 u[8];
#pragma unroll
    for (int i = 0; i < 8; i++) u[i] = ldg_rlx128(src + i * 512);
    if (q == E_LI) {
#pragma unroll
      for (int i = 0; i < 8; i++) stg128((char*)out + off + i * 512, u[i].x, u[i].y, u[i].z, u[i].w);
    }
    int* const fl = q == E_LI ? &g_xa[0][ev] : q == E_LX2 ? &g_xa[1][ev] : &g_dep[q == E_LX1A ? E_G1 + ev : E_G2 + (ev >> 1)];
    float mean[2], rs[2];
#pragma unroll
    for (int r = 0; r < 2; r++) {
      float s0 = 0, s1 = 0;
#pragma unroll
      for (int i = 0; i < 16; i++) { const uint32_t v = (&u[4*r + (i >> 2)].x)[i & 3]; s0 += bf_lo(v); s1 += bf_hi(v); }
      mean[r] = (s0 + s1) * (1.f / 32);
      s0 = s1 = 0;
#pragma unroll
      for (int i = 0; i < 16; i++) { const uint32_t v = (&u[4*r + (i >> 2)].x)[i & 3]; const float a = bf_lo(v) - mean[r], b = bf_hi(v) - mean[r]; s0 = fmaf(a, a, s0); s1 = fmaf(b, b, s1); }
      rs[r] = s0 + s1;
    }
    {
      const bool hi = lane & 16;
      float m1 = hi ? mean[1] : mean[0], q1 = hi ? rs[1] : rs[0], m2 = hi ? mean[0] : mean[1], q2 = hi ? rs[0] : rs[1], cnt = 16;
#pragma unroll
      for (int o = 16; o; o >>= 1) {
        m2 = __shfl_xor_sync(0xffffffffu, m2, o); q2 = __shfl_xor_sync(0xffffffffu, q2, o);
        const float dl = m1 - m2;
        q2 = q1 = fmaf(dl * dl, cnt, q1 + q2); m2 = m1 = 0.5f * (m1 + m2);
        cnt *= 2;
      }
      q1 = rsqrtf(q1 * (1.f / DM) + 1e-5f);
      m2 = __shfl_xor_sync(0xffffffffu, m1, 16); q2 = __shfl_xor_sync(0xffffffffu, q1, 16);
      mean[0] = hi ? m2 : m1; mean[1] = hi ? m1 : m2; rs[0] = hi ? q2 : q1; rs[1] = hi ? q1 : q2;
    }
#pragma unroll
    for (int i = 0; i < 8; i++) {
      uint32_t y[4];
#pragma unroll
      for (int c = 0; c < 4; c++) { const uint32_t v = (&u[i].x)[c]; y[c] = pack_bf16((bf_lo(v) - mean[i >> 2]) * rs[i >> 2], (bf_hi(v) - mean[i >> 2]) * rs[i >> 2]); }
      stg128((char*)g_xn + off + i * 512, y[0], y[1], y[2], y[3]);
      u[i] = make_uint4(y[0], y[1], y[2], y[3]);
    }
    if (q == E_LI && (task & 15) >= 12) {
      uint32_t* const xr = g_xr[task >> 4] + lane * 32 + (task & 3);
#pragma unroll
      for (int i = 0; i < 16; i++) {
        const uint32_t a = (&u[i >> 2].x)[i & 3], b = (&u[4 + (i >> 2)].x)[i & 3];
        xr[(i >> 2) * 1024 + (i & 3) * 8] = __byte_perm(a, b, 0x5410); xr[(i >> 2) * 1024 + (i & 3) * 8 + 4] = __byte_perm(a, b, 0x7632);
      }
    }
    fence_proxy_global();
    __syncwarp();
    if (lane == 0) flag_add(fl);
    __syncwarp();
  }
}
}

__global__ void __cluster_dims__(2, 1, 1) __launch_bounds__(384, 1)
gemm_kernel(const __grid_constant__ gm::Maps M, const bf16* __restrict__ x, bf16* out) {
  using namespace gm;
  extern __shared__ __align__(1024) uint8_t smem[];
  const uint32_t sb = __shfl_sync(0xffffffffu, smem_u32(smem), 0);
  const int tid = threadIdx.x, wi = __shfl_sync(0xffffffffu, tid >> 5, 0);
  if (tid < 21) mbar_init(sb + BARS + tid * 8, tid == 14 || tid == 15 ? 4 : tid >= 6 && tid < 12 ? 2 : 1);
  fence_mbar_init();
  cluster_arrive(); cluster_wait();
  if (wi < 8) { reg_inc<208>(); consumer(sb, M, wi >> 2); cluster_arrive(); cluster_wait(); }
  else {
    reg_dec<88>();
    if (wi == 8) producer(sb, M);
    else if (wi == 11 && cluster_rank() == 0) scheduler(sb);
    else {
      norm_helper(x, out);
      asm volatile("griddepcontrol.wait;" ::: "memory");
    }
    __syncwarp();
    cluster_arrive(); cluster_wait();
  }
}

typedef CUresult (*PFN_encodeTiled)(CUtensorMap*, CUtensorMapDataType, cuuint32_t, void*, const cuuint64_t*, const cuuint64_t*,
                                    const cuuint32_t*, const cuuint32_t*, CUtensorMapInterleave, CUtensorMapSwizzle,
                                    CUtensorMapL2promotion, CUtensorMapFloatOOBfill);
static PFN_encodeTiled g_encode = nullptr;
static CUtensorMap make_map(const void* ptr, uint64_t rows, uint64_t cols, uint32_t box_rows, CUtensorMapL2promotion pr = CU_TENSOR_MAP_L2_PROMOTION_L2_256B) {
  CUtensorMap m;
  cuuint64_t dims[2] = {cols, rows}, strides[1] = {cols * 2};
  cuuint32_t box[2] = {64, box_rows}, es[2] = {1, 1};
  g_encode(&m, CU_TENSOR_MAP_DATA_TYPE_BFLOAT16, 2, (void*)ptr, dims, strides, box, es, CU_TENSOR_MAP_INTERLEAVE_NONE,
           CU_TENSOR_MAP_SWIZZLE_128B, pr, CU_TENSOR_MAP_FLOAT_OOB_FILL_NONE);
  return m;
}

static CUtensorMap make_map3(const void* ptr, uint64_t d0, uint64_t d1, uint64_t d2, uint64_t stride2) {
  CUtensorMap m;
  cuuint64_t dims[3] = {d0, d1, d2}, strides[2] = {DM * 2, stride2};
  cuuint32_t box[3] = {64, 32, 2}, es[3] = {1, 1, 1};
  g_encode(&m, CU_TENSOR_MAP_DATA_TYPE_BFLOAT16, 3, (void*)ptr, dims, strides, box, es, CU_TENSOR_MAP_INTERLEAVE_NONE,
           CU_TENSOR_MAP_SWIZZLE_128B, CU_TENSOR_MAP_L2_PROMOTION_L2_256B, CU_TENSOR_MAP_FLOAT_OOB_FILL_NONE);
  return m;
}

extern "C" void kernel_launch(void* const* d_in, const int* in_sizes, int n_in, void* d_out, int out_size) {
  const bf16* x = (const bf16*)d_in[0];
  const bf16* mem0 = (const bf16*)d_in[1];
  if (!g_encode) {
    void* p = nullptr; cudaDriverEntryPointQueryResult q;
    cudaGetDriverEntryPoint("cuTensorMapEncodeTiled", &p, cudaEnableDefault, &q);
    g_encode = (PFN_encodeTiled)p;
    cudaFuncSetAttribute(gemm_kernel, cudaFuncAttributeMaxDynamicSharedMemorySize, gm::SMEM);
    cudaFuncSetAttribute(rec_kernel, cudaFuncAttributeMaxDynamicSharedMemorySize, rec::SMEM);
  }
  bf16 *xn, *ot, *hh;
  cudaGetSymbolAddress((void**)&xn, g_xn); cudaGetSymbolAddress((void**)&ot, g_ot); cudaGetSymbolAddress((void**)&hh, g_h);
  rec::Maps R;
  for (int i = 0; i < 3; i++) R.w[i] = make_map(d_in[2 + i], DM, NH * DH, 16, CU_TENSOR_MAP_L2_PROMOTION_NONE);
  R.wo = make_map(d_in[5], NH * DH, DM, 128);
  R.xd = make_map3(xn, DM, SEQ - LAG * 32, 2, (uint64_t)LAG * 32 * DM * 2); R.xs = make_map3(xn, 64, SEQ, DM / 64, 128);
  gm::Maps G;
  G.ot = make_map(ot, NH * DH + O_LAYER / SEQ, SEQ, 64); G.wo = make_map(d_in[5], NH * DH, DM, 64); G.xn = make_map(xn, SEQ, DM, 64);
  G.wg = make_map(d_in[8], DM, DF, 64); G.wu = make_map(d_in[9], DM, DF, 64); G.hl = make_map(hh, SEQ, DF, 64); G.hs = make_map(hh, SEQ, DF, 128);
  G.wd = make_map(d_in[10], DF, DM, 64); G.out = make_map(d_out, SEQ, DM, 128);
  cudaLaunchConfig_t cfg = {};
  cudaLaunchAttribute at[1];
  cfg.attrs = at; cfg.numAttrs = 1;
  cfg.gridDim = dim3(3 * NH); cfg.blockDim = dim3(384); cfg.dynamicSmemBytes = rec::SMEM; cfg.stream = cudaStreamPerThread;
  at[0].id = cudaLaunchAttributeClusterDimension; at[0].val.clusterDim.y = at[0].val.clusterDim.z = 1;
  static int csize = 0;
  if (!csize) {
    int n = 0;
    at[0].val.clusterDim.x = 6;
    csize = cudaOccupancyMaxActiveClusters(&n, rec_kernel, &cfg) == cudaSuccess && n >= NH / 2 ? CSIZE : 3;
  }
  at[0].val.clusterDim.x = csize;
  cudaLaunchKernelEx(&cfg, rec_kernel, R, mem0);
  cfg.gridDim = dim3(132); cfg.blockDim = dim3(384); cfg.dynamicSmemBytes = gm::SMEM; cfg.stream = cudaStreamPerThread;
  at[0].id = cudaLaunchAttributeProgrammaticStreamSerialization; at[0].val.programmaticStreamSerializationAllowed = 1;
  cudaLaunchKernelEx(&cfg, gemm_kernel, G, x, (bf16*)d_out);
}
```

```cpp
#include <cuda_runtime.h>
#include <cuda_bf16.h>
#include <cuda.h>
#include <stdint.h>

#define DEVI __device__ __forceinline__
typedef __nv_bfloat16 bf16;

constexpr int SEQ = 2048, DM = 1024, NH = 32, DH = 128, DF = 3584, NSEG = 64;
#define LAG 20
constexpr int NSTEP = NSEG + LAG;

#define TSD 1700
constexpr size_t O_LAYER = 0;
__device__ __align__(1024) bf16 g_xn[SEQ * DM];
__device__ __align__(1024) bf16 g_ot[SEQ * NH * DH + O_LAYER];
__device__ __align__(1024) bf16 g_h[SEQ * DF];
__device__ __align__(1024) uint32_t g_xr[NSEG][DM * 4];
__device__ __align__(1024) uint2 g_h1[4][256 * 256];
__device__ __align__(1024) uint4 g_h2[4][2048];
__device__ __align__(128) uint32_t g_ts[2][32];
enum { E_D1 = 0, E_G1 = 32, E_O1 = 48, E_O2 = 64, E_G2 = 80, E_D2 = 96,
       E_LI = 128, E_LX2 = 144, E_LX1A = 160, E_LX1B = 176, NEV = 256 };
__device__ __align__(128) int g_dep[NEV];
__device__ __align__(128) int g_claim[NEV];
__device__ __align__(128) int g_xa[2][32];

#define TUNE_DEFAULTS 1650, 2350, 6, 50, 100, 8, 14, 100, 1550, 2200, 100, 125, 1550, 2250, 200, 0
constexpr int c_D[16] = {TUNE_DEFAULTS};
template<int I> struct TPV { static constexpr int v = c_D[I]; };
#define TP(i) TPV<i>::v

DEVI uint32_t smem_u32(const void* p) { return (uint32_t)__cvta_generic_to_shared(p); }
DEVI void mbar_init(uint32_t bar, uint32_t cnt) { asm volatile("mbarrier.init.shared::cta.b64 [%0], %1;" :: "r"(bar), "r"(cnt) : "memory"); }
DEVI void mbar_arrive(uint32_t bar) { asm volatile("mbarrier.arrive.shared::cta.b64 _, [%0];" :: "r"(bar) : "memory"); }
DEVI bool mbar_try(uint32_t bar, uint32_t parity) {
  uint32_t p;
  asm volatile("{.reg .pred p; mbarrier.try_wait.parity.shared::cta.b64 p, [%1], %2; selp.u32 %0, 1, 0, p;}" : "=r"(p) : "r"(bar), "r"(parity) : "memory");
  return p;
}
DEVI bool mbar_test(uint32_t bar, uint32_t parity) {
  uint32_t p;
  asm volatile("{.reg .pred p; mbarrier.test_wait.parity.shared::cta.b64 p, [%1], %2; selp.u32 %0, 1, 0, p;}" : "=r"(p) : "r"(bar), "r"(parity) : "memory");
  return p;
}
constexpr int SPIN_BUDGET = 1 << 18;
DEVI void mbar_wait(uint32_t bar, uint32_t parity, int& budget) {
  while (!mbar_try(bar, parity)) { if (--budget < 0) break; }
}
DEVI bool mbar_try_cluster(uint32_t bar, uint32_t parity) {
  uint32_t p;
  asm volatile("{.reg .pred p; mbarrier.try_wait.parity.acquire.cluster.shared::cta.b64 p, [%1], %2; selp.u32 %0, 1, 0, p;}" : "=r"(p) : "r"(bar), "r"(parity) : "memory");
  return p;
}
DEVI void mbar_wait_cluster(uint32_t bar, uint32_t parity, int& budget) {
  while (!mbar_try_cluster(bar, parity)) { if (--budget < 0) break; }
}
DEVI uint32_t mapa(uint32_t addr, uint32_t rank) { uint32_t r; asm("mapa.shared::cluster.u32 %0, %1, %2;" : "=r"(r) : "r"(addr), "r"(rank)); return r; }
DEVI void cluster_arrive() { asm volatile("barrier.cluster.arrive.release.aligned;" ::: "memory"); }
DEVI void cluster_wait() { asm volatile("barrier.cluster.wait.acquire.aligned;" ::: "memory"); }
DEVI void fence_mbar_init() { asm volatile("fence.mbarrier_init.release.cluster;" ::: "memory"); }
DEVI void fence_proxy_async() { asm volatile("fence.proxy.async.shared::cta;" ::: "memory"); }
DEVI void fence_proxy_global() { asm volatile("fence.proxy.async.global;" ::: "memory"); }
#define ELECT "{.reg .pred p; elect.sync _|p, 0xffffffff;\n @p "
DEVI void e_expect_tx(uint32_t bar, uint32_t bytes) { asm volatile(ELECT "mbarrier.arrive.expect_tx.shared::cta.b64 _, [%0], %1;}" :: "r"(bar), "r"(bytes) : "memory"); }
DEVI void e_complete_tx(uint32_t bar, uint32_t bytes) { asm volatile("fence.acq_rel.cta;\n" ELECT "mbarrier.complete_tx.relaxed.cta.shared::cta.b64 [%0], %1;}" :: "r"(bar), "r"(bytes) : "memory"); }
DEVI void e_arrive(uint32_t bar) { asm volatile(ELECT "mbarrier.arrive.shared::cta.b64 _, [%0];}" :: "r"(bar) : "memory"); }
DEVI void e_tma_2d(uint32_t dst, const CUtensorMap* m, int c0, int c1, uint32_t bar) {
  asm volatile(ELECT "cp.async.bulk.tensor.2d.shared::cluster.global.mbarrier::complete_tx::bytes [%0], [%1, {%3, %4}], [%2];}"
    :: "r"(dst), "l"(m), "r"(bar), "r"(c0), "r"(c1) : "memory");
}
DEVI void e_prefetch_3d(const CUtensorMap* m, int c0, int c1, int c2) {
  asm volatile(ELECT "cp.async.bulk.prefetch.tensor.3d.L2.global [%0, {%1, %2, %3}];}" :: "l"(m), "r"(c0), "r"(c1), "r"(c2) : "memory");
}
DEVI void e_bulk_g2s(uint32_t dst, const void* src, uint32_t bytes, uint32_t bar) {
  asm volatile(ELECT "cp.async.bulk.shared::cluster.global.mbarrier::complete_tx::bytes [%0], [%1], %2, [%3];}" :: "r"(dst), "l"(src), "r"(bytes), "r"(bar) : "memory");
}
DEVI void e_tma_3d(uint32_t dst, const CUtensorMap* m, int c0, int c1, int c2, uint32_t bar) {
  asm volatile(ELECT "cp.async.bulk.tensor.3d.shared::cluster.global.mbarrier::complete_tx::bytes [%0], [%1, {%3, %4, %5}], [%2];}"
    :: "r"(dst), "l"(m), "r"(bar), "r"(c0), "r"(c1), "r"(c2) : "memory");
}
DEVI void e_tma_3d_mc(uint32_t dst, const CUtensorMap* m, int c0, int c1, int c2, uint32_t bar, int rb) {
  asm volatile(ELECT "cp.async.bulk.tensor.3d.shared::cluster.global.mbarrier::complete_tx::bytes.multicast::cluster [%0], [%1, {%3, %4, %5}], [%2], %6;}"
    :: "r"(dst), "l"(m), "r"(bar), "r"(c0), "r"(c1), "r"(c2), "h"((uint16_t)(7 << rb)) : "memory");
}
DEVI void e_tma_2d_mc(uint32_t dst, const CUtensorMap* m, int c0, int c1, uint32_t bar) {
  asm volatile(ELECT "cp.async.bulk.tensor.2d.shared::cluster.global.mbarrier::complete_tx::bytes.multicast::cluster [%0], [%1, {%3, %4}], [%2], %5;}"
    :: "r"(dst), "l"(m), "r"(bar), "r"(c0), "r"(c1), "h"((uint16_t)3) : "memory");
}
DEVI void p_arrive_at(uint32_t bar, uint32_t rank, bool c) {
  asm volatile("{.reg .pred p; .reg .b32 a; setp.ne.u32 p, %2, 0; mapa.shared::cluster.u32 a, %0, %1; @p mbarrier.arrive.shared::cluster.b64 _, [a];}"
    :: "r"(bar), "r"(rank), "r"((uint32_t)c) : "memory");
}
DEVI void p_expect_tx(uint32_t bar, uint32_t bytes, bool c) {
  asm volatile("{.reg .pred p; setp.ne.u32 p, %2, 0; @p mbarrier.arrive.expect_tx.shared::cta.b64 _, [%0], %1;}" :: "r"(bar), "r"(bytes), "r"((uint32_t)c) : "memory");
}
DEVI void p_arrive(uint32_t bar, bool c) { asm volatile("{.reg .pred p; setp.ne.u32 p, %1, 0; @p mbarrier.arrive.shared::cta.b64 _, [%0];}" :: "r"(bar), "r"((uint32_t)c) : "memory"); }
DEVI void tma_store_2d(const CUtensorMap* m, uint32_t src, int c0, int c1) {
  asm volatile("cp.async.bulk.tensor.2d.global.shared::cta.bulk_group [%0, {%2, %3}], [%1];" :: "l"(m), "r"(src), "r"(c0), "r"(c1) : "memory");
}
DEVI void tma_radd_2d(const CUtensorMap* m, uint32_t src, int c0, int c1) {
  asm volatile("cp.reduce.async.bulk.tensor.2d.global.shared::cta.add.bulk_group [%0, {%2, %3}], [%1];" :: "l"(m), "r"(src), "r"(c0), "r"(c1) : "memory");
}
DEVI void bulk_commit() { asm volatile("cp.async.bulk.commit_group;" ::: "memory"); }
template<int N> DEVI void bulk_wait_read() { asm volatile("cp.async.bulk.wait_group.read %0;" :: "n"(N) : "memory"); }
template<int N> DEVI void bulk_wait() { asm volatile("cp.async.bulk.wait_group %0;" :: "n"(N) : "memory"); }
template<int ID, int N> DEVI void nbar_sync() { asm volatile("bar.sync %0, %1;" :: "n"(ID), "n"(N) : "memory"); }
template<int ID, int N> DEVI void nbar_arrive() { asm volatile("bar.arrive %0, %1;" :: "n"(ID), "n"(N) : "memory"); }
DEVI void nbar_sync_r(int id, int n) { asm volatile("bar.sync %0, %1;" :: "r"(id), "r"(n) : "memory"); }
template<int R> DEVI void reg_inc() { asm volatile("setmaxnreg.inc.sync.aligned.u32 %0;" :: "n"(R)); }
template<int R> DEVI void reg_dec() { asm volatile("setmaxnreg.dec.sync.aligned.u32 %0;" :: "n"(R)); }
DEVI void wg_fence() { asm volatile("wgmma.fence.sync.aligned;" ::: "memory"); }
DEVI void wg_commit() { asm volatile("wgmma.commit_group.sync.aligned;" ::: "memory"); }
template<int N> DEVI void wg_wait() { asm volatile("wgmma.wait_group.sync.aligned %0;" :: "n"(N) : "memory"); }
DEVI uint64_t mkdesc(uint32_t addr, uint32_t lbo, uint32_t sbo, uint32_t sw = 1) {
  return ((uint64_t)((addr & 0x3FFFF) >> 4)) | ((uint64_t)(lbo >> 4) << 16) | ((uint64_t)(sbo >> 4) << 32) | ((uint64_t)sw << 62);
}
constexpr uint32_t SMEM_BASE = 1024;
__host__ __device__ constexpr long long CD(uint32_t off, uint32_t lbo, uint32_t sbo, uint32_t sw) {
  return (long long)(((uint64_t)((SMEM_BASE + off) >> 4)) | ((uint64_t)(lbo >> 4) << 16) | ((uint64_t)(sbo >> 4) << 32) | ((uint64_t)sw << 62));
}
DEVI uint32_t pack_bf16(float lo, float hi) { uint32_t r; asm("cvt.rn.bf16x2.f32 %0, %1, %2;" : "=r"(r) : "f"(hi), "f"(lo)); return r; }
DEVI float bf_lo(uint32_t v) { return __uint_as_float(v << 16); }
DEVI float bf_hi(uint32_t v) { return __uint_as_float(v & 0xffff0000u); }
DEVI void ldsm4t(uint32_t addr, uint32_t& r0, uint32_t& r1, uint32_t& r2, uint32_t& r3) {
  asm volatile("ldmatrix.sync.aligned.m8n8.x4.trans.shared.b16 {%0,%1,%2,%3}, [%4];" : "=r"(r0), "=r"(r1), "=r"(r2), "=r"(r3) : "r"(addr) : "memory");
}
DEVI void stsm4(uint32_t addr, uint32_t r0, uint32_t r1, uint32_t r2, uint32_t r3) {
  asm volatile("stmatrix.sync.aligned.m8n8.x4.shared.b16 [%0], {%1,%2,%3,%4};" :: "r"(addr), "r"(r0), "r"(r1), "r"(r2), "r"(r3) : "memory");
}
DEVI uint2 lds64v(uint32_t a) { uint2 v; asm volatile("ld.volatile.shared.v2.u32 {%0,%1}, [%2];" : "=r"(v.x), "=r"(v.y) : "r"(a) : "memory"); return v; }
DEVI uint32_t lds32v(uint32_t a) { uint32_t v; asm volatile("ld.volatile.shared.u32 %0, [%1];" : "=r"(v) : "r"(a) : "memory"); return v; }
DEVI uint4 lds128v(uint32_t a) { uint4 v; asm volatile("ld.volatile.shared.v4.u32 {%0,%1,%2,%3}, [%4];" : "=r"(v.x), "=r"(v.y), "=r"(v.z), "=r"(v.w) : "r"(a) : "memory"); return v; }
DEVI void sts32(uint32_t a, uint32_t x) { asm volatile("st.shared.u32 [%0], %1;" :: "r"(a), "r"(x) : "memory"); }
DEVI int lane_id() { int r; asm volatile("mov.u32 %0, %%laneid;" : "=r"(r)); return r; }
DEVI void sts64(uint32_t a, uint32_t x, uint32_t y) { asm volatile("st.shared.v2.u32 [%0], {%1,%2};" :: "r"(a), "r"(x), "r"(y) : "memory"); }
DEVI void st_async128(uint32_t a, uint32_t x, uint32_t y, uint32_t z, uint32_t w, uint32_t bar) {
  asm volatile("st.async.weak.shared::cluster.mbarrier::complete_tx::bytes.v4.b32 [%0], {%1,%2,%3,%4}, [%5];" :: "r"(a), "r"(x), "r"(y), "r"(z), "r"(w), "r"(bar) : "memory");
}
DEVI void st_async32(uint32_t a, uint32_t x, uint32_t bar) {
  asm volatile("st.async.weak.shared::cluster.mbarrier::complete_tx::bytes.b32 [%0], %1, [%2];" :: "r"(a), "r"(x), "r"(bar) : "memory");
}
DEVI uint4 ldg_rlx128(const void* p) {
  uint4 v;
  asm volatile("ld.relaxed.gpu.global.v4.b32 {%0,%1,%2,%3}, [%4];" : "=r"(v.x), "=r"(v.y), "=r"(v.z), "=r"(v.w) : "l"(p) : "memory");
  return v;
}
DEVI int ldg_rlx32(const void* p) { int v; asm volatile("ld.relaxed.gpu.global.b32 %0, [%1];" : "=r"(v) : "l"(p) : "memory"); return v; }
DEVI int ldg_acq32(const void* p) { int v; asm volatile("ld.acquire.gpu.global.b32 %0, [%1];" : "=r"(v) : "l"(p) : "memory"); return v; }
DEVI void stg128(void* p, uint32_t x, uint32_t y, uint32_t z, uint32_t w) {
  asm volatile("st.global.v4.b32 [%0], {%1,%2,%3,%4};" :: "l"(p), "r"(x), "r"(y), "r"(z), "r"(w) : "memory");
}
DEVI uint2 ldg_rlx64(const void* p) { uint2 v; asm volatile("{.reg .b64 a; ld.relaxed.gpu.global.b64 a, [%2]; mov.b64 {%0,%1}, a;}" : "=r"(v.x), "=r"(v.y) : "l"(p) : "memory"); return v; }
DEVI void stg_rlx64(void* p, uint32_t x, uint32_t y) { asm volatile("{.reg .b64 a; mov.b64 a, {%1,%2}; st.relaxed.gpu.global.b64 [%0], a;}" :: "l"(p), "r"(x), "r"(y) : "memory"); }
DEVI void stg_rlx32(void* p, uint32_t x) { asm volatile("st.relaxed.gpu.global.b32 [%0], %1;" :: "l"(p), "r"(x) : "memory"); }
DEVI void flag_add(int* p) { asm volatile("fence.proxy.async.global; red.release.gpu.global.add.s32 [%0], 1;" :: "l"(p) : "memory"); }
DEVI void e_stg_rlx32(void* p, uint32_t x) { asm volatile(ELECT "st.relaxed.gpu.global.b32 [%0], %1;}" :: "l"(p), "r"(x) : "memory"); }
DEVI void e_flag_add(int* p) { asm volatile("fence.proxy.async.global;\n" ELECT "red.release.gpu.global.add.s32 [%0], 1;}" :: "l"(p) : "memory"); }
DEVI int cluster_rank() { int r; asm volatile("mov.u32 %0, %%cluster_ctarank;" : "=r"(r)); return __shfl_sync(0xffffffffu, r, 0); }
DEVI int cta_id() { int r; asm volatile("mov.u32 %0, %%ctaid.x;" : "=r"(r)); return __shfl_sync(0xffffffffu, r, 0); }
DEVI uint32_t clock32() { uint32_t c; asm volatile("mov.u32 %0, %%clock;" : "=r"(c)); return c; }
DEVI uint32_t gtime() { uint32_t c; asm volatile("mov.u32 %0, %%globaltimer_lo;" : "=r"(c)); return c; }
DEVI void wait_time(uint32_t t) { while (__any_sync(0xffffffffu, t - gtime() - 1 < 4000u)) {} }
DEVI void spin_until(uint32_t t0, int d) {
  int r;
  while (__any_sync(0xffffffffu, (r = d - (int)(clock32() - t0)) > 0)) {
    if (r > 300) __nanosleep(r >> 2);
  }
}
DEVI void pin2(const void* a, const void* b) { asm volatile("{.reg .pred p; setp.eq.u64 p, %0, %1; @p st.volatile.global.u64 [%0], %1;}" :: "l"(a), "l"(b) : "memory"); }
DEVI void pin2(uint32_t a, uint32_t b) { asm volatile("{.reg .pred p; setp.eq.u32 p, %0, %1; @p st.volatile.shared.u32 [%0], %1;}" :: "r"(a), "r"(b) : "memory"); }
DEVI void p_stg_rlx64(void* p, uint32_t x, uint32_t y, bool c) {
  asm volatile("{.reg .pred p; .reg .b64 a; setp.ne.u32 p, %3, 0; mov.b64 a, {%1,%2}; @p st.relaxed.gpu.global.b64 [%0], a;}" :: "l"(p), "r"(x), "r"(y), "r"((uint32_t)c) : "memory");
}
DEVI void pin2(uint64_t a, uint64_t b) { pin2((const void*)a, (const void*)b); }
DEVI uint64_t pair(uint32_t a, uint32_t bar) { return a | (uint64_t)bar << 32; }
DEVI void st_async32(uint64_t q, uint32_t x) { st_async32((uint32_t)q, x, (uint32_t)(q >> 32)); }
DEVI void st_async128(uint64_t q, uint4 v) { st_async128((uint32_t)q, v.x, v.y, v.z, v.w, (uint32_t)(q >> 32)); }
DEVI float ex2(float x) { float r; asm("ex2.approx.ftz.f32 %0, %1;" : "=f"(r) : "f"(x)); return r; }
DEVI float rcp(float x) { float r; asm("rcp.approx.ftz.f32 %0, %1;" : "=f"(r) : "f"(x)); return r; }
DEVI uint32_t xor_or(uint32_t a, uint32_t t, uint32_t acc) { uint32_t r; asm("lop3.b32 %0, %1, %2, %3, 0xbe;" : "=r"(r) : "r"(a), "r"(t), "r"(acc)); return r; }
DEVI void stsm2(uint32_t addr, uint32_t r0, uint32_t r1) {
  asm volatile("stmatrix.sync.aligned.m8n8.x2.shared.b16 [%0], {%1,%2};" :: "r"(addr), "r"(r0), "r"(r1) : "memory");
}
DEVI uint32_t settag(uint32_t v, uint32_t tag) { return (v & ~1u) | tag; }

#define A4(c, o)  c(d[o+0]), c(d[o+1]), c(d[o+2]), c(d[o+3])
#define A8(c, o)  A4(c, o), A4(c, o+4)
#define A16(c, o) A8(c, o), A8(c, o+8)
#define A12(c, o) A8(c, o), A4(c, o+8)
#define A28(c, o) A16(c, o), A12(c, o+16)
#define RL12 "{%0,%1,%2,%3,%4,%5,%6,%7,%8,%9,%10,%11}"
#define RL28 "{%0,%1,%2,%3,%4,%5,%6,%7,%8,%9,%10,%11,%12,%13,%14,%15,%16,%17,%18,%19,%20,%21,%22,%23,%24,%25,%26,%27}"
#define A20(c, o) A16(c, o), A4(c, o+16)
#define A32(c, o) A16(c, o), A16(c, o+16)
#define RL8  "{%0,%1,%2,%3,%4,%5,%6,%7}"
#define RL16 "{%0,%1,%2,%3,%4,%5,%6,%7,%8,%9,%10,%11,%12,%13,%14,%15}"
#define RL20 "{%0,%1,%2,%3,%4,%5,%6,%7,%8,%9,%10,%11,%12,%13,%14,%15,%16,%17,%18,%19}"
#define RL32 "{%0,%1,%2,%3,%4,%5,%6,%7,%8,%9,%10,%11,%12,%13,%14,%15,%16,%17,%18,%19,%20,%21,%22,%23,%24,%25,%26,%27,%28,%29,%30,%31}"
#define RL64 "{%0,%1,%2,%3,%4,%5,%6,%7,%8,%9,%10,%11,%12,%13,%14,%15,%16,%17,%18,%19,%20,%21,%22,%23,%24,%25,%26,%27,%28,%29,%30,%31," \
  "%32,%33,%34,%35,%36,%37,%38,%39,%40,%41,%42,%43,%44,%45,%46,%47,%48,%49,%50,%51,%52,%53,%54,%55,%56,%57,%58,%59,%60,%61,%62,%63}"
#define WG_OP(shape) "wgmma.mma_async.sync.aligned." shape "k16.f32.bf16.bf16 "
#define DEF_WGMMA(N, RL, AL, i0, i1, i2, i3, i4, i5, i6)                                                                         \
  template<int SC, int TB, long long CB> DEVI void rs##N(float* d, const uint32_t* a) {                                          \
    if (SC) asm volatile("{.reg .b64 tb; mov.b64 tb, %" #i4 ";\n" WG_OP("m64n" #N) RL ", {%" #i0 ",%" #i1 ",%" #i2 ",%" #i3 "}, tb, 1, 1, 1, %" #i5 ";}" \
      : AL("+f", 0) : "r"(a[0]), "r"(a[1]), "r"(a[2]), "r"(a[3]), "n"(CB), "n"(TB));                                             \
    else asm volatile("{.reg .b64 tb; mov.b64 tb, %" #i4 ";\n" WG_OP("m64n" #N) RL ", {%" #i0 ",%" #i1 ",%" #i2 ",%" #i3 "}, tb, 0, 1, 1, %" #i5 ";}" \
      : AL("=f", 0) : "r"(a[0]), "r"(a[1]), "r"(a[2]), "r"(a[3]), "n"(CB), "n"(TB));                                             \
  }                                                                                                                              \
  template<int SC, int TA, int TB, long long CA, long long CB> DEVI void ss##N(float* d, uint32_t a) {                           \
    if (SC) asm volatile("{.reg .b64 ta, tb; .reg .b32 lo, hi; add.u32 lo, %" #i0 ", %" #i1 "; mov.b32 hi, %" #i2 "; mov.b64 ta, {lo, hi}; mov.b64 tb, %" #i3 ";\n" \
      WG_OP("m64n" #N) RL ", ta, tb, 1, 1, 1, %" #i4 ", %" #i5 ";}"                                                              \
      : AL("+f", 0) : "r"(a), "n"((int)CA), "n"((int)(CA >> 32)), "n"(CB), "n"(TA), "n"(TB));                                    \
    else asm volatile("{.reg .b64 ta, tb; .reg .b32 lo, hi; add.u32 lo, %" #i0 ", %" #i1 "; mov.b32 hi, %" #i2 "; mov.b64 ta, {lo, hi}; mov.b64 tb, %" #i3 ";\n" \
      WG_OP("m64n" #N) RL ", ta, tb, 0, 1, 1, %" #i4 ", %" #i5 ";}"                                                              \
      : AL("=f", 0) : "r"(a), "n"((int)CA), "n"((int)(CA >> 32)), "n"(CB), "n"(TA), "n"(TB));                                    \
  }
DEF_WGMMA(8, "{%0,%1,%2,%3}", A4, 4, 5, 6, 7, 8, 9, 10)
DEF_WGMMA(16, RL8, A8, 8, 9, 10, 11, 12, 13, 14)
DEF_WGMMA(32, RL16, A16, 16, 17, 18, 19, 20, 21, 22)
DEF_WGMMA(40, RL20, A20, 20, 21, 22, 23, 24, 25, 26)
DEF_WGMMA(24, RL12, A12, 12, 13, 14, 15, 16, 17, 18)
DEF_WGMMA(56, RL28, A28, 28, 29, 30, 31, 32, 33, 34)
template<int TA> DEVI void wgmma_n128(float* d, uint64_t a, uint64_t b, int scale_d) {
  asm volatile("{.reg .pred p; setp.ne.b32 p, %66, 0;\n" WG_OP("m64n128") RL64 ", %64, %65, p, 1, 1, %67, 1;}"
    : A32("+f", 0), A32("+f", 32) : "l"(a), "l"(b), "r"(scale_d), "n"(TA));
}

namespace rec {
constexpr int KR = 43;
constexpr uint32_t WSZ = (64 - KR) * 2048, STG = KR * 2048;
constexpr uint32_t WS = 0;
constexpr uint32_t RING = 2 * WSZ;
constexpr uint32_t OB = RING + 3 * 8192;
constexpr uint32_t PB = OB + 4096;
constexpr uint32_t WO = RING + 32768;
constexpr uint32_t ATT = WO + 5 * 16384;
constexpr uint32_t AK = ATT + 10240, AV = ATT + 20480;
constexpr uint32_t PAD = ATT + 30720;
constexpr uint32_t BARS = PAD + 128;
constexpr uint32_t B_XE = BARS  , B_FA = BARS + 64  , B_FB = BARS + 88, B_FO = BARS + 96;
constexpr uint32_t B_ME = BARS + 104  , B_WE = BARS + 136, B_PD = BARS + 144;
constexpr uint32_t B_XF = BARS + 152  , B_MF = BARS + 216  , B_CP = BARS + 248  , B_WT = BARS + 280  ;
constexpr uint32_t B_AB = BARS + 296, B_OB = BARS + 304, B_ST = BARS + 312  , B_WS = BARS + 328, B_WO = BARS + 336, B_AT = BARS + 352, B_AV = BARS + 360;
constexpr int NBAR = 46;
constexpr uint32_t M0 = BARS + 384;
constexpr uint32_t SMEM = 232448;
constexpr int NB_P = 1, NB_ST = 2, NB_O = 3, NB_W0 = 4, NB_W1 = 5;
__host__ __device__ constexpr int wo_tile(int rank, int g, int i) { return i < 2 ? i * 6 + (rank == 2 ? g : 4 - 2 * g + rank) : 13 + rank - g; }
constexpr long long D_W = CD(WS, 16, 1024, 1), D_X = CD(0, 16, 1024, 1), D_O = CD(OB, 128, 256, 0);
constexpr long long D_WO = CD(WO, 16, 1024, 1), D_QM = CD(ATT, 640, 0, 0), D_QT = CD(ATT + 128, 640, 64, 0), D_K = CD(AK, 640, 128, 0);
constexpr long long D_V = CD(AV, 128, 640, 0), D_P = CD(PB, 128, 768, 0);
struct Maps { CUtensorMap w[3], wo, xd, xs; };
__host__ __device__ constexpr uint32_t mslot(int c) { return (c ^ (c >> 1)) * 12288; }
__host__ __device__ constexpr uint32_t xslot(int s) { return s < 3 ? RING + s * 8192 : s < 5 ? WO + (s - 3) * 8192 : s < 7 ? WO + (s + 1) * 8192 : OB; }
__host__ __device__ constexpr bool k_smem(int k) { return k % 3 == 2; }
__host__ __device__ constexpr int k_idx(int k) { return k % 3 == 2 ? k / 3 : k - k / 3; }
__host__ __device__ constexpr int k_of_reg(int i) { return i + (i >> 1); }
__host__ __device__ constexpr int k_of_smem(int i) { return 3 * i + 2; }

#define RPROF(i)
#define RPROF_STEP
#define CPROF(i, v)

template<bool DUAL, int K0, int K1> DEVI void seq_mem(float* d, const uint32_t* w, uint32_t dw) {
  if constexpr (K0 < K1) {
    constexpr long long B = CD(RING, 128, DUAL ? 4096 : 8192, 0) + mslot(K0 >> 4) / 16 + (K0 & 15) * 16;
    if constexpr (DUAL) {
      if constexpr (!k_smem(K0)) rs24<K0 != 0, 1, B>(d, w + 4 * k_idx(K0)); else ss24<1, 1, 1, D_W + k_idx(K0) * 128, B>(d, dw);
    } else {
      if constexpr (!k_smem(K0)) rs16<K0 != 0, 1, B>(d, w + 4 * k_idx(K0)); else ss16<1, 1, 1, D_W + k_idx(K0) * 128, B>(d, dw);
    }
    seq_mem<DUAL, K0 + 1, K1>(d, w, dw);
  }
}
template<int N, int K0, int K1> DEVI void seq_tok(float* d, const uint32_t* w, uint32_t dw) {
  if constexpr (K0 < K1) {
    constexpr bool DUAL = N > 32;
    constexpr long long B = D_X + (DUAL ? xslot((K0 >> 2) & 7) / 16 : xslot(K0 >> 3) / 16 + ((K0 >> 2) & 1) * 256) + (K0 & 3) * 2;
    if constexpr (DUAL) {
      if constexpr (!k_smem(K0)) rs56<K0 != 0, 0, B>(d, w + 4 * k_idx(K0)); else ss56<1, 1, 0, D_W + k_idx(K0) * 128, B>(d, dw);
    } else if constexpr (N == 24) {
      if constexpr (!k_smem(K0)) rs24<K0 != 0, 0, B>(d, w + 4 * k_idx(K0)); else ss24<1, 1, 0, D_W + k_idx(K0) * 128, B>(d, dw);
    } else {
      if constexpr (!k_smem(K0)) rs32<K0 != 0, 0, B>(d, w + 4 * k_idx(K0)); else ss32<1, 1, 0, D_W + k_idx(K0) * 128, B>(d, dw);
    }
    seq_tok<N, K0 + 1, K1>(d, w, dw);
  }
}
template<int T, int K0> DEVI void seq_wo(float* d, uint32_t dw) {
  if constexpr (K0 < 8) { ss16<K0 != 0, 1, 1, D_WO + T * 1024 + K0 * 128, D_O + K0 * 32>(d, dw); seq_wo<T, K0 + 1>(d, dw); }
}
template<long long Q, int K0> DEVI void seq_s(float* d) {
  if constexpr (K0 < 8) { ss40<K0 != 0, 1, 1, Q + K0 * 80, D_K + K0 * 80>(d, 0); seq_s<Q, K0 + 1>(d); }
}
template<bool DUAL, int J> DEVI void load_x(uint32_t sb, const Maps* M, int t, int rb) {
  if (DUAL) e_tma_3d_mc(sb + xslot(J & 7), &M->xd, J * 64, (t - LAG) * 32, 0, sb + B_XF + (J & 7) * 8, rb);
  else e_tma_3d_mc(sb + xslot(J & 7), &M->xs, 0, (t < NSEG ? t : t - LAG) * 32, J * 2, sb + B_XF + (J & 7) * 8, rb);
}
DEVI void load_x_lent(uint32_t sb, const Maps* M, int t, int j) {
  const bool dual = t >= LAG && t < NSEG;
  const uint32_t dst = sb + (j == 3 ? xslot(3) : xslot(5));
#pragma unroll
  for (int i = 0; i < 2; i++)
    e_tma_3d(dst + i * 8192, dual ? &M->xd : &M->xs, dual ? (j + i) * 64 : 0, (t < LAG ? t : t - LAG) * 32, dual ? 0 : (j + i) * 2, sb + B_XF + (j + i) * 8);
}
struct True { static constexpr bool value = true; };
struct False { static constexpr bool value = false; };
struct Ctx { uint32_t sb; const Maps* M; int rb, rank, wi; bool lead; uint32_t par; };
#define PFN 2
#define XD 2
template<bool DUAL, int J> DEVI void tok_release(const Ctx& c, int t, int& budget) {
  constexpr int NC = DUAL ? 16 : 8, S = J & 7;
  if constexpr (J + 8 < NC) {
    p_arrive_at(c.sb + B_XE + S * 8, c.rb + J % 3, c.lead);
    p_expect_tx(c.sb + B_XF + S * 8, 8192, c.lead && c.wi == 0);
  } else if constexpr (S == 1 || S == 2 || S == 4 || S == 7) p_arrive(c.sb + B_ME + (S >> 1) * 8, c.lead);
  if constexpr (J == XD - 1) {
    if (c.rank == 1 && c.wi == 5) { mbar_wait(c.sb + B_FO, t & 1, budget); load_x<DUAL, 7>(c.sb, c.M, t, c.rb); }
  } else if constexpr (J >= XD && J - XD + 8 < NC) {
    constexpr int I = J - XD;
    if (c.rank == I % 3 && c.wi == (I & 1) * 4 + 1) { mbar_wait(c.sb + B_XE + I * 8, (t - LAG) & 1, budget); load_x<DUAL, I + 8>(c.sb, c.M, t, c.rb); }
  }
}
template<int N, int J, class F, class G> DEVI bool tok_pass(float* d, const uint32_t* w, uint32_t dw, Ctx& c, int t, int& budget, F after0, G setup) {
  constexpr bool DUAL = N > 32;
  constexpr int NC = DUAL ? 16 : 8, KC = 64 / NC;
  if constexpr (J < NC) {
    if constexpr (J > 1) mbar_wait(c.sb + B_XF + (J & 7) * 8, c.par ^ (J >> 3), budget);
    wg_fence();
    seq_tok<N, J * KC, (J + 1) * KC>(d, w, dw);
    wg_commit();
    if constexpr (J == 1) after0();
    if constexpr (J >= NC - 5 && J < NC - 2) setup(J - (NC - 5));
    if constexpr (J > 0) { wg_wait<1>(); tok_release<DUAL, J - 1>(c, t, budget); }
    return tok_pass<N, J + 1>(d, w, dw, c, t, budget, after0, setup);
  } else {
    const bool ok = mbar_test(c.sb + B_MF, t & 1);
    wg_wait<0>();
    tok_release<DUAL, NC - 1>(c, t, budget);
    if (!DUAL) c.par ^= 1;
    return ok;
  }
}
template<int NB> DEVI void pack_tok(uint32_t* e, const float* d) {
#pragma unroll
  for (int i = 0; i < 8; i++) if ((i & 3) < NB) e[i] = pack_bf16(d[4 * (i & 3) + 2 * (i >> 2)], d[4 * (i & 3) + 2 * (i >> 2) + 1]);
}
DEVI void push_tok(const uint32_t* e, uint32_t sb, uint32_t o, int r, int rank) {
  const uint32_t b = mapa(sb, r);
  st_async128(b + o, e[0], e[1], e[2], e[3], b + (rank == 2 ? B_AV : B_AT));
}
DEVI uint32_t h1_tag(int seg) { return ((seg >> 1) & 1) ^ 1; }
DEVI uint4 pack_part(const float* c, int t) {
  return make_uint4(settag(pack_bf16(c[0], c[1]), h1_tag(t)), pack_bf16(c[2], c[3]), settag(pack_bf16(c[4], c[5]), h1_tag(t - LAG)), pack_bf16(c[6], c[7]));
}
DEVI void put_part(char* p1, char* p2, uint4 z, int t) { p_stg_rlx64(p1, z.x, z.y, t < NSEG); p_stg_rlx64(p2, z.z, z.w, t >= LAG); }

DEVI void rec_math(const uint32_t sb, const int wi, const Maps& M) {
  const int h = cta_id() / 3, rb = cluster_rank() >= 3 ? 3 : 0, rank = cluster_rank() - rb;
  const int warp = wi & 3, wg = wi >> 2;
  const bool lead = (threadIdx.x & 127) == 0;
  int budget = SPIN_BUDGET;
  uint32_t w[4 * KR];
  Ctx cx{sb, &M, rb, rank, wi, lead, 0};
  {
    const int lane = lane_id();
    const uint32_t a = sb + wg * STG + ((lane & 7) + (lane >> 4) * 8) * 128 + (((warp * 2 + ((lane >> 3) & 1)) ^ (lane & 7)) << 4);
    for (int i = 0; i < (wg == 1 || rank == 2 ? 12 : 8); i++)
      stg_rlx64((char*)g_h1[i & 3] + ((wo_tile(rank, wg, i >> 2) * 4 + warp) * 4 + (lane >> 3)) * 2048 + h * 64 + (lane & 7) * 8, 0, 0);
    mbar_wait(sb + B_ST + wg * 8, 0, budget);
#pragma unroll
    for (int k = 0; k < KR; k++) ldsm4t(a + k * 2048, w[4*k], w[4*k+1], w[4*k+2], w[4*k+3]);
    nbar_arrive<NB_ST, 384>();
    nbar_sync_r(NB_W0 + wg, 128);
    for (int i = 0; i < 5; i++) p_arrive_at(sb + B_FA + i * 8, rb + (i == 4), lead);
    mbar_wait(sb + B_WS, 0, budget);
  }
  uint4 z = make_uint4(0, 0, 0, 0);
  char *z1 = nullptr, *z2 = nullptr;
  uint32_t rt0 = 0, rt1 = 0;
  mbar_wait(sb + B_XF, 0, budget); mbar_wait(sb + B_XF + 8, 0, budget);
#pragma unroll 1
  for (int t = 0;; t++) {
    const uint32_t dw = wg * (WSZ >> 4);
    uint32_t e[16];
    bool ok;
    auto finish = [&]() { put_part(z1, z2, z, t - 1); p_arrive_at(sb + B_FO, rb + 1, lead); };
    const int seg = t - rank * LAG;
    const bool att = rank < 2 && (unsigned)seg < (unsigned)NSEG;
    char* p1;
    uint32_t pw, oo;
    uint64_t u0, u1;
    int lane;
    auto setup = [&](int part) {
      if (part == 0) {
        lane = lane_id();
      } else if (part == 1) {
        char* const p = (char*)g_h1 + ((wo_tile(rank, wg, 0) * 4 + warp) * 4 + (lane >> 3)) * 2048 + h * 64 + (lane & 7) * 8;
        p1 = p + (t & 1) * sizeof(g_h1[0]);
        pin2(p1, nullptr);
      } else if (part == 2) {
        oo = OB + (lane >> 4) * 2048 + warp * 512 + rank * 256 + (lane & 15) * 16;
        pw = sb + PB + (wg ? lane * 4 : 768 + warp * 768 + lane * 16);
        pin2(pw, oo);
      } else {
        if (wg) {
          const uint32_t ra = mapa(sb, rb + ((warp & 1) ? 2 : (rank ^ 1) & 1)), rc = mapa(sb, rb + ((warp & 1) ? (rank ^ 1) & 1 : 2));
          u0 = pair(ra + oo, ra + B_OB); u1 = pair(rc + oo, rc + B_OB);
        } else {
          u0 = (uint64_t)((char*)(g_ot + rank * O_LAYER) + (size_t)(h * DH + warp * 16 + (lane >> 2)) * (SEQ * 2) + seg * 64 + (lane & 3) * 16);
          u1 = (uint32_t)((lane & 24) + ((lane >> 2) & 1) + 2 * warp - 8 * (lane & 3));
        }
        pin2(u0, u1);
      }
    };
    RPROF_STEP;
    auto mem_pass = [&](auto dual_c) {
      constexpr bool DUAL = decltype(dual_c)::value;
      float m[DUAL ? 12 : 8];
      RPROF(8 + wg * 12 - 32);
      if (!ok) mbar_wait(sb + B_MF, t & 1, budget);
      wg_fence(); seq_mem<DUAL, 0, 8>(m, w, dw); wg_commit();
      const uint32_t ao = ATT + rank * 10240 + wi * 1280, to = ao + 128 + (lane & 3) * 128 + (lane >> 2) * 16;
      const int la = DUAL ? rank == 0 : t >= NSEG;
      RPROF(1 + wg * 12);
      if (DUAL && rank == 0) {
#pragma unroll
        for (int i = 0; i < 8; i++) { const uint32_t x = e[i]; e[i] = e[8 + i]; e[8 + i] = x; }
      }
      auto piece = [&](int i) { push_tok(e + 4 * i, sb, to + (i & 1) * 640, rb + (la ^ (i >> 1)), rank); };
      piece(0);
      wg_fence(); seq_mem<DUAL, 8, 16>(m, w, dw); wg_commit();
      piece(1);
      mbar_wait(sb + B_MF + 8, t & 1, budget);
      wg_fence(); seq_mem<DUAL, 16, 24>(m, w, dw); wg_commit();
      if (DUAL) piece(2);
      wg_fence(); seq_mem<DUAL, 24, 32>(m, w, dw); wg_commit();
      if (DUAL) piece(3);
      mbar_wait(sb + B_MF + 16, t & 1, budget);
      wg_fence(); seq_mem<DUAL, 32, 48>(m, w, dw); wg_commit();
      wg_wait<1>(); p_arrive(sb + B_PD, lead);
      const uint32_t r0 = mapa(sb, rb + la), r1 = mapa(sb, rb + (la ^ 1)), m0 = r0 + ao + lane * 4, m1 = r1 + ao + lane * 4, ab = rank == 2 ? B_AV : B_AB;
      const uint64_t q0 = pair(m0, r0 + ab), q1 = pair(m0 + 640, r0 + ab), q2 = pair(m1, r1 + ab), q3 = pair(m1 + 640, r1 + ab);
      pin2(q0, q1);
      if (DUAL) pin2(q2, q3);
      mbar_wait(sb + B_MF + 24, t & 1, budget);
      wg_fence(); seq_mem<DUAL, 48, 64>(m, w, dw); wg_commit();
      wg_wait<1>(); p_arrive_at(sb + B_FA, rb, lead);
      wg_wait<0>();
      const uint32_t a0 = pack_bf16(m[0], m[1]), a1 = pack_bf16(m[2], m[3]), a2 = pack_bf16(m[4], m[5]), a3 = pack_bf16(m[6], m[7]);
      if constexpr (DUAL) {
        st_async32(q0, la ? a2 : a0); st_async32(q1, la ? a3 : a1); st_async32(q2, la ? a0 : a2); st_async32(q3, la ? a1 : a3);
        rt0 = pack_bf16(m[8], m[9]); rt1 = pack_bf16(m[10], m[11]);
      } else { st_async32(q0, a0); st_async32(q1, a1); rt0 = a2; rt1 = a3; }
      p_arrive(sb + B_WE, lead);
    };
    if (t >= LAG && t < NSEG) {
      float d[28];
      ok = tok_pass<56, 0>(d, w, dw, cx, t, budget, finish, setup);
      pack_tok<4>(e + 8, d); pack_tok<3>(e, d + 16); e[3] = rt0; e[7] = rt1;
      mem_pass(True());
    } else {
      float d[16];
      if (t > 0) finish();
      if (t > 0 && t < LAG) {
        ok = tok_pass<24, 0>(d, w, dw, cx, t, budget, []() {}, setup);
        pack_tok<3>(e, d); e[3] = rt0; e[7] = rt1;
      } else {
        ok = tok_pass<32, 0>(d, w, dw, cx, t, budget, []() {}, setup);
        pack_tok<4>(e, d);
      }
      mem_pass(False());
    }
    {
      RPROF(2 + wg * 12);
      auto wo_ready = [&]() { if (t == 0) mbar_wait(sb + B_WO, 0, budget); if (t < NSTEP - 1) mbar_wait(sb + B_WT, t & 1, budget); };
      constexpr float SC = 0.08838834764831845f * 1.4426950408889634f;
      if (!att) wo_ready();
      else {
        float s[32];
        setup(3);
        if (wg) {
          uint32_t one[4];
#pragma unroll
          for (int i = 0; i < 4; i++) one[i] = 0x3F803F80u + (pw >> 31);
          mbar_wait_cluster(sb + B_AT, seg & 1, budget);
          mbar_wait_cluster(sb + B_AB, seg & 1, budget);
          fence_proxy_async();
          RPROF(3 + 12);
          wg_fence(); seq_s<D_QM, 0>(s); wg_commit();
          nbar_arrive<NB_P, 256>();
          if (warp == 1) sts32(pw + 640, 0);
          mbar_wait_cluster(sb + B_AV, seg & 1, budget);
          wg_wait<0>();
          float mx = fmaxf(fmaxf(fmaxf(s[0], s[1]), fmaxf(s[4], s[5])), fmaxf(fmaxf(fmaxf(s[8], s[9]), fmaxf(s[12], s[13])), fmaxf(s[16], s[17])));
          const float x1 = __shfl_xor_sync(0xffffffffu, mx, 1), x2 = __shfl_xor_sync(0xffffffffu, mx, 2), x3 = __shfl_xor_sync(0xffffffffu, mx, 3);
          const float u = (warp & 2) ? ((warp & 1) ? s[16] : s[12]) : ((warp & 1) ? s[8] : s[4]);
          const float v = (warp & 2) ? ((warp & 1) ? s[17] : s[13]) : ((warp & 1) ? s[9] : s[5]);
          const float ms = -SC * fmaxf(fmaxf(mx, x1), fmaxf(x2, x3));
          sts32(pw + 128 + warp * 128, pack_bf16(ex2(fmaf(u, SC, ms)), ex2(fmaf(v, SC, ms))));
          if (warp == 0) sts32(pw, pack_bf16(ex2(fmaf(s[0], SC, ms)), ex2(fmaf(s[1], SC, ms))));
          fence_proxy_async();
          nbar_sync<NB_W1, 128>();
          RPROF(4 + 12);
          wg_fence();
          rs8<0, 0, D_P>(s + 8, one); rs8<1, 0, D_P + 16>(s + 8, one); rs8<1, 0, D_P + 32>(s + 8, one);
          wg_commit();
          ss8<0, 0, 0, D_V, D_P>(s, 0); ss8<0, 0, 0, D_V + 320, D_P>(s + 4, 0);
          ss8<1, 0, 0, D_V + 16, D_P + 16>(s, 0); ss8<1, 0, 0, D_V + 336, D_P + 16>(s + 4, 0);
          ss8<1, 0, 0, D_V + 32, D_P + 32>(s, 0); ss8<1, 0, 0, D_V + 352, D_P + 32>(s + 4, 0);
          wg_commit();
          wg_wait<1>();
          const float i0 = rcp(s[8]), i1 = rcp(s[9]);
          wg_wait<0>();
          stsm4(sb + oo, pack_bf16(s[0] * i0, s[1] * i1), pack_bf16(s[2] * i0, s[3] * i1), pack_bf16(s[4] * i0, s[5] * i1), pack_bf16(s[6] * i0, s[7] * i1));
          __syncwarp();
          const uint4 y = lds128v(sb + oo);
          if (t < NSTEP - 1) { st_async128(u0, y); st_async128(u1, y); e_complete_tx(sb + B_OB, 512); }
          wo_ready();
        } else {
          const int lim = (int)u1;
          char* const og = (char*)u0;
          nbar_sync<NB_P, 256>();
          RPROF(3);
          wg_fence();
          seq_s<D_QT, 0>(s);
          wg_commit();
          mbar_wait_cluster(sb + B_AV, seg & 1, budget);
          wg_wait<0>();
#pragma unroll
          for (int i = 0; i < 8; i++) { float& v = s[4 + 4 * (i >> 1) + (i & 1)]; v = i <= lim ? v : -INFINITY; }
          float mx = fmaxf(fmaxf(fmaxf(s[0], s[1]), fmaxf(s[4], s[5])), fmaxf(fmaxf(fmaxf(s[8], s[9]), fmaxf(s[12], s[13])), fmaxf(s[16], s[17])));
          const float x1 = __shfl_xor_sync(0xffffffffu, mx, 1), x2 = __shfl_xor_sync(0xffffffffu, mx, 2), x3 = __shfl_xor_sync(0xffffffffu, mx, 3);
          const float ms = -SC * fmaxf(fmaxf(mx, x1), fmaxf(x2, x3));
#pragma unroll
          for (int i = 0; i < 10; i++) { float& v = s[4 * (i >> 1) + (i & 1)]; v = ex2(fmaf(v, SC, ms)); }
          const float sum = (((s[0] + s[1]) + (s[4] + s[5])) + ((s[8] + s[9]) + (s[12] + s[13]))) + (s[16] + s[17]);
          const float y1 = __shfl_xor_sync(0xffffffffu, sum, 1), y2 = __shfl_xor_sync(0xffffffffu, sum, 2), y3 = __shfl_xor_sync(0xffffffffu, sum, 3);
          const float inv = rcp((sum + y1) + (y2 + y3));
          stsm4(pw, pack_bf16(s[0] * inv, s[1] * inv), pack_bf16(s[4] * inv, s[5] * inv), pack_bf16(s[8] * inv, s[9] * inv), pack_bf16(s[12] * inv, s[13] * inv));
          stsm2(pw + 512, pack_bf16(s[16] * inv, s[17] * inv), 0);
          fence_proxy_async();
          nbar_sync<NB_W0, 128>();
          RPROF(4);
          wg_fence();
          ss32<0, 0, 0, D_V, D_P + 48>(s, 0); ss32<0, 0, 0, D_V + 320, D_P + 48>(s + 16, 0);
          ss32<1, 0, 0, D_V + 16, D_P + 64>(s, 0); ss32<1, 0, 0, D_V + 336, D_P + 64>(s + 16, 0);
          ss32<1, 0, 0, D_V + 32, D_P + 80>(s, 0); ss32<1, 0, 0, D_V + 352, D_P + 80>(s + 16, 0);
          wg_commit();
          wo_ready();
          wg_wait<0>();
#pragma unroll
          for (int i = 0; i < 4; i++) {
            const float* d = s + (i >> 1) * 16 + (i & 1) * 2;
            stg128(og + ((i >> 1) * 64 + (i & 1) * 8) * (SEQ * 2), pack_bf16(d[0], d[1]), pack_bf16(d[4], d[5]), pack_bf16(d[8], d[9]), pack_bf16(d[12], d[13]));
          }
          if ((seg & 3) == 3) nbar_arrive<NB_O, 160>();
        }
      }
      RPROF(5 + wg * 12);
      const bool three = wg == 1 || rank == 2;
      char* const p2 = p1 + (2 + ((t - LAG) & 1) - (t & 1)) * (int)sizeof(g_h1[0]);
      if (t < NSTEP - 1) {
        float c[24];
        const uint32_t dt = wg ? 0 : 3072;
        mbar_wait_cluster(sb + B_OB, t & 1, budget);
        fence_proxy_async();
        RPROF(6 + wg * 12);
        wg_fence(); seq_wo<0, 0>(c, dt); wg_commit(); seq_wo<1, 0>(c + 8, dt); wg_commit();
        mbar_wait(sb + B_XF, cx.par, budget);
        wg_wait<1>();
        if (warp == 2) load_x_lent(sb, &M, t + 1, wg ? 3 : 5);
        put_part(p1, p2, pack_part(c, t), t);
        const int o3 = (wo_tile(rank, wg, three ? 2 : 1) - wo_tile(rank, wg, 0)) * 32768;
        z1 = p1 + o3; z2 = p2 + o3;
        if (three) {
          wg_fence(); seq_wo<2, 0>(c + 16, dt); wg_commit();
          wg_wait<1>(); put_part(p1 + 6 * 32768, p2 + 6 * 32768, pack_part(c + 8, t), t);
          mbar_wait(sb + B_XF + 8, cx.par, budget);
          wg_wait<0>(); z = pack_part(c + 16, t);
        } else { mbar_wait(sb + B_XF + 8, cx.par, budget); wg_wait<0>(); z = pack_part(c + 8, t); }
      } else break;
      RPROF(7 + wg * 12);
    }
  }
}

DEVI void wait_xa(const int* p, int& budget) {
  while (__any_sync(0xffffffffu, ldg_acq32(p) < 64) && --budget > 0) {}
  fence_proxy_global();
}
template<bool DUAL> DEVI void first_loads(uint32_t sb, const Maps* M, int n, int h, int rb, int& budget) {
#pragma unroll
  for (int i = 0; i < PFN; i++) {
    if (DUAL) e_prefetch_3d(&M->xd, ((h + i * (16 / PFN)) & 15) * 64, (n - LAG) * 32, 0);
    else e_prefetch_3d(&M->xs, 0, (n < NSEG ? n : n - LAG) * 32, ((h + i * (8 / PFN)) & 7) * 2);
  }
  if (n + 1 < NSEG) asm volatile(ELECT "cp.async.bulk.prefetch.L2.global [%0], 2048;}" :: "l"((const char*)g_xr[n + 1] + (h & 7) * 2048) : "memory");
  mbar_wait(sb + B_FA, n & 1, budget);
  load_x<DUAL, 0>(sb, M, n, rb); load_x<DUAL, 1>(sb, M, n, rb); load_x<DUAL, 2>(sb, M, n, rb);
}
template<bool DUAL> DEVI void lent_loads(uint32_t sb, const Maps* M, int n, int rb, int& budget) {
  mbar_wait(sb + B_FB, n & 1, budget);
  load_x<DUAL, 3>(sb, M, n, rb); load_x<DUAL, 4>(sb, M, n, rb); load_x<DUAL, 5>(sb, M, n, rb); load_x<DUAL, 6>(sb, M, n, rb);
}
DEVI void rec_comm(const uint32_t sb, const int warp, const Maps& M, const bf16* __restrict__ mem0) {
  const int lane = threadIdx.x & 31, h = cta_id() / 3, rb = cluster_rank() >= 3 ? 3 : 0, rank = cluster_rank() - rb;
  int budget = SPIN_BUDGET;
  const bool two = warp == 3 || (rank == 2 && warp == 2);
  const int ntask = two ? 2 : 1, qi = two ? (warp == 3 ? rank : 3) : rank * 3 + warp;
  const int task0 = two ? h * 2 + (qi >> 1) : 64 + h * 4 + (qi >> 1);
  auto h2_word = [&](int i, int ln) {
    const int task = task0 + i * 192;
    return (char*)g_h2 + (task >> 6) * 8192 + ((qi ^ i) & 1) * 4096 + ((task >> 2) & 15) * 256 + (task & 3) * 32 + (ln & 8) * 16 + (ln & 7) * 4;
  };
  auto first_x = [&](int t) {
    const int n = t + 1;
    p_expect_tx(sb + B_XF + (lane_id() & 7) * 8, 8192, lane_id() < 8);
    if (rank == 0) {
      if (n >= LAG && ((n - LAG) & 3) == 0) wait_xa(&g_xa[1][(n - LAG) >> 2], budget);
      if (n >= LAG && n < NSEG) first_loads<true>(sb, &M, n, h, rb, budget); else first_loads<false>(sb, &M, n, h, rb, budget);
    }
  };
  {
    const int task = task0 + (lane >> 4) * 192, L = (task & 3) * 8 + (lane & 7);
    if ((lane >> 4) < ntask) {
      const bf16* p = mem0 + (L & 3) * 2 * DM + (task >> 2) * 16 + (L >> 2) + (lane & 8);
      uint32_t m0 = (uint32_t)__bfloat16_as_ushort(p[0]) | (uint32_t)__bfloat16_as_ushort(p[DM]) << 16;
      m0 = m0 ? m0 : 0x8000u;
      stg_rlx32(h2_word(lane >> 4, lane), ((qi ^ (lane >> 4)) & 1) ? 0 : m0);
      for (int i = 1; i < 4; i++) stg_rlx32(h2_word(lane >> 4, lane) + i * sizeof(g_h2[0]), 0);
      sts32(sb + M0 + warp * 128 + lane * 4, m0);
    }
    __syncwarp();
    nbar_sync<NB_ST, 384>();
    if (warp == 2) {
      e_expect_tx(sb + B_WS, 2 * WSZ);
#pragma unroll 1
      for (int i = 0; i < 2 * (64 - KR); i++) e_tma_2d(sb + WS + (i & 1) * WSZ + (i >> 1) * 2048, &M.w[rank], h * DH + (i & 1) * 64, k_of_smem(i >> 1) * 16, sb + B_WS);
      const int nt = rank == 2 ? 6 : 5;
      e_expect_tx(sb + B_WO, (nt - 2) * 16384);
#pragma unroll 1
      for (int i = 1; i < nt; i++) if (i != 3) e_tma_2d(sb + WO + i * 16384, &M.wo, wo_tile(rank, 1 - i / 3, i % 3) * 64, h * DH, sb + B_WO);
    }
    wait_xa(&g_xa[0][0], budget);
    if (warp == 3) { first_x(-1); if (rank == 0) lent_loads<false>(sb, &M, 0, rb, budget); }
  }
  uint32_t t0 = gtime() - 4000, cpp = 0;
  const uint32_t cp = sb + B_CP + warp * 8;
#pragma unroll 1
  for (int t = 0;; t++) {
    const int n = t + 1, seg = t - rank * LAG;
    RPROF_STEP;
    const bool att = rank < 2 && (unsigned)seg < (unsigned)NSEG;
    if (warp == 3) {
      if (att) { e_expect_tx(sb + B_AT, 16384); e_expect_tx(sb + B_AB, 4096); e_expect_tx(sb + B_AV, 10240); }
      if (n < NSTEP) e_expect_tx(sb + B_OB, t < NSEG && t >= LAG ? 4096 : 2048);
    }
    {
      const bool dual = t >= LAG && t < NSEG;
      const int ck = warp ^ (warp < 2 && !dual && (rank & 1) == (t >= NSEG));
      const uint32_t lo = t >= NSEG ? 4096 : 0, dst = sb + RING + mslot(ck), bytes = dual ? 8192 : 4096;
      const uint32_t chk = dst + lane_id() * 32 + (lane_id() >> 2) * 4;
      mbar_wait(sb + B_ME + ck * 8, t & 1, budget);
      uint32_t tx = bytes;
      if (n < NSEG) { e_bulk_g2s(dst + 8192, (const char*)g_xr[n] + ck * 4096, 4096, cp); tx += 4096; }
      wait_time(t0 + (t <= LAG ? TP(9) + ck * TP(11) : t <= NSEG ? TP(1) + ck * TP(4) : TP(13) + ck * TP(11)));
      RPROF(24); CPROF(0, gtime());
      int tries = 0;
      while (true) {
        tries++;
        e_bulk_g2s(dst, (const char*)g_h2[t & 3] + ck * 8192 + lo, bytes, cp);
        e_expect_tx(cp, tx); tx = bytes;
        mbar_wait(cp, cpp, budget); cpp ^= 1;
        uint32_t mn = min(min(lds32v(chk), lds32v(chk + 1024)), min(lds32v(chk + 2048), lds32v(chk + 3072)));
        if (dual) mn = min(min(mn, min(lds32v(chk + 4096), lds32v(chk + 5120))), min(lds32v(chk + 6144), lds32v(chk + 7168)));
        if (!__any_sync(0xffffffffu, mn == 0) || --budget < 0) break;
      }
      e_arrive(sb + B_MF + ck * 8);
      RPROF(25); CPROF(1, gtime()); CPROF(2, tries);
      if (n + 1 < NSEG && (n & 3) == 3) wait_xa(&g_xa[0][(n + 1) >> 2], budget);
    }
    {
      const int ln = lane_id(), i = ln >> 4;
      char* const w = h2_word(i, ln);
      if (i < ntask) {
        stg_rlx32(w + ((t + 3) & 3) * sizeof(g_h2[0]), 0);
        if (n == LAG && ((qi ^ i) & 1)) stg_rlx32(w + (n & 3) * sizeof(g_h2[0]), lds32v(sb + M0 + warp * 128 + ln * 4));
      }
      __syncwarp();
    }
    if (n < NSTEP) {
      const uint32_t tag = (n >> 1) & 31;
      mbar_wait(sb + B_PD, t & 1, budget);
      t0 = clock32();
      if (warp == 2) {
        mbar_wait(sb + B_ME + 24, t & 1, budget);
        e_expect_tx(sb + B_WT, 32768);
        e_tma_2d(sb + WO + 49152, &M.wo, wo_tile(rank, 0, 0) * 64, h * DH, sb + B_WT);
        mbar_wait(sb + B_WE, t & 1, budget);
        e_tma_2d(sb + WO, &M.wo, wo_tile(rank, 1, 0) * 64, h * DH, sb + B_WT);
      }
      if (warp == 3) first_x(t);
      if (warp == 0 && rank == (t >= NSEG)) { mbar_wait(sb + B_AB, seg & 1, budget); e_stg_rlx32(&g_ts[t & 1][h], (gtime() & ~31u) | tag); }
      spin_until(t0, TSD);
      uint32_t v;
      do { v = ldg_rlx32(&g_ts[t & 1][lane_id()]); } while (__any_sync(0xffffffffu, (v & 31) != tag) && --budget > 0);
      const uint32_t now = __shfl_sync(0xffffffffu, v, 0);
      t0 = now + __reduce_max_sync(0xffffffffu, (int)(v - now));
      if (warp == 3) mbar_wait(sb + B_OB, t & 1, budget);
    }
    if (n < NSTEP) {
      RPROF(26); CPROF(3, t0);
#pragma unroll 1
      for (int i = 0; i < ntask; i++) {
        const int layer = (qi ^ i) & 1, sg = t - layer * LAG, task = task0 + i * 192;
        if ((unsigned)sg >= (unsigned)(NSEG - 1)) continue;
        const uint32_t tag = h1_tag(sg);
        const int ln = lane_id();
        const char* const src = (const char*)g_h1[layer * 2 + (sg & 1)] + task * 2048 + ln * 8;
        char* const dst = h2_word(i, ln) + (n & 3) * sizeof(g_h2[0]);
        uint2 v[8];
        pin2(src, dst);
        const int wave = task < 64 ? 0 : task < 192 ? 1 : 2;
        wait_time(t0 + (t < LAG ? TP(8) : t < NSEG ? TP(0) : TP(12)) + (wave == 0 ? -TP(10) : wave == 1 ? 0 : TP(3)));
        int tries = 0;
        float a[4];
        while (true) {
          tries++;
#pragma unroll
          for (int k = 0; k < 8; k++) v[k] = ldg_rlx64(src + k * 256);
          uint32_t bad = 0;
#pragma unroll
          for (int k = 0; k < 8; k++) {
            bad = xor_or(v[k].x, tag, bad);
            a[0] = k ? a[0] + bf_lo(v[k].x) : bf_lo(v[k].x); a[1] = k ? a[1] + bf_hi(v[k].x) : bf_hi(v[k].x);
            a[2] = k ? a[2] + bf_lo(v[k].y) : bf_lo(v[k].y); a[3] = k ? a[3] + bf_hi(v[k].y) : bf_hi(v[k].y);
          }
#pragma unroll
        for (int k = 0; k < 2; k++) {
          const float keep = (ln & 8) ? a[2+k] : a[k], send = (ln & 8) ? a[k] : a[2+k];
          a[k] = keep + __shfl_xor_sync(0xffffffffu, send, 8);
        }
#pragma unroll
        for (int k = 0; k < 2; k++) a[k] += __shfl_xor_sync(0xffffffffu, a[k], 16);
          if (!__any_sync(0xffffffffu, bad & 1) || --budget < 0) break;
        }
        const uint32_t out = pack_bf16(a[0], a[1]);
        if (ln < 16) stg_rlx32(dst, out ? out : 0x8000u);
        __syncwarp();
        if (i == 0) { RPROF(28); CPROF(6, gtime()); CPROF(4, gtime()); CPROF(5, tries); } else CPROF(7, gtime());
      }
    }
    if (warp == (t >= LAG && t < NSEG ? 2 : 1) && att && (seg & 3) == 3) {
      nbar_sync<NB_O, 160>(); e_flag_add(&g_dep[E_O1 + rank * 16 + (seg >> 2)]); }
    if (n == NSTEP) break;
  }
  if (h == 0 && rank == 0 && warp < 2) g_xa[warp][lane_id()] = 0;
}
}

__global__ void __launch_bounds__(384, 1)
rec_kernel(const __grid_constant__ rec::Maps M, const bf16* __restrict__ mem0) {
  using namespace rec;
  extern __shared__ __align__(1024) uint8_t smem[];
  const uint32_t sb = __shfl_sync(0xffffffffu, smem_u32(smem), 0);
  const int tid = threadIdx.x, wi = __shfl_sync(0xffffffffu, tid >> 5, 0);
  if ((sb & 0x3FFFF) != SMEM_BASE) __trap();
  if (wi == 0) {
    const int h = cta_id() / 3, rank = cta_id() - h * 3;
    for (int i = tid; i < NBAR; i += 32) mbar_init(sb + BARS + i * 8, i < 13 ? 6 : i < 19 ? 2 : 1);
    ((uint32_t*)(smem + PAD))[tid] = 0;
    fence_mbar_init(); fence_proxy_async();
    __syncwarp();
    e_expect_tx(sb + B_ST, STG); e_expect_tx(sb + B_ST + 8, STG);
    for (int i = 0; i < 2 * KR; i++) e_tma_2d(sb + (i & 1) * STG + (i >> 1) * 2048, &M.w[rank], h * DH + (i & 1) * 64, k_of_reg(i >> 1) * 16, sb + B_ST + (i & 1) * 8);
  } else if (wi == 1) {
    if (blockIdx.x < NEV / 32) { g_dep[blockIdx.x * 32 + (tid & 31)] = 0; g_claim[blockIdx.x * 32 + (tid & 31)] = 0; __threadfence(); }
    __syncwarp();
    asm volatile("griddepcontrol.launch_dependents;" ::: "memory");
  }
  cluster_arrive(); cluster_wait();
  if (wi < 8) { reg_inc<232>(); rec_math(sb, wi, M); cluster_arrive(); cluster_wait(); }
  else { reg_dec<40>(); rec_comm(sb, wi & 3, M, mem0); cluster_arrive(); cluster_wait(); }
}

namespace gm {
struct Maps { CUtensorMap ot, wo, xn, wg, wu, hl, hs, wd, out; };
constexpr int STAGES = 6, STAGE = 32768;
constexpr uint32_t SO = STAGES * STAGE, BARS = SO + 32768;
constexpr uint32_t B_FULL = BARS, B_EMPTY = BARS + 48, B_TF = BARS + 96, B_TE = BARS + 112, B_ORD = BARS + 128, B_PM = BARS + 144, B_GO = BARS + 160;
constexpr uint32_t MAIL = BARS + 176, PMAIL = BARS + 192;
constexpr uint32_t SMEM = BARS + 256;
constexpr int END = -1;
#define GT gtime

struct Tile {
  bool isO, isG, l2; int blk, col, k0, n;
  DEVI Tile(int task, int rank) {
    const int e = task >> 8, id = task & 255;
    const bool isD = e < E_G1 || e >= E_D2;
    isO = e >= E_O1 && e < E_G2; isG = !isD && !isO; l2 = e >= E_O2;
    blk = isG && l2 ? (e & 15) * 2 + rank : isD && !l2 ? e >> 1 : e & 15;
    col = isG ? (l2 ? id : id * 2 + rank) : (id & 3) * 2 + rank;
    k0 = isO ? (id >> 2) * 2048 : isG ? 0 : ((l2 ? e >> 4 : e) & 1) * 1792;
    n = isO ? 32 : isG ? 16 : 28;
  }
};

DEVI float geglu(float g, float u) {
  const float z = g * (0.7978845608028654f + 0.035677408136300125f * g * g);
  float t; asm("tanh.approx.f32 %0, %1;" : "=f"(t) : "f"(z));
  const float hg = 0.5f * g;
  return fmaf(hg, t, hg) * u;
}
struct Sched {
  int need, size, e;
  bool filler;
  uint4 dep, cl;
  DEVI void init(int lane) {
    e = (lane < 4 ? lane + 12 : lane < 16 ? lane - 4 : lane) * 4;
    const bool d = e < E_G1 || e >= E_D2, o = e >= E_O1 && e < E_G2;
    need = d ? 28 : e < E_O1 ? 64 : o ? 32 : 128;
    size = d ? 4 : o ? 8 : e < E_O1 ? 28 : e < E_G2 + 8 ? 56 : 0;
    filler = (int)blockIdx.x >= TP(5);
  }
  DEVI void scan(int lane) { cl = ldg_rlx128(g_claim + e); dep = ldg_rlx128(g_dep + e); }
  DEVI int next(int lane, int& budget) {
    while (--budget > 0) {
      int av[4], open = 0;
#pragma unroll
      for (int i = 0; i < 4; i++) { const int r = max(size - (int)(&cl.x)[i], 0); open |= r; av[i] = ((int)(&dep.x)[i] >= need ? r : 0) + (i ? av[i - 1] : 0); }
      const uint32_t mo = __ballot_sync(0xffffffffu, open);
      if (!mo) break;
      if (filler) {
        const int x = TP(6) & 3, dx = x == 0 ? dep.x : x == 1 ? dep.y : x == 2 ? dep.z : dep.w;
        filler = !__any_sync(0xffffffffu, e == ((E_O1 + TP(6)) & ~3) && dx >= need);
      }
      if (!filler && (mo & 0xffff) && lane >= E_O2 / 4) av[3] = 0;
      int inc = av[3], pos = 0;
      while (true) {
        const uint32_t m = __ballot_sync(0xffffffffu, inc > pos && av[3]);
        if (!m) break;
        const int l = __ffs(m) - 1, rel = pos - (inc - av[3]), i = (rel >= av[0]) + (rel >= av[1]) + (rel >= av[2]);
        int r = 0;
        if (lane == l) {
          const int tk = atomicAdd(g_claim + e + i, 1);
          r = tk < size ? (e + i) << 8 | tk : -1 - (inc - av[3] + (i == 0 ? av[0] : i == 1 ? av[1] : i == 2 ? av[2] : av[3]) + tk - size);
        }
        r = __shfl_sync(0xffffffffu, r, l);
        if (r >= 0) return r;
        if (pos == 0) {
#pragma unroll
          for (int o = 1; o < 32; o <<= 1) { const int v = __shfl_up_sync(0xffffffffu, inc, o); if (lane >= o) inc += v; }
        }
        pos = -1 - r;
      }
      if (pos == 0) __nanosleep(TP(7));
      scan(lane);
    }
    return END;
  }
};

DEVI void scheduler(const uint32_t sb) {
  const int lane = threadIdx.x & 31;
  int budget = SPIN_BUDGET;
  Sched sc; sc.init(lane);
#pragma unroll 1
  for (int i = 0;; i++) {
    mbar_wait(sb + B_GO, (i & 1) ^ 1, budget);
    sc.scan(lane);
    const int task = sc.next(lane, budget);
    const uint32_t r = mapa(sb, lane & 1);
    if (lane < 2) st_async32(r + PMAIL + (i & 1) * 4, task, r + B_PM + (i & 1) * 8);
    __syncwarp();
    if (task == END) break;
  }
}

DEVI void producer(const uint32_t sb, const Maps& M) {
  const int lane = threadIdx.x & 31, rank = cluster_rank();
  int budget = SPIN_BUDGET, s = 0, ph = 0;
#pragma unroll 1
  for (int i = 0;; i++) {
    e_expect_tx(sb + B_PM + (i & 1) * 8, 4);
    mbar_wait_cluster(sb + B_PM + (i & 1) * 8, (i >> 1) & 1, budget);
    const int task = budget < 0 ? END : __shfl_sync(0xffffffffu, (int)lds32v(sb + PMAIL + (i & 1) * 4), 0);
    fence_proxy_global();
    for (int z = 0; z < (task == END ? 2 : 1); z++) {
      const int g = (i + z) & 1;
      mbar_wait(sb + B_TE + g * 8, (((i + z) >> 1) & 1) ^ 1, budget);
      if (lane == 0) { sts64(sb + MAIL + g * 8, task, s | ph << 8); mbar_arrive(sb + B_TF + g * 8); }
      __syncwarp();
    }
    if (task == END) break;
    const Tile T(task, rank);
    const bool shareB = T.isG && T.l2;
    const CUtensorMap* mA = T.isO ? &M.ot : T.isG ? &M.xn : &M.hl;
    const CUtensorMap* mB0 = T.isO ? &M.wo : T.isG ? &M.wg : &M.wd;
    const CUtensorMap* mB1 = T.isG ? &M.wu : mB0;
    const int c0 = T.col * (T.isG ? 64 : 128), c1 = T.isG ? c0 : c0 + 64, row = T.blk * 128;
    const int ok = 0;
    int k = T.k0;
#pragma unroll 1
    for (int it = 0; it < T.n; it++, k += 64) {
      const uint32_t a = sb + s * STAGE, fb = sb + B_FULL + s * 8;
      mbar_wait(sb + B_EMPTY + s * 8, ph ^ 1, budget);
      e_expect_tx(fb, STAGE);
      if (shareB) {
        e_tma_2d_mc(a + 16384 + rank * 8192, rank ? mB1 : mB0, c0, k, fb);
        e_tma_2d(a, mA, k, row, fb); e_tma_2d(a + 8192, mA, k, row + 64, fb);
      } else {
        e_tma_2d_mc(a + rank * 8192, mA, T.isO ? row + rank * 64 : k, T.isO ? k + ok : row + rank * 64, fb);
        e_tma_2d(a + 16384, mB0, c0, k, fb); e_tma_2d(a + 24576, mB1, c1, k, fb);
      }
      if (it == T.n - TP(2)) e_arrive(sb + B_GO);
      if (++s == STAGES) { s = 0; ph ^= 1; }
    }
  }
}

template<int TA> DEVI void mainloop(float* d0, float* d1, uint32_t sb, int n, int s, int ph, bool lead, uint32_t ord, int& budget) {
  int prev = 0;
  const uint32_t rel = threadIdx.x & 127;
#pragma unroll 1
  for (int i = 0; i < n; i++) {
    mbar_wait(sb + B_FULL + s * 8, ph, budget);
    const uint32_t a = sb + s * STAGE;
    const uint64_t da = mkdesc(a, 16, 1024), db = mkdesc(a + 16384, 8192, 1024);
    wg_fence();
#pragma unroll
    for (int k = 0; k < 4; k++) {
      wgmma_n128<TA>(d0, da + k * (TA ? 128 : 2), db + k * 128, (i | k) != 0);
      wgmma_n128<TA>(d1, da + 512 + k * (TA ? 128 : 2), db + k * 128, (i | k) != 0);
    }
    wg_commit();
    if (i > 0) { wg_wait<1>(); p_arrive_at(sb + B_EMPTY + prev * 8, rel & 1, rel < 2); }
    prev = s;
    if (++s == STAGES) { s = 0; ph ^= 1; }
  }
  p_arrive(ord, lead);
  wg_wait<0>();
  p_arrive_at(sb + B_EMPTY + prev * 8, rel & 1, rel < 2);
}

DEVI void consumer(const uint32_t sb, const Maps& M, const int wg) {
  const int tid = threadIdx.x, lane = tid & 31, warp = (tid >> 5) & 3;
  const bool lead = (tid & 127) == 0;
  const uint32_t so = sb + SO + wg * 16384;
  int budget = SPIN_BUDGET;
  float d0[64], d1[64];
#pragma unroll 1
  for (int m = 0;; m++) {
    mbar_wait(sb + B_TF + wg * 8, m & 1, budget);
    const uint2 mail = lds64v(sb + MAIL + wg * 8);
    const int task = __shfl_sync(0xffffffffu, (int)mail.x, 0), pos = __shfl_sync(0xffffffffu, (int)mail.y, 0);
    e_arrive(sb + B_TE + wg * 8);
    if (task == END || budget < 0) break;
    const Tile T(task, cluster_rank());
    mbar_wait(sb + B_ORD + wg * 8, (m & 1) ^ wg ^ 1, budget);
    if (T.isO) mainloop<1>(d0, d1, sb, T.n, pos & 255, pos >> 8, lead, sb + B_ORD + (wg ^ 1) * 8, budget);
    else mainloop<0>(d0, d1, sb, T.n, pos & 255, pos >> 8, lead, sb + B_ORD + (wg ^ 1) * 8, budget);
    const uint32_t st = so + (warp * 16 + (lane & 15)) * 128;
    if (T.isG) {
      int* const fl = &g_dep[T.l2 ? E_D2 + (T.col >= 28) * 16 + T.blk : E_D1 + T.blk * 2 + (T.col >= 28)];
#pragma unroll
      for (int mm = 0; mm < 2; mm++) {
        const float* d = mm ? d1 : d0;
#pragma unroll
        for (int c = 0; c < 4; c++) {
          uint32_t r[4];
#pragma unroll
          for (int i = 0; i < 4; i++) r[i] = pack_bf16(geglu(d[8*c+2*i], d[32+8*c+2*i]), geglu(d[8*c+2*i+1], d[33+8*c+2*i]));
          stsm4(st + mm * 8192 + (((2 * c + (lane >> 4)) ^ (lane & 7)) << 4), r[0], r[1], r[2], r[3]);
        }
      }
      fence_proxy_async();
      nbar_sync_r(1 + wg, 128);
      if (lead) {
        tma_store_2d(&M.hs, so, T.col * 64, T.blk * 128);
        bulk_commit();
        bulk_wait<0>();
        flag_add(fl);
      }
    } else {
#pragma unroll
      for (int hf = 0; hf < 2; hf++) {
        if (hf) { if (lead) bulk_wait_read<0>(); nbar_sync_r(1 + wg, 128); }
#pragma unroll
        for (int mm = 0; mm < 2; mm++) {
          const float* d = (mm ? d1 : d0) + hf * 32;
#pragma unroll
          for (int c = 0; c < 4; c++)
            stsm4(st + mm * 8192 + (((2 * c + (lane >> 4)) ^ (lane & 7)) << 4), pack_bf16(d[8*c], d[8*c+1]), pack_bf16(d[8*c+2], d[8*c+3]),
                  pack_bf16(d[8*c+4], d[8*c+5]), pack_bf16(d[8*c+6], d[8*c+7]));
        }
        fence_proxy_async();
        nbar_sync_r(1 + wg, 128);
        if (lead) { tma_radd_2d(&M.out, so, T.col * 128 + hf * 64, T.blk * 128); bulk_commit(); }
      }
      if (lead) {
        bulk_wait<0>();
        if (T.isO || !T.l2) flag_add(&g_dep[(!T.isO ? E_LX2 : T.l2 ? E_LX1B : E_LX1A) + T.blk]);
      }
    }
    __syncwarp();
  }
}

DEVI void norm_helper(const bf16* __restrict__ x, bf16* out) {
  const int lane = threadIdx.x & 31;
  int budget = SPIN_BUDGET, tk = lane < 4 ? -1 : 1024;
#pragma unroll 1
  while (--budget > 0) {
    if (tk < 0) tk = atomicAdd(g_claim + E_LI + lane, 1);
    if (__all_sync(0xffffffffu, tk >= 1024)) break;
    const uint32_t m = __ballot_sync(0xffffffffu, tk < 1024 && (lane == 0 || ldg_acq32(g_dep + E_LI + lane * 16 + (tk >> 6)) >= 16));
    if (!m) { __nanosleep(TP(7)); continue; }
    const int ql = __ffs(m) - 1, task = __shfl_sync(0xffffffffu, tk, ql), q = E_LI + ql * 16, ev = task >> 6;
    if (lane == ql) tk = -1;
    const size_t off = (size_t)task * (DM * 4) + lane * 16;
    const char* src = (const char*)(q == E_LI ? x : out) + off;
    uint4 u[8];
#pragma unroll
    for (int i = 0; i < 8; i++) u[i] = ldg_rlx128(src + i * 512);
    if (q == E_LI) {
#pragma unroll
      for (int i = 0; i < 8; i++) stg128((char*)out + off + i * 512, u[i].x, u[i].y, u[i].z, u[i].w);
    }
    int* const fl = q == E_LI ? &g_xa[0][ev] : q == E_LX2 ? &g_xa[1][ev] : &g_dep[q == E_LX1A ? E_G1 + ev : E_G2 + (ev >> 1)];
    float mean[2], rs[2];
#pragma unroll
    for (int r = 0; r < 2; r++) {
      float s0 = 0, s1 = 0;
#pragma unroll
      for (int i = 0; i < 16; i++) { const uint32_t v = (&u[4*r + (i >> 2)].x)[i & 3]; s0 += bf_lo(v); s1 += bf_hi(v); }
      mean[r] = (s0 + s1) * (1.f / 32);
      s0 = s1 = 0;
#pragma unroll
      for (int i = 0; i < 16; i++) { const uint32_t v = (&u[4*r + (i >> 2)].x)[i & 3]; const float a = bf_lo(v) - mean[r], b = bf_hi(v) - mean[r]; s0 = fmaf(a, a, s0); s1 = fmaf(b, b, s1); }
      rs[r] = s0 + s1;
    }
    {
      const bool hi = lane & 16;
      float m1 = hi ? mean[1] : mean[0], q1 = hi ? rs[1] : rs[0], m2 = hi ? mean[0] : mean[1], q2 = hi ? rs[0] : rs[1], cnt = 16;
#pragma unroll
      for (int o = 16; o; o >>= 1) {
        m2 = __shfl_xor_sync(0xffffffffu, m2, o); q2 = __shfl_xor_sync(0xffffffffu, q2, o);
        const float dl = m1 - m2;
        q2 = q1 = fmaf(dl * dl, cnt, q1 + q2); m2 = m1 = 0.5f * (m1 + m2);
        cnt *= 2;
      }
      q1 = rsqrtf(q1 * (1.f / DM) + 1e-5f);
      m2 = __shfl_xor_sync(0xffffffffu, m1, 16); q2 = __shfl_xor_sync(0xffffffffu, q1, 16);
      mean[0] = hi ? m2 : m1; mean[1] = hi ? m1 : m2; rs[0] = hi ? q2 : q1; rs[1] = hi ? q1 : q2;
    }
#pragma unroll
    for (int i = 0; i < 8; i++) {
      uint32_t y[4];
#pragma unroll
      for (int c = 0; c < 4; c++) { const uint32_t v = (&u[i].x)[c]; y[c] = pack_bf16((bf_lo(v) - mean[i >> 2]) * rs[i >> 2], (bf_hi(v) - mean[i >> 2]) * rs[i >> 2]); }
      stg128((char*)g_xn + off + i * 512, y[0], y[1], y[2], y[3]);
      u[i] = make_uint4(y[0], y[1], y[2], y[3]);
    }
    if (q == E_LI && (task & 15) >= 12) {
      uint32_t* const xr = g_xr[task >> 4] + lane * 32 + (task & 3);
#pragma unroll
      for (int i = 0; i < 16; i++) {
        const uint32_t a = (&u[i >> 2].x)[i & 3], b = (&u[4 + (i >> 2)].x)[i & 3];
        xr[(i >> 2) * 1024 + (i & 3) * 8] = __byte_perm(a, b, 0x5410); xr[(i >> 2) * 1024 + (i & 3) * 8 + 4] = __byte_perm(a, b, 0x7632);
      }
    }
    fence_proxy_global();
    __syncwarp();
    if (lane == 0) flag_add(fl);
    __syncwarp();
  }
}
}

__global__ void __cluster_dims__(2, 1, 1) __launch_bounds__(384, 1)
gemm_kernel(const __grid_constant__ gm::Maps M, const bf16* __restrict__ x, bf16* out) {
  using namespace gm;
  extern __shared__ __align__(1024) uint8_t smem[];
  const uint32_t sb = __shfl_sync(0xffffffffu, smem_u32(smem), 0);
  const int tid = threadIdx.x, wi = __shfl_sync(0xffffffffu, tid >> 5, 0);
  if (tid < 21) mbar_init(sb + BARS + tid * 8, tid == 14 || tid == 15 ? 4 : tid >= 6 && tid < 12 ? 2 : 1);
  fence_mbar_init();
  cluster_arrive(); cluster_wait();
  if (wi < 8) { reg_inc<208>(); consumer(sb, M, wi >> 2); cluster_arrive(); cluster_wait(); }
  else {
    reg_dec<88>();
    if (wi == 8) producer(sb, M);
    else if (wi == 11 && cluster_rank() == 0) scheduler(sb);
    else {
      norm_helper(x, out);
      asm volatile("griddepcontrol.wait;" ::: "memory");
    }
    __syncwarp();
    cluster_arrive(); cluster_wait();
  }
}

typedef CUresult (*PFN_encodeTiled)(CUtensorMap*, CUtensorMapDataType, cuuint32_t, void*, const cuuint64_t*, const cuuint64_t*,
                                    const cuuint32_t*, const cuuint32_t*, CUtensorMapInterleave, CUtensorMapSwizzle,
                                    CUtensorMapL2promotion, CUtensorMapFloatOOBfill);
static PFN_encodeTiled g_encode = nullptr;
static CUtensorMap make_map(const void* ptr, uint64_t rows, uint64_t cols, uint32_t box_rows, CUtensorMapL2promotion pr = CU_TENSOR_MAP_L2_PROMOTION_L2_256B) {
  CUtensorMap m;
  cuuint64_t dims[2] = {cols, rows}, strides[1] = {cols * 2};
  cuuint32_t box[2] = {64, box_rows}, es[2] = {1, 1};
  g_encode(&m, CU_TENSOR_MAP_DATA_TYPE_BFLOAT16, 2, (void*)ptr, dims, strides, box, es, CU_TENSOR_MAP_INTERLEAVE_NONE,
           CU_TENSOR_MAP_SWIZZLE_128B, pr, CU_TENSOR_MAP_FLOAT_OOB_FILL_NONE);
  return m;
}

static CUtensorMap make_map3(const void* ptr, uint64_t d0, uint64_t d1, uint64_t d2, uint64_t stride2) {
  CUtensorMap m;
  cuuint64_t dims[3] = {d0, d1, d2}, strides[2] = {DM * 2, stride2};
  cuuint32_t box[3] = {64, 32, 2}, es[3] = {1, 1, 1};
  g_encode(&m, CU_TENSOR_MAP_DATA_TYPE_BFLOAT16, 3, (void*)ptr, dims, strides, box, es, CU_TENSOR_MAP_INTERLEAVE_NONE,
           CU_TENSOR_MAP_SWIZZLE_128B, CU_TENSOR_MAP_L2_PROMOTION_L2_256B, CU_TENSOR_MAP_FLOAT_OOB_FILL_NONE);
  return m;
}

extern "C" void kernel_launch(void* const* d_in, const int* in_sizes, int n_in, void* d_out, int out_size) {
  const bf16* x = (const bf16*)d_in[0];
  const bf16* mem0 = (const bf16*)d_in[1];
  if (!g_encode) {
    void* p = nullptr; cudaDriverEntryPointQueryResult q;
    cudaGetDriverEntryPoint("cuTensorMapEncodeTiled", &p, cudaEnableDefault, &q);
    g_encode = (PFN_encodeTiled)p;
    cudaFuncSetAttribute(gemm_kernel, cudaFuncAttributeMaxDynamicSharedMemorySize, gm::SMEM);
    cudaFuncSetAttribute(rec_kernel, cudaFuncAttributeMaxDynamicSharedMemorySize, rec::SMEM);
  }
  bf16 *xn, *ot, *hh;
  cudaGetSymbolAddress((void**)&xn, g_xn); cudaGetSymbolAddress((void**)&ot, g_ot); cudaGetSymbolAddress((void**)&hh, g_h);
  rec::Maps R;
  for (int i = 0; i < 3; i++) R.w[i] = make_map(d_in[2 + i], DM, NH * DH, 16, CU_TENSOR_MAP_L2_PROMOTION_NONE);
  R.wo = make_map(d_in[5], NH * DH, DM, 128);
  R.xd = make_map3(xn, DM, SEQ - LAG * 32, 2, (uint64_t)LAG * 32 * DM * 2); R.xs = make_map3(xn, 64, SEQ, DM / 64, 128);
  gm::Maps G;
  G.ot = make_map(ot, NH * DH + O_LAYER / SEQ, SEQ, 64); G.wo = make_map(d_in[5], NH * DH, DM, 64); G.xn = make_map(xn, SEQ, DM, 64);
  G.wg = make_map(d_in[8], DM, DF, 64); G.wu = make_map(d_in[9], DM, DF, 64); G.hl = make_map(hh, SEQ, DF, 64); G.hs = make_map(hh, SEQ, DF, 128);
  G.wd = make_map(d_in[10], DF, DM, 64); G.out = make_map(d_out, SEQ, DM, 128);
  cudaLaunchConfig_t cfg = {};
  cudaLaunchAttribute at[1];
  cfg.attrs = at; cfg.numAttrs = 1;
  cfg.gridDim = dim3(3 * NH); cfg.blockDim = dim3(384); cfg.dynamicSmemBytes = rec::SMEM; cfg.stream = cudaStreamPerThread;
  at[0].id = cudaLaunchAttributeClusterDimension; at[0].val.clusterDim.y = at[0].val.clusterDim.z = 1;
  static int csize = 0;
  if (!csize) {
    int n = 0;
    at[0].val.clusterDim.x = 6;
    csize = cudaOccupancyMaxActiveClusters(&n, rec_kernel, &cfg) == cudaSuccess && n >= NH / 2 ? 6 : 3;
  }
  at[0].val.clusterDim.x = csize;
  cudaLaunchKernelEx(&cfg, rec_kernel, R, mem0);
  cfg.gridDim = dim3(132); cfg.blockDim = dim3(384); cfg.dynamicSmemBytes = gm::SMEM; cfg.stream = cudaStreamPerThread;
  at[0].id = cudaLaunchAttributeProgrammaticStreamSerialization; at[0].val.programmaticStreamSerializationAllowed = 1;
  cudaLaunchKernelEx(&cfg, gemm_kernel, G, x, (bf16*)d_out);
}
```

```cpp
#include <cuda_runtime.h>
#include <cuda_bf16.h>
#include <cuda.h>
#include <stdint.h>

#define DEVI __device__ __forceinline__
typedef __nv_bfloat16 bf16;

constexpr int SEQ = 2048, DM = 1024, NH = 32, DH = 128, DF = 3584, NSEG = 64;
#define LAG 20
constexpr int NSTEP = NSEG + LAG;

#define TSD 1800
constexpr size_t O_LAYER = 0;
__device__ __align__(1024) bf16 g_xn[SEQ * DM];
__device__ __align__(1024) bf16 g_ot[SEQ * NH * DH + O_LAYER];
__device__ __align__(1024) bf16 g_h[SEQ * DF];
__device__ __align__(1024) uint32_t g_xr[NSEG][DM * 4];
__device__ __align__(1024) uint2 g_h1[4][256 * 256];
__device__ __align__(1024) uint4 g_h2[4][2048];
__device__ __align__(128) uint32_t g_ts[2][32];
enum { E_D1 = 0, E_G1 = 32, E_O1 = 48, E_O2 = 64, E_G2 = 80, E_D2 = 96,
       E_LI = 128, E_LX2 = 144, E_LX1A = 160, E_LX1B = 176, NEV = 256 };
__device__ __align__(128) int g_dep[NEV];
__device__ __align__(128) int g_claim[NEV];
__device__ __align__(128) int g_xa[2][32];

#define TUNE_DEFAULTS 1650, 2450, 6, 100, 100, 8, 14, 100, 1550, 2280, 100, 110, 1550, 2320, 200, 0
constexpr int c_D[16] = {TUNE_DEFAULTS};
template<int I> struct TPV { static constexpr int v = c_D[I]; };
#define TP(i) TPV<i>::v

DEVI uint32_t smem_u32(const void* p) { return (uint32_t)__cvta_generic_to_shared(p); }
DEVI void mbar_init(uint32_t bar, uint32_t cnt) { asm volatile("mbarrier.init.shared::cta.b64 [%0], %1;" :: "r"(bar), "r"(cnt) : "memory"); }
DEVI void mbar_arrive(uint32_t bar) { asm volatile("mbarrier.arrive.shared::cta.b64 _, [%0];" :: "r"(bar) : "memory"); }
DEVI bool mbar_try(uint32_t bar, uint32_t parity) {
  uint32_t p;
  asm volatile("{.reg .pred p; mbarrier.try_wait.parity.shared::cta.b64 p, [%1], %2; selp.u32 %0, 1, 0, p;}" : "=r"(p) : "r"(bar), "r"(parity) : "memory");
  return p;
}
DEVI bool mbar_test(uint32_t bar, uint32_t parity) {
  uint32_t p;
  asm volatile("{.reg .pred p; mbarrier.test_wait.parity.shared::cta.b64 p, [%1], %2; selp.u32 %0, 1, 0, p;}" : "=r"(p) : "r"(bar), "r"(parity) : "memory");
  return p;
}
constexpr int SPIN_BUDGET = 1 << 18;
DEVI void mbar_wait(uint32_t bar, uint32_t parity, int& budget) {
  while (!mbar_try(bar, parity)) { if (--budget < 0) break; }
}
DEVI bool mbar_try_cluster(uint32_t bar, uint32_t parity) {
  uint32_t p;
  asm volatile("{.reg .pred p; mbarrier.try_wait.parity.acquire.cluster.shared::cta.b64 p, [%1], %2; selp.u32 %0, 1, 0, p;}" : "=r"(p) : "r"(bar), "r"(parity) : "memory");
  return p;
}
DEVI void mbar_wait_cluster(uint32_t bar, uint32_t parity, int& budget) {
  while (!mbar_try_cluster(bar, parity)) { if (--budget < 0) break; }
}
DEVI uint32_t mapa(uint32_t addr, uint32_t rank) { uint32_t r; asm("mapa.shared::cluster.u32 %0, %1, %2;" : "=r"(r) : "r"(addr), "r"(rank)); return r; }
DEVI void cluster_arrive() { asm volatile("barrier.cluster.arrive.release.aligned;" ::: "memory"); }
DEVI void cluster_wait() { asm volatile("barrier.cluster.wait.acquire.aligned;" ::: "memory"); }
DEVI void fence_mbar_init() { asm volatile("fence.mbarrier_init.release.cluster;" ::: "memory"); }
DEVI void fence_proxy_async() { asm volatile("fence.proxy.async.shared::cta;" ::: "memory"); }
DEVI void fence_proxy_global() { asm volatile("fence.proxy.async.global;" ::: "memory"); }
#define ELECT "{.reg .pred p; elect.sync _|p, 0xffffffff;\n @p "
DEVI void e_expect_tx(uint32_t bar, uint32_t bytes) { asm volatile(ELECT "mbarrier.arrive.expect_tx.shared::cta.b64 _, [%0], %1;}" :: "r"(bar), "r"(bytes) : "memory"); }
DEVI void e_complete_tx(uint32_t bar, uint32_t bytes) { asm volatile("fence.acq_rel.cta;\n" ELECT "mbarrier.complete_tx.relaxed.cta.shared::cta.b64 [%0], %1;}" :: "r"(bar), "r"(bytes) : "memory"); }
DEVI void e_arrive(uint32_t bar) { asm volatile(ELECT "mbarrier.arrive.shared::cta.b64 _, [%0];}" :: "r"(bar) : "memory"); }
DEVI void e_tma_2d(uint32_t dst, const CUtensorMap* m, int c0, int c1, uint32_t bar) {
  asm volatile(ELECT "cp.async.bulk.tensor.2d.shared::cluster.global.mbarrier::complete_tx::bytes [%0], [%1, {%3, %4}], [%2];}"
    :: "r"(dst), "l"(m), "r"(bar), "r"(c0), "r"(c1) : "memory");
}
DEVI void e_prefetch_3d(const CUtensorMap* m, int c0, int c1, int c2) {
  asm volatile(ELECT "cp.async.bulk.prefetch.tensor.3d.L2.global [%0, {%1, %2, %3}];}" :: "l"(m), "r"(c0), "r"(c1), "r"(c2) : "memory");
}
DEVI void e_bulk_g2s(uint32_t dst, const void* src, uint32_t bytes, uint32_t bar) {
  asm volatile(ELECT "cp.async.bulk.shared::cluster.global.mbarrier::complete_tx::bytes [%0], [%1], %2, [%3];}" :: "r"(dst), "l"(src), "r"(bytes), "r"(bar) : "memory");
}
DEVI void e_tma_3d(uint32_t dst, const CUtensorMap* m, int c0, int c1, int c2, uint32_t bar) {
  asm volatile(ELECT "cp.async.bulk.tensor.3d.shared::cluster.global.mbarrier::complete_tx::bytes [%0], [%1, {%3, %4, %5}], [%2];}"
    :: "r"(dst), "l"(m), "r"(bar), "r"(c0), "r"(c1), "r"(c2) : "memory");
}
DEVI void e_tma_3d_mc(uint32_t dst, const CUtensorMap* m, int c0, int c1, int c2, uint32_t bar, int rb) {
  asm volatile(ELECT "cp.async.bulk.tensor.3d.shared::cluster.global.mbarrier::complete_tx::bytes.multicast::cluster [%0], [%1, {%3, %4, %5}], [%2], %6;}"
    :: "r"(dst), "l"(m), "r"(bar), "r"(c0), "r"(c1), "r"(c2), "h"((uint16_t)(7 << rb)) : "memory");
}
DEVI void e_tma_2d_mc(uint32_t dst, const CUtensorMap* m, int c0, int c1, uint32_t bar) {
  asm volatile(ELECT "cp.async.bulk.tensor.2d.shared::cluster.global.mbarrier::complete_tx::bytes.multicast::cluster [%0], [%1, {%3, %4}], [%2], %5;}"
    :: "r"(dst), "l"(m), "r"(bar), "r"(c0), "r"(c1), "h"((uint16_t)3) : "memory");
}
DEVI void p_arrive_at(uint32_t bar, uint32_t rank, bool c) {
  asm volatile("{.reg .pred p; .reg .b32 a; setp.ne.u32 p, %2, 0; mapa.shared::cluster.u32 a, %0, %1; @p mbarrier.arrive.shared::cluster.b64 _, [a];}"
    :: "r"(bar), "r"(rank), "r"((uint32_t)c) : "memory");
}
DEVI void p_expect_tx(uint32_t bar, uint32_t bytes, bool c) {
  asm volatile("{.reg .pred p; setp.ne.u32 p, %2, 0; @p mbarrier.arrive.expect_tx.shared::cta.b64 _, [%0], %1;}" :: "r"(bar), "r"(bytes), "r"((uint32_t)c) : "memory");
}
DEVI void p_arrive(uint32_t bar, bool c) { asm volatile("{.reg .pred p; setp.ne.u32 p, %1, 0; @p mbarrier.arrive.shared::cta.b64 _, [%0];}" :: "r"(bar), "r"((uint32_t)c) : "memory"); }
DEVI void tma_store_2d(const CUtensorMap* m, uint32_t src, int c0, int c1) {
  asm volatile("cp.async.bulk.tensor.2d.global.shared::cta.bulk_group [%0, {%2, %3}], [%1];" :: "l"(m), "r"(src), "r"(c0), "r"(c1) : "memory");
}
DEVI void tma_radd_2d(const CUtensorMap* m, uint32_t src, int c0, int c1) {
  asm volatile("cp.reduce.async.bulk.tensor.2d.global.shared::cta.add.bulk_group [%0, {%2, %3}], [%1];" :: "l"(m), "r"(src), "r"(c0), "r"(c1) : "memory");
}
DEVI void bulk_commit() { asm volatile("cp.async.bulk.commit_group;" ::: "memory"); }
template<int N> DEVI void bulk_wait_read() { asm volatile("cp.async.bulk.wait_group.read %0;" :: "n"(N) : "memory"); }
template<int N> DEVI void bulk_wait() { asm volatile("cp.async.bulk.wait_group %0;" :: "n"(N) : "memory"); }
template<int ID, int N> DEVI void nbar_sync() { asm volatile("bar.sync %0, %1;" :: "n"(ID), "n"(N) : "memory"); }
template<int ID, int N> DEVI void nbar_arrive() { asm volatile("bar.arrive %0, %1;" :: "n"(ID), "n"(N) : "memory"); }
DEVI void nbar_sync_r(int id, int n) { asm volatile("bar.sync %0, %1;" :: "r"(id), "r"(n) : "memory"); }
template<int R> DEVI void reg_inc() { asm volatile("setmaxnreg.inc.sync.aligned.u32 %0;" :: "n"(R)); }
template<int R> DEVI void reg_dec() { asm volatile("setmaxnreg.dec.sync.aligned.u32 %0;" :: "n"(R)); }
DEVI void wg_fence() { asm volatile("wgmma.fence.sync.aligned;" ::: "memory"); }
DEVI void wg_commit() { asm volatile("wgmma.commit_group.sync.aligned;" ::: "memory"); }
template<int N> DEVI void wg_wait() { asm volatile("wgmma.wait_group.sync.aligned %0;" :: "n"(N) : "memory"); }
DEVI uint64_t mkdesc(uint32_t addr, uint32_t lbo, uint32_t sbo, uint32_t sw = 1) {
  return ((uint64_t)((addr & 0x3FFFF) >> 4)) | ((uint64_t)(lbo >> 4) << 16) | ((uint64_t)(sbo >> 4) << 32) | ((uint64_t)sw << 62);
}
constexpr uint32_t SMEM_BASE = 1024;
__host__ __device__ constexpr long long CD(uint32_t off, uint32_t lbo, uint32_t sbo, uint32_t sw) {
  return (long long)(((uint64_t)((SMEM_BASE + off) >> 4)) | ((uint64_t)(lbo >> 4) << 16) | ((uint64_t)(sbo >> 4) << 32) | ((uint64_t)sw << 62));
}
DEVI uint32_t pack_bf16(float lo, float hi) { uint32_t r; asm("cvt.rn.bf16x2.f32 %0, %1, %2;" : "=r"(r) : "f"(hi), "f"(lo)); return r; }
DEVI float bf_lo(uint32_t v) { return __uint_as_float(v << 16); }
DEVI float bf_hi(uint32_t v) { return __uint_as_float(v & 0xffff0000u); }
DEVI void ldsm4t(uint32_t addr, uint32_t& r0, uint32_t& r1, uint32_t& r2, uint32_t& r3) {
  asm volatile("ldmatrix.sync.aligned.m8n8.x4.trans.shared.b16 {%0,%1,%2,%3}, [%4];" : "=r"(r0), "=r"(r1), "=r"(r2), "=r"(r3) : "r"(addr) : "memory");
}
DEVI void stsm4(uint32_t addr, uint32_t r0, uint32_t r1, uint32_t r2, uint32_t r3) {
  asm volatile("stmatrix.sync.aligned.m8n8.x4.shared.b16 [%0], {%1,%2,%3,%4};" :: "r"(addr), "r"(r0), "r"(r1), "r"(r2), "r"(r3) : "memory");
}
DEVI uint2 lds64v(uint32_t a) { uint2 v; asm volatile("ld.volatile.shared.v2.u32 {%0,%1}, [%2];" : "=r"(v.x), "=r"(v.y) : "r"(a) : "memory"); return v; }
DEVI uint32_t lds32v(uint32_t a) { uint32_t v; asm volatile("ld.volatile.shared.u32 %0, [%1];" : "=r"(v) : "r"(a) : "memory"); return v; }
DEVI uint4 lds128v(uint32_t a) { uint4 v; asm volatile("ld.volatile.shared.v4.u32 {%0,%1,%2,%3}, [%4];" : "=r"(v.x), "=r"(v.y), "=r"(v.z), "=r"(v.w) : "r"(a) : "memory"); return v; }
DEVI void sts32(uint32_t a, uint32_t x) { asm volatile("st.shared.u32 [%0], %1;" :: "r"(a), "r"(x) : "memory"); }
DEVI int lane_id() { int r; asm volatile("mov.u32 %0, %%laneid;" : "=r"(r)); return r; }
DEVI void sts64(uint32_t a, uint32_t x, uint32_t y) { asm volatile("st.shared.v2.u32 [%0], {%1,%2};" :: "r"(a), "r"(x), "r"(y) : "memory"); }
DEVI void st_async128(uint32_t a, uint32_t x, uint32_t y, uint32_t z, uint32_t w, uint32_t bar) {
  asm volatile("st.async.weak.shared::cluster.mbarrier::complete_tx::bytes.v4.b32 [%0], {%1,%2,%3,%4}, [%5];" :: "r"(a), "r"(x), "r"(y), "r"(z), "r"(w), "r"(bar) : "memory");
}
DEVI void st_async32(uint32_t a, uint32_t x, uint32_t bar) {
  asm volatile("st.async.weak.shared::cluster.mbarrier::complete_tx::bytes.b32 [%0], %1, [%2];" :: "r"(a), "r"(x), "r"(bar) : "memory");
}
DEVI uint4 ldg_rlx128(const void* p) {
  uint4 v;
  asm volatile("ld.relaxed.gpu.global.v4.b32 {%0,%1,%2,%3}, [%4];" : "=r"(v.x), "=r"(v.y), "=r"(v.z), "=r"(v.w) : "l"(p) : "memory");
  return v;
}
DEVI int ldg_rlx32(const void* p) { int v; asm volatile("ld.relaxed.gpu.global.b32 %0, [%1];" : "=r"(v) : "l"(p) : "memory"); return v; }
DEVI int ldg_acq32(const void* p) { int v; asm volatile("ld.acquire.gpu.global.b32 %0, [%1];" : "=r"(v) : "l"(p) : "memory"); return v; }
DEVI void stg128(void* p, uint32_t x, uint32_t y, uint32_t z, uint32_t w) {
  asm volatile("st.global.v4.b32 [%0], {%1,%2,%3,%4};" :: "l"(p), "r"(x), "r"(y), "r"(z), "r"(w) : "memory");
}
DEVI uint2 ldg_rlx64(const void* p) { uint2 v; asm volatile("{.reg .b64 a; ld.relaxed.gpu.global.b64 a, [%2]; mov.b64 {%0,%1}, a;}" : "=r"(v.x), "=r"(v.y) : "l"(p) : "memory"); return v; }
DEVI void stg_rlx64(void* p, uint32_t x, uint32_t y) { asm volatile("{.reg .b64 a; mov.b64 a, {%1,%2}; st.relaxed.gpu.global.b64 [%0], a;}" :: "l"(p), "r"(x), "r"(y) : "memory"); }
DEVI void stg_rlx32(void* p, uint32_t x) { asm volatile("st.relaxed.gpu.global.b32 [%0], %1;" :: "l"(p), "r"(x) : "memory"); }
DEVI void flag_add(int* p) { asm volatile("fence.proxy.async.global; red.release.gpu.global.add.s32 [%0], 1;" :: "l"(p) : "memory"); }
DEVI void e_stg_rlx32(void* p, uint32_t x) { asm volatile(ELECT "st.relaxed.gpu.global.b32 [%0], %1;}" :: "l"(p), "r"(x) : "memory"); }
DEVI void e_flag_add(int* p) { asm volatile("fence.proxy.async.global;\n" ELECT "red.release.gpu.global.add.s32 [%0], 1;}" :: "l"(p) : "memory"); }
DEVI int cluster_rank() { int r; asm volatile("mov.u32 %0, %%cluster_ctarank;" : "=r"(r)); return __shfl_sync(0xffffffffu, r, 0); }
DEVI int cta_id() { int r; asm volatile("mov.u32 %0, %%ctaid.x;" : "=r"(r)); return __shfl_sync(0xffffffffu, r, 0); }
DEVI uint32_t clock32() { uint32_t c; asm volatile("mov.u32 %0, %%clock;" : "=r"(c)); return c; }
DEVI uint32_t gtime() { uint32_t c; asm volatile("mov.u32 %0, %%globaltimer_lo;" : "=r"(c)); return c; }
DEVI void wait_time(uint32_t t) { while (__any_sync(0xffffffffu, t - gtime() - 1 < 4000u)) {} }
DEVI void spin_until(uint32_t t0, int d) {
  int r;
  while (__any_sync(0xffffffffu, (r = d - (int)(clock32() - t0)) > 0)) {
    if (r > 300) __nanosleep(r >> 2);
  }
}
DEVI void pin2(const void* a, const void* b) { asm volatile("{.reg .pred p; setp.eq.u64 p, %0, %1; @p st.volatile.global.u64 [%0], %1;}" :: "l"(a), "l"(b) : "memory"); }
DEVI void pin2(uint32_t a, uint32_t b) { asm volatile("{.reg .pred p; setp.eq.u32 p, %0, %1; @p st.volatile.shared.u32 [%0], %1;}" :: "r"(a), "r"(b) : "memory"); }
DEVI void p_stg_rlx64(void* p, uint32_t x, uint32_t y, bool c) {
  asm volatile("{.reg .pred p; .reg .b64 a; setp.ne.u32 p, %3, 0; mov.b64 a, {%1,%2}; @p st.relaxed.gpu.global.b64 [%0], a;}" :: "l"(p), "r"(x), "r"(y), "r"((uint32_t)c) : "memory");
}
DEVI void pin2(uint64_t a, uint64_t b) { pin2((const void*)a, (const void*)b); }
DEVI uint64_t pair(uint32_t a, uint32_t bar) { return a | (uint64_t)bar << 32; }
DEVI void st_async32(uint64_t q, uint32_t x) { st_async32((uint32_t)q, x, (uint32_t)(q >> 32)); }
DEVI void st_async128(uint64_t q, uint4 v) { st_async128((uint32_t)q, v.x, v.y, v.z, v.w, (uint32_t)(q >> 32)); }
DEVI float ex2(float x) { float r; asm("ex2.approx.ftz.f32 %0, %1;" : "=f"(r) : "f"(x)); return r; }
DEVI float rcp(float x) { float r; asm("rcp.approx.ftz.f32 %0, %1;" : "=f"(r) : "f"(x)); return r; }
DEVI uint32_t xor_or(uint32_t a, uint32_t t, uint32_t acc) { uint32_t r; asm("lop3.b32 %0, %1, %2, %3, 0xbe;" : "=r"(r) : "r"(a), "r"(t), "r"(acc)); return r; }
DEVI void stsm2(uint32_t addr, uint32_t r0, uint32_t r1) {
  asm volatile("stmatrix.sync.aligned.m8n8.x2.shared.b16 [%0], {%1,%2};" :: "r"(addr), "r"(r0), "r"(r1) : "memory");
}
DEVI uint32_t settag(uint32_t v, uint32_t tag) { return (v & ~1u) | tag; }

#define A4(c, o)  c(d[o+0]), c(d[o+1]), c(d[o+2]), c(d[o+3])
#define A8(c, o)  A4(c, o), A4(c, o+4)
#define A16(c, o) A8(c, o), A8(c, o+8)
#define A12(c, o) A8(c, o), A4(c, o+8)
#define A28(c, o) A16(c, o), A12(c, o+16)
#define RL12 "{%0,%1,%2,%3,%4,%5,%6,%7,%8,%9,%10,%11}"
#define RL28 "{%0,%1,%2,%3,%4,%5,%6,%7,%8,%9,%10,%11,%12,%13,%14,%15,%16,%17,%18,%19,%20,%21,%22,%23,%24,%25,%26,%27}"
#define A20(c, o) A16(c, o), A4(c, o+16)
#define A32(c, o) A16(c, o), A16(c, o+16)
#define RL8  "{%0,%1,%2,%3,%4,%5,%6,%7}"
#define RL16 "{%0,%1,%2,%3,%4,%5,%6,%7,%8,%9,%10,%11,%12,%13,%14,%15}"
#define RL20 "{%0,%1,%2,%3,%4,%5,%6,%7,%8,%9,%10,%11,%12,%13,%14,%15,%16,%17,%18,%19}"
#define RL32 "{%0,%1,%2,%3,%4,%5,%6,%7,%8,%9,%10,%11,%12,%13,%14,%15,%16,%17,%18,%19,%20,%21,%22,%23,%24,%25,%26,%27,%28,%29,%30,%31}"
#define RL64 "{%0,%1,%2,%3,%4,%5,%6,%7,%8,%9,%10,%11,%12,%13,%14,%15,%16,%17,%18,%19,%20,%21,%22,%23,%24,%25,%26,%27,%28,%29,%30,%31," \
  "%32,%33,%34,%35,%36,%37,%38,%39,%40,%41,%42,%43,%44,%45,%46,%47,%48,%49,%50,%51,%52,%53,%54,%55,%56,%57,%58,%59,%60,%61,%62,%63}"
#define WG_OP(shape) "wgmma.mma_async.sync.aligned." shape "k16.f32.bf16.bf16 "
#define DEF_WGMMA(N, RL, AL, i0, i1, i2, i3, i4, i5, i6)                                                                         \
  template<int SC, int TB, long long CB> DEVI void rs##N(float* d, const uint32_t* a) {                                          \
    if (SC) asm volatile("{.reg .b64 tb; mov.b64 tb, %" #i4 ";\n" WG_OP("m64n" #N) RL ", {%" #i0 ",%" #i1 ",%" #i2 ",%" #i3 "}, tb, 1, 1, 1, %" #i5 ";}" \
      : AL("+f", 0) : "r"(a[0]), "r"(a[1]), "r"(a[2]), "r"(a[3]), "n"(CB), "n"(TB));                                             \
    else asm volatile("{.reg .b64 tb; mov.b64 tb, %" #i4 ";\n" WG_OP("m64n" #N) RL ", {%" #i0 ",%" #i1 ",%" #i2 ",%" #i3 "}, tb, 0, 1, 1, %" #i5 ";}" \
      : AL("=f", 0) : "r"(a[0]), "r"(a[1]), "r"(a[2]), "r"(a[3]), "n"(CB), "n"(TB));                                             \
  }                                                                                                                              \
  template<int SC, int TA, int TB, long long CA, long long CB> DEVI void ss##N(float* d, uint32_t a) {                           \
    if (SC) asm volatile("{.reg .b64 ta, tb; .reg .b32 lo, hi; add.u32 lo, %" #i0 ", %" #i1 "; mov.b32 hi, %" #i2 "; mov.b64 ta, {lo, hi}; mov.b64 tb, %" #i3 ";\n" \
      WG_OP("m64n" #N) RL ", ta, tb, 1, 1, 1, %" #i4 ", %" #i5 ";}"                                                              \
      : AL("+f", 0) : "r"(a), "n"((int)CA), "n"((int)(CA >> 32)), "n"(CB), "n"(TA), "n"(TB));                                    \
    else asm volatile("{.reg .b64 ta, tb; .reg .b32 lo, hi; add.u32 lo, %" #i0 ", %" #i1 "; mov.b32 hi, %" #i2 "; mov.b64 ta, {lo, hi}; mov.b64 tb, %" #i3 ";\n" \
      WG_OP("m64n" #N) RL ", ta, tb, 0, 1, 1, %" #i4 ", %" #i5 ";}"                                                              \
      : AL("=f", 0) : "r"(a), "n"((int)CA), "n"((int)(CA >> 32)), "n"(CB), "n"(TA), "n"(TB));                                    \
  }
DEF_WGMMA(8, "{%0,%1,%2,%3}", A4, 4, 5, 6, 7, 8, 9, 10)
DEF_WGMMA(16, RL8, A8, 8, 9, 10, 11, 12, 13, 14)
DEF_WGMMA(32, RL16, A16, 16, 17, 18, 19, 20, 21, 22)
DEF_WGMMA(40, RL20, A20, 20, 21, 22, 23, 24, 25, 26)
DEF_WGMMA(24, RL12, A12, 12, 13, 14, 15, 16, 17, 18)
DEF_WGMMA(56, RL28, A28, 28, 29, 30, 31, 32, 33, 34)
template<int TA> DEVI void wgmma_n128(float* d, uint64_t a, uint64_t b, int scale_d) {
  asm volatile("{.reg .pred p; setp.ne.b32 p, %66, 0;\n" WG_OP("m64n128") RL64 ", %64, %65, p, 1, 1, %67, 1;}"
    : A32("+f", 0), A32("+f", 32) : "l"(a), "l"(b), "r"(scale_d), "n"(TA));
}

namespace rec {
constexpr int KR = 43;
constexpr uint32_t WSZ = (64 - KR) * 2048, STG = KR * 2048;
constexpr uint32_t WS = 0;
constexpr uint32_t RING = 2 * WSZ;
constexpr uint32_t OB = RING + 3 * 8192;
constexpr uint32_t PB = OB + 4096;
constexpr uint32_t WO = RING + 32768;
constexpr uint32_t ATT = WO + 5 * 16384;
constexpr uint32_t AK = ATT + 10240, AV = ATT + 20480;
constexpr uint32_t PAD = ATT + 30720;
constexpr uint32_t BARS = PAD + 128;
constexpr uint32_t B_XE = BARS  , B_FA = BARS + 64  , B_FB = BARS + 88, B_FO = BARS + 96;
constexpr uint32_t B_ME = BARS + 104  , B_WE = BARS + 136, B_PD = BARS + 144;
constexpr uint32_t B_XF = BARS + 152  , B_MF = BARS + 216  , B_CP = BARS + 248  , B_WT = BARS + 280  ;
constexpr uint32_t B_AB = BARS + 296, B_OB = BARS + 304, B_ST = BARS + 312  , B_WS = BARS + 328, B_WO = BARS + 336, B_AT = BARS + 352, B_AV = BARS + 360;
constexpr int NBAR = 46;
constexpr uint32_t M0 = BARS + 384;
constexpr uint32_t SMEM = 232448;
constexpr int NB_P = 1, NB_ST = 2, NB_O = 3, NB_W0 = 4, NB_W1 = 5;
__host__ __device__ constexpr int wo_tile(int rank, int g, int i) { return i < 2 ? i * 6 + (rank == 2 ? g : 4 - 2 * g + rank) : 13 + rank - g; }
constexpr long long D_W = CD(WS, 16, 1024, 1), D_X = CD(0, 16, 1024, 1), D_O = CD(OB, 128, 256, 0);
constexpr long long D_WO = CD(WO, 16, 1024, 1), D_QM = CD(ATT, 640, 0, 0), D_QT = CD(ATT + 128, 640, 64, 0), D_K = CD(AK, 640, 128, 0);
constexpr long long D_V = CD(AV, 128, 640, 0), D_P = CD(PB, 128, 768, 0);
struct Maps { CUtensorMap w[3], wo, xd, xs; };
__host__ __device__ constexpr uint32_t mslot(int c) { return (c ^ (c >> 1)) * 12288; }
__host__ __device__ constexpr uint32_t xslot(int s) { return s < 3 ? RING + s * 8192 : s < 5 ? WO + (s - 3) * 8192 : s < 7 ? WO + (s + 1) * 8192 : OB; }
__host__ __device__ constexpr bool k_smem(int k) { return k % 3 == 2; }
__host__ __device__ constexpr int k_idx(int k) { return k % 3 == 2 ? k / 3 : k - k / 3; }
__host__ __device__ constexpr int k_of_reg(int i) { return i + (i >> 1); }
__host__ __device__ constexpr int k_of_smem(int i) { return 3 * i + 2; }

#define RPROF(i)
#define RPROF_STEP
#define CPROF(i, v)

template<bool DUAL, int K0, int K1> DEVI void seq_mem(float* d, const uint32_t* w, uint32_t dw) {
  if constexpr (K0 < K1) {
    constexpr long long B = CD(RING, 128, DUAL ? 4096 : 8192, 0) + mslot(K0 >> 4) / 16 + (K0 & 15) * 16;
    if constexpr (DUAL) {
      if constexpr (!k_smem(K0)) rs24<K0 != 0, 1, B>(d, w + 4 * k_idx(K0)); else ss24<1, 1, 1, D_W + k_idx(K0) * 128, B>(d, dw);
    } else {
      if constexpr (!k_smem(K0)) rs16<K0 != 0, 1, B>(d, w + 4 * k_idx(K0)); else ss16<1, 1, 1, D_W + k_idx(K0) * 128, B>(d, dw);
    }
    seq_mem<DUAL, K0 + 1, K1>(d, w, dw);
  }
}
template<int N, int K0, int K1> DEVI void seq_tok(float* d, const uint32_t* w, uint32_t dw) {
  if constexpr (K0 < K1) {
    constexpr bool DUAL = N > 32;
    constexpr long long B = D_X + (DUAL ? xslot((K0 >> 2) & 7) / 16 : xslot(K0 >> 3) / 16 + ((K0 >> 2) & 1) * 256) + (K0 & 3) * 2;
    if constexpr (DUAL) {
      if constexpr (!k_smem(K0)) rs56<K0 != 0, 0, B>(d, w + 4 * k_idx(K0)); else ss56<1, 1, 0, D_W + k_idx(K0) * 128, B>(d, dw);
    } else if constexpr (N == 24) {
      if constexpr (!k_smem(K0)) rs24<K0 != 0, 0, B>(d, w + 4 * k_idx(K0)); else ss24<1, 1, 0, D_W + k_idx(K0) * 128, B>(d, dw);
    } else {
      if constexpr (!k_smem(K0)) rs32<K0 != 0, 0, B>(d, w + 4 * k_idx(K0)); else ss32<1, 1, 0, D_W + k_idx(K0) * 128, B>(d, dw);
    }
    seq_tok<N, K0 + 1, K1>(d, w, dw);
  }
}
template<int T, int K0> DEVI void seq_wo(float* d, uint32_t dw) {
  if constexpr (K0 < 8) { ss16<K0 != 0, 1, 1, D_WO + T * 1024 + K0 * 128, D_O + K0 * 32>(d, dw); seq_wo<T, K0 + 1>(d, dw); }
}
template<long long Q, int K0> DEVI void seq_s(float* d) {
  if constexpr (K0 < 8) { ss40<K0 != 0, 1, 1, Q + K0 * 80, D_K + K0 * 80>(d, 0); seq_s<Q, K0 + 1>(d); }
}
template<bool DUAL, int J> DEVI void load_x(uint32_t sb, const Maps* M, int t, int rb) {
  if (DUAL) e_tma_3d_mc(sb + xslot(J & 7), &M->xd, J * 64, (t - LAG) * 32, 0, sb + B_XF + (J & 7) * 8, rb);
  else e_tma_3d_mc(sb + xslot(J & 7), &M->xs, 0, (t < NSEG ? t : t - LAG) * 32, J * 2, sb + B_XF + (J & 7) * 8, rb);
}
DEVI void load_x_lent(uint32_t sb, const Maps* M, int t, int j) {
  const bool dual = t >= LAG && t < NSEG;
  const uint32_t dst = sb + (j == 3 ? xslot(3) : xslot(5));
#pragma unroll
  for (int i = 0; i < 2; i++)
    e_tma_3d(dst + i * 8192, dual ? &M->xd : &M->xs, dual ? (j + i) * 64 : 0, (t < LAG ? t : t - LAG) * 32, dual ? 0 : (j + i) * 2, sb + B_XF + (j + i) * 8);
}
struct True { static constexpr bool value = true; };
struct False { static constexpr bool value = false; };
struct Ctx { uint32_t sb; const Maps* M; int rb, rank, wi; bool lead; uint32_t par; };
#define PFN 2
#define XD 2
template<bool DUAL, int J> DEVI void tok_release(const Ctx& c, int t, int& budget) {
  constexpr int NC = DUAL ? 16 : 8, S = J & 7;
  if constexpr (J + 8 < NC) {
    p_arrive_at(c.sb + B_XE + S * 8, c.rb + J % 3, c.lead);
    p_expect_tx(c.sb + B_XF + S * 8, 8192, c.lead && c.wi == 0);
  } else if constexpr (S == 1 || S == 2 || S == 4 || S == 7) p_arrive(c.sb + B_ME + (S >> 1) * 8, c.lead);
  if constexpr (J == XD - 1) {
    if (c.rank == 1 && c.wi == 5) { mbar_wait(c.sb + B_FO, t & 1, budget); load_x<DUAL, 7>(c.sb, c.M, t, c.rb); }
  } else if constexpr (J >= XD && J - XD + 8 < NC) {
    constexpr int I = J - XD;
    if (c.rank == I % 3 && c.wi == (I & 1) * 4 + 1) { mbar_wait(c.sb + B_XE + I * 8, (t - LAG) & 1, budget); load_x<DUAL, I + 8>(c.sb, c.M, t, c.rb); }
  }
}
template<int N, int J, class F, class G> DEVI bool tok_pass(float* d, const uint32_t* w, uint32_t dw, Ctx& c, int t, int& budget, F after0, G setup) {
  constexpr bool DUAL = N > 32;
  constexpr int NC = DUAL ? 16 : 8, KC = 64 / NC;
  if constexpr (J < NC) {
    if constexpr (J > 1) mbar_wait(c.sb + B_XF + (J & 7) * 8, c.par ^ (J >> 3), budget);
    wg_fence();
    seq_tok<N, J * KC, (J + 1) * KC>(d, w, dw);
    wg_commit();
    if constexpr (J == 1) after0();
    if constexpr (J >= NC - 5 && J < NC - 2) setup(J - (NC - 5));
    if constexpr (J > 0) { wg_wait<1>(); tok_release<DUAL, J - 1>(c, t, budget); }
    return tok_pass<N, J + 1>(d, w, dw, c, t, budget, after0, setup);
  } else {
    const bool ok = mbar_test(c.sb + B_MF, t & 1);
    wg_wait<0>();
    tok_release<DUAL, NC - 1>(c, t, budget);
    if (!DUAL) c.par ^= 1;
    return ok;
  }
}
template<int NB> DEVI void pack_tok(uint32_t* e, const float* d) {
#pragma unroll
  for (int i = 0; i < 8; i++) if ((i & 3) < NB) e[i] = pack_bf16(d[4 * (i & 3) + 2 * (i >> 2)], d[4 * (i & 3) + 2 * (i >> 2) + 1]);
}
DEVI void push_tok(const uint32_t* e, uint32_t sb, uint32_t o, int r, int rank) {
  const uint32_t b = mapa(sb, r);
  st_async128(b + o, e[0], e[1], e[2], e[3], b + (rank == 2 ? B_AV : B_AT));
}
DEVI uint32_t h1_tag(int seg) { return ((seg >> 1) & 1) ^ 1; }
DEVI uint4 pack_part(const float* c, int t) {
  return make_uint4(settag(pack_bf16(c[0], c[1]), h1_tag(t)), pack_bf16(c[2], c[3]), settag(pack_bf16(c[4], c[5]), h1_tag(t - LAG)), pack_bf16(c[6], c[7]));
}
DEVI void put_part(char* p1, char* p2, uint4 z, int t) { p_stg_rlx64(p1, z.x, z.y, t < NSEG); p_stg_rlx64(p2, z.z, z.w, t >= LAG); }

DEVI void rec_math(const uint32_t sb, const int wi, const Maps& M) {
  const int h = cta_id() / 3, rb = cluster_rank() >= 3 ? 3 : 0, rank = cluster_rank() - rb;
  const int warp = wi & 3, wg = wi >> 2;
  const bool lead = (threadIdx.x & 127) == 0;
  int budget = SPIN_BUDGET;
  uint32_t w[4 * KR];
  Ctx cx{sb, &M, rb, rank, wi, lead, 0};
  {
    const int lane = lane_id();
    const uint32_t a = sb + wg * STG + ((lane & 7) + (lane >> 4) * 8) * 128 + (((warp * 2 + ((lane >> 3) & 1)) ^ (lane & 7)) << 4);
    for (int i = 0; i < (wg == 1 || rank == 2 ? 12 : 8); i++)
      stg_rlx64((char*)g_h1[i & 3] + ((wo_tile(rank, wg, i >> 2) * 4 + warp) * 4 + (lane >> 3)) * 2048 + h * 64 + (lane & 7) * 8, 0, 0);
    mbar_wait(sb + B_ST + wg * 8, 0, budget);
#pragma unroll
    for (int k = 0; k < KR; k++) ldsm4t(a + k * 2048, w[4*k], w[4*k+1], w[4*k+2], w[4*k+3]);
    nbar_arrive<NB_ST, 384>();
    nbar_sync_r(NB_W0 + wg, 128);
    for (int i = 0; i < 5; i++) p_arrive_at(sb + B_FA + i * 8, rb + (i == 4), lead);
    mbar_wait(sb + B_WS, 0, budget);
  }
  uint4 z = make_uint4(0, 0, 0, 0);
  char *z1 = nullptr, *z2 = nullptr;
  uint32_t rt0 = 0, rt1 = 0;
  mbar_wait(sb + B_XF, 0, budget); mbar_wait(sb + B_XF + 8, 0, budget);
#pragma unroll 1
  for (int t = 0;; t++) {
    const uint32_t dw = wg * (WSZ >> 4);
    uint32_t e[16];
    bool ok;
    auto finish = [&]() { put_part(z1, z2, z, t - 1); p_arrive_at(sb + B_FO, rb + 1, lead); };
    const int seg = t - rank * LAG;
    const bool att = rank < 2 && (unsigned)seg < (unsigned)NSEG;
    char* p1;
    uint32_t pw, oo;
    uint64_t u0, u1;
    int lane;
    auto setup = [&](int part) {
      if (part == 0) {
        lane = lane_id();
      } else if (part == 1) {
        char* const p = (char*)g_h1 + ((wo_tile(rank, wg, 0) * 4 + warp) * 4 + (lane >> 3)) * 2048 + h * 64 + (lane & 7) * 8;
        p1 = p + (t & 1) * sizeof(g_h1[0]);
        pin2(p1, nullptr);
      } else if (part == 2) {
        oo = OB + (lane >> 4) * 2048 + warp * 512 + rank * 256 + (lane & 15) * 16;
        pw = sb + PB + (wg ? lane * 4 : 768 + warp * 768 + lane * 16);
        pin2(pw, oo);
      } else {
        if (wg) {
          const uint32_t ra = mapa(sb, rb + ((warp & 1) ? 2 : (rank ^ 1) & 1)), rc = mapa(sb, rb + ((warp & 1) ? (rank ^ 1) & 1 : 2));
          u0 = pair(ra + oo, ra + B_OB); u1 = pair(rc + oo, rc + B_OB);
        } else {
          u0 = (uint64_t)((char*)(g_ot + rank * O_LAYER) + (size_t)(h * DH + warp * 16 + (lane >> 2)) * (SEQ * 2) + seg * 64 + (lane & 3) * 16);
          u1 = (uint32_t)((lane & 24) + ((lane >> 2) & 1) + 2 * warp - 8 * (lane & 3));
        }
        pin2(u0, u1);
      }
    };
    RPROF_STEP;
    auto mem_pass = [&](auto dual_c) {
      constexpr bool DUAL = decltype(dual_c)::value;
      float m[DUAL ? 12 : 8];
      RPROF(8 + wg * 12 - 32);
      if (!ok) mbar_wait(sb + B_MF, t & 1, budget);
      wg_fence(); seq_mem<DUAL, 0, 8>(m, w, dw); wg_commit();
      const uint32_t ao = ATT + rank * 10240 + wi * 1280, to = ao + 128 + (lane & 3) * 128 + (lane >> 2) * 16;
      const int la = DUAL ? rank == 0 : t >= NSEG;
      RPROF(1 + wg * 12);
      if (DUAL && rank == 0) {
#pragma unroll
        for (int i = 0; i < 8; i++) { const uint32_t x = e[i]; e[i] = e[8 + i]; e[8 + i] = x; }
      }
      auto piece = [&](int i) { push_tok(e + 4 * i, sb, to + (i & 1) * 640, rb + (la ^ (i >> 1)), rank); };
      piece(0);
      wg_fence(); seq_mem<DUAL, 8, 16>(m, w, dw); wg_commit();
      piece(1);
      mbar_wait(sb + B_MF + 8, t & 1, budget);
      wg_fence(); seq_mem<DUAL, 16, 24>(m, w, dw); wg_commit();
      if (DUAL) piece(2);
      wg_fence(); seq_mem<DUAL, 24, 32>(m, w, dw); wg_commit();
      if (DUAL) piece(3);
      mbar_wait(sb + B_MF + 16, t & 1, budget);
      wg_fence(); seq_mem<DUAL, 32, 48>(m, w, dw); wg_commit();
      wg_wait<1>(); p_arrive(sb + B_PD, lead);
      const uint32_t r0 = mapa(sb, rb + la), r1 = mapa(sb, rb + (la ^ 1)), m0 = r0 + ao + lane * 4, m1 = r1 + ao + lane * 4, ab = rank == 2 ? B_AV : B_AB;
      const uint64_t q0 = pair(m0, r0 + ab), q1 = pair(m0 + 640, r0 + ab), q2 = pair(m1, r1 + ab), q3 = pair(m1 + 640, r1 + ab);
      pin2(q0, q1);
      if (DUAL) pin2(q2, q3);
      mbar_wait(sb + B_MF + 24, t & 1, budget);
      wg_fence(); seq_mem<DUAL, 48, 64>(m, w, dw); wg_commit();
      wg_wait<1>(); p_arrive_at(sb + B_FA, rb, lead);
      wg_wait<0>();
      const uint32_t a0 = pack_bf16(m[0], m[1]), a1 = pack_bf16(m[2], m[3]), a2 = pack_bf16(m[4], m[5]), a3 = pack_bf16(m[6], m[7]);
      if constexpr (DUAL) {
        st_async32(q0, la ? a2 : a0); st_async32(q1, la ? a3 : a1); st_async32(q2, la ? a0 : a2); st_async32(q3, la ? a1 : a3);
        rt0 = pack_bf16(m[8], m[9]); rt1 = pack_bf16(m[10], m[11]);
      } else { st_async32(q0, a0); st_async32(q1, a1); rt0 = a2; rt1 = a3; }
      p_arrive(sb + B_WE, lead);
    };
    if (t >= LAG && t < NSEG) {
      float d[28];
      ok = tok_pass<56, 0>(d, w, dw, cx, t, budget, finish, setup);
      pack_tok<4>(e + 8, d); pack_tok<3>(e, d + 16); e[3] = rt0; e[7] = rt1;
      mem_pass(True());
    } else {
      float d[16];
      if (t > 0) finish();
      if (t > 0 && t < LAG) {
        ok = tok_pass<24, 0>(d, w, dw, cx, t, budget, []() {}, setup);
        pack_tok<3>(e, d); e[3] = rt0; e[7] = rt1;
      } else {
        ok = tok_pass<32, 0>(d, w, dw, cx, t, budget, []() {}, setup);
        pack_tok<4>(e, d);
      }
      mem_pass(False());
    }
    {
      RPROF(2 + wg * 12);
      auto wo_ready = [&]() { if (t == 0) mbar_wait(sb + B_WO, 0, budget); if (t < NSTEP - 1) mbar_wait(sb + B_WT, t & 1, budget); };
      constexpr float SC = 0.08838834764831845f * 1.4426950408889634f;
      if (!att) wo_ready();
      else {
        float s[32];
        setup(3);
        if (wg) {
          uint32_t one[4];
#pragma unroll
          for (int i = 0; i < 4; i++) one[i] = 0x3F803F80u + (pw >> 31);
          mbar_wait_cluster(sb + B_AT, seg & 1, budget);
          mbar_wait_cluster(sb + B_AB, seg & 1, budget);
          fence_proxy_async();
          RPROF(3 + 12);
          wg_fence(); seq_s<D_QM, 0>(s); wg_commit();
          nbar_arrive<NB_P, 256>();
          if (warp == 1) sts32(pw + 640, 0);
          mbar_wait_cluster(sb + B_AV, seg & 1, budget);
          wg_wait<0>();
          float mx = fmaxf(fmaxf(fmaxf(s[0], s[1]), fmaxf(s[4], s[5])), fmaxf(fmaxf(fmaxf(s[8], s[9]), fmaxf(s[12], s[13])), fmaxf(s[16], s[17])));
          const float x1 = __shfl_xor_sync(0xffffffffu, mx, 1), x2 = __shfl_xor_sync(0xffffffffu, mx, 2), x3 = __shfl_xor_sync(0xffffffffu, mx, 3);
          const float u = (warp & 2) ? ((warp & 1) ? s[16] : s[12]) : ((warp & 1) ? s[8] : s[4]);
          const float v = (warp & 2) ? ((warp & 1) ? s[17] : s[13]) : ((warp & 1) ? s[9] : s[5]);
          const float ms = -SC * fmaxf(fmaxf(mx, x1), fmaxf(x2, x3));
          sts32(pw + 128 + warp * 128, pack_bf16(ex2(fmaf(u, SC, ms)), ex2(fmaf(v, SC, ms))));
          if (warp == 0) sts32(pw, pack_bf16(ex2(fmaf(s[0], SC, ms)), ex2(fmaf(s[1], SC, ms))));
          fence_proxy_async();
          nbar_sync<NB_W1, 128>();
          RPROF(4 + 12);
          wg_fence();
          rs8<0, 0, D_P>(s + 8, one); rs8<1, 0, D_P + 16>(s + 8, one); rs8<1, 0, D_P + 32>(s + 8, one);
          wg_commit();
          ss8<0, 0, 0, D_V, D_P>(s, 0); ss8<0, 0, 0, D_V + 320, D_P>(s + 4, 0);
          ss8<1, 0, 0, D_V + 16, D_P + 16>(s, 0); ss8<1, 0, 0, D_V + 336, D_P + 16>(s + 4, 0);
          ss8<1, 0, 0, D_V + 32, D_P + 32>(s, 0); ss8<1, 0, 0, D_V + 352, D_P + 32>(s + 4, 0);
          wg_commit();
          wg_wait<1>();
          const float i0 = rcp(s[8]), i1 = rcp(s[9]);
          wg_wait<0>();
          stsm4(sb + oo, pack_bf16(s[0] * i0, s[1] * i1), pack_bf16(s[2] * i0, s[3] * i1), pack_bf16(s[4] * i0, s[5] * i1), pack_bf16(s[6] * i0, s[7] * i1));
          __syncwarp();
          const uint4 y = lds128v(sb + oo);
          if (t < NSTEP - 1) { st_async128(u0, y); st_async128(u1, y); e_complete_tx(sb + B_OB, 512); }
          wo_ready();
        } else {
          const int lim = (int)u1;
          char* const og = (char*)u0;
          nbar_sync<NB_P, 256>();
          RPROF(3);
          wg_fence();
          seq_s<D_QT, 0>(s);
          wg_commit();
          mbar_wait_cluster(sb + B_AV, seg & 1, budget);
          wg_wait<0>();
#pragma unroll
          for (int i = 0; i < 8; i++) { float& v = s[4 + 4 * (i >> 1) + (i & 1)]; v = i <= lim ? v : -INFINITY; }
          float mx = fmaxf(fmaxf(fmaxf(s[0], s[1]), fmaxf(s[4], s[5])), fmaxf(fmaxf(fmaxf(s[8], s[9]), fmaxf(s[12], s[13])), fmaxf(s[16], s[17])));
          const float x1 = __shfl_xor_sync(0xffffffffu, mx, 1), x2 = __shfl_xor_sync(0xffffffffu, mx, 2), x3 = __shfl_xor_sync(0xffffffffu, mx, 3);
          const float ms = -SC * fmaxf(fmaxf(mx, x1), fmaxf(x2, x3));
#pragma unroll
          for (int i = 0; i < 10; i++) { float& v = s[4 * (i >> 1) + (i & 1)]; v = ex2(fmaf(v, SC, ms)); }
          const float sum = (((s[0] + s[1]) + (s[4] + s[5])) + ((s[8] + s[9]) + (s[12] + s[13]))) + (s[16] + s[17]);
          const float y1 = __shfl_xor_sync(0xffffffffu, sum, 1), y2 = __shfl_xor_sync(0xffffffffu, sum, 2), y3 = __shfl_xor_sync(0xffffffffu, sum, 3);
          const float inv = rcp((sum + y1) + (y2 + y3));
          stsm4(pw, pack_bf16(s[0] * inv, s[1] * inv), pack_bf16(s[4] * inv, s[5] * inv), pack_bf16(s[8] * inv, s[9] * inv), pack_bf16(s[12] * inv, s[13] * inv));
          stsm2(pw + 512, pack_bf16(s[16] * inv, s[17] * inv), 0);
          fence_proxy_async();
          nbar_sync<NB_W0, 128>();
          RPROF(4);
          wg_fence();
          ss32<0, 0, 0, D_V, D_P + 48>(s, 0); ss32<0, 0, 0, D_V + 320, D_P + 48>(s + 16, 0);
          ss32<1, 0, 0, D_V + 16, D_P + 64>(s, 0); ss32<1, 0, 0, D_V + 336, D_P + 64>(s + 16, 0);
          ss32<1, 0, 0, D_V + 32, D_P + 80>(s, 0); ss32<1, 0, 0, D_V + 352, D_P + 80>(s + 16, 0);
          wg_commit();
          wo_ready();
          wg_wait<0>();
#pragma unroll
          for (int i = 0; i < 4; i++) {
            const float* d = s + (i >> 1) * 16 + (i & 1) * 2;
            stg128(og + ((i >> 1) * 64 + (i & 1) * 8) * (SEQ * 2), pack_bf16(d[0], d[1]), pack_bf16(d[4], d[5]), pack_bf16(d[8], d[9]), pack_bf16(d[12], d[13]));
          }
          if ((seg & 3) == 3) nbar_arrive<NB_O, 160>();
        }
      }
      RPROF(5 + wg * 12);
      const bool three = wg == 1 || rank == 2;
      char* const p2 = p1 + (2 + ((t - LAG) & 1) - (t & 1)) * (int)sizeof(g_h1[0]);
      if (t < NSTEP - 1) {
        float c[24];
        const uint32_t dt = wg ? 0 : 3072;
        mbar_wait_cluster(sb + B_OB, t & 1, budget);
        fence_proxy_async();
        RPROF(6 + wg * 12);
        wg_fence(); seq_wo<0, 0>(c, dt); wg_commit(); seq_wo<1, 0>(c + 8, dt); wg_commit();
        mbar_wait(sb + B_XF, cx.par, budget);
        wg_wait<1>();
        if (warp == 2) load_x_lent(sb, &M, t + 1, wg ? 3 : 5);
        put_part(p1, p2, pack_part(c, t), t);
        const int o3 = (wo_tile(rank, wg, three ? 2 : 1) - wo_tile(rank, wg, 0)) * 32768;
        z1 = p1 + o3; z2 = p2 + o3;
        if (three) {
          wg_fence(); seq_wo<2, 0>(c + 16, dt); wg_commit();
          wg_wait<1>(); put_part(p1 + 6 * 32768, p2 + 6 * 32768, pack_part(c + 8, t), t);
          mbar_wait(sb + B_XF + 8, cx.par, budget);
          wg_wait<0>(); z = pack_part(c + 16, t);
        } else { mbar_wait(sb + B_XF + 8, cx.par, budget); wg_wait<0>(); z = pack_part(c + 8, t); }
      } else break;
      RPROF(7 + wg * 12);
    }
  }
}

DEVI void wait_xa(const int* p, int& budget) {
  while (__any_sync(0xffffffffu, ldg_acq32(p) < 64) && --budget > 0) {}
  fence_proxy_global();
}
template<bool DUAL> DEVI void first_loads(uint32_t sb, const Maps* M, int n, int h, int rb, int& budget) {
#pragma unroll
  for (int i = 0; i < PFN; i++) {
    if (DUAL) e_prefetch_3d(&M->xd, ((h + i * (16 / PFN)) & 15) * 64, (n - LAG) * 32, 0);
    else e_prefetch_3d(&M->xs, 0, (n < NSEG ? n : n - LAG) * 32, ((h + i * (8 / PFN)) & 7) * 2);
  }
  if (n + 1 < NSEG) asm volatile(ELECT "cp.async.bulk.prefetch.L2.global [%0], 2048;}" :: "l"((const char*)g_xr[n + 1] + (h & 7) * 2048) : "memory");
  mbar_wait(sb + B_FA, n & 1, budget);
  load_x<DUAL, 0>(sb, M, n, rb); load_x<DUAL, 1>(sb, M, n, rb); load_x<DUAL, 2>(sb, M, n, rb);
}
template<bool DUAL> DEVI void lent_loads(uint32_t sb, const Maps* M, int n, int rb, int& budget) {
  mbar_wait(sb + B_FB, n & 1, budget);
  load_x<DUAL, 3>(sb, M, n, rb); load_x<DUAL, 4>(sb, M, n, rb); load_x<DUAL, 5>(sb, M, n, rb); load_x<DUAL, 6>(sb, M, n, rb);
}
DEVI void rec_comm(const uint32_t sb, const int warp, const Maps& M, const bf16* __restrict__ mem0) {
  const int lane = threadIdx.x & 31, h = cta_id() / 3, rb = cluster_rank() >= 3 ? 3 : 0, rank = cluster_rank() - rb;
  int budget = SPIN_BUDGET;
  const bool two = warp == 3 || (rank == 2 && warp == 2);
  const int ntask = two ? 2 : 1, qi = two ? (warp == 3 ? rank : 3) : rank * 3 + warp;
  const int task0 = two ? h * 2 + (qi >> 1) : 64 + h * 4 + (qi >> 1);
  auto h2_word = [&](int i, int ln) {
    const int task = task0 + i * 192;
    return (char*)g_h2 + (task >> 6) * 8192 + ((qi ^ i) & 1) * 4096 + ((task >> 2) & 15) * 256 + (task & 3) * 32 + (ln & 8) * 16 + (ln & 7) * 4;
  };
  auto first_x = [&](int t) {
    const int n = t + 1;
    p_expect_tx(sb + B_XF + (lane_id() & 7) * 8, 8192, lane_id() < 8);
    if (rank == 0) {
      if (n >= LAG && ((n - LAG) & 3) == 0) wait_xa(&g_xa[1][(n - LAG) >> 2], budget);
      if (n >= LAG && n < NSEG) first_loads<true>(sb, &M, n, h, rb, budget); else first_loads<false>(sb, &M, n, h, rb, budget);
    }
  };
  {
    const int task = task0 + (lane >> 4) * 192, L = (task & 3) * 8 + (lane & 7);
    if ((lane >> 4) < ntask) {
      const bf16* p = mem0 + (L & 3) * 2 * DM + (task >> 2) * 16 + (L >> 2) + (lane & 8);
      uint32_t m0 = (uint32_t)__bfloat16_as_ushort(p[0]) | (uint32_t)__bfloat16_as_ushort(p[DM]) << 16;
      m0 = m0 ? m0 : 0x8000u;
      stg_rlx32(h2_word(lane >> 4, lane), ((qi ^ (lane >> 4)) & 1) ? 0 : m0);
      for (int i = 1; i < 4; i++) stg_rlx32(h2_word(lane >> 4, lane) + i * sizeof(g_h2[0]), 0);
      sts32(sb + M0 + warp * 128 + lane * 4, m0);
    }
    __syncwarp();
    nbar_sync<NB_ST, 384>();
    if (warp == 2) {
      e_expect_tx(sb + B_WS, 2 * WSZ);
#pragma unroll 1
      for (int i = 0; i < 2 * (64 - KR); i++) e_tma_2d(sb + WS + (i & 1) * WSZ + (i >> 1) * 2048, &M.w[rank], h * DH + (i & 1) * 64, k_of_smem(i >> 1) * 16, sb + B_WS);
      const int nt = rank == 2 ? 6 : 5;
      e_expect_tx(sb + B_WO, (nt - 2) * 16384);
#pragma unroll 1
      for (int i = 1; i < nt; i++) if (i != 3) e_tma_2d(sb + WO + i * 16384, &M.wo, wo_tile(rank, 1 - i / 3, i % 3) * 64, h * DH, sb + B_WO);
    }
    wait_xa(&g_xa[0][0], budget);
    if (warp == 3) { first_x(-1); if (rank == 0) lent_loads<false>(sb, &M, 0, rb, budget); }
  }
  uint32_t cpp = 0;
  const uint32_t cp = sb + B_CP + warp * 8;
  uint32_t f_dst, f_chk, f_bar, f_time = gtime() - 4000;
  const char *f_src, *f_xr;
  auto prepare = [&](int s) {
    const int ck = warp ^ (warp < 2 && (s < LAG || s >= NSEG) && (rank & 1) == (s >= NSEG)), ln = lane_id();
    f_dst = sb + RING + mslot(ck); f_chk = f_dst + ln * 32 + (ln >> 2) * 4; f_bar = sb + ck * 8;
    f_src = (const char*)g_h2[s & 3] + ck * 8192 + (s >= NSEG ? 4096 : 0);
    f_xr = (const char*)g_xr[(s + 1) & 63] + ck * 4096;
    pin2(f_chk, 0u);
    return s <= LAG ? TP(9) + ck * TP(11) : s <= NSEG ? TP(1) + ck * TP(4) : TP(13) + ck * TP(11);
  };
  prepare(0);
#pragma unroll 1
  for (int t = 0;; t++) {
    const int n = t + 1;
    const bool dual = t >= LAG && t < NSEG;
    RPROF_STEP;
    {
      const uint32_t bytes = dual ? 8192 : 4096;
      e_expect_tx(cp, bytes + (n < NSEG ? 4096 : 0));
      mbar_wait(f_bar + B_ME, t & 1, budget);
      if (n < NSEG) e_bulk_g2s(f_dst + 8192, f_xr, 4096, cp);
      wait_time(f_time);
      RPROF(24); CPROF(0, gtime());
      int tries = 0;
      while (true) {
        tries++;
        e_bulk_g2s(f_dst, f_src, bytes, cp);
        mbar_wait(cp, cpp, budget); cpp ^= 1;
        uint32_t mn = min(min(lds32v(f_chk), lds32v(f_chk + 1024)), min(lds32v(f_chk + 2048), lds32v(f_chk + 3072)));
        if (dual) mn = min(min(mn, min(lds32v(f_chk + 4096), lds32v(f_chk + 5120))), min(lds32v(f_chk + 6144), lds32v(f_chk + 7168)));
        if (!__any_sync(0xffffffffu, mn == 0) || --budget < 0) break;
        e_expect_tx(cp, bytes);
      }
      e_arrive(f_bar + B_MF);
      RPROF(25); CPROF(1, gtime()); CPROF(2, tries);
    }
    const int seg = t - rank * LAG;
    const bool att = rank < 2 && (unsigned)seg < (unsigned)NSEG;
    if (warp == 0) {
      if (att) { e_expect_tx(sb + B_AT, 16384); e_expect_tx(sb + B_AB, 4096); e_expect_tx(sb + B_AV, 10240); }
      if (n < NSTEP) e_expect_tx(sb + B_OB, dual ? 4096 : 2048);
    }
    if (n + 1 < NSEG && (n & 3) == 3) wait_xa(&g_xa[0][(n + 1) >> 2], budget);
    {
      const int ln = lane_id(), i = ln >> 4;
      char* const w = h2_word(i, ln);
      if (i < ntask) {
        stg_rlx32(w + ((t + 3) & 3) * sizeof(g_h2[0]), 0);
        if (n == LAG && ((qi ^ i) & 1)) stg_rlx32(w + (n & 3) * sizeof(g_h2[0]), lds32v(sb + M0 + warp * 128 + ln * 4));
      }
      __syncwarp();
    }
    if (n < NSTEP) {
      const uint32_t tag = (n >> 1) & 31;
      mbar_wait(sb + B_PD, t & 1, budget);
      uint32_t t0 = clock32();
      if (warp == 2) {
        e_expect_tx(sb + B_WT, 32768);
        e_tma_2d(sb + WO + 49152, &M.wo, wo_tile(rank, 0, 0) * 64, h * DH, sb + B_WT);
        mbar_wait(sb + B_WE, t & 1, budget);
        e_tma_2d(sb + WO, &M.wo, wo_tile(rank, 1, 0) * 64, h * DH, sb + B_WT);
      }
      if (warp == 3) first_x(t);
      if (warp == 0 && rank == (t >= NSEG)) { mbar_wait(sb + B_AB, seg & 1, budget); e_stg_rlx32(&g_ts[t & 1][h], (gtime() & ~31u) | tag); }
      const int fd = prepare(n), ln = lane_id();
      const int sa = t - (qi & 1) * LAG, sc = t - (~qi & 1) * LAG;
      const int i0 = (unsigned)sa < (unsigned)(NSEG - 1) ? 0 : 1, i1 = two && (unsigned)sc < (unsigned)(NSEG - 1) ? 2 : 1;
      const char* src = (const char*)g_h1[(qi & 1) * 2 + (sa & 1)] + task0 * 2048 + ln * 8;
      char* dst = h2_word(0, ln) + (n & 3) * sizeof(g_h2[0]);
      const int ds = ((~qi & 1) * 2 + (sc & 1) - (qi & 1) * 2 - (sa & 1)) * (int)sizeof(g_h1[0]) + 192 * 2048, dd = 3 * 8192 + ((qi & 1) ? -4096 : 4096);
      if (i0) { src += ds; dst += dd; }
      pin2(src, dst);
      spin_until(t0, TSD);
      uint32_t v0;
      do { v0 = ldg_rlx32(&g_ts[t & 1][ln]); } while (__any_sync(0xffffffffu, (v0 & 31) != tag) && --budget > 0);
      const uint32_t now = __shfl_sync(0xffffffffu, v0, 0);
      t0 = now + __reduce_max_sync(0xffffffffu, (int)(v0 - now));
      f_time = t0 + fd;
      RPROF(26); CPROF(3, t0);
      t0 += t < LAG ? TP(8) : t < NSEG ? TP(0) : TP(12);
#pragma unroll 1
      for (int i = i0; i < i1; i++) {
        const uint32_t tg = h1_tag(i ? sc : sa);
        uint2 v[8];
        wait_time(t0 + (!two ? 0 : i ? TP(3) : -TP(10)));
        int tries = 0;
        float a[4];
        while (true) {
          tries++;
#pragma unroll
          for (int k = 0; k < 8; k++) v[k] = ldg_rlx64(src + k * 256);
          asm volatile("{.reg .pred p; setp.eq.s32 p, %0, 0x7fffffff; @p exit;}" :: "r"(budget) : "memory");
          uint32_t bad = 0;
#pragma unroll
          for (int k = 0; k < 8; k++) {
            bad = xor_or(v[k].x, tg, bad);
            a[0] = k ? a[0] + bf_lo(v[k].x) : bf_lo(v[k].x); a[1] = k ? a[1] + bf_hi(v[k].x) : bf_hi(v[k].x);
            a[2] = k ? a[2] + bf_lo(v[k].y) : bf_lo(v[k].y); a[3] = k ? a[3] + bf_hi(v[k].y) : bf_hi(v[k].y);
          }
#pragma unroll
          for (int k = 0; k < 2; k++) {
            const float keep = (ln & 8) ? a[2+k] : a[k], send = (ln & 8) ? a[k] : a[2+k];
            a[k] = keep + __shfl_xor_sync(0xffffffffu, send, 8);
          }
#pragma unroll
          for (int k = 0; k < 2; k++) a[k] += __shfl_xor_sync(0xffffffffu, a[k], 16);
          if (!__any_sync(0xffffffffu, bad & 1) || --budget < 0) break;
        }
        const uint32_t out = pack_bf16(a[0], a[1]);
        if (ln < 16) stg_rlx32(dst, out ? out : 0x8000u);
        __syncwarp();
        src += ds; dst += dd;
        if (i == 0) { RPROF(28); CPROF(6, gtime()); CPROF(4, gtime()); CPROF(5, tries); } else CPROF(7, gtime());
      }
    }
    if (warp == (dual ? 2 : 1) && att && (seg & 3) == 3) { nbar_sync<NB_O, 160>(); e_flag_add(&g_dep[E_O1 + rank * 16 + (seg >> 2)]); }
    if (n == NSTEP) break;
  }
  if (h == 0 && rank == 0 && warp < 2) g_xa[warp][lane_id()] = 0;
}
}

__global__ void __launch_bounds__(384, 1)
rec_kernel(const __grid_constant__ rec::Maps M, const bf16* __restrict__ mem0) {
  using namespace rec;
  extern __shared__ __align__(1024) uint8_t smem[];
  const uint32_t sb = __shfl_sync(0xffffffffu, smem_u32(smem), 0);
  const int tid = threadIdx.x, wi = __shfl_sync(0xffffffffu, tid >> 5, 0);
  if ((sb & 0x3FFFF) != SMEM_BASE) __trap();
  if (wi == 0) {
    const int h = cta_id() / 3, rank = cta_id() - h * 3;
    for (int i = tid; i < NBAR; i += 32) mbar_init(sb + BARS + i * 8, i < 13 ? 6 : i < 19 ? 2 : 1);
    ((uint32_t*)(smem + PAD))[tid] = 0;
    fence_mbar_init(); fence_proxy_async();
    __syncwarp();
    e_expect_tx(sb + B_ST, STG); e_expect_tx(sb + B_ST + 8, STG);
    for (int i = 0; i < 2 * KR; i++) e_tma_2d(sb + (i & 1) * STG + (i >> 1) * 2048, &M.w[rank], h * DH + (i & 1) * 64, k_of_reg(i >> 1) * 16, sb + B_ST + (i & 1) * 8);
  } else if (wi == 1) {
    if (blockIdx.x < NEV / 32) { g_dep[blockIdx.x * 32 + (tid & 31)] = 0; g_claim[blockIdx.x * 32 + (tid & 31)] = 0; __threadfence(); }
    __syncwarp();
    asm volatile("griddepcontrol.launch_dependents;" ::: "memory");
  }
  cluster_arrive(); cluster_wait();
  if (wi < 8) { reg_inc<232>(); rec_math(sb, wi, M); cluster_arrive(); cluster_wait(); }
  else { reg_dec<40>(); rec_comm(sb, wi & 3, M, mem0); cluster_arrive(); cluster_wait(); }
}

namespace gm {
struct Maps { CUtensorMap ot, wo, xn, wg, wu, hl, hs, wd, out; };
constexpr int STAGES = 6, STAGE = 32768;
constexpr uint32_t SO = STAGES * STAGE, BARS = SO + 32768;
constexpr uint32_t B_FULL = BARS, B_EMPTY = BARS + 48, B_TF = BARS + 96, B_TE = BARS + 112, B_ORD = BARS + 128, B_PM = BARS + 144, B_GO = BARS + 160;
constexpr uint32_t MAIL = BARS + 176, PMAIL = BARS + 192;
constexpr uint32_t SMEM = BARS + 256;
constexpr int END = -1;
#define GT gtime

struct Tile {
  bool isO, isG, l2; int blk, col, k0, n;
  DEVI Tile(int task, int rank) {
    const int e = task >> 8, id = task & 255;
    const bool isD = e < E_G1 || e >= E_D2;
    isO = e >= E_O1 && e < E_G2; isG = !isD && !isO; l2 = e >= E_O2;
    blk = isG && l2 ? (e & 15) * 2 + rank : isD && !l2 ? e >> 1 : e & 15;
    col = isG ? (l2 ? id : id * 2 + rank) : (id & 3) * 2 + rank;
    k0 = isO ? (id >> 2) * 2048 : isG ? 0 : ((l2 ? e >> 4 : e) & 1) * 1792;
    n = isO ? 32 : isG ? 16 : 28;
  }
};

DEVI float geglu(float g, float u) {
  const float z = g * (0.7978845608028654f + 0.035677408136300125f * g * g);
  float t; asm("tanh.approx.f32 %0, %1;" : "=f"(t) : "f"(z));
  const float hg = 0.5f * g;
  return fmaf(hg, t, hg) * u;
}
struct Sched {
  int need, size, e;
  bool filler;
  uint4 dep, cl;
  DEVI void init(int lane) {
    e = (lane < 4 ? lane + 12 : lane < 16 ? lane - 4 : lane) * 4;
    const bool d = e < E_G1 || e >= E_D2, o = e >= E_O1 && e < E_G2;
    need = d ? 28 : e < E_O1 ? 64 : o ? 32 : 128;
    size = d ? 4 : o ? 8 : e < E_O1 ? 28 : e < E_G2 + 8 ? 56 : 0;
    filler = (int)blockIdx.x >= TP(5);
  }
  DEVI void scan(int lane) { cl = ldg_rlx128(g_claim + e); dep = ldg_rlx128(g_dep + e); }
  DEVI int next(int lane, int& budget) {
    while (--budget > 0) {
      int av[4], open = 0;
#pragma unroll
      for (int i = 0; i < 4; i++) { const int r = max(size - (int)(&cl.x)[i], 0); open |= r; av[i] = ((int)(&dep.x)[i] >= need ? r : 0) + (i ? av[i - 1] : 0); }
      const uint32_t mo = __ballot_sync(0xffffffffu, open);
      if (!mo) break;
      if (filler) {
        const int x = TP(6) & 3, dx = x == 0 ? dep.x : x == 1 ? dep.y : x == 2 ? dep.z : dep.w;
        filler = !__any_sync(0xffffffffu, e == ((E_O1 + TP(6)) & ~3) && dx >= need);
      }
      if (!filler && (mo & 0xffff) && lane >= E_O2 / 4) av[3] = 0;
      int inc = av[3], pos = 0;
      while (true) {
        const uint32_t m = __ballot_sync(0xffffffffu, inc > pos && av[3]);
        if (!m) break;
        const int l = __ffs(m) - 1, rel = pos - (inc - av[3]), i = (rel >= av[0]) + (rel >= av[1]) + (rel >= av[2]);
        int r = 0;
        if (lane == l) {
          const int tk = atomicAdd(g_claim + e + i, 1);
          r = tk < size ? (e + i) << 8 | tk : -1 - (inc - av[3] + (i == 0 ? av[0] : i == 1 ? av[1] : i == 2 ? av[2] : av[3]) + tk - size);
        }
        r = __shfl_sync(0xffffffffu, r, l);
        if (r >= 0) return r;
        if (pos == 0) {
#pragma unroll
          for (int o = 1; o < 32; o <<= 1) { const int v = __shfl_up_sync(0xffffffffu, inc, o); if (lane >= o) inc += v; }
        }
        pos = -1 - r;
      }
      if (pos == 0) __nanosleep(TP(7));
      scan(lane);
    }
    return END;
  }
};

DEVI void scheduler(const uint32_t sb) {
  const int lane = threadIdx.x & 31;
  int budget = SPIN_BUDGET;
  Sched sc; sc.init(lane);
#pragma unroll 1
  for (int i = 0;; i++) {
    mbar_wait(sb + B_GO, (i & 1) ^ 1, budget);
    sc.scan(lane);
    const int task = sc.next(lane, budget);
    const uint32_t r = mapa(sb, lane & 1);
    if (lane < 2) st_async32(r + PMAIL + (i & 1) * 4, task, r + B_PM + (i & 1) * 8);
    __syncwarp();
    if (task == END) break;
  }
}

DEVI void producer(const uint32_t sb, const Maps& M) {
  const int lane = threadIdx.x & 31, rank = cluster_rank();
  int budget = SPIN_BUDGET, s = 0, ph = 0;
#pragma unroll 1
  for (int i = 0;; i++) {
    e_expect_tx(sb + B_PM + (i & 1) * 8, 4);
    mbar_wait_cluster(sb + B_PM + (i & 1) * 8, (i >> 1) & 1, budget);
    const int task = budget < 0 ? END : __shfl_sync(0xffffffffu, (int)lds32v(sb + PMAIL + (i & 1) * 4), 0);
    fence_proxy_global();
    for (int z = 0; z < (task == END ? 2 : 1); z++) {
      const int g = (i + z) & 1;
      mbar_wait(sb + B_TE + g * 8, (((i + z) >> 1) & 1) ^ 1, budget);
      if (lane == 0) { sts64(sb + MAIL + g * 8, task, s | ph << 8); mbar_arrive(sb + B_TF + g * 8); }
      __syncwarp();
    }
    if (task == END) break;
    const Tile T(task, rank);
    const bool shareB = T.isG && T.l2;
    const CUtensorMap* mA = T.isO ? &M.ot : T.isG ? &M.xn : &M.hl;
    const CUtensorMap* mB0 = T.isO ? &M.wo : T.isG ? &M.wg : &M.wd;
    const CUtensorMap* mB1 = T.isG ? &M.wu : mB0;
    const int c0 = T.col * (T.isG ? 64 : 128), c1 = T.isG ? c0 : c0 + 64, row = T.blk * 128;
    const int ok = 0;
    int k = T.k0;
#pragma unroll 1
    for (int it = 0; it < T.n; it++, k += 64) {
      const uint32_t a = sb + s * STAGE, fb = sb + B_FULL + s * 8;
      mbar_wait(sb + B_EMPTY + s * 8, ph ^ 1, budget);
      e_expect_tx(fb, STAGE);
      if (shareB) {
        e_tma_2d_mc(a + 16384 + rank * 8192, rank ? mB1 : mB0, c0, k, fb);
        e_tma_2d(a, mA, k, row, fb); e_tma_2d(a + 8192, mA, k, row + 64, fb);
      } else {
        e_tma_2d_mc(a + rank * 8192, mA, T.isO ? row + rank * 64 : k, T.isO ? k + ok : row + rank * 64, fb);
        e_tma_2d(a + 16384, mB0, c0, k, fb); e_tma_2d(a + 24576, mB1, c1, k, fb);
      }
      if (it == T.n - TP(2)) e_arrive(sb + B_GO);
      if (++s == STAGES) { s = 0; ph ^= 1; }
    }
  }
}

template<int TA> DEVI void mainloop(float* d0, float* d1, uint32_t sb, int n, int s, int ph, bool lead, uint32_t ord, int& budget) {
  int prev = 0;
  const uint32_t rel = threadIdx.x & 127;
#pragma unroll 1
  for (int i = 0; i < n; i++) {
    mbar_wait(sb + B_FULL + s * 8, ph, budget);
    const uint32_t a = sb + s * STAGE;
    const uint64_t da = mkdesc(a, 16, 1024), db = mkdesc(a + 16384, 8192, 1024);
    wg_fence();
#pragma unroll
    for (int k = 0; k < 4; k++) {
      wgmma_n128<TA>(d0, da + k * (TA ? 128 : 2), db + k * 128, (i | k) != 0);
      wgmma_n128<TA>(d1, da + 512 + k * (TA ? 128 : 2), db + k * 128, (i | k) != 0);
    }
    wg_commit();
    if (i > 0) { wg_wait<1>(); p_arrive_at(sb + B_EMPTY + prev * 8, rel & 1, rel < 2); }
    prev = s;
    if (++s == STAGES) { s = 0; ph ^= 1; }
  }
  p_arrive(ord, lead);
  wg_wait<0>();
  p_arrive_at(sb + B_EMPTY + prev * 8, rel & 1, rel < 2);
}

DEVI void consumer(const uint32_t sb, const Maps& M, const int wg) {
  const int tid = threadIdx.x, lane = tid & 31, warp = (tid >> 5) & 3;
  const bool lead = (tid & 127) == 0;
  const uint32_t so = sb + SO + wg * 16384;
  int budget = SPIN_BUDGET;
  float d0[64], d1[64];
#pragma unroll 1
  for (int m = 0;; m++) {
    mbar_wait(sb + B_TF + wg * 8, m & 1, budget);
    const uint2 mail = lds64v(sb + MAIL + wg * 8);
    const int task = __shfl_sync(0xffffffffu, (int)mail.x, 0), pos = __shfl_sync(0xffffffffu, (int)mail.y, 0);
    e_arrive(sb + B_TE + wg * 8);
    if (task == END || budget < 0) break;
    const Tile T(task, cluster_rank());
    mbar_wait(sb + B_ORD + wg * 8, (m & 1) ^ wg ^ 1, budget);
    if (T.isO) mainloop<1>(d0, d1, sb, T.n, pos & 255, pos >> 8, lead, sb + B_ORD + (wg ^ 1) * 8, budget);
    else mainloop<0>(d0, d1, sb, T.n, pos & 255, pos >> 8, lead, sb + B_ORD + (wg ^ 1) * 8, budget);
    const uint32_t st = so + (warp * 16 + (lane & 15)) * 128;
    if (T.isG) {
      int* const fl = &g_dep[T.l2 ? E_D2 + (T.col >= 28) * 16 + T.blk : E_D1 + T.blk * 2 + (T.col >= 28)];
#pragma unroll
      for (int mm = 0; mm < 2; mm++) {
        const float* d = mm ? d1 : d0;
#pragma unroll
        for (int c = 0; c < 4; c++) {
          uint32_t r[4];
#pragma unroll
          for (int i = 0; i < 4; i++) r[i] = pack_bf16(geglu(d[8*c+2*i], d[32+8*c+2*i]), geglu(d[8*c+2*i+1], d[33+8*c+2*i]));
          stsm4(st + mm * 8192 + (((2 * c + (lane >> 4)) ^ (lane & 7)) << 4), r[0], r[1], r[2], r[3]);
        }
      }
      fence_proxy_async();
      nbar_sync_r(1 + wg, 128);
      if (lead) {
        tma_store_2d(&M.hs, so, T.col * 64, T.blk * 128);
        bulk_commit();
        bulk_wait<0>();
        flag_add(fl);
      }
    } else {
#pragma unroll
      for (int hf = 0; hf < 2; hf++) {
        if (hf) { if (lead) bulk_wait_read<0>(); nbar_sync_r(1 + wg, 128); }
#pragma unroll
        for (int mm = 0; mm < 2; mm++) {
          const float* d = (mm ? d1 : d0) + hf * 32;
#pragma unroll
          for (int c = 0; c < 4; c++)
            stsm4(st + mm * 8192 + (((2 * c + (lane >> 4)) ^ (lane & 7)) << 4), pack_bf16(d[8*c], d[8*c+1]), pack_bf16(d[8*c+2], d[8*c+3]),
                  pack_bf16(d[8*c+4], d[8*c+5]), pack_bf16(d[8*c+6], d[8*c+7]));
        }
        fence_proxy_async();
        nbar_sync_r(1 + wg, 128);
        if (lead) { tma_radd_2d(&M.out, so, T.col * 128 + hf * 64, T.blk * 128); bulk_commit(); }
      }
      if (lead) {
        bulk_wait<0>();
        if (T.isO || !T.l2) flag_add(&g_dep[(!T.isO ? E_LX2 : T.l2 ? E_LX1B : E_LX1A) + T.blk]);
      }
    }
    __syncwarp();
  }
}

DEVI void norm_helper(const bf16* __restrict__ x, bf16* out) {
  const int lane = threadIdx.x & 31;
  int budget = SPIN_BUDGET, tk = lane < 4 ? -1 : 1024;
#pragma unroll 1
  while (--budget > 0) {
    if (tk < 0) tk = atomicAdd(g_claim + E_LI + lane, 1);
    if (__all_sync(0xffffffffu, tk >= 1024)) break;
    const uint32_t m = __ballot_sync(0xffffffffu, tk < 1024 && (lane == 0 || ldg_acq32(g_dep + E_LI + lane * 16 + (tk >> 6)) >= 16));
    if (!m) { __nanosleep(TP(7)); continue; }
    const int ql = __ffs(m) - 1, task = __shfl_sync(0xffffffffu, tk, ql), q = E_LI + ql * 16, ev = task >> 6;
    if (lane == ql) tk = -1;
    const size_t off = (size_t)task * (DM * 4) + lane * 16;
    const char* src = (const char*)(q == E_LI ? x : out) + off;
    uint4 u[8];
#pragma unroll
    for (int i = 0; i < 8; i++) u[i] = ldg_rlx128(src + i * 512);
    if (q == E_LI) {
#pragma unroll
      for (int i = 0; i < 8; i++) stg128((char*)out + off + i * 512, u[i].x, u[i].y, u[i].z, u[i].w);
    }
    int* const fl = q == E_LI ? &g_xa[0][ev] : q == E_LX2 ? &g_xa[1][ev] : &g_dep[q == E_LX1A ? E_G1 + ev : E_G2 + (ev >> 1)];
    float mean[2], rs[2];
#pragma unroll
    for (int r = 0; r < 2; r++) {
      float s0 = 0, s1 = 0;
#pragma unroll
      for (int i = 0; i < 16; i++) { const uint32_t v = (&u[4*r + (i >> 2)].x)[i & 3]; s0 += bf_lo(v); s1 += bf_hi(v); }
      mean[r] = (s0 + s1) * (1.f / 32);
      s0 = s1 = 0;
#pragma unroll
      for (int i = 0; i < 16; i++) { const uint32_t v = (&u[4*r + (i >> 2)].x)[i & 3]; const float a = bf_lo(v) - mean[r], b = bf_hi(v) - mean[r]; s0 = fmaf(a, a, s0); s1 = fmaf(b, b, s1); }
      rs[r] = s0 + s1;
    }
    {
      const bool hi = lane & 16;
      float m1 = hi ? mean[1] : mean[0], q1 = hi ? rs[1] : rs[0], m2 = hi ? mean[0] : mean[1], q2 = hi ? rs[0] : rs[1], cnt = 16;
#pragma unroll
      for (int o = 16; o; o >>= 1) {
        m2 = __shfl_xor_sync(0xffffffffu, m2, o); q2 = __shfl_xor_sync(0xffffffffu, q2, o);
        const float dl = m1 - m2;
        q2 = q1 = fmaf(dl * dl, cnt, q1 + q2); m2 = m1 = 0.5f * (m1 + m2);
        cnt *= 2;
      }
      q1 = rsqrtf(q1 * (1.f / DM) + 1e-5f);
      m2 = __shfl_xor_sync(0xffffffffu, m1, 16); q2 = __shfl_xor_sync(0xffffffffu, q1, 16);
      mean[0] = hi ? m2 : m1; mean[1] = hi ? m1 : m2; rs[0] = hi ? q2 : q1; rs[1] = hi ? q1 : q2;
    }
#pragma unroll
    for (int i = 0; i < 8; i++) {
      uint32_t y[4];
#pragma unroll
      for (int c = 0; c < 4; c++) { const uint32_t v = (&u[i].x)[c]; y[c] = pack_bf16((bf_lo(v) - mean[i >> 2]) * rs[i >> 2], (bf_hi(v) - mean[i >> 2]) * rs[i >> 2]); }
      stg128((char*)g_xn + off + i * 512, y[0], y[1], y[2], y[3]);
      u[i] = make_uint4(y[0], y[1], y[2], y[3]);
    }
    if (q == E_LI && (task & 15) >= 12) {
      uint32_t* const xr = g_xr[task >> 4] + lane * 32 + (task & 3);
#pragma unroll
      for (int i = 0; i < 16; i++) {
        const uint32_t a = (&u[i >> 2].x)[i & 3], b = (&u[4 + (i >> 2)].x)[i & 3];
        xr[(i >> 2) * 1024 + (i & 3) * 8] = __byte_perm(a, b, 0x5410); xr[(i >> 2) * 1024 + (i & 3) * 8 + 4] = __byte_perm(a, b, 0x7632);
      }
    }
    fence_proxy_global();
    __syncwarp();
    if (lane == 0) flag_add(fl);
    __syncwarp();
  }
}
}

__global__ void __cluster_dims__(2, 1, 1) __launch_bounds__(384, 1)
gemm_kernel(const __grid_constant__ gm::Maps M, const bf16* __restrict__ x, bf16* out) {
  using namespace gm;
  extern __shared__ __align__(1024) uint8_t smem[];
  const uint32_t sb = __shfl_sync(0xffffffffu, smem_u32(smem), 0);
  const int tid = threadIdx.x, wi = __shfl_sync(0xffffffffu, tid >> 5, 0);
  if (tid < 21) mbar_init(sb + BARS + tid * 8, tid == 14 || tid == 15 ? 4 : tid >= 6 && tid < 12 ? 2 : 1);
  fence_mbar_init();
  cluster_arrive(); cluster_wait();
  if (wi < 8) { reg_inc<208>(); consumer(sb, M, wi >> 2); cluster_arrive(); cluster_wait(); }
  else {
    reg_dec<88>();
    if (wi == 8) producer(sb, M);
    else if (wi == 11 && cluster_rank() == 0) scheduler(sb);
    else {
      norm_helper(x, out);
      asm volatile("griddepcontrol.wait;" ::: "memory");
    }
    __syncwarp();
    cluster_arrive(); cluster_wait();
  }
}

typedef CUresult (*PFN_encodeTiled)(CUtensorMap*, CUtensorMapDataType, cuuint32_t, void*, const cuuint64_t*, const cuuint64_t*,
                                    const cuuint32_t*, const cuuint32_t*, CUtensorMapInterleave, CUtensorMapSwizzle,
                                    CUtensorMapL2promotion, CUtensorMapFloatOOBfill);
static PFN_encodeTiled g_encode = nullptr;
static CUtensorMap make_map(const void* ptr, uint64_t rows, uint64_t cols, uint32_t box_rows, CUtensorMapL2promotion pr = CU_TENSOR_MAP_L2_PROMOTION_L2_256B) {
  CUtensorMap m;
  cuuint64_t dims[2] = {cols, rows}, strides[1] = {cols * 2};
  cuuint32_t box[2] = {64, box_rows}, es[2] = {1, 1};
  g_encode(&m, CU_TENSOR_MAP_DATA_TYPE_BFLOAT16, 2, (void*)ptr, dims, strides, box, es, CU_TENSOR_MAP_INTERLEAVE_NONE,
           CU_TENSOR_MAP_SWIZZLE_128B, pr, CU_TENSOR_MAP_FLOAT_OOB_FILL_NONE);
  return m;
}

static CUtensorMap make_map3(const void* ptr, uint64_t d0, uint64_t d1, uint64_t d2, uint64_t stride2) {
  CUtensorMap m;
  cuuint64_t dims[3] = {d0, d1, d2}, strides[2] = {DM * 2, stride2};
  cuuint32_t box[3] = {64, 32, 2}, es[3] = {1, 1, 1};
  g_encode(&m, CU_TENSOR_MAP_DATA_TYPE_BFLOAT16, 3, (void*)ptr, dims, strides, box, es, CU_TENSOR_MAP_INTERLEAVE_NONE,
           CU_TENSOR_MAP_SWIZZLE_128B, CU_TENSOR_MAP_L2_PROMOTION_L2_256B, CU_TENSOR_MAP_FLOAT_OOB_FILL_NONE);
  return m;
}

extern "C" void kernel_launch(void* const* d_in, const int* in_sizes, int n_in, void* d_out, int out_size) {
  const bf16* x = (const bf16*)d_in[0];
  const bf16* mem0 = (const bf16*)d_in[1];
  if (!g_encode) {
    void* p = nullptr; cudaDriverEntryPointQueryResult q;
    cudaGetDriverEntryPoint("cuTensorMapEncodeTiled", &p, cudaEnableDefault, &q);
    g_encode = (PFN_encodeTiled)p;
    cudaFuncSetAttribute(gemm_kernel, cudaFuncAttributeMaxDynamicSharedMemorySize, gm::SMEM);
    cudaFuncSetAttribute(rec_kernel, cudaFuncAttributeMaxDynamicSharedMemorySize, rec::SMEM);
  }
  bf16 *xn, *ot, *hh;
  cudaGetSymbolAddress((void**)&xn, g_xn); cudaGetSymbolAddress((void**)&ot, g_ot); cudaGetSymbolAddress((void**)&hh, g_h);
  rec::Maps R;
  for (int i = 0; i < 3; i++) R.w[i] = make_map(d_in[2 + i], DM, NH * DH, 16, CU_TENSOR_MAP_L2_PROMOTION_NONE);
  R.wo = make_map(d_in[5], NH * DH, DM, 128);
  R.xd = make_map3(xn, DM, SEQ - LAG * 32, 2, (uint64_t)LAG * 32 * DM * 2); R.xs = make_map3(xn, 64, SEQ, DM / 64, 128);
  gm::Maps G;
  G.ot = make_map(ot, NH * DH + O_LAYER / SEQ, SEQ, 64); G.wo = make_map(d_in[5], NH * DH, DM, 64); G.xn = make_map(xn, SEQ, DM, 64);
  G.wg = make_map(d_in[8], DM, DF, 64); G.wu = make_map(d_in[9], DM, DF, 64); G.hl = make_map(hh, SEQ, DF, 64); G.hs = make_map(hh, SEQ, DF, 128);
  G.wd = make_map(d_in[10], DF, DM, 64); G.out = make_map(d_out, SEQ, DM, 128);
  cudaLaunchConfig_t cfg = {};
  cudaLaunchAttribute at[1];
  cfg.attrs = at; cfg.numAttrs = 1;
  cfg.gridDim = dim3(3 * NH); cfg.blockDim = dim3(384); cfg.dynamicSmemBytes = rec::SMEM; cfg.stream = cudaStreamPerThread;
  at[0].id = cudaLaunchAttributeClusterDimension; at[0].val.clusterDim.y = at[0].val.clusterDim.z = 1;
  static int csize = 0;
  if (!csize) {
    int n = 0;
    at[0].val.clusterDim.x = 6;
    csize = cudaOccupancyMaxActiveClusters(&n, rec_kernel, &cfg) == cudaSuccess && n >= NH / 2 ? 6 : 3;
  }
  at[0].val.clusterDim.x = csize;
  cudaLaunchKernelEx(&cfg, rec_kernel, R, mem0);
  cfg.gridDim = dim3(132); cfg.blockDim = dim3(384); cfg.dynamicSmemBytes = gm::SMEM; cfg.stream = cudaStreamPerThread;
  at[0].id = cudaLaunchAttributeProgrammaticStreamSerialization; at[0].val.programmaticStreamSerializationAllowed = 1;
  cudaLaunchKernelEx(&cfg, gemm_kernel, G, x, (bf16*)d_out);
}
```

```cpp
#include <cuda_runtime.h>
#include <cuda_bf16.h>
#include <cuda.h>
#include <stdint.h>

#define DEVI __device__ __forceinline__
typedef __nv_bfloat16 bf16;

constexpr int SEQ = 2048, DM = 1024, NH = 32, DH = 128, DF = 3584, NSEG = 64;
#define LAG 20
constexpr int NSTEP = NSEG + LAG;

#define TSD 1800
constexpr size_t O_LAYER = 0;
__device__ __align__(1024) bf16 g_xn[SEQ * DM];
__device__ __align__(1024) bf16 g_ot[SEQ * NH * DH + O_LAYER];
__device__ __align__(1024) bf16 g_h[SEQ * DF];
__device__ __align__(1024) uint32_t g_xr[NSEG][DM * 4];
__device__ __align__(1024) uint2 g_h1[4][256 * 256];
__device__ __align__(1024) uint4 g_h2[4][2048];
__device__ __align__(128) uint32_t g_ts[2][32];
enum { E_D1 = 0, E_G1 = 32, E_O1 = 48, E_O2 = 64, E_G2 = 80, E_D2 = 96,
       E_LI = 128, E_LX2 = 144, E_LX1A = 160, E_LX1B = 176, NEV = 256 };
__device__ __align__(128) int g_dep[NEV];
__device__ __align__(128) int g_claim[NEV];
__device__ __align__(128) int g_xa[2][32];

#define TUNE_DEFAULTS 1650, 2450, 6, 100, 100, 8, 14, 100, 1550, 2280, 100, 110, 1550, 2320, 200, 0
constexpr int c_D[16] = {TUNE_DEFAULTS};
template<int I> struct TPV { static constexpr int v = c_D[I]; };
#define TP(i) TPV<i>::v

DEVI uint32_t smem_u32(const void* p) { return (uint32_t)__cvta_generic_to_shared(p); }
DEVI void mbar_init(uint32_t bar, uint32_t cnt) { asm volatile("mbarrier.init.shared::cta.b64 [%0], %1;" :: "r"(bar), "r"(cnt) : "memory"); }
DEVI void mbar_arrive(uint32_t bar) { asm volatile("mbarrier.arrive.shared::cta.b64 _, [%0];" :: "r"(bar) : "memory"); }
DEVI bool mbar_try(uint32_t bar, uint32_t parity) {
  uint32_t p;
  asm volatile("{.reg .pred p; mbarrier.try_wait.parity.shared::cta.b64 p, [%1], %2; selp.u32 %0, 1, 0, p;}" : "=r"(p) : "r"(bar), "r"(parity) : "memory");
  return p;
}
DEVI bool mbar_test(uint32_t bar, uint32_t parity) {
  uint32_t p;
  asm volatile("{.reg .pred p; mbarrier.test_wait.parity.shared::cta.b64 p, [%1], %2; selp.u32 %0, 1, 0, p;}" : "=r"(p) : "r"(bar), "r"(parity) : "memory");
  return p;
}
constexpr int SPIN_BUDGET = 1 << 18;
DEVI void mbar_wait(uint32_t bar, uint32_t parity, int& budget) {
  while (!mbar_try(bar, parity)) { if (--budget < 0) break; }
}
DEVI bool mbar_try_cluster(uint32_t bar, uint32_t parity) {
  uint32_t p;
  asm volatile("{.reg .pred p; mbarrier.try_wait.parity.acquire.cluster.shared::cta.b64 p, [%1], %2; selp.u32 %0, 1, 0, p;}" : "=r"(p) : "r"(bar), "r"(parity) : "memory");
  return p;
}
DEVI void mbar_wait_cluster(uint32_t bar, uint32_t parity, int& budget) {
  while (!mbar_try_cluster(bar, parity)) { if (--budget < 0) break; }
}
DEVI uint32_t mapa(uint32_t addr, uint32_t rank) { uint32_t r; asm("mapa.shared::cluster.u32 %0, %1, %2;" : "=r"(r) : "r"(addr), "r"(rank)); return r; }
DEVI void cluster_arrive() { asm volatile("barrier.cluster.arrive.release.aligned;" ::: "memory"); }
DEVI void cluster_wait() { asm volatile("barrier.cluster.wait.acquire.aligned;" ::: "memory"); }
DEVI void fence_mbar_init() { asm volatile("fence.mbarrier_init.release.cluster;" ::: "memory"); }
DEVI void fence_proxy_async() { asm volatile("fence.proxy.async.shared::cta;" ::: "memory"); }
DEVI void fence_proxy_global() { asm volatile("fence.proxy.async.global;" ::: "memory"); }
#define ELECT "{.reg .pred p; elect.sync _|p, 0xffffffff;\n @p "
DEVI void e_expect_tx(uint32_t bar, uint32_t bytes) { asm volatile(ELECT "mbarrier.arrive.expect_tx.shared::cta.b64 _, [%0], %1;}" :: "r"(bar), "r"(bytes) : "memory"); }
DEVI void e_complete_tx(uint32_t bar, uint32_t bytes) { asm volatile("fence.acq_rel.cta;\n" ELECT "mbarrier.complete_tx.relaxed.cta.shared::cta.b64 [%0], %1;}" :: "r"(bar), "r"(bytes) : "memory"); }
DEVI void e_arrive(uint32_t bar) { asm volatile(ELECT "mbarrier.arrive.shared::cta.b64 _, [%0];}" :: "r"(bar) : "memory"); }
DEVI void e_tma_2d(uint32_t dst, const CUtensorMap* m, int c0, int c1, uint32_t bar) {
  asm volatile(ELECT "cp.async.bulk.tensor.2d.shared::cluster.global.mbarrier::complete_tx::bytes [%0], [%1, {%3, %4}], [%2];}"
    :: "r"(dst), "l"(m), "r"(bar), "r"(c0), "r"(c1) : "memory");
}
DEVI void e_prefetch_3d(const CUtensorMap* m, int c0, int c1, int c2) {
  asm volatile(ELECT "cp.async.bulk.prefetch.tensor.3d.L2.global [%0, {%1, %2, %3}];}" :: "l"(m), "r"(c0), "r"(c1), "r"(c2) : "memory");
}
DEVI void e_bulk_g2s(uint32_t dst, const void* src, uint32_t bytes, uint32_t bar) {
  asm volatile(ELECT "cp.async.bulk.shared::cluster.global.mbarrier::complete_tx::bytes [%0], [%1], %2, [%3];}" :: "r"(dst), "l"(src), "r"(bytes), "r"(bar) : "memory");
}
DEVI void e_tma_3d(uint32_t dst, const CUtensorMap* m, int c0, int c1, int c2, uint32_t bar) {
  asm volatile(ELECT "cp.async.bulk.tensor.3d.shared::cluster.global.mbarrier::complete_tx::bytes [%0], [%1, {%3, %4, %5}], [%2];}"
    :: "r"(dst), "l"(m), "r"(bar), "r"(c0), "r"(c1), "r"(c2) : "memory");
}
DEVI void e_tma_3d_mc(uint32_t dst, const CUtensorMap* m, int c0, int c1, int c2, uint32_t bar, int rb) {
  asm volatile(ELECT "cp.async.bulk.tensor.3d.shared::cluster.global.mbarrier::complete_tx::bytes.multicast::cluster [%0], [%1, {%3, %4, %5}], [%2], %6;}"
    :: "r"(dst), "l"(m), "r"(bar), "r"(c0), "r"(c1), "r"(c2), "h"((uint16_t)(7 << rb)) : "memory");
}
DEVI void e_tma_2d_mc(uint32_t dst, const CUtensorMap* m, int c0, int c1, uint32_t bar) {
  asm volatile(ELECT "cp.async.bulk.tensor.2d.shared::cluster.global.mbarrier::complete_tx::bytes.multicast::cluster [%0], [%1, {%3, %4}], [%2], %5;}"
    :: "r"(dst), "l"(m), "r"(bar), "r"(c0), "r"(c1), "h"((uint16_t)3) : "memory");
}
DEVI void p_arrive_at(uint32_t bar, uint32_t rank, bool c) {
  asm volatile("{.reg .pred p; .reg .b32 a; setp.ne.u32 p, %2, 0; mapa.shared::cluster.u32 a, %0, %1; @p mbarrier.arrive.shared::cluster.b64 _, [a];}"
    :: "r"(bar), "r"(rank), "r"((uint32_t)c) : "memory");
}
DEVI void p_expect_tx(uint32_t bar, uint32_t bytes, bool c) {
  asm volatile("{.reg .pred p; setp.ne.u32 p, %2, 0; @p mbarrier.arrive.expect_tx.shared::cta.b64 _, [%0], %1;}" :: "r"(bar), "r"(bytes), "r"((uint32_t)c) : "memory");
}
DEVI void p_arrive(uint32_t bar, bool c) { asm volatile("{.reg .pred p; setp.ne.u32 p, %1, 0; @p mbarrier.arrive.shared::cta.b64 _, [%0];}" :: "r"(bar), "r"((uint32_t)c) : "memory"); }
DEVI void tma_store_2d(const CUtensorMap* m, uint32_t src, int c0, int c1) {
  asm volatile("cp.async.bulk.tensor.2d.global.shared::cta.bulk_group [%0, {%2, %3}], [%1];" :: "l"(m), "r"(src), "r"(c0), "r"(c1) : "memory");
}
DEVI void tma_radd_2d(const CUtensorMap* m, uint32_t src, int c0, int c1) {
  asm volatile("cp.reduce.async.bulk.tensor.2d.global.shared::cta.add.bulk_group [%0, {%2, %3}], [%1];" :: "l"(m), "r"(src), "r"(c0), "r"(c1) : "memory");
}
DEVI void bulk_commit() { asm volatile("cp.async.bulk.commit_group;" ::: "memory"); }
template<int N> DEVI void bulk_wait_read() { asm volatile("cp.async.bulk.wait_group.read %0;" :: "n"(N) : "memory"); }
template<int N> DEVI void bulk_wait() { asm volatile("cp.async.bulk.wait_group %0;" :: "n"(N) : "memory"); }
template<int ID, int N> DEVI void nbar_sync() { asm volatile("bar.sync %0, %1;" :: "n"(ID), "n"(N) : "memory"); }
template<int ID, int N> DEVI void nbar_arrive() { asm volatile("bar.arrive %0, %1;" :: "n"(ID), "n"(N) : "memory"); }
DEVI void nbar_sync_r(int id, int n) { asm volatile("bar.sync %0, %1;" :: "r"(id), "r"(n) : "memory"); }
template<int R> DEVI void reg_inc() { asm volatile("setmaxnreg.inc.sync.aligned.u32 %0;" :: "n"(R)); }
template<int R> DEVI void reg_dec() { asm volatile("setmaxnreg.dec.sync.aligned.u32 %0;" :: "n"(R)); }
DEVI void wg_fence() { asm volatile("wgmma.fence.sync.aligned;" ::: "memory"); }
DEVI void wg_commit() { asm volatile("wgmma.commit_group.sync.aligned;" ::: "memory"); }
template<int N> DEVI void wg_wait() { asm volatile("wgmma.wait_group.sync.aligned %0;" :: "n"(N) : "memory"); }
DEVI uint64_t mkdesc(uint32_t addr, uint32_t lbo, uint32_t sbo, uint32_t sw = 1) {
  return ((uint64_t)((addr & 0x3FFFF) >> 4)) | ((uint64_t)(lbo >> 4) << 16) | ((uint64_t)(sbo >> 4) << 32) | ((uint64_t)sw << 62);
}
constexpr uint32_t SMEM_BASE = 1024;
__host__ __device__ constexpr long long CD(uint32_t off, uint32_t lbo, uint32_t sbo, uint32_t sw) {
  return (long long)(((uint64_t)((SMEM_BASE + off) >> 4)) | ((uint64_t)(lbo >> 4) << 16) | ((uint64_t)(sbo >> 4) << 32) | ((uint64_t)sw << 62));
}
DEVI uint32_t pack_bf16(float lo, float hi) { uint32_t r; asm("cvt.rn.bf16x2.f32 %0, %1, %2;" : "=r"(r) : "f"(hi), "f"(lo)); return r; }
DEVI float bf_lo(uint32_t v) { return __uint_as_float(v << 16); }
DEVI float bf_hi(uint32_t v) { return __uint_as_float(v & 0xffff0000u); }
DEVI void ldsm4t(uint32_t addr, uint32_t& r0, uint32_t& r1, uint32_t& r2, uint32_t& r3) {
  asm volatile("ldmatrix.sync.aligned.m8n8.x4.trans.shared.b16 {%0,%1,%2,%3}, [%4];" : "=r"(r0), "=r"(r1), "=r"(r2), "=r"(r3) : "r"(addr) : "memory");
}
DEVI void stsm4(uint32_t addr, uint32_t r0, uint32_t r1, uint32_t r2, uint32_t r3) {
  asm volatile("stmatrix.sync.aligned.m8n8.x4.shared.b16 [%0], {%1,%2,%3,%4};" :: "r"(addr), "r"(r0), "r"(r1), "r"(r2), "r"(r3) : "memory");
}
DEVI uint2 lds64v(uint32_t a) { uint2 v; asm volatile("ld.volatile.shared.v2.u32 {%0,%1}, [%2];" : "=r"(v.x), "=r"(v.y) : "r"(a) : "memory"); return v; }
DEVI uint32_t lds32v(uint32_t a) { uint32_t v; asm volatile("ld.volatile.shared.u32 %0, [%1];" : "=r"(v) : "r"(a) : "memory"); return v; }
DEVI uint4 lds128v(uint32_t a) { uint4 v; asm volatile("ld.volatile.shared.v4.u32 {%0,%1,%2,%3}, [%4];" : "=r"(v.x), "=r"(v.y), "=r"(v.z), "=r"(v.w) : "r"(a) : "memory"); return v; }
DEVI void sts32(uint32_t a, uint32_t x) { asm volatile("st.shared.u32 [%0], %1;" :: "r"(a), "r"(x) : "memory"); }
DEVI int lane_id() { int r; asm volatile("mov.u32 %0, %%laneid;" : "=r"(r)); return r; }
DEVI void sts64(uint32_t a, uint32_t x, uint32_t y) { asm volatile("st.shared.v2.u32 [%0], {%1,%2};" :: "r"(a), "r"(x), "r"(y) : "memory"); }
DEVI void st_async128(uint32_t a, uint32_t x, uint32_t y, uint32_t z, uint32_t w, uint32_t bar) {
  asm volatile("st.async.weak.shared::cluster.mbarrier::complete_tx::bytes.v4.b32 [%0], {%1,%2,%3,%4}, [%5];" :: "r"(a), "r"(x), "r"(y), "r"(z), "r"(w), "r"(bar) : "memory");
}
DEVI void st_async32(uint32_t a, uint32_t x, uint32_t bar) {
  asm volatile("st.async.weak.shared::cluster.mbarrier::complete_tx::bytes.b32 [%0], %1, [%2];" :: "r"(a), "r"(x), "r"(bar) : "memory");
}
DEVI uint4 ldg_rlx128(const void* p) {
  uint4 v;
  asm volatile("ld.relaxed.gpu.global.v4.b32 {%0,%1,%2,%3}, [%4];" : "=r"(v.x), "=r"(v.y), "=r"(v.z), "=r"(v.w) : "l"(p) : "memory");
  return v;
}
DEVI int ldg_rlx32(const void* p) { int v; asm volatile("ld.relaxed.gpu.global.b32 %0, [%1];" : "=r"(v) : "l"(p) : "memory"); return v; }
DEVI int ldg_acq32(const void* p) { int v; asm volatile("ld.acquire.gpu.global.b32 %0, [%1];" : "=r"(v) : "l"(p) : "memory"); return v; }
DEVI void stg128(void* p, uint32_t x, uint32_t y, uint32_t z, uint32_t w) {
  asm volatile("st.global.v4.b32 [%0], {%1,%2,%3,%4};" :: "l"(p), "r"(x), "r"(y), "r"(z), "r"(w) : "memory");
}
DEVI uint2 ldg_rlx64(const void* p) { uint2 v; asm volatile("{.reg .b64 a; ld.relaxed.gpu.global.b64 a, [%2]; mov.b64 {%0,%1}, a;}" : "=r"(v.x), "=r"(v.y) : "l"(p) : "memory"); return v; }
DEVI void stg_rlx64(void* p, uint32_t x, uint32_t y) { asm volatile("{.reg .b64 a; mov.b64 a, {%1,%2}; st.relaxed.gpu.global.b64 [%0], a;}" :: "l"(p), "r"(x), "r"(y) : "memory"); }
DEVI void stg_rlx32(void* p, uint32_t x) { asm volatile("st.relaxed.gpu.global.b32 [%0], %1;" :: "l"(p), "r"(x) : "memory"); }
DEVI void flag_add(int* p) { asm volatile("fence.proxy.async.global; red.release.gpu.global.add.s32 [%0], 1;" :: "l"(p) : "memory"); }
DEVI void e_stg_rlx32(void* p, uint32_t x) { asm volatile(ELECT "st.relaxed.gpu.global.b32 [%0], %1;}" :: "l"(p), "r"(x) : "memory"); }
DEVI void e_flag_add(int* p) { asm volatile("fence.proxy.async.global;\n" ELECT "red.release.gpu.global.add.s32 [%0], 1;}" :: "l"(p) : "memory"); }
DEVI int cluster_rank() { int r; asm volatile("mov.u32 %0, %%cluster_ctarank;" : "=r"(r)); return __shfl_sync(0xffffffffu, r, 0); }
DEVI int cta_id() { int r; asm volatile("mov.u32 %0, %%ctaid.x;" : "=r"(r)); return __shfl_sync(0xffffffffu, r, 0); }
DEVI uint32_t clock32() { uint32_t c; asm volatile("mov.u32 %0, %%clock;" : "=r"(c)); return c; }
DEVI uint32_t gtime() { uint32_t c; asm volatile("mov.u32 %0, %%globaltimer_lo;" : "=r"(c)); return c; }
DEVI void wait_time(uint32_t t) { while (__any_sync(0xffffffffu, t - gtime() - 1 < 4000u)) {} }
DEVI void spin_until(uint32_t t0, int d) {
  int r;
  while (__any_sync(0xffffffffu, (r = d - (int)(clock32() - t0)) > 0)) {
    if (r > 300) __nanosleep(r >> 2);
  }
}
DEVI void pin2(const void* a, const void* b) { asm volatile("{.reg .pred p; setp.eq.u64 p, %0, %1; @p st.volatile.global.u64 [%0], %1;}" :: "l"(a), "l"(b) : "memory"); }
DEVI void pin2(uint32_t a, uint32_t b) { asm volatile("{.reg .pred p; setp.eq.u32 p, %0, %1; @p st.volatile.shared.u32 [%0], %1;}" :: "r"(a), "r"(b) : "memory"); }
DEVI void p_stg_rlx64(void* p, uint32_t x, uint32_t y, bool c) {
  asm volatile("{.reg .pred p; .reg .b64 a; setp.ne.u32 p, %3, 0; mov.b64 a, {%1,%2}; @p st.relaxed.gpu.global.b64 [%0], a;}" :: "l"(p), "r"(x), "r"(y), "r"((uint32_t)c) : "memory");
}
DEVI void pin2(uint64_t a, uint64_t b) { pin2((const void*)a, (const void*)b); }
DEVI uint64_t pair(uint32_t a, uint32_t bar) { return a | (uint64_t)bar << 32; }
DEVI void st_async32(uint64_t q, uint32_t x) { st_async32((uint32_t)q, x, (uint32_t)(q >> 32)); }
DEVI void st_async128(uint64_t q, uint4 v) { st_async128((uint32_t)q, v.x, v.y, v.z, v.w, (uint32_t)(q >> 32)); }
DEVI float ex2(float x) { float r; asm("ex2.approx.ftz.f32 %0, %1;" : "=f"(r) : "f"(x)); return r; }
DEVI float rcp(float x) { float r; asm("rcp.approx.ftz.f32 %0, %1;" : "=f"(r) : "f"(x)); return r; }
DEVI uint32_t xor_or(uint32_t a, uint32_t t, uint32_t acc) { uint32_t r; asm("lop3.b32 %0, %1, %2, %3, 0xbe;" : "=r"(r) : "r"(a), "r"(t), "r"(acc)); return r; }
DEVI void stsm2(uint32_t addr, uint32_t r0, uint32_t r1) {
  asm volatile("stmatrix.sync.aligned.m8n8.x2.shared.b16 [%0], {%1,%2};" :: "r"(addr), "r"(r0), "r"(r1) : "memory");
}
DEVI uint32_t settag(uint32_t v, uint32_t tag) { return (v & ~1u) | tag; }

#define A4(c, o)  c(d[o+0]), c(d[o+1]), c(d[o+2]), c(d[o+3])
#define A8(c, o)  A4(c, o), A4(c, o+4)
#define A16(c, o) A8(c, o), A8(c, o+8)
#define A12(c, o) A8(c, o), A4(c, o+8)
#define A28(c, o) A16(c, o), A12(c, o+16)
#define RL12 "{%0,%1,%2,%3,%4,%5,%6,%7,%8,%9,%10,%11}"
#define RL28 "{%0,%1,%2,%3,%4,%5,%6,%7,%8,%9,%10,%11,%12,%13,%14,%15,%16,%17,%18,%19,%20,%21,%22,%23,%24,%25,%26,%27}"
#define A20(c, o) A16(c, o), A4(c, o+16)
#define A32(c, o) A16(c, o), A16(c, o+16)
#define RL8  "{%0,%1,%2,%3,%4,%5,%6,%7}"
#define RL16 "{%0,%1,%2,%3,%4,%5,%6,%7,%8,%9,%10,%11,%12,%13,%14,%15}"
#define RL20 "{%0,%1,%2,%3,%4,%5,%6,%7,%8,%9,%10,%11,%12,%13,%14,%15,%16,%17,%18,%19}"
#define RL32 "{%0,%1,%2,%3,%4,%5,%6,%7,%8,%9,%10,%11,%12,%13,%14,%15,%16,%17,%18,%19,%20,%21,%22,%23,%24,%25,%26,%27,%28,%29,%30,%31}"
#define RL64 "{%0,%1,%2,%3,%4,%5,%6,%7,%8,%9,%10,%11,%12,%13,%14,%15,%16,%17,%18,%19,%20,%21,%22,%23,%24,%25,%26,%27,%28,%29,%30,%31," \
  "%32,%33,%34,%35,%36,%37,%38,%39,%40,%41,%42,%43,%44,%45,%46,%47,%48,%49,%50,%51,%52,%53,%54,%55,%56,%57,%58,%59,%60,%61,%62,%63}"
#define WG_OP(shape) "wgmma.mma_async.sync.aligned." shape "k16.f32.bf16.bf16 "
#define DEF_WGMMA(N, RL, AL, i0, i1, i2, i3, i4, i5, i6)                                                                         \
  template<int SC, int TB, long long CB> DEVI void rs##N(float* d, const uint32_t* a) {                                          \
    if (SC) asm volatile("{.reg .b64 tb; mov.b64 tb, %" #i4 ";\n" WG_OP("m64n" #N) RL ", {%" #i0 ",%" #i1 ",%" #i2 ",%" #i3 "}, tb, 1, 1, 1, %" #i5 ";}" \
      : AL("+f", 0) : "r"(a[0]), "r"(a[1]), "r"(a[2]), "r"(a[3]), "n"(CB), "n"(TB));                                             \
    else asm volatile("{.reg .b64 tb; mov.b64 tb, %" #i4 ";\n" WG_OP("m64n" #N) RL ", {%" #i0 ",%" #i1 ",%" #i2 ",%" #i3 "}, tb, 0, 1, 1, %" #i5 ";}" \
      : AL("=f", 0) : "r"(a[0]), "r"(a[1]), "r"(a[2]), "r"(a[3]), "n"(CB), "n"(TB));                                             \
  }                                                                                                                              \
  template<int SC, int TA, int TB, long long CA, long long CB> DEVI void ss##N(float* d, uint32_t a) {                           \
    if (SC) asm volatile("{.reg .b64 ta, tb; .reg .b32 lo, hi; add.u32 lo, %" #i0 ", %" #i1 "; mov.b32 hi, %" #i2 "; mov.b64 ta, {lo, hi}; mov.b64 tb, %" #i3 ";\n" \
      WG_OP("m64n" #N) RL ", ta, tb, 1, 1, 1, %" #i4 ", %" #i5 ";}"                                                              \
      : AL("+f", 0) : "r"(a), "n"((int)CA), "n"((int)(CA >> 32)), "n"(CB), "n"(TA), "n"(TB));                                    \
    else asm volatile("{.reg .b64 ta, tb; .reg .b32 lo, hi; add.u32 lo, %" #i0 ", %" #i1 "; mov.b32 hi, %" #i2 "; mov.b64 ta, {lo, hi}; mov.b64 tb, %" #i3 ";\n" \
      WG_OP("m64n" #N) RL ", ta, tb, 0, 1, 1, %" #i4 ", %" #i5 ";}"                                                              \
      : AL("=f", 0) : "r"(a), "n"((int)CA), "n"((int)(CA >> 32)), "n"(CB), "n"(TA), "n"(TB));                                    \
  }
DEF_WGMMA(8, "{%0,%1,%2,%3}", A4, 4, 5, 6, 7, 8, 9, 10)
DEF_WGMMA(16, RL8, A8, 8, 9, 10, 11, 12, 13, 14)
DEF_WGMMA(32, RL16, A16, 16, 17, 18, 19, 20, 21, 22)
DEF_WGMMA(40, RL20, A20, 20, 21, 22, 23, 24, 25, 26)
DEF_WGMMA(24, RL12, A12, 12, 13, 14, 15, 16, 17, 18)
DEF_WGMMA(56, RL28, A28, 28, 29, 30, 31, 32, 33, 34)
template<int TA> DEVI void wgmma_n128(float* d, uint64_t a, uint64_t b, int scale_d) {
  asm volatile("{.reg .pred p; setp.ne.b32 p, %66, 0;\n" WG_OP("m64n128") RL64 ", %64, %65, p, 1, 1, %67, 1;}"
    : A32("+f", 0), A32("+f", 32) : "l"(a), "l"(b), "r"(scale_d), "n"(TA));
}

namespace rec {
constexpr int KR = 43;
constexpr uint32_t WSZ = (64 - KR) * 2048, STG = KR * 2048;
constexpr uint32_t WS = 0;
constexpr uint32_t RING = 2 * WSZ;
constexpr uint32_t OB = RING + 3 * 8192;
constexpr uint32_t PB = OB + 4096;
constexpr uint32_t WO = RING + 32768;
constexpr uint32_t ATT = WO + 5 * 16384;
constexpr uint32_t AK = ATT + 10240, AV = ATT + 20480;
constexpr uint32_t PAD = ATT + 30720;
constexpr uint32_t BARS = PAD + 128;
constexpr uint32_t B_XE = BARS  , B_FA = BARS + 64  , B_FB = BARS + 88, B_FO = BARS + 96;
constexpr uint32_t B_ME = BARS + 104  , B_WE = BARS + 136, B_PD = BARS + 144;
constexpr uint32_t B_XF = BARS + 152  , B_MF = BARS + 216  , B_CP = BARS + 248  , B_WT = BARS + 280  ;
constexpr uint32_t B_AB = BARS + 296, B_OB = BARS + 304, B_ST = BARS + 312  , B_WS = BARS + 328, B_WO = BARS + 336, B_AT = BARS + 352, B_AV = BARS + 360;
constexpr int NBAR = 46;
constexpr uint32_t M0 = BARS + 384;
constexpr uint32_t SMEM = 232448;
constexpr int NB_P = 1, NB_ST = 2, NB_O = 3, NB_W0 = 4, NB_W1 = 5;
__host__ __device__ constexpr int wo_tile(int rank, int g, int i) { return i < 2 ? i * 6 + (rank == 2 ? g : 4 - 2 * g + rank) : 13 + rank - g; }
constexpr long long D_W = CD(WS, 16, 1024, 1), D_X = CD(0, 16, 1024, 1), D_O = CD(OB, 128, 256, 0);
constexpr long long D_WO = CD(WO, 16, 1024, 1), D_QM = CD(ATT, 640, 0, 0), D_QT = CD(ATT + 128, 640, 64, 0), D_K = CD(AK, 640, 128, 0);
constexpr long long D_V = CD(AV, 128, 640, 0), D_P = CD(PB, 128, 768, 0);
struct Maps { CUtensorMap w[3], wo, xd, xs; };
__host__ __device__ constexpr uint32_t mslot(int c) { return (c ^ (c >> 1)) * 12288; }
__host__ __device__ constexpr uint32_t xslot(int s) { return s < 3 ? RING + s * 8192 : s < 5 ? WO + (s - 3) * 8192 : s < 7 ? WO + (s + 1) * 8192 : OB; }
__host__ __device__ constexpr bool k_smem(int k) { return k % 3 == 2; }
__host__ __device__ constexpr int k_idx(int k) { return k % 3 == 2 ? k / 3 : k - k / 3; }
__host__ __device__ constexpr int k_of_reg(int i) { return i + (i >> 1); }
__host__ __device__ constexpr int k_of_smem(int i) { return 3 * i + 2; }

#define RPROF(i)
#define RPROF_STEP
#define CPROF(i, v)

template<bool DUAL, int K0, int K1> DEVI void seq_mem(float* d, const uint32_t* w, uint32_t dw) {
  if constexpr (K0 < K1) {
    constexpr long long B = CD(RING, 128, DUAL ? 4096 : 8192, 0) + mslot(K0 >> 4) / 16 + (K0 & 15) * 16;
    if constexpr (DUAL) {
      if constexpr (!k_smem(K0)) rs24<K0 != 0, 1, B>(d, w + 4 * k_idx(K0)); else ss24<1, 1, 1, D_W + k_idx(K0) * 128, B>(d, dw);
    } else {
      if constexpr (!k_smem(K0)) rs16<K0 != 0, 1, B>(d, w + 4 * k_idx(K0)); else ss16<1, 1, 1, D_W + k_idx(K0) * 128, B>(d, dw);
    }
    seq_mem<DUAL, K0 + 1, K1>(d, w, dw);
  }
}
template<int N, int K0, int K1> DEVI void seq_tok(float* d, const uint32_t* w, uint32_t dw) {
  if constexpr (K0 < K1) {
    constexpr bool DUAL = N > 32;
    constexpr long long B = D_X + (DUAL ? xslot((K0 >> 2) & 7) / 16 : xslot(K0 >> 3) / 16 + ((K0 >> 2) & 1) * 256) + (K0 & 3) * 2;
    if constexpr (DUAL) {
      if constexpr (!k_smem(K0)) rs56<K0 != 0, 0, B>(d, w + 4 * k_idx(K0)); else ss56<1, 1, 0, D_W + k_idx(K0) * 128, B>(d, dw);
    } else if constexpr (N == 24) {
      if constexpr (!k_smem(K0)) rs24<K0 != 0, 0, B>(d, w + 4 * k_idx(K0)); else ss24<1, 1, 0, D_W + k_idx(K0) * 128, B>(d, dw);
    } else {
      if constexpr (!k_smem(K0)) rs32<K0 != 0, 0, B>(d, w + 4 * k_idx(K0)); else ss32<1, 1, 0, D_W + k_idx(K0) * 128, B>(d, dw);
    }
    seq_tok<N, K0 + 1, K1>(d, w, dw);
  }
}
template<int T, int K0> DEVI void seq_wo(float* d, uint32_t dw) {
  if constexpr (K0 < 8) { ss16<K0 != 0, 1, 1, D_WO + T * 1024 + K0 * 128, D_O + K0 * 32>(d, dw); seq_wo<T, K0 + 1>(d, dw); }
}
template<long long Q, int K0> DEVI void seq_s(float* d) {
  if constexpr (K0 < 8) { ss40<K0 != 0, 1, 1, Q + K0 * 80, D_K + K0 * 80>(d, 0); seq_s<Q, K0 + 1>(d); }
}
template<bool DUAL, int J> DEVI void load_x(uint32_t sb, const Maps* M, int t, int rb) {
  if (DUAL) e_tma_3d_mc(sb + xslot(J & 7), &M->xd, J * 64, (t - LAG) * 32, 0, sb + B_XF + (J & 7) * 8, rb);
  else e_tma_3d_mc(sb + xslot(J & 7), &M->xs, 0, (t < NSEG ? t : t - LAG) * 32, J * 2, sb + B_XF + (J & 7) * 8, rb);
}
DEVI void load_x_lent(uint32_t sb, const Maps* M, int t, int j) {
  const bool dual = t >= LAG && t < NSEG;
  const uint32_t dst = sb + (j == 3 ? xslot(3) : xslot(5));
#pragma unroll
  for (int i = 0; i < 2; i++)
    e_tma_3d(dst + i * 8192, dual ? &M->xd : &M->xs, dual ? (j + i) * 64 : 0, (t < LAG ? t : t - LAG) * 32, dual ? 0 : (j + i) * 2, sb + B_XF + (j + i) * 8);
}
struct True { static constexpr bool value = true; };
struct False { static constexpr bool value = false; };
struct Ctx { uint32_t sb; const Maps* M; int rb, rank, wi; bool lead; uint32_t par; };
#define XD 1
template<bool DUAL, int J> DEVI void tok_release(const Ctx& c, int t, int& budget) {
  constexpr int NC = DUAL ? 16 : 8, S = J & 7;
  if constexpr (J + 8 < NC) {
    p_arrive_at(c.sb + B_XE + S * 8, c.rb + 2, c.lead);
    p_expect_tx(c.sb + B_XF + S * 8, 8192, c.lead && c.wi == 0);
  } else if constexpr (S == 1 || S == 2 || S == 4 || S == 7) p_arrive(c.sb + B_ME + (S >> 1) * 8, c.lead);
  if constexpr (J == 0) {
    if (c.rank == 2 && c.wi == 6) { mbar_wait(c.sb + B_FO, t & 1, budget); load_x<DUAL, 7>(c.sb, c.M, t, c.rb); }
  }
  if constexpr (J >= XD && J - XD + 8 < NC) {
    constexpr int I = J - XD;
    if (c.rank == 2 && c.wi == (I & 1) * 4 + 1) { mbar_wait(c.sb + B_XE + I * 8, (t - LAG) & 1, budget); load_x<DUAL, I + 8>(c.sb, c.M, t, c.rb); }
  }
}
template<int N, int J, class F, class G> DEVI bool tok_pass(float* d, const uint32_t* w, uint32_t dw, Ctx& c, int t, int& budget, F after0, G setup) {
  constexpr bool DUAL = N > 32;
  constexpr int NC = DUAL ? 16 : 8, KC = 64 / NC;
  if constexpr (J < NC) {
    if constexpr (J > 1) mbar_wait(c.sb + B_XF + (J & 7) * 8, c.par ^ (J >> 3), budget);
    wg_fence();
    seq_tok<N, J * KC, (J + 1) * KC>(d, w, dw);
    wg_commit();
    if constexpr (J == 1) after0();
    if constexpr (J >= NC - 5 && J < NC - 2) setup(J - (NC - 5));
    if constexpr (J > 0) { wg_wait<1>(); tok_release<DUAL, J - 1>(c, t, budget); }
    return tok_pass<N, J + 1>(d, w, dw, c, t, budget, after0, setup);
  } else {
    const bool ok = mbar_test(c.sb + B_MF, t & 1);
    wg_wait<0>();
    tok_release<DUAL, NC - 1>(c, t, budget);
    if (!DUAL) c.par ^= 1;
    return ok;
  }
}
template<int NB> DEVI void pack_tok(uint32_t* e, const float* d) {
#pragma unroll
  for (int i = 0; i < 8; i++) if ((i & 3) < NB) e[i] = pack_bf16(d[4 * (i & 3) + 2 * (i >> 2)], d[4 * (i & 3) + 2 * (i >> 2) + 1]);
}
DEVI void push_tok(const uint32_t* e, uint32_t sb, uint32_t o, int r, int rank) {
  const uint32_t b = mapa(sb, r);
  st_async128(b + o, e[0], e[1], e[2], e[3], b + (rank == 2 ? B_AV : B_AT));
}
DEVI uint32_t h1_tag(int seg) { return ((seg >> 1) & 1) ^ 1; }
DEVI uint4 pack_part(const float* c, int t) {
  return make_uint4(settag(pack_bf16(c[0], c[1]), h1_tag(t)), pack_bf16(c[2], c[3]), settag(pack_bf16(c[4], c[5]), h1_tag(t - LAG)), pack_bf16(c[6], c[7]));
}
DEVI void put_part(char* p1, char* p2, uint4 z, int t) { p_stg_rlx64(p1, z.x, z.y, t < NSEG); p_stg_rlx64(p2, z.z, z.w, t >= LAG); }

DEVI void rec_math(const uint32_t sb, const int wi, const Maps& M) {
  const int h = cta_id() / 3, rb = cluster_rank() >= 3 ? 3 : 0, rank = cluster_rank() - rb;
  const int warp = wi & 3, wg = wi >> 2;
  const bool lead = (threadIdx.x & 127) == 0;
  int budget = SPIN_BUDGET;
  uint32_t w[4 * KR];
  Ctx cx{sb, &M, rb, rank, wi, lead, 0};
  {
    const int lane = lane_id();
    const uint32_t a = sb + wg * STG + ((lane & 7) + (lane >> 4) * 8) * 128 + (((warp * 2 + ((lane >> 3) & 1)) ^ (lane & 7)) << 4);
    for (int i = 0; i < (wg == 1 || rank == 2 ? 12 : 8); i++)
      stg_rlx64((char*)g_h1[i & 3] + ((wo_tile(rank, wg, i >> 2) * 4 + warp) * 4 + (lane >> 3)) * 2048 + h * 64 + (lane & 7) * 8, 0, 0);
    mbar_wait(sb + B_ST + wg * 8, 0, budget);
#pragma unroll
    for (int k = 0; k < KR; k++) ldsm4t(a + k * 2048, w[4*k], w[4*k+1], w[4*k+2], w[4*k+3]);
    nbar_arrive<NB_ST, 384>();
    nbar_sync_r(NB_W0 + wg, 128);
    for (int i = 0; i < 5; i++) p_arrive_at(sb + B_FA + i * 8, rb + (i == 4) * 2, lead);
    mbar_wait(sb + B_WS, 0, budget);
  }
  uint4 z = make_uint4(0, 0, 0, 0);
  char *z1 = nullptr, *z2 = nullptr;
  uint32_t rt0 = 0, rt1 = 0;
  mbar_wait(sb + B_XF, 0, budget); mbar_wait(sb + B_XF + 8, 0, budget);
#pragma unroll 1
  for (int t = 0;; t++) {
    const uint32_t dw = wg * (WSZ >> 4);
    uint32_t e[16];
    bool ok;
    auto finish = [&]() { put_part(z1, z2, z, t - 1); p_arrive_at(sb + B_FO, rb + 2, lead); };
    const int seg = t - rank * LAG;
    const bool att = rank < 2 && (unsigned)seg < (unsigned)NSEG;
    char* p1;
    uint32_t pw, oo;
    uint64_t u0, u1;
    int lane;
    auto setup = [&](int part) {
      if (part == 0) {
        lane = lane_id();
      } else if (part == 1) {
        char* const p = (char*)g_h1 + ((wo_tile(rank, wg, 0) * 4 + warp) * 4 + (lane >> 3)) * 2048 + h * 64 + (lane & 7) * 8;
        p1 = p + (t & 1) * sizeof(g_h1[0]);
        pin2(p1, nullptr);
      } else if (part == 2) {
        oo = OB + (lane >> 4) * 2048 + warp * 512 + rank * 256 + (lane & 15) * 16;
        pw = sb + PB + (wg ? lane * 4 : 768 + warp * 768 + lane * 16);
        pin2(pw, oo);
      } else {
        if (wg) {
          const uint32_t ra = mapa(sb, rb + ((warp & 1) ? 2 : (rank ^ 1) & 1)), rc = mapa(sb, rb + ((warp & 1) ? (rank ^ 1) & 1 : 2));
          u0 = pair(ra + oo, ra + B_OB); u1 = pair(rc + oo, rc + B_OB);
        } else {
          u0 = (uint64_t)((char*)(g_ot + rank * O_LAYER) + (size_t)(h * DH + warp * 16 + (lane >> 2)) * (SEQ * 2) + seg * 64 + (lane & 3) * 16);
          u1 = (uint32_t)((lane & 24) + ((lane >> 2) & 1) + 2 * warp - 8 * (lane & 3));
        }
        pin2(u0, u1);
      }
    };
    RPROF_STEP;
    auto mem_pass = [&](auto dual_c) {
      constexpr bool DUAL = decltype(dual_c)::value;
      float m[DUAL ? 12 : 8];
      RPROF(8 + wg * 12 - 32);
      if (!ok) mbar_wait(sb + B_MF, t & 1, budget);
      wg_fence(); seq_mem<DUAL, 0, 8>(m, w, dw); wg_commit();
      const uint32_t ao = ATT + rank * 10240 + wi * 1280, to = ao + 128 + (lane & 3) * 128 + (lane >> 2) * 16;
      const int la = DUAL ? rank == 0 : t >= NSEG;
      RPROF(1 + wg * 12);
      if (DUAL && rank == 0) {
#pragma unroll
        for (int i = 0; i < 8; i++) { const uint32_t x = e[i]; e[i] = e[8 + i]; e[8 + i] = x; }
      }
      auto piece = [&](int i) { push_tok(e + 4 * i, sb, to + (i & 1) * 640, rb + (la ^ (i >> 1)), rank); };
      piece(0);
      wg_fence(); seq_mem<DUAL, 8, 16>(m, w, dw); wg_commit();
      piece(1);
      mbar_wait(sb + B_MF + 8, t & 1, budget);
      wg_fence(); seq_mem<DUAL, 16, 24>(m, w, dw); wg_commit();
      if (DUAL) piece(2);
      wg_fence(); seq_mem<DUAL, 24, 32>(m, w, dw); wg_commit();
      if (DUAL) piece(3);
      mbar_wait(sb + B_MF + 16, t & 1, budget);
      wg_fence(); seq_mem<DUAL, 32, 48>(m, w, dw); wg_commit();
      wg_wait<1>(); p_arrive(sb + B_PD, lead);
      const uint32_t r0 = mapa(sb, rb + la), r1 = mapa(sb, rb + (la ^ 1)), m0 = r0 + ao + lane * 4, m1 = r1 + ao + lane * 4, ab = rank == 2 ? B_AV : B_AB;
      const uint64_t q0 = pair(m0, r0 + ab), q1 = pair(m0 + 640, r0 + ab), q2 = pair(m1, r1 + ab), q3 = pair(m1 + 640, r1 + ab);
      pin2(q0, q1);
      if (DUAL) pin2(q2, q3);
      mbar_wait(sb + B_MF + 24, t & 1, budget);
      wg_fence(); seq_mem<DUAL, 48, 64>(m, w, dw); wg_commit();
      wg_wait<1>(); p_arrive_at(sb + B_FA, rb, lead);
      wg_wait<0>();
      const uint32_t a0 = pack_bf16(m[0], m[1]), a1 = pack_bf16(m[2], m[3]), a2 = pack_bf16(m[4], m[5]), a3 = pack_bf16(m[6], m[7]);
      if constexpr (DUAL) {
        st_async32(q0, la ? a2 : a0); st_async32(q1, la ? a3 : a1); st_async32(q2, la ? a0 : a2); st_async32(q3, la ? a1 : a3);
        rt0 = pack_bf16(m[8], m[9]); rt1 = pack_bf16(m[10], m[11]);
      } else { st_async32(q0, a0); st_async32(q1, a1); rt0 = a2; rt1 = a3; }
      p_arrive(sb + B_WE, lead);
    };
    if (t >= LAG && t < NSEG) {
      float d[28];
      ok = tok_pass<56, 0>(d, w, dw, cx, t, budget, finish, setup);
      pack_tok<4>(e + 8, d); pack_tok<3>(e, d + 16); e[3] = rt0; e[7] = rt1;
      mem_pass(True());
    } else {
      float d[16];
      if (t > 0) finish();
      if (t > 0 && t < LAG) {
        ok = tok_pass<24, 0>(d, w, dw, cx, t, budget, []() {}, setup);
        pack_tok<3>(e, d); e[3] = rt0; e[7] = rt1;
      } else {
        ok = tok_pass<32, 0>(d, w, dw, cx, t, budget, []() {}, setup);
        pack_tok<4>(e, d);
      }
      mem_pass(False());
    }
    {
      RPROF(2 + wg * 12);
      auto wo_ready = [&]() { if (t == 0) mbar_wait(sb + B_WO, 0, budget); if (t < NSTEP - 1) mbar_wait(sb + B_WT, t & 1, budget); };
      constexpr float SC = 0.08838834764831845f * 1.4426950408889634f;
      if (!att) wo_ready();
      else {
        float s[32];
        setup(3);
        if (wg) {
          uint32_t one[4];
#pragma unroll
          for (int i = 0; i < 4; i++) one[i] = 0x3F803F80u + (pw >> 31);
          mbar_wait_cluster(sb + B_AT, seg & 1, budget);
          mbar_wait_cluster(sb + B_AB, seg & 1, budget);
          fence_proxy_async();
          RPROF(3 + 12);
          wg_fence(); seq_s<D_QM, 0>(s); wg_commit();
          nbar_arrive<NB_P, 256>();
          if (warp == 1) sts32(pw + 640, 0);
          mbar_wait_cluster(sb + B_AV, seg & 1, budget);
          wg_wait<0>();
          float mx = fmaxf(fmaxf(fmaxf(s[0], s[1]), fmaxf(s[4], s[5])), fmaxf(fmaxf(fmaxf(s[8], s[9]), fmaxf(s[12], s[13])), fmaxf(s[16], s[17])));
          const float x1 = __shfl_xor_sync(0xffffffffu, mx, 1), x2 = __shfl_xor_sync(0xffffffffu, mx, 2), x3 = __shfl_xor_sync(0xffffffffu, mx, 3);
          const float u = (warp & 2) ? ((warp & 1) ? s[16] : s[12]) : ((warp & 1) ? s[8] : s[4]);
          const float v = (warp & 2) ? ((warp & 1) ? s[17] : s[13]) : ((warp & 1) ? s[9] : s[5]);
          const float ms = -SC * fmaxf(fmaxf(mx, x1), fmaxf(x2, x3));
          sts32(pw + 128 + warp * 128, pack_bf16(ex2(fmaf(u, SC, ms)), ex2(fmaf(v, SC, ms))));
          if (warp == 0) sts32(pw, pack_bf16(ex2(fmaf(s[0], SC, ms)), ex2(fmaf(s[1], SC, ms))));
          fence_proxy_async();
          nbar_sync<NB_W1, 128>();
          RPROF(4 + 12);
          wg_fence();
          rs8<0, 0, D_P>(s + 8, one); rs8<1, 0, D_P + 16>(s + 8, one); rs8<1, 0, D_P + 32>(s + 8, one);
          wg_commit();
          ss8<0, 0, 0, D_V, D_P>(s, 0); ss8<0, 0, 0, D_V + 320, D_P>(s + 4, 0);
          ss8<1, 0, 0, D_V + 16, D_P + 16>(s, 0); ss8<1, 0, 0, D_V + 336, D_P + 16>(s + 4, 0);
          ss8<1, 0, 0, D_V + 32, D_P + 32>(s, 0); ss8<1, 0, 0, D_V + 352, D_P + 32>(s + 4, 0);
          wg_commit();
          wg_wait<1>();
          const float i0 = rcp(s[8]), i1 = rcp(s[9]);
          wg_wait<0>();
          stsm4(sb + oo, pack_bf16(s[0] * i0, s[1] * i1), pack_bf16(s[2] * i0, s[3] * i1), pack_bf16(s[4] * i0, s[5] * i1), pack_bf16(s[6] * i0, s[7] * i1));
          __syncwarp();
          const uint4 y = lds128v(sb + oo);
          if (t < NSTEP - 1) { st_async128(u0, y); st_async128(u1, y); e_complete_tx(sb + B_OB, 512); }
          wo_ready();
        } else {
          const int lim = (int)u1;
          char* const og = (char*)u0;
          nbar_sync<NB_P, 256>();
          RPROF(3);
          wg_fence();
          seq_s<D_QT, 0>(s);
          wg_commit();
          mbar_wait_cluster(sb + B_AV, seg & 1, budget);
          wg_wait<0>();
#pragma unroll
          for (int i = 0; i < 8; i++) { float& v = s[4 + 4 * (i >> 1) + (i & 1)]; v = i <= lim ? v : -INFINITY; }
          float mx = fmaxf(fmaxf(fmaxf(s[0], s[1]), fmaxf(s[4], s[5])), fmaxf(fmaxf(fmaxf(s[8], s[9]), fmaxf(s[12], s[13])), fmaxf(s[16], s[17])));
          const float x1 = __shfl_xor_sync(0xffffffffu, mx, 1), x2 = __shfl_xor_sync(0xffffffffu, mx, 2), x3 = __shfl_xor_sync(0xffffffffu, mx, 3);
          const float ms = -SC * fmaxf(fmaxf(mx, x1), fmaxf(x2, x3));
#pragma unroll
          for (int i = 0; i < 10; i++) { float& v = s[4 * (i >> 1) + (i & 1)]; v = ex2(fmaf(v, SC, ms)); }
          const float sum = (((s[0] + s[1]) + (s[4] + s[5])) + ((s[8] + s[9]) + (s[12] + s[13]))) + (s[16] + s[17]);
          const float y1 = __shfl_xor_sync(0xffffffffu, sum, 1), y2 = __shfl_xor_sync(0xffffffffu, sum, 2), y3 = __shfl_xor_sync(0xffffffffu, sum, 3);
          const float inv = rcp((sum + y1) + (y2 + y3));
          stsm4(pw, pack_bf16(s[0] * inv, s[1] * inv), pack_bf16(s[4] * inv, s[5] * inv), pack_bf16(s[8] * inv, s[9] * inv), pack_bf16(s[12] * inv, s[13] * inv));
          stsm2(pw + 512, pack_bf16(s[16] * inv, s[17] * inv), 0);
          fence_proxy_async();
          nbar_sync<NB_W0, 128>();
          RPROF(4);
          wg_fence();
          ss32<0, 0, 0, D_V, D_P + 48>(s, 0); ss32<0, 0, 0, D_V + 320, D_P + 48>(s + 16, 0);
          ss32<1, 0, 0, D_V + 16, D_P + 64>(s, 0); ss32<1, 0, 0, D_V + 336, D_P + 64>(s + 16, 0);
          ss32<1, 0, 0, D_V + 32, D_P + 80>(s, 0); ss32<1, 0, 0, D_V + 352, D_P + 80>(s + 16, 0);
          wg_commit();
          wo_ready();
          wg_wait<0>();
#pragma unroll
          for (int i = 0; i < 4; i++) {
            const float* d = s + (i >> 1) * 16 + (i & 1) * 2;
            stg128(og + ((i >> 1) * 64 + (i & 1) * 8) * (SEQ * 2), pack_bf16(d[0], d[1]), pack_bf16(d[4], d[5]), pack_bf16(d[8], d[9]), pack_bf16(d[12], d[13]));
          }
          if ((seg & 3) == 3) nbar_arrive<NB_O, 160>();
        }
      }
      RPROF(5 + wg * 12);
      const bool three = wg == 1 || rank == 2;
      char* const p2 = p1 + (2 + ((t - LAG) & 1) - (t & 1)) * (int)sizeof(g_h1[0]);
      if (t < NSTEP - 1) {
        float c[24];
        const uint32_t dt = wg ? 0 : 3072;
        mbar_wait_cluster(sb + B_OB, t & 1, budget);
        fence_proxy_async();
        RPROF(6 + wg * 12);
        wg_fence(); seq_wo<0, 0>(c, dt); wg_commit(); seq_wo<1, 0>(c + 8, dt); wg_commit();
        mbar_wait(sb + B_XF, cx.par, budget);
        wg_wait<1>();
        if (warp == 2) load_x_lent(sb, &M, t + 1, wg ? 3 : 5);
        put_part(p1, p2, pack_part(c, t), t);
        const int o3 = (wo_tile(rank, wg, three ? 2 : 1) - wo_tile(rank, wg, 0)) * 32768;
        z1 = p1 + o3; z2 = p2 + o3;
        if (three) {
          wg_fence(); seq_wo<2, 0>(c + 16, dt); wg_commit();
          wg_wait<1>(); put_part(p1 + 6 * 32768, p2 + 6 * 32768, pack_part(c + 8, t), t);
          mbar_wait(sb + B_XF + 8, cx.par, budget);
          wg_wait<0>(); z = pack_part(c + 16, t);
        } else { mbar_wait(sb + B_XF + 8, cx.par, budget); wg_wait<0>(); z = pack_part(c + 8, t); }
      } else break;
      RPROF(7 + wg * 12);
    }
  }
}

DEVI void wait_xa(const int* p, int& budget) {
  while (__any_sync(0xffffffffu, ldg_acq32(p) < 64) && --budget > 0) {}
  fence_proxy_global();
}
template<bool DUAL> DEVI void first_loads(uint32_t sb, const Maps* M, int n, int h, int rb, int& budget) {
  if (h >= 16 && n >= LAG && ((n - LAG) & 3) == 0) e_prefetch_3d(&M->xs, 0, (n - LAG) * 32, (h & 7) * 2);
  mbar_wait(sb + B_FA, n & 1, budget);
  load_x<DUAL, 0>(sb, M, n, rb); load_x<DUAL, 1>(sb, M, n, rb); load_x<DUAL, 2>(sb, M, n, rb);
}
template<bool DUAL> DEVI void lent_loads(uint32_t sb, const Maps* M, int n, int rb, int& budget) {
  mbar_wait(sb + B_FB, n & 1, budget);
  load_x<DUAL, 3>(sb, M, n, rb); load_x<DUAL, 4>(sb, M, n, rb); load_x<DUAL, 5>(sb, M, n, rb); load_x<DUAL, 6>(sb, M, n, rb);
}
DEVI void rec_comm(const uint32_t sb, const int warp, const Maps& M, const bf16* __restrict__ mem0) {
  const int lane = threadIdx.x & 31, h = cta_id() / 3, rb = cluster_rank() >= 3 ? 3 : 0, rank = cluster_rank() - rb;
  int budget = SPIN_BUDGET;
  const bool two = warp == 3 || (rank == 2 && warp == 2);
  const int ntask = two ? 2 : 1, qi = two ? (warp == 3 ? rank : 3) : rank * 3 + warp;
  const int task0 = two ? h * 2 + (qi >> 1) : 64 + h * 4 + (qi >> 1);
  auto h2_word = [&](int i, int ln) {
    const int task = task0 + i * 192;
    return (char*)g_h2 + (task >> 6) * 8192 + ((qi ^ i) & 1) * 4096 + ((task >> 2) & 15) * 256 + (task & 3) * 32 + (ln & 8) * 16 + (ln & 7) * 4;
  };
  auto first_x = [&](int t) {
    const int n = t + 1;
    p_expect_tx(sb + B_XF + (lane_id() & 7) * 8, 8192, lane_id() < 8);
    if (rank == 0) {
      if (n >= LAG && ((n - LAG) & 3) == 0) wait_xa(&g_xa[1][(n - LAG) >> 2], budget);
      if (n >= LAG && n < NSEG) first_loads<true>(sb, &M, n, h, rb, budget); else first_loads<false>(sb, &M, n, h, rb, budget);
    }
  };
  {
    const int task = task0 + (lane >> 4) * 192, L = (task & 3) * 8 + (lane & 7);
    if ((lane >> 4) < ntask) {
      const bf16* p = mem0 + (L & 3) * 2 * DM + (task >> 2) * 16 + (L >> 2) + (lane & 8);
      uint32_t m0 = (uint32_t)__bfloat16_as_ushort(p[0]) | (uint32_t)__bfloat16_as_ushort(p[DM]) << 16;
      m0 = m0 ? m0 : 0x8000u;
      stg_rlx32(h2_word(lane >> 4, lane), ((qi ^ (lane >> 4)) & 1) ? 0 : m0);
      for (int i = 1; i < 4; i++) stg_rlx32(h2_word(lane >> 4, lane) + i * sizeof(g_h2[0]), 0);
      sts32(sb + M0 + warp * 128 + lane * 4, m0);
    }
    __syncwarp();
    nbar_sync<NB_ST, 384>();
    if (warp == 2) {
      e_expect_tx(sb + B_WS, 2 * WSZ);
#pragma unroll 1
      for (int i = 0; i < 2 * (64 - KR); i++) e_tma_2d(sb + WS + (i & 1) * WSZ + (i >> 1) * 2048, &M.w[rank], h * DH + (i & 1) * 64, k_of_smem(i >> 1) * 16, sb + B_WS);
      const int nt = rank == 2 ? 6 : 5;
      e_expect_tx(sb + B_WO, (nt - 2) * 16384);
#pragma unroll 1
      for (int i = 1; i < nt; i++) if (i != 3) e_tma_2d(sb + WO + i * 16384, &M.wo, wo_tile(rank, 1 - i / 3, i % 3) * 64, h * DH, sb + B_WO);
    }
    wait_xa(&g_xa[0][0], budget);
    if (warp == 3) { first_x(-1); if (rank == 0) lent_loads<false>(sb, &M, 0, rb, budget); }
  }
  uint32_t cpp = 0;
  const uint32_t cp = sb + B_CP + warp * 8;
  uint32_t f_dst, f_chk, f_bar, f_time = gtime() - 4000;
  const char *f_src, *f_xr;
  auto prepare = [&](int s) {
    const int ck = warp ^ (warp < 2 && (s < LAG || s >= NSEG) && (rank & 1) == (s >= NSEG)), ln = lane_id();
    f_dst = sb + RING + mslot(ck); f_chk = f_dst + ln * 32 + (ln >> 2) * 4; f_bar = sb + ck * 8;
    f_src = (const char*)g_h2[s & 3] + ck * 8192 + (s >= NSEG ? 4096 : 0);
    f_xr = (const char*)g_xr[(s + 1) & 63] + ck * 4096;
    pin2(f_chk, 0u);
    return s <= LAG ? TP(9) + ck * TP(11) : s <= NSEG ? TP(1) + ck * TP(4) : TP(13) + ck * TP(11);
  };
  prepare(0);
#pragma unroll 1
  for (int t = 0;; t++) {
    const int n = t + 1;
    const bool dual = t >= LAG && t < NSEG;
    RPROF_STEP;
    {
      const uint32_t bytes = dual ? 8192 : 4096;
      e_expect_tx(cp, bytes + (n < NSEG ? 4096 : 0));
      mbar_wait(f_bar + B_ME, t & 1, budget);
      if (n < NSEG) e_bulk_g2s(f_dst + 8192, f_xr, 4096, cp);
      wait_time(f_time);
      RPROF(24); CPROF(0, gtime());
      int tries = 0;
      while (true) {
        tries++;
        e_bulk_g2s(f_dst, f_src, bytes, cp);
        mbar_wait(cp, cpp, budget); cpp ^= 1;
        uint32_t mn = min(min(lds32v(f_chk), lds32v(f_chk + 1024)), min(lds32v(f_chk + 2048), lds32v(f_chk + 3072)));
        if (dual) mn = min(min(mn, min(lds32v(f_chk + 4096), lds32v(f_chk + 5120))), min(lds32v(f_chk + 6144), lds32v(f_chk + 7168)));
        if (!__any_sync(0xffffffffu, mn == 0) || --budget < 0) break;
        e_expect_tx(cp, bytes);
      }
      e_arrive(f_bar + B_MF);
      RPROF(25); CPROF(1, gtime()); CPROF(2, tries);
    }
    const int seg = t - rank * LAG;
    const bool att = rank < 2 && (unsigned)seg < (unsigned)NSEG;
    if (warp == 0) {
      if (att) { e_expect_tx(sb + B_AT, 16384); e_expect_tx(sb + B_AB, 4096); e_expect_tx(sb + B_AV, 10240); }
      if (n < NSTEP) e_expect_tx(sb + B_OB, dual ? 4096 : 2048);
    }
    if (n + 1 < NSEG && (n & 3) == 3) wait_xa(&g_xa[0][(n + 1) >> 2], budget);
    if (rank == 2 && warp == 1) {
      if (h < 16 ? n < NSEG : n > LAG && n < NSTEP && ((n - LAG) & 3)) e_prefetch_3d(&M.xs, 0, (h < 16 ? n : n - LAG) * 32, (h & 7) * 2);
      if (h >= 16 && n + 1 < NSEG) asm volatile(ELECT "cp.async.bulk.prefetch.L2.global [%0], 2048;}" :: "l"((const char*)g_xr[n + 1] + (h & 7) * 2048) : "memory");
    }
    {
      const int ln = lane_id(), i = ln >> 4;
      char* const w = h2_word(i, ln);
      if (i < ntask) {
        stg_rlx32(w + ((t + 3) & 3) * sizeof(g_h2[0]), 0);
        if (n == LAG && ((qi ^ i) & 1)) stg_rlx32(w + (n & 3) * sizeof(g_h2[0]), lds32v(sb + M0 + warp * 128 + ln * 4));
      }
      __syncwarp();
    }
    if (n < NSTEP) {
      const uint32_t tag = (n >> 1) & 31;
      mbar_wait(sb + B_PD, t & 1, budget);
      uint32_t t0 = clock32();
      if (warp == 2) {
        e_expect_tx(sb + B_WT, 32768);
        e_tma_2d(sb + WO + 49152, &M.wo, wo_tile(rank, 0, 0) * 64, h * DH, sb + B_WT);
        mbar_wait(sb + B_WE, t & 1, budget);
        e_tma_2d(sb + WO, &M.wo, wo_tile(rank, 1, 0) * 64, h * DH, sb + B_WT);
      }
      if (warp == 3) first_x(t);
      if (warp == 0 && rank == (t >= NSEG)) { mbar_wait(sb + B_AB, seg & 1, budget); e_stg_rlx32(&g_ts[t & 1][h], (gtime() & ~31u) | tag); }
      const int fd = prepare(n), ln = lane_id();
      const int sa = t - (qi & 1) * LAG, sc = t - (~qi & 1) * LAG;
      const int i0 = (unsigned)sa < (unsigned)(NSEG - 1) ? 0 : 1, i1 = two && (unsigned)sc < (unsigned)(NSEG - 1) ? 2 : 1;
      const char* src = (const char*)g_h1[(qi & 1) * 2 + (sa & 1)] + task0 * 2048 + ln * 8;
      char* dst = h2_word(0, ln) + (n & 3) * sizeof(g_h2[0]);
      const int ds = ((~qi & 1) * 2 + (sc & 1) - (qi & 1) * 2 - (sa & 1)) * (int)sizeof(g_h1[0]) + 192 * 2048, dd = 3 * 8192 + ((qi & 1) ? -4096 : 4096);
      if (i0) { src += ds; dst += dd; }
      pin2(src, dst);
      spin_until(t0, TSD);
      uint32_t v0;
      do { v0 = ldg_rlx32(&g_ts[t & 1][ln]); } while (__any_sync(0xffffffffu, (v0 & 31) != tag) && --budget > 0);
      const uint32_t now = __shfl_sync(0xffffffffu, v0, 0);
      t0 = now + __reduce_max_sync(0xffffffffu, (int)(v0 - now));
      f_time = t0 + fd;
      RPROF(26); CPROF(3, t0);
      t0 += t < LAG ? TP(8) : t < NSEG ? TP(0) : TP(12);
#pragma unroll 1
      for (int i = i0; i < i1; i++) {
        const uint32_t tg = h1_tag(i ? sc : sa);
        uint2 v[8];
        wait_time(t0 + (!two ? 0 : i ? TP(3) : -TP(10)));
        int tries = 0;
        float a[4];
        while (true) {
          tries++;
#pragma unroll
          for (int k = 0; k < 8; k++) v[k] = ldg_rlx64(src + k * 256);
          asm volatile("{.reg .pred p; setp.eq.s32 p, %0, 0x7fffffff; @p exit;}" :: "r"(budget) : "memory");
          uint32_t bad = 0;
#pragma unroll
          for (int k = 0; k < 8; k++) {
            bad = xor_or(v[k].x, tg, bad);
            a[0] = k ? a[0] + bf_lo(v[k].x) : bf_lo(v[k].x); a[1] = k ? a[1] + bf_hi(v[k].x) : bf_hi(v[k].x);
            a[2] = k ? a[2] + bf_lo(v[k].y) : bf_lo(v[k].y); a[3] = k ? a[3] + bf_hi(v[k].y) : bf_hi(v[k].y);
          }
#pragma unroll
          for (int k = 0; k < 2; k++) {
            const float keep = (ln & 8) ? a[2+k] : a[k], send = (ln & 8) ? a[k] : a[2+k];
            a[k] = keep + __shfl_xor_sync(0xffffffffu, send, 8);
          }
#pragma unroll
          for (int k = 0; k < 2; k++) a[k] += __shfl_xor_sync(0xffffffffu, a[k], 16);
          if (!__any_sync(0xffffffffu, bad & 1) || --budget < 0) break;
        }
        const uint32_t out = pack_bf16(a[0], a[1]);
        if (ln < 16) stg_rlx32(dst, out ? out : 0x8000u);
        __syncwarp();
        src += ds; dst += dd;
        if (i == 0) { RPROF(28); CPROF(6, gtime()); CPROF(4, gtime()); CPROF(5, tries); } else CPROF(7, gtime());
      }
    }
    if (warp == (dual ? 2 : 1) && att && (seg & 3) == 3) { nbar_sync<NB_O, 160>(); e_flag_add(&g_dep[E_O1 + rank * 16 + (seg >> 2)]); }
    if (n == NSTEP) break;
  }
  if (h == 0 && rank == 0 && warp < 2) g_xa[warp][lane_id()] = 0;
}
}

__global__ void __launch_bounds__(384, 1)
rec_kernel(const __grid_constant__ rec::Maps M, const bf16* __restrict__ mem0) {
  using namespace rec;
  extern __shared__ __align__(1024) uint8_t smem[];
  const uint32_t sb = __shfl_sync(0xffffffffu, smem_u32(smem), 0);
  const int tid = threadIdx.x, wi = __shfl_sync(0xffffffffu, tid >> 5, 0);
  if ((sb & 0x3FFFF) != SMEM_BASE) __trap();
  if (wi == 0) {
    const int h = cta_id() / 3, rank = cta_id() - h * 3;
    for (int i = tid; i < NBAR; i += 32) mbar_init(sb + BARS + i * 8, i < 13 ? 6 : i < 19 ? 2 : 1);
    ((uint32_t*)(smem + PAD))[tid] = 0;
    fence_mbar_init(); fence_proxy_async();
    __syncwarp();
    e_expect_tx(sb + B_ST, STG); e_expect_tx(sb + B_ST + 8, STG);
    for (int i = 0; i < 2 * KR; i++) e_tma_2d(sb + (i & 1) * STG + (i >> 1) * 2048, &M.w[rank], h * DH + (i & 1) * 64, k_of_reg(i >> 1) * 16, sb + B_ST + (i & 1) * 8);
  } else if (wi == 1) {
    if (blockIdx.x < NEV / 32) { g_dep[blockIdx.x * 32 + (tid & 31)] = 0; g_claim[blockIdx.x * 32 + (tid & 31)] = 0; __threadfence(); }
    __syncwarp();
    asm volatile("griddepcontrol.launch_dependents;" ::: "memory");
  }
  cluster_arrive(); cluster_wait();
  if (wi < 8) { reg_inc<232>(); rec_math(sb, wi, M); cluster_arrive(); cluster_wait(); }
  else { reg_dec<40>(); rec_comm(sb, wi & 3, M, mem0); cluster_arrive(); cluster_wait(); }
}

namespace gm {
struct Maps { CUtensorMap ot, wo, xn, wg, wu, hl, hs, wd, out; };
constexpr int STAGES = 6, STAGE = 32768;
constexpr uint32_t SO = STAGES * STAGE, BARS = SO + 32768;
constexpr uint32_t B_FULL = BARS, B_EMPTY = BARS + 48, B_TF = BARS + 96, B_TE = BARS + 112, B_ORD = BARS + 128, B_PM = BARS + 144, B_GO = BARS + 160;
constexpr uint32_t MAIL = BARS + 176, PMAIL = BARS + 192;
constexpr uint32_t SMEM = BARS + 256;
constexpr int END = -1;
#define GT gtime

struct Tile {
  bool isO, isG, l2; int blk, col, k0, n;
  DEVI Tile(int task, int rank) {
    const int e = task >> 8, id = task & 255;
    const bool isD = e < E_G1 || e >= E_D2;
    isO = e >= E_O1 && e < E_G2; isG = !isD && !isO; l2 = e >= E_O2;
    blk = isG && l2 ? (e & 15) * 2 + rank : isD && !l2 ? e >> 1 : e & 15;
    col = isG ? (l2 ? id : id * 2 + rank) : (id & 3) * 2 + rank;
    k0 = isO ? (id >> 2) * 2048 : isG ? 0 : ((l2 ? e >> 4 : e) & 1) * 1792;
    n = isO ? 32 : isG ? 16 : 28;
  }
};

DEVI float geglu(float g, float u) {
  const float z = g * (0.7978845608028654f + 0.035677408136300125f * g * g);
  float t; asm("tanh.approx.f32 %0, %1;" : "=f"(t) : "f"(z));
  const float hg = 0.5f * g;
  return fmaf(hg, t, hg) * u;
}
struct Sched {
  int need, size, e;
  bool filler;
  uint4 dep, cl;
  DEVI void init(int lane) {
    e = (lane < 4 ? lane + 12 : lane < 16 ? lane - 4 : lane) * 4;
    const bool d = e < E_G1 || e >= E_D2, o = e >= E_O1 && e < E_G2;
    need = d ? 28 : e < E_O1 ? 64 : o ? 32 : 128;
    size = d ? 4 : o ? 8 : e < E_O1 ? 28 : e < E_G2 + 8 ? 56 : 0;
    filler = (int)blockIdx.x >= TP(5);
  }
  DEVI void scan(int lane) { cl = ldg_rlx128(g_claim + e); dep = ldg_rlx128(g_dep + e); }
  DEVI int next(int lane, int& budget) {
    while (--budget > 0) {
      int av[4], open = 0;
#pragma unroll
      for (int i = 0; i < 4; i++) { const int r = max(size - (int)(&cl.x)[i], 0); open |= r; av[i] = ((int)(&dep.x)[i] >= need ? r : 0) + (i ? av[i - 1] : 0); }
      const uint32_t mo = __ballot_sync(0xffffffffu, open);
      if (!mo) break;
      if (filler) {
        const int x = TP(6) & 3, dx = x == 0 ? dep.x : x == 1 ? dep.y : x == 2 ? dep.z : dep.w;
        filler = !__any_sync(0xffffffffu, e == ((E_O1 + TP(6)) & ~3) && dx >= need);
      }
      if (!filler && (mo & 0xffff) && lane >= E_O2 / 4) av[3] = 0;
      int inc = av[3], pos = 0;
      while (true) {
        const uint32_t m = __ballot_sync(0xffffffffu, inc > pos && av[3]);
        if (!m) break;
        const int l = __ffs(m) - 1, rel = pos - (inc - av[3]), i = (rel >= av[0]) + (rel >= av[1]) + (rel >= av[2]);
        int r = 0;
        if (lane == l) {
          const int tk = atomicAdd(g_claim + e + i, 1);
          r = tk < size ? (e + i) << 8 | tk : -1 - (inc - av[3] + (i == 0 ? av[0] : i == 1 ? av[1] : i == 2 ? av[2] : av[3]) + tk - size);
        }
        r = __shfl_sync(0xffffffffu, r, l);
        if (r >= 0) return r;
        if (pos == 0) {
#pragma unroll
          for (int o = 1; o < 32; o <<= 1) { const int v = __shfl_up_sync(0xffffffffu, inc, o); if (lane >= o) inc += v; }
        }
        pos = -1 - r;
      }
      if (pos == 0) __nanosleep(TP(7));
      scan(lane);
    }
    return END;
  }
};

DEVI void scheduler(const uint32_t sb) {
  const int lane = threadIdx.x & 31;
  int budget = SPIN_BUDGET;
  Sched sc; sc.init(lane);
#pragma unroll 1
  for (int i = 0;; i++) {
    mbar_wait(sb + B_GO, (i & 1) ^ 1, budget);
    sc.scan(lane);
    const int task = sc.next(lane, budget);
    const uint32_t r = mapa(sb, lane & 1);
    if (lane < 2) st_async32(r + PMAIL + (i & 1) * 4, task, r + B_PM + (i & 1) * 8);
    __syncwarp();
    if (task == END) break;
  }
}

DEVI void producer(const uint32_t sb, const Maps& M) {
  const int lane = threadIdx.x & 31, rank = cluster_rank();
  int budget = SPIN_BUDGET, s = 0, ph = 0;
#pragma unroll 1
  for (int i = 0;; i++) {
    e_expect_tx(sb + B_PM + (i & 1) * 8, 4);
    mbar_wait_cluster(sb + B_PM + (i & 1) * 8, (i >> 1) & 1, budget);
    const int task = budget < 0 ? END : __shfl_sync(0xffffffffu, (int)lds32v(sb + PMAIL + (i & 1) * 4), 0);
    fence_proxy_global();
    for (int z = 0; z < (task == END ? 2 : 1); z++) {
      const int g = (i + z) & 1;
      mbar_wait(sb + B_TE + g * 8, (((i + z) >> 1) & 1) ^ 1, budget);
      if (lane == 0) { sts64(sb + MAIL + g * 8, task, s | ph << 8); mbar_arrive(sb + B_TF + g * 8); }
      __syncwarp();
    }
    if (task == END) break;
    const Tile T(task, rank);
    const bool shareB = T.isG && T.l2;
    const CUtensorMap* mA = T.isO ? &M.ot : T.isG ? &M.xn : &M.hl;
    const CUtensorMap* mB0 = T.isO ? &M.wo : T.isG ? &M.wg : &M.wd;
    const CUtensorMap* mB1 = T.isG ? &M.wu : mB0;
    const int c0 = T.col * (T.isG ? 64 : 128), c1 = T.isG ? c0 : c0 + 64, row = T.blk * 128;
    const int ok = 0;
    int k = T.k0;
#pragma unroll 1
    for (int it = 0; it < T.n; it++, k += 64) {
      const uint32_t a = sb + s * STAGE, fb = sb + B_FULL + s * 8;
      mbar_wait(sb + B_EMPTY + s * 8, ph ^ 1, budget);
      e_expect_tx(fb, STAGE);
      if (shareB) {
        e_tma_2d_mc(a + 16384 + rank * 8192, rank ? mB1 : mB0, c0, k, fb);
        e_tma_2d(a, mA, k, row, fb); e_tma_2d(a + 8192, mA, k, row + 64, fb);
      } else {
        e_tma_2d_mc(a + rank * 8192, mA, T.isO ? row + rank * 64 : k, T.isO ? k + ok : row + rank * 64, fb);
        e_tma_2d(a + 16384, mB0, c0, k, fb); e_tma_2d(a + 24576, mB1, c1, k, fb);
      }
      if (it == T.n - TP(2)) e_arrive(sb + B_GO);
      if (++s == STAGES) { s = 0; ph ^= 1; }
    }
  }
}

template<int TA> DEVI void mainloop(float* d0, float* d1, uint32_t sb, int n, int s, int ph, bool lead, uint32_t ord, int& budget) {
  int prev = 0;
  const uint32_t rel = threadIdx.x & 127;
#pragma unroll 1
  for (int i = 0; i < n; i++) {
    mbar_wait(sb + B_FULL + s * 8, ph, budget);
    const uint32_t a = sb + s * STAGE;
    const uint64_t da = mkdesc(a, 16, 1024), db = mkdesc(a + 16384, 8192, 1024);
    wg_fence();
#pragma unroll
    for (int k = 0; k < 4; k++) {
      wgmma_n128<TA>(d0, da + k * (TA ? 128 : 2), db + k * 128, (i | k) != 0);
      wgmma_n128<TA>(d1, da + 512 + k * (TA ? 128 : 2), db + k * 128, (i | k) != 0);
    }
    wg_commit();
    if (i > 0) { wg_wait<1>(); p_arrive_at(sb + B_EMPTY + prev * 8, rel & 1, rel < 2); }
    prev = s;
    if (++s == STAGES) { s = 0; ph ^= 1; }
  }
  p_arrive(ord, lead);
  wg_wait<0>();
  p_arrive_at(sb + B_EMPTY + prev * 8, rel & 1, rel < 2);
}

DEVI void consumer(const uint32_t sb, const Maps& M, const int wg) {
  const int tid = threadIdx.x, lane = tid & 31, warp = (tid >> 5) & 3;
  const bool lead = (tid & 127) == 0;
  const uint32_t so = sb + SO + wg * 16384;
  int budget = SPIN_BUDGET;
  float d0[64], d1[64];
#pragma unroll 1
  for (int m = 0;; m++) {
    mbar_wait(sb + B_TF + wg * 8, m & 1, budget);
    const uint2 mail = lds64v(sb + MAIL + wg * 8);
    const int task = __shfl_sync(0xffffffffu, (int)mail.x, 0), pos = __shfl_sync(0xffffffffu, (int)mail.y, 0);
    e_arrive(sb + B_TE + wg * 8);
    if (task == END || budget < 0) break;
    const Tile T(task, cluster_rank());
    mbar_wait(sb + B_ORD + wg * 8, (m & 1) ^ wg ^ 1, budget);
    if (T.isO) mainloop<1>(d0, d1, sb, T.n, pos & 255, pos >> 8, lead, sb + B_ORD + (wg ^ 1) * 8, budget);
    else mainloop<0>(d0, d1, sb, T.n, pos & 255, pos >> 8, lead, sb + B_ORD + (wg ^ 1) * 8, budget);
    const uint32_t st = so + (warp * 16 + (lane & 15)) * 128;
    if (T.isG) {
      int* const fl = &g_dep[T.l2 ? E_D2 + (T.col >= 28) * 16 + T.blk : E_D1 + T.blk * 2 + (T.col >= 28)];
#pragma unroll
      for (int mm = 0; mm < 2; mm++) {
        const float* d = mm ? d1 : d0;
#pragma unroll
        for (int c = 0; c < 4; c++) {
          uint32_t r[4];
#pragma unroll
          for (int i = 0; i < 4; i++) r[i] = pack_bf16(geglu(d[8*c+2*i], d[32+8*c+2*i]), geglu(d[8*c+2*i+1], d[33+8*c+2*i]));
          stsm4(st + mm * 8192 + (((2 * c + (lane >> 4)) ^ (lane & 7)) << 4), r[0], r[1], r[2], r[3]);
        }
      }
      fence_proxy_async();
      nbar_sync_r(1 + wg, 128);
      if (lead) {
        tma_store_2d(&M.hs, so, T.col * 64, T.blk * 128);
        bulk_commit();
        bulk_wait<0>();
        flag_add(fl);
      }
    } else {
#pragma unroll
      for (int hf = 0; hf < 2; hf++) {
        if (hf) { if (lead) bulk_wait_read<0>(); nbar_sync_r(1 + wg, 128); }
#pragma unroll
        for (int mm = 0; mm < 2; mm++) {
          const float* d = (mm ? d1 : d0) + hf * 32;
#pragma unroll
          for (int c = 0; c < 4; c++)
            stsm4(st + mm * 8192 + (((2 * c + (lane >> 4)) ^ (lane & 7)) << 4), pack_bf16(d[8*c], d[8*c+1]), pack_bf16(d[8*c+2], d[8*c+3]),
                  pack_bf16(d[8*c+4], d[8*c+5]), pack_bf16(d[8*c+6], d[8*c+7]));
        }
        fence_proxy_async();
        nbar_sync_r(1 + wg, 128);
        if (lead) { tma_radd_2d(&M.out, so, T.col * 128 + hf * 64, T.blk * 128); bulk_commit(); }
      }
      if (lead) {
        bulk_wait<0>();
        if (T.isO || !T.l2) flag_add(&g_dep[(!T.isO ? E_LX2 : T.l2 ? E_LX1B : E_LX1A) + T.blk]);
      }
    }
    __syncwarp();
  }
}

DEVI void norm_helper(const bf16* __restrict__ x, bf16* out) {
  const int lane = threadIdx.x & 31;
  int budget = SPIN_BUDGET, tk = lane < 4 ? -1 : 1024;
#pragma unroll 1
  while (--budget > 0) {
    if (tk < 0) tk = atomicAdd(g_claim + E_LI + lane, 1);
    if (__all_sync(0xffffffffu, tk >= 1024)) break;
    const uint32_t m = __ballot_sync(0xffffffffu, tk < 1024 && (lane == 0 || ldg_acq32(g_dep + E_LI + lane * 16 + (tk >> 6)) >= 16));
    if (!m) { __nanosleep(TP(7)); continue; }
    const int ql = __ffs(m) - 1, task = __shfl_sync(0xffffffffu, tk, ql), q = E_LI + ql * 16, ev = task >> 6;
    if (lane == ql) tk = -1;
    const size_t off = (size_t)task * (DM * 4) + lane * 16;
    const char* src = (const char*)(q == E_LI ? x : out) + off;
    uint4 u[8];
#pragma unroll
    for (int i = 0; i < 8; i++) u[i] = ldg_rlx128(src + i * 512);
    if (q == E_LI) {
#pragma unroll
      for (int i = 0; i < 8; i++) stg128((char*)out + off + i * 512, u[i].x, u[i].y, u[i].z, u[i].w);
    }
    int* const fl = q == E_LI ? &g_xa[0][ev] : q == E_LX2 ? &g_xa[1][ev] : &g_dep[q == E_LX1A ? E_G1 + ev : E_G2 + (ev >> 1)];
    float mean[2], rs[2];
#pragma unroll
    for (int r = 0; r < 2; r++) {
      float s0 = 0, s1 = 0;
#pragma unroll
      for (int i = 0; i < 16; i++) { const uint32_t v = (&u[4*r + (i >> 2)].x)[i & 3]; s0 += bf_lo(v); s1 += bf_hi(v); }
      mean[r] = (s0 + s1) * (1.f / 32);
      s0 = s1 = 0;
#pragma unroll
      for (int i = 0; i < 16; i++) { const uint32_t v = (&u[4*r + (i >> 2)].x)[i & 3]; const float a = bf_lo(v) - mean[r], b = bf_hi(v) - mean[r]; s0 = fmaf(a, a, s0); s1 = fmaf(b, b, s1); }
      rs[r] = s0 + s1;
    }
    {
      const bool hi = lane & 16;
      float m1 = hi ? mean[1] : mean[0], q1 = hi ? rs[1] : rs[0], m2 = hi ? mean[0] : mean[1], q2 = hi ? rs[0] : rs[1], cnt = 16;
#pragma unroll
      for (int o = 16; o; o >>= 1) {
        m2 = __shfl_xor_sync(0xffffffffu, m2, o); q2 = __shfl_xor_sync(0xffffffffu, q2, o);
        const float dl = m1 - m2;
        q2 = q1 = fmaf(dl * dl, cnt, q1 + q2); m2 = m1 = 0.5f * (m1 + m2);
        cnt *= 2;
      }
      q1 = rsqrtf(q1 * (1.f / DM) + 1e-5f);
      m2 = __shfl_xor_sync(0xffffffffu, m1, 16); q2 = __shfl_xor_sync(0xffffffffu, q1, 16);
      mean[0] = hi ? m2 : m1; mean[1] = hi ? m1 : m2; rs[0] = hi ? q2 : q1; rs[1] = hi ? q1 : q2;
    }
#pragma unroll
    for (int i = 0; i < 8; i++) {
      uint32_t y[4];
#pragma unroll
      for (int c = 0; c < 4; c++) { const uint32_t v = (&u[i].x)[c]; y[c] = pack_bf16((bf_lo(v) - mean[i >> 2]) * rs[i >> 2], (bf_hi(v) - mean[i >> 2]) * rs[i >> 2]); }
      stg128((char*)g_xn + off + i * 512, y[0], y[1], y[2], y[3]);
      u[i] = make_uint4(y[0], y[1], y[2], y[3]);
    }
    if (q == E_LI && (task & 15) >= 12) {
      uint32_t* const xr = g_xr[task >> 4] + lane * 32 + (task & 3);
#pragma unroll
      for (int i = 0; i < 16; i++) {
        const uint32_t a = (&u[i >> 2].x)[i & 3], b = (&u[4 + (i >> 2)].x)[i & 3];
        xr[(i >> 2) * 1024 + (i & 3) * 8] = __byte_perm(a, b, 0x5410); xr[(i >> 2) * 1024 + (i & 3) * 8 + 4] = __byte_perm(a, b, 0x7632);
      }
    }
    fence_proxy_global();
    __syncwarp();
    if (lane == 0) flag_add(fl);
    __syncwarp();
  }
}
}

__global__ void __cluster_dims__(2, 1, 1) __launch_bounds__(384, 1)
gemm_kernel(const __grid_constant__ gm::Maps M, const bf16* __restrict__ x, bf16* out) {
  using namespace gm;
  extern __shared__ __align__(1024) uint8_t smem[];
  const uint32_t sb = __shfl_sync(0xffffffffu, smem_u32(smem), 0);
  const int tid = threadIdx.x, wi = __shfl_sync(0xffffffffu, tid >> 5, 0);
  if (tid < 21) mbar_init(sb + BARS + tid * 8, tid == 14 || tid == 15 ? 4 : tid >= 6 && tid < 12 ? 2 : 1);
  fence_mbar_init();
  cluster_arrive(); cluster_wait();
  if (wi < 8) { reg_inc<208>(); consumer(sb, M, wi >> 2); cluster_arrive(); cluster_wait(); }
  else {
    reg_dec<88>();
    if (wi == 8) producer(sb, M);
    else if (wi == 11 && cluster_rank() == 0) scheduler(sb);
    else {
      norm_helper(x, out);
      asm volatile("griddepcontrol.wait;" ::: "memory");
    }
    __syncwarp();
    cluster_arrive(); cluster_wait();
  }
}

typedef CUresult (*PFN_encodeTiled)(CUtensorMap*, CUtensorMapDataType, cuuint32_t, void*, const cuuint64_t*, const cuuint64_t*,
                                    const cuuint32_t*, const cuuint32_t*, CUtensorMapInterleave, CUtensorMapSwizzle,
                                    CUtensorMapL2promotion, CUtensorMapFloatOOBfill);
static PFN_encodeTiled g_encode = nullptr;
static CUtensorMap make_map(const void* ptr, uint64_t rows, uint64_t cols, uint32_t box_rows, CUtensorMapL2promotion pr = CU_TENSOR_MAP_L2_PROMOTION_L2_256B) {
  CUtensorMap m;
  cuuint64_t dims[2] = {cols, rows}, strides[1] = {cols * 2};
  cuuint32_t box[2] = {64, box_rows}, es[2] = {1, 1};
  g_encode(&m, CU_TENSOR_MAP_DATA_TYPE_BFLOAT16, 2, (void*)ptr, dims, strides, box, es, CU_TENSOR_MAP_INTERLEAVE_NONE,
           CU_TENSOR_MAP_SWIZZLE_128B, pr, CU_TENSOR_MAP_FLOAT_OOB_FILL_NONE);
  return m;
}

static CUtensorMap make_map3(const void* ptr, uint64_t d0, uint64_t d1, uint64_t d2, uint64_t stride2) {
  CUtensorMap m;
  cuuint64_t dims[3] = {d0, d1, d2}, strides[2] = {DM * 2, stride2};
  cuuint32_t box[3] = {64, 32, 2}, es[3] = {1, 1, 1};
  g_encode(&m, CU_TENSOR_MAP_DATA_TYPE_BFLOAT16, 3, (void*)ptr, dims, strides, box, es, CU_TENSOR_MAP_INTERLEAVE_NONE,
           CU_TENSOR_MAP_SWIZZLE_128B, CU_TENSOR_MAP_L2_PROMOTION_L2_256B, CU_TENSOR_MAP_FLOAT_OOB_FILL_NONE);
  return m;
}

extern "C" void kernel_launch(void* const* d_in, const int* in_sizes, int n_in, void* d_out, int out_size) {
  const bf16* x = (const bf16*)d_in[0];
  const bf16* mem0 = (const bf16*)d_in[1];
  if (!g_encode) {
    void* p = nullptr; cudaDriverEntryPointQueryResult q;
    cudaGetDriverEntryPoint("cuTensorMapEncodeTiled", &p, cudaEnableDefault, &q);
    g_encode = (PFN_encodeTiled)p;
    cudaFuncSetAttribute(gemm_kernel, cudaFuncAttributeMaxDynamicSharedMemorySize, gm::SMEM);
    cudaFuncSetAttribute(rec_kernel, cudaFuncAttributeMaxDynamicSharedMemorySize, rec::SMEM);
  }
  bf16 *xn, *ot, *hh;
  cudaGetSymbolAddress((void**)&xn, g_xn); cudaGetSymbolAddress((void**)&ot, g_ot); cudaGetSymbolAddress((void**)&hh, g_h);
  rec::Maps R;
  for (int i = 0; i < 3; i++) R.w[i] = make_map(d_in[2 + i], DM, NH * DH, 16, CU_TENSOR_MAP_L2_PROMOTION_NONE);
  R.wo = make_map(d_in[5], NH * DH, DM, 128);
  R.xd = make_map3(xn, DM, SEQ - LAG * 32, 2, (uint64_t)LAG * 32 * DM * 2); R.xs = make_map3(xn, 64, SEQ, DM / 64, 128);
  gm::Maps G;
  G.ot = make_map(ot, NH * DH + O_LAYER / SEQ, SEQ, 64); G.wo = make_map(d_in[5], NH * DH, DM, 64); G.xn = make_map(xn, SEQ, DM, 64);
  G.wg = make_map(d_in[8], DM, DF, 64); G.wu = make_map(d_in[9], DM, DF, 64); G.hl = make_map(hh, SEQ, DF, 64); G.hs = make_map(hh, SEQ, DF, 128);
  G.wd = make_map(d_in[10], DF, DM, 64); G.out = make_map(d_out, SEQ, DM, 128);
  cudaLaunchConfig_t cfg = {};
  cudaLaunchAttribute at[1];
  cfg.attrs = at; cfg.numAttrs = 1;
  cfg.gridDim = dim3(3 * NH); cfg.blockDim = dim3(384); cfg.dynamicSmemBytes = rec::SMEM; cfg.stream = cudaStreamPerThread;
  at[0].id = cudaLaunchAttributeClusterDimension; at[0].val.clusterDim.y = at[0].val.clusterDim.z = 1;
  static int csize = 0;
  if (!csize) {
    int n = 0;
    at[0].val.clusterDim.x = 6;
    csize = cudaOccupancyMaxActiveClusters(&n, rec_kernel, &cfg) == cudaSuccess && n >= NH / 2 ? 6 : 3;
  }
  at[0].val.clusterDim.x = csize;
  cudaLaunchKernelEx(&cfg, rec_kernel, R, mem0);
  cfg.gridDim = dim3(132); cfg.blockDim = dim3(384); cfg.dynamicSmemBytes = gm::SMEM; cfg.stream = cudaStreamPerThread;
  at[0].id = cudaLaunchAttributeProgrammaticStreamSerialization; at[0].val.programmaticStreamSerializationAllowed = 1;
  cudaLaunchKernelEx(&cfg, gemm_kernel, G, x, (bf16*)d_out);
}
```

```cpp
#include <cuda_runtime.h>
#include <cuda_bf16.h>
#include <cuda.h>
#include <stdint.h>

#define DEVI __device__ __forceinline__
typedef __nv_bfloat16 bf16;

constexpr int SEQ = 2048, DM = 1024, NH = 32, DH = 128, DF = 3584, NSEG = 64;
#define LAG 20
constexpr int NSTEP = NSEG + LAG;

#define TSD 1800
constexpr size_t O_LAYER = 0;
__device__ __align__(1024) bf16 g_xn[SEQ * DM];
__device__ __align__(1024) bf16 g_ot[SEQ * NH * DH + O_LAYER];
__device__ __align__(1024) bf16 g_h[SEQ * DF];
__device__ __align__(1024) uint32_t g_xr[NSEG][DM * 4];
__device__ __align__(1024) uint2 g_h1[4][256 * 256];
__device__ __align__(1024) uint4 g_h2[4][2048];
__device__ __align__(128) uint32_t g_ts[2][32];
enum { E_D1 = 0, E_G1 = 32, E_O1 = 48, E_O2 = 64, E_G2 = 80, E_D2 = 96,
       E_LI = 128, E_LX2 = 144, E_LX1A = 160, E_LX1B = 176, NEV = 256 };
__device__ __align__(128) int g_dep[NEV];
__device__ __align__(128) int g_claim[NEV];
__device__ __align__(128) int g_xa[2][32];

#define TUNE_DEFAULTS 1650, 2450, 6, 100, 100, 8, 14, 100, 1550, 2280, 100, 110, 1550, 2320, 200, 0
constexpr int c_D[16] = {TUNE_DEFAULTS};
template<int I> struct TPV { static constexpr int v = c_D[I]; };
#define TP(i) TPV<i>::v

DEVI uint32_t smem_u32(const void* p) { return (uint32_t)__cvta_generic_to_shared(p); }
DEVI void mbar_init(uint32_t bar, uint32_t cnt) { asm volatile("mbarrier.init.shared::cta.b64 [%0], %1;" :: "r"(bar), "r"(cnt) : "memory"); }
DEVI void mbar_arrive(uint32_t bar) { asm volatile("mbarrier.arrive.shared::cta.b64 _, [%0];" :: "r"(bar) : "memory"); }
DEVI bool mbar_try(uint32_t bar, uint32_t parity) {
  uint32_t p;
  asm volatile("{.reg .pred p; mbarrier.try_wait.parity.shared::cta.b64 p, [%1], %2; selp.u32 %0, 1, 0, p;}" : "=r"(p) : "r"(bar), "r"(parity) : "memory");
  return p;
}
DEVI bool mbar_test(uint32_t bar, uint32_t parity) {
  uint32_t p;
  asm volatile("{.reg .pred p; mbarrier.test_wait.parity.shared::cta.b64 p, [%1], %2; selp.u32 %0, 1, 0, p;}" : "=r"(p) : "r"(bar), "r"(parity) : "memory");
  return p;
}
constexpr int SPIN_BUDGET = 1 << 18;
DEVI void mbar_wait(uint32_t bar, uint32_t parity, int& budget) {
  while (!mbar_try(bar, parity)) { if (--budget < 0) break; }
}
DEVI bool mbar_try_cluster(uint32_t bar, uint32_t parity) {
  uint32_t p;
  asm volatile("{.reg .pred p; mbarrier.try_wait.parity.acquire.cluster.shared::cta.b64 p, [%1], %2; selp.u32 %0, 1, 0, p;}" : "=r"(p) : "r"(bar), "r"(parity) : "memory");
  return p;
}
DEVI void mbar_wait_cluster(uint32_t bar, uint32_t parity, int& budget) {
  while (!mbar_try_cluster(bar, parity)) { if (--budget < 0) break; }
}
DEVI uint32_t mapa(uint32_t addr, uint32_t rank) { uint32_t r; asm("mapa.shared::cluster.u32 %0, %1, %2;" : "=r"(r) : "r"(addr), "r"(rank)); return r; }
DEVI void cluster_arrive() { asm volatile("barrier.cluster.arrive.release.aligned;" ::: "memory"); }
DEVI void cluster_wait() { asm volatile("barrier.cluster.wait.acquire.aligned;" ::: "memory"); }
DEVI void fence_mbar_init() { asm volatile("fence.mbarrier_init.release.cluster;" ::: "memory"); }
DEVI void fence_proxy_async() { asm volatile("fence.proxy.async.shared::cta;" ::: "memory"); }
DEVI void fence_proxy_global() { asm volatile("fence.proxy.async.global;" ::: "memory"); }
#define ELECT "{.reg .pred p; elect.sync _|p, 0xffffffff;\n @p "
DEVI void e_expect_tx(uint32_t bar, uint32_t bytes) { asm volatile(ELECT "mbarrier.arrive.expect_tx.shared::cta.b64 _, [%0], %1;}" :: "r"(bar), "r"(bytes) : "memory"); }
DEVI void e_complete_tx(uint32_t bar, uint32_t bytes) { asm volatile("fence.acq_rel.cta;\n" ELECT "mbarrier.complete_tx.relaxed.cta.shared::cta.b64 [%0], %1;}" :: "r"(bar), "r"(bytes) : "memory"); }
DEVI void e_arrive(uint32_t bar) { asm volatile(ELECT "mbarrier.arrive.shared::cta.b64 _, [%0];}" :: "r"(bar) : "memory"); }
DEVI void e_tma_2d(uint32_t dst, const CUtensorMap* m, int c0, int c1, uint32_t bar) {
  asm volatile(ELECT "cp.async.bulk.tensor.2d.shared::cluster.global.mbarrier::complete_tx::bytes [%0], [%1, {%3, %4}], [%2];}"
    :: "r"(dst), "l"(m), "r"(bar), "r"(c0), "r"(c1) : "memory");
}
DEVI void e_prefetch_3d(const CUtensorMap* m, int c0, int c1, int c2) {
  asm volatile(ELECT "cp.async.bulk.prefetch.tensor.3d.L2.global [%0, {%1, %2, %3}];}" :: "l"(m), "r"(c0), "r"(c1), "r"(c2) : "memory");
}
DEVI void e_bulk_g2s(uint32_t dst, const void* src, uint32_t bytes, uint32_t bar) {
  asm volatile(ELECT "cp.async.bulk.shared::cluster.global.mbarrier::complete_tx::bytes [%0], [%1], %2, [%3];}" :: "r"(dst), "l"(src), "r"(bytes), "r"(bar) : "memory");
}
DEVI void e_tma_3d(uint32_t dst, const CUtensorMap* m, int c0, int c1, int c2, uint32_t bar) {
  asm volatile(ELECT "cp.async.bulk.tensor.3d.shared::cluster.global.mbarrier::complete_tx::bytes [%0], [%1, {%3, %4, %5}], [%2];}"
    :: "r"(dst), "l"(m), "r"(bar), "r"(c0), "r"(c1), "r"(c2) : "memory");
}
DEVI void e_tma_3d_mc(uint32_t dst, const CUtensorMap* m, int c0, int c1, int c2, uint32_t bar, int last) {
  asm volatile(ELECT "cp.async.bulk.tensor.3d.shared::cluster.global.mbarrier::complete_tx::bytes.multicast::cluster [%0], [%1, {%3, %4, %5}], [%2], %6;}"
    :: "r"(dst), "l"(m), "r"(bar), "r"(c0), "r"(c1), "r"(c2), "h"((uint16_t)((2 << last) - 1)) : "memory");
}
DEVI void e_tma_2d_mc(uint32_t dst, const CUtensorMap* m, int c0, int c1, uint32_t bar) {
  asm volatile(ELECT "cp.async.bulk.tensor.2d.shared::cluster.global.mbarrier::complete_tx::bytes.multicast::cluster [%0], [%1, {%3, %4}], [%2], %5;}"
    :: "r"(dst), "l"(m), "r"(bar), "r"(c0), "r"(c1), "h"((uint16_t)3) : "memory");
}
DEVI void p_arrive_at(uint32_t bar, uint32_t rank, bool c) {
  asm volatile("{.reg .pred p; .reg .b32 a; setp.ne.u32 p, %2, 0; mapa.shared::cluster.u32 a, %0, %1; @p mbarrier.arrive.shared::cluster.b64 _, [a];}"
    :: "r"(bar), "r"(rank), "r"((uint32_t)c) : "memory");
}
DEVI void p_expect_tx(uint32_t bar, uint32_t bytes, bool c) {
  asm volatile("{.reg .pred p; setp.ne.u32 p, %2, 0; @p mbarrier.arrive.expect_tx.shared::cta.b64 _, [%0], %1;}" :: "r"(bar), "r"(bytes), "r"((uint32_t)c) : "memory");
}
DEVI void p_arrive(uint32_t bar, bool c) { asm volatile("{.reg .pred p; setp.ne.u32 p, %1, 0; @p mbarrier.arrive.shared::cta.b64 _, [%0];}" :: "r"(bar), "r"((uint32_t)c) : "memory"); }
DEVI void tma_store_2d(const CUtensorMap* m, uint32_t src, int c0, int c1) {
  asm volatile("cp.async.bulk.tensor.2d.global.shared::cta.bulk_group [%0, {%2, %3}], [%1];" :: "l"(m), "r"(src), "r"(c0), "r"(c1) : "memory");
}
DEVI void tma_radd_2d(const CUtensorMap* m, uint32_t src, int c0, int c1) {
  asm volatile("cp.reduce.async.bulk.tensor.2d.global.shared::cta.add.bulk_group [%0, {%2, %3}], [%1];" :: "l"(m), "r"(src), "r"(c0), "r"(c1) : "memory");
}
DEVI void bulk_commit() { asm volatile("cp.async.bulk.commit_group;" ::: "memory"); }
template<int N> DEVI void bulk_wait_read() { asm volatile("cp.async.bulk.wait_group.read %0;" :: "n"(N) : "memory"); }
template<int N> DEVI void bulk_wait() { asm volatile("cp.async.bulk.wait_group %0;" :: "n"(N) : "memory"); }
template<int ID, int N> DEVI void nbar_sync() { asm volatile("bar.sync %0, %1;" :: "n"(ID), "n"(N) : "memory"); }
template<int ID, int N> DEVI void nbar_arrive() { asm volatile("bar.arrive %0, %1;" :: "n"(ID), "n"(N) : "memory"); }
DEVI void nbar_sync_r(int id, int n) { asm volatile("bar.sync %0, %1;" :: "r"(id), "r"(n) : "memory"); }
template<int R> DEVI void reg_inc() { asm volatile("setmaxnreg.inc.sync.aligned.u32 %0;" :: "n"(R)); }
template<int R> DEVI void reg_dec() { asm volatile("setmaxnreg.dec.sync.aligned.u32 %0;" :: "n"(R)); }
DEVI void wg_fence() { asm volatile("wgmma.fence.sync.aligned;" ::: "memory"); }
DEVI void wg_commit() { asm volatile("wgmma.commit_group.sync.aligned;" ::: "memory"); }
template<int N> DEVI void wg_wait() { asm volatile("wgmma.wait_group.sync.aligned %0;" :: "n"(N) : "memory"); }
DEVI uint64_t mkdesc(uint32_t addr, uint32_t lbo, uint32_t sbo, uint32_t sw = 1) {
  return ((uint64_t)((addr & 0x3FFFF) >> 4)) | ((uint64_t)(lbo >> 4) << 16) | ((uint64_t)(sbo >> 4) << 32) | ((uint64_t)sw << 62);
}
constexpr uint32_t SMEM_BASE = 1024;
__host__ __device__ constexpr long long CD(uint32_t off, uint32_t lbo, uint32_t sbo, uint32_t sw) {
  return (long long)(((uint64_t)((SMEM_BASE + off) >> 4)) | ((uint64_t)(lbo >> 4) << 16) | ((uint64_t)(sbo >> 4) << 32) | ((uint64_t)sw << 62));
}
DEVI uint32_t pack_bf16(float lo, float hi) { uint32_t r; asm("cvt.rn.bf16x2.f32 %0, %1, %2;" : "=r"(r) : "f"(hi), "f"(lo)); return r; }
DEVI float bf_lo(uint32_t v) { return __uint_as_float(v << 16); }
DEVI float bf_hi(uint32_t v) { return __uint_as_float(v & 0xffff0000u); }
DEVI void ldsm4t(uint32_t addr, uint32_t& r0, uint32_t& r1, uint32_t& r2, uint32_t& r3) {
  asm volatile("ldmatrix.sync.aligned.m8n8.x4.trans.shared.b16 {%0,%1,%2,%3}, [%4];" : "=r"(r0), "=r"(r1), "=r"(r2), "=r"(r3) : "r"(addr) : "memory");
}
DEVI void stsm4(uint32_t addr, uint32_t r0, uint32_t r1, uint32_t r2, uint32_t r3) {
  asm volatile("stmatrix.sync.aligned.m8n8.x4.shared.b16 [%0], {%1,%2,%3,%4};" :: "r"(addr), "r"(r0), "r"(r1), "r"(r2), "r"(r3) : "memory");
}
DEVI uint2 lds64v(uint32_t a) { uint2 v; asm volatile("ld.volatile.shared.v2.u32 {%0,%1}, [%2];" : "=r"(v.x), "=r"(v.y) : "r"(a) : "memory"); return v; }
DEVI uint32_t lds32v(uint32_t a) { uint32_t v; asm volatile("ld.volatile.shared.u32 %0, [%1];" : "=r"(v) : "r"(a) : "memory"); return v; }
DEVI uint4 lds128v(uint32_t a) { uint4 v; asm volatile("ld.volatile.shared.v4.u32 {%0,%1,%2,%3}, [%4];" : "=r"(v.x), "=r"(v.y), "=r"(v.z), "=r"(v.w) : "r"(a) : "memory"); return v; }
DEVI void sts32(uint32_t a, uint32_t x) { asm volatile("st.shared.u32 [%0], %1;" :: "r"(a), "r"(x) : "memory"); }
DEVI int lane_id() { int r; asm volatile("mov.u32 %0, %%laneid;" : "=r"(r)); return r; }
DEVI void sts64(uint32_t a, uint32_t x, uint32_t y) { asm volatile("st.shared.v2.u32 [%0], {%1,%2};" :: "r"(a), "r"(x), "r"(y) : "memory"); }
DEVI void st_async128(uint32_t a, uint32_t x, uint32_t y, uint32_t z, uint32_t w, uint32_t bar) {
  asm volatile("st.async.weak.shared::cluster.mbarrier::complete_tx::bytes.v4.b32 [%0], {%1,%2,%3,%4}, [%5];" :: "r"(a), "r"(x), "r"(y), "r"(z), "r"(w), "r"(bar) : "memory");
}
DEVI void st_async32(uint32_t a, uint32_t x, uint32_t bar) {
  asm volatile("st.async.weak.shared::cluster.mbarrier::complete_tx::bytes.b32 [%0], %1, [%2];" :: "r"(a), "r"(x), "r"(bar) : "memory");
}
DEVI uint4 ldg_rlx128(const void* p) {
  uint4 v;
  asm volatile("ld.relaxed.gpu.global.v4.b32 {%0,%1,%2,%3}, [%4];" : "=r"(v.x), "=r"(v.y), "=r"(v.z), "=r"(v.w) : "l"(p) : "memory");
  return v;
}
DEVI int ldg_rlx32(const void* p) { int v; asm volatile("ld.relaxed.gpu.global.b32 %0, [%1];" : "=r"(v) : "l"(p) : "memory"); return v; }
DEVI int ldg_acq32(const void* p) { int v; asm volatile("ld.acquire.gpu.global.b32 %0, [%1];" : "=r"(v) : "l"(p) : "memory"); return v; }
DEVI void stg128(void* p, uint32_t x, uint32_t y, uint32_t z, uint32_t w) {
  asm volatile("st.global.v4.b32 [%0], {%1,%2,%3,%4};" :: "l"(p), "r"(x), "r"(y), "r"(z), "r"(w) : "memory");
}
DEVI uint2 ldg_rlx64(const void* p) { uint2 v; asm volatile("{.reg .b64 a; ld.relaxed.gpu.global.b64 a, [%2]; mov.b64 {%0,%1}, a;}" : "=r"(v.x), "=r"(v.y) : "l"(p) : "memory"); return v; }
DEVI void stg_rlx64(void* p, uint32_t x, uint32_t y) { asm volatile("{.reg .b64 a; mov.b64 a, {%1,%2}; st.relaxed.gpu.global.b64 [%0], a;}" :: "l"(p), "r"(x), "r"(y) : "memory"); }
DEVI void stg_rlx32(void* p, uint32_t x) { asm volatile("st.relaxed.gpu.global.b32 [%0], %1;" :: "l"(p), "r"(x) : "memory"); }
DEVI void flag_add(int* p) { asm volatile("fence.proxy.async.global; red.release.gpu.global.add.s32 [%0], 1;" :: "l"(p) : "memory"); }
DEVI void e_stg_rlx32(void* p, uint32_t x) { asm volatile(ELECT "st.relaxed.gpu.global.b32 [%0], %1;}" :: "l"(p), "r"(x) : "memory"); }
DEVI void e_flag_add(int* p) { asm volatile("fence.proxy.async.global;\n" ELECT "red.release.gpu.global.add.s32 [%0], 1;}" :: "l"(p) : "memory"); }
DEVI int cluster_rank() { int r; asm volatile("mov.u32 %0, %%cluster_ctarank;" : "=r"(r)); return __shfl_sync(0xffffffffu, r, 0); }
DEVI int cluster_last() { int r; asm volatile("mov.u32 %0, %%cluster_nctarank;" : "=r"(r)); return __shfl_sync(0xffffffffu, r, 0) - 1; }
DEVI int cta_id() { int r; asm volatile("mov.u32 %0, %%ctaid.x;" : "=r"(r)); return __shfl_sync(0xffffffffu, r, 0); }
DEVI uint32_t clock32() { uint32_t c; asm volatile("mov.u32 %0, %%clock;" : "=r"(c)); return c; }
DEVI uint32_t gtime() { uint32_t c; asm volatile("mov.u32 %0, %%globaltimer_lo;" : "=r"(c)); return c; }
DEVI void wait_time(uint32_t t) { while (__any_sync(0xffffffffu, t - gtime() - 1 < 4000u)) {} }
DEVI void spin_until(uint32_t t0, int d) {
  int r;
  while (__any_sync(0xffffffffu, (r = d - (int)(clock32() - t0)) > 0)) {
    if (r > 300) __nanosleep(r >> 2);
  }
}
DEVI void pin2(const void* a, const void* b) { asm volatile("{.reg .pred p; setp.eq.u64 p, %0, %1; @p st.volatile.global.u64 [%0], %1;}" :: "l"(a), "l"(b) : "memory"); }
DEVI void pin2(uint32_t a, uint32_t b) { asm volatile("{.reg .pred p; setp.eq.u32 p, %0, %1; @p st.volatile.shared.u32 [%0], %1;}" :: "r"(a), "r"(b) : "memory"); }
DEVI void p_stg_rlx64(void* p, uint32_t x, uint32_t y, bool c) {
  asm volatile("{.reg .pred p; .reg .b64 a; setp.ne.u32 p, %3, 0; mov.b64 a, {%1,%2}; @p st.relaxed.gpu.global.b64 [%0], a;}" :: "l"(p), "r"(x), "r"(y), "r"((uint32_t)c) : "memory");
}
DEVI void pin2(uint64_t a, uint64_t b) { pin2((const void*)a, (const void*)b); }
DEVI uint64_t pair(uint32_t a, uint32_t bar) { return a | (uint64_t)bar << 32; }
DEVI void st_async32(uint64_t q, uint32_t x) { st_async32((uint32_t)q, x, (uint32_t)(q >> 32)); }
DEVI void st_async128(uint64_t q, uint4 v) { st_async128((uint32_t)q, v.x, v.y, v.z, v.w, (uint32_t)(q >> 32)); }
DEVI float ex2(float x) { float r; asm("ex2.approx.ftz.f32 %0, %1;" : "=f"(r) : "f"(x)); return r; }
DEVI float rcp(float x) { float r; asm("rcp.approx.ftz.f32 %0, %1;" : "=f"(r) : "f"(x)); return r; }
DEVI uint32_t xor_or(uint32_t a, uint32_t t, uint32_t acc) { uint32_t r; asm("lop3.b32 %0, %1, %2, %3, 0xbe;" : "=r"(r) : "r"(a), "r"(t), "r"(acc)); return r; }
DEVI void stsm2(uint32_t addr, uint32_t r0, uint32_t r1) {
  asm volatile("stmatrix.sync.aligned.m8n8.x2.shared.b16 [%0], {%1,%2};" :: "r"(addr), "r"(r0), "r"(r1) : "memory");
}
DEVI uint32_t settag(uint32_t v, uint32_t tag) { return (v & ~1u) | tag; }

#define A4(c, o)  c(d[o+0]), c(d[o+1]), c(d[o+2]), c(d[o+3])
#define A8(c, o)  A4(c, o), A4(c, o+4)
#define A16(c, o) A8(c, o), A8(c, o+8)
#define A12(c, o) A8(c, o), A4(c, o+8)
#define A28(c, o) A16(c, o), A12(c, o+16)
#define RL12 "{%0,%1,%2,%3,%4,%5,%6,%7,%8,%9,%10,%11}"
#define RL28 "{%0,%1,%2,%3,%4,%5,%6,%7,%8,%9,%10,%11,%12,%13,%14,%15,%16,%17,%18,%19,%20,%21,%22,%23,%24,%25,%26,%27}"
#define A20(c, o) A16(c, o), A4(c, o+16)
#define A32(c, o) A16(c, o), A16(c, o+16)
#define RL8  "{%0,%1,%2,%3,%4,%5,%6,%7}"
#define RL16 "{%0,%1,%2,%3,%4,%5,%6,%7,%8,%9,%10,%11,%12,%13,%14,%15}"
#define RL20 "{%0,%1,%2,%3,%4,%5,%6,%7,%8,%9,%10,%11,%12,%13,%14,%15,%16,%17,%18,%19}"
#define RL32 "{%0,%1,%2,%3,%4,%5,%6,%7,%8,%9,%10,%11,%12,%13,%14,%15,%16,%17,%18,%19,%20,%21,%22,%23,%24,%25,%26,%27,%28,%29,%30,%31}"
#define RL64 "{%0,%1,%2,%3,%4,%5,%6,%7,%8,%9,%10,%11,%12,%13,%14,%15,%16,%17,%18,%19,%20,%21,%22,%23,%24,%25,%26,%27,%28,%29,%30,%31," \
  "%32,%33,%34,%35,%36,%37,%38,%39,%40,%41,%42,%43,%44,%45,%46,%47,%48,%49,%50,%51,%52,%53,%54,%55,%56,%57,%58,%59,%60,%61,%62,%63}"
#define WG_OP(shape) "wgmma.mma_async.sync.aligned." shape "k16.f32.bf16.bf16 "
#define DEF_WGMMA(N, RL, AL, i0, i1, i2, i3, i4, i5, i6)                                                                         \
  template<int SC, int TB, long long CB> DEVI void rs##N(float* d, const uint32_t* a) {                                          \
    if (SC) asm volatile("{.reg .b64 tb; mov.b64 tb, %" #i4 ";\n" WG_OP("m64n" #N) RL ", {%" #i0 ",%" #i1 ",%" #i2 ",%" #i3 "}, tb, 1, 1, 1, %" #i5 ";}" \
      : AL("+f", 0) : "r"(a[0]), "r"(a[1]), "r"(a[2]), "r"(a[3]), "n"(CB), "n"(TB));                                             \
    else asm volatile("{.reg .b64 tb; mov.b64 tb, %" #i4 ";\n" WG_OP("m64n" #N) RL ", {%" #i0 ",%" #i1 ",%" #i2 ",%" #i3 "}, tb, 0, 1, 1, %" #i5 ";}" \
      : AL("=f", 0) : "r"(a[0]), "r"(a[1]), "r"(a[2]), "r"(a[3]), "n"(CB), "n"(TB));                                             \
  }                                                                                                                              \
  template<int SC, int TA, int TB, long long CA, long long CB> DEVI void ss##N(float* d, uint32_t a) {                           \
    if (SC) asm volatile("{.reg .b64 ta, tb; .reg .b32 lo, hi; add.u32 lo, %" #i0 ", %" #i1 "; mov.b32 hi, %" #i2 "; mov.b64 ta, {lo, hi}; mov.b64 tb, %" #i3 ";\n" \
      WG_OP("m64n" #N) RL ", ta, tb, 1, 1, 1, %" #i4 ", %" #i5 ";}"                                                              \
      : AL("+f", 0) : "r"(a), "n"((int)CA), "n"((int)(CA >> 32)), "n"(CB), "n"(TA), "n"(TB));                                    \
    else asm volatile("{.reg .b64 ta, tb; .reg .b32 lo, hi; add.u32 lo, %" #i0 ", %" #i1 "; mov.b32 hi, %" #i2 "; mov.b64 ta, {lo, hi}; mov.b64 tb, %" #i3 ";\n" \
      WG_OP("m64n" #N) RL ", ta, tb, 0, 1, 1, %" #i4 ", %" #i5 ";}"                                                              \
      : AL("=f", 0) : "r"(a), "n"((int)CA), "n"((int)(CA >> 32)), "n"(CB), "n"(TA), "n"(TB));                                    \
  }
DEF_WGMMA(8, "{%0,%1,%2,%3}", A4, 4, 5, 6, 7, 8, 9, 10)
DEF_WGMMA(16, RL8, A8, 8, 9, 10, 11, 12, 13, 14)
DEF_WGMMA(32, RL16, A16, 16, 17, 18, 19, 20, 21, 22)
DEF_WGMMA(40, RL20, A20, 20, 21, 22, 23, 24, 25, 26)
DEF_WGMMA(24, RL12, A12, 12, 13, 14, 15, 16, 17, 18)
DEF_WGMMA(56, RL28, A28, 28, 29, 30, 31, 32, 33, 34)
template<int TA> DEVI void wgmma_n128(float* d, uint64_t a, uint64_t b, int scale_d) {
  asm volatile("{.reg .pred p; setp.ne.b32 p, %66, 0;\n" WG_OP("m64n128") RL64 ", %64, %65, p, 1, 1, %67, 1;}"
    : A32("+f", 0), A32("+f", 32) : "l"(a), "l"(b), "r"(scale_d), "n"(TA));
}

namespace rec {
constexpr int KR = 43;
constexpr uint32_t WSZ = (64 - KR) * 2048, STG = KR * 2048;
constexpr uint32_t WS = 0;
constexpr uint32_t RING = 2 * WSZ;
constexpr uint32_t OB = RING + 3 * 8192;
constexpr uint32_t PB = OB + 4096;
constexpr uint32_t WO = RING + 32768;
constexpr uint32_t ATT = WO + 5 * 16384;
constexpr uint32_t AK = ATT + 10240, AV = ATT + 20480;
constexpr uint32_t PAD = ATT + 30720;
constexpr uint32_t BARS = PAD + 128;
constexpr uint32_t B_XE = BARS  , B_FA = BARS + 64  , B_FB = BARS + 88, B_FO = BARS + 96;
constexpr uint32_t B_ME = BARS + 104  , B_WE = BARS + 136, B_PD = BARS + 144;
constexpr uint32_t B_XF = BARS + 152  , B_MF = BARS + 216  , B_CP = BARS + 248  , B_WT = BARS + 280  ;
constexpr uint32_t B_AB = BARS + 296, B_OB = BARS + 304, B_ST = BARS + 312  , B_WS = BARS + 328, B_WO = BARS + 336, B_AT = BARS + 352, B_AV = BARS + 360;
constexpr int NBAR = 46;
constexpr uint32_t M0 = BARS + 384;
constexpr uint32_t SMEM = 232448;
constexpr int NB_P = 1, NB_ST = 2, NB_O = 3, NB_W0 = 4, NB_W1 = 5;
__host__ __device__ constexpr int wo_tile(int rank, int g, int i) { return i < 2 ? i * 6 + (rank == 2 ? g : 4 - 2 * g + rank) : 13 + rank - g; }
constexpr long long D_W = CD(WS, 16, 1024, 1), D_X = CD(0, 16, 1024, 1), D_O = CD(OB, 128, 256, 0);
constexpr long long D_WO = CD(WO, 16, 1024, 1), D_QM = CD(ATT, 640, 0, 0), D_QT = CD(ATT + 128, 640, 64, 0), D_K = CD(AK, 640, 128, 0);
constexpr long long D_V = CD(AV, 128, 640, 0), D_P = CD(PB, 128, 768, 0);
struct Maps { CUtensorMap w[3], wo, xd, xs; };
__host__ __device__ constexpr uint32_t mslot(int c) { return (c ^ (c >> 1)) * 12288; }
__host__ __device__ constexpr uint32_t xslot(int s) { return s < 3 ? RING + s * 8192 : s < 5 ? WO + (s - 3) * 8192 : s < 7 ? WO + (s + 1) * 8192 : OB; }
__host__ __device__ constexpr bool k_smem(int k) { return k % 3 == 2; }
__host__ __device__ constexpr int k_idx(int k) { return k % 3 == 2 ? k / 3 : k - k / 3; }
__host__ __device__ constexpr int k_of_reg(int i) { return i + (i >> 1); }
__host__ __device__ constexpr int k_of_smem(int i) { return 3 * i + 2; }

#define RPROF(i)
#define RPROF_STEP
#define CPROF(i, v)

template<bool DUAL, int K0, int K1> DEVI void seq_mem(float* d, const uint32_t* w, uint32_t dw) {
  if constexpr (K0 < K1) {
    constexpr long long B = CD(RING, 128, DUAL ? 4096 : 8192, 0) + mslot(K0 >> 4) / 16 + (K0 & 15) * 16;
    if constexpr (DUAL) {
      if constexpr (!k_smem(K0)) rs24<K0 != 0, 1, B>(d, w + 4 * k_idx(K0)); else ss24<1, 1, 1, D_W + k_idx(K0) * 128, B>(d, dw);
    } else {
      if constexpr (!k_smem(K0)) rs16<K0 != 0, 1, B>(d, w + 4 * k_idx(K0)); else ss16<1, 1, 1, D_W + k_idx(K0) * 128, B>(d, dw);
    }
    seq_mem<DUAL, K0 + 1, K1>(d, w, dw);
  }
}
template<int N, int K0, int K1> DEVI void seq_tok(float* d, const uint32_t* w, uint32_t dw) {
  if constexpr (K0 < K1) {
    constexpr bool DUAL = N > 32;
    constexpr long long B = D_X + (DUAL ? xslot((K0 >> 2) & 7) / 16 : xslot(K0 >> 3) / 16 + ((K0 >> 2) & 1) * 256) + (K0 & 3) * 2;
    if constexpr (DUAL) {
      if constexpr (!k_smem(K0)) rs56<K0 != 0, 0, B>(d, w + 4 * k_idx(K0)); else ss56<1, 1, 0, D_W + k_idx(K0) * 128, B>(d, dw);
    } else if constexpr (N == 24) {
      if constexpr (!k_smem(K0)) rs24<K0 != 0, 0, B>(d, w + 4 * k_idx(K0)); else ss24<1, 1, 0, D_W + k_idx(K0) * 128, B>(d, dw);
    } else {
      if constexpr (!k_smem(K0)) rs32<K0 != 0, 0, B>(d, w + 4 * k_idx(K0)); else ss32<1, 1, 0, D_W + k_idx(K0) * 128, B>(d, dw);
    }
    seq_tok<N, K0 + 1, K1>(d, w, dw);
  }
}
template<int T, int K0> DEVI void seq_wo(float* d, uint32_t dw) {
  if constexpr (K0 < 8) { ss16<K0 != 0, 1, 1, D_WO + T * 1024 + K0 * 128, D_O + K0 * 32>(d, dw); seq_wo<T, K0 + 1>(d, dw); }
}
template<long long Q, int K0> DEVI void seq_s(float* d) {
  if constexpr (K0 < 8) { ss40<K0 != 0, 1, 1, Q + K0 * 80, D_K + K0 * 80>(d, 0); seq_s<Q, K0 + 1>(d); }
}
template<bool DUAL, int J> DEVI void load_x(uint32_t sb, const Maps* M, int t, int rb) {
  if (DUAL) e_tma_3d_mc(sb + xslot(J & 7), &M->xd, J * 64, (t - LAG) * 32, 0, sb + B_XF + (J & 7) * 8, rb);
  else e_tma_3d_mc(sb + xslot(J & 7), &M->xs, 0, (t < NSEG ? t : t - LAG) * 32, J * 2, sb + B_XF + (J & 7) * 8, rb);
}
DEVI void load_x_lent(uint32_t sb, const Maps* M, int t, int j) {
  const bool dual = t >= LAG && t < NSEG;
  const uint32_t dst = sb + (j == 3 ? xslot(3) : xslot(5));
#pragma unroll
  for (int i = 0; i < 2; i++)
    e_tma_3d(dst + i * 8192, dual ? &M->xd : &M->xs, dual ? (j + i) * 64 : 0, (t < LAG ? t : t - LAG) * 32, dual ? 0 : (j + i) * 2, sb + B_XF + (j + i) * 8);
}
struct True { static constexpr bool value = true; };
struct False { static constexpr bool value = false; };
struct Ctx { uint32_t sb; const Maps* M; int last; bool issuer; int wi; bool lead; uint32_t par; };
#define XD 1
template<bool DUAL, int J> DEVI void tok_release(const Ctx& c, int t, int& budget) {
  constexpr int NC = DUAL ? 16 : 8, S = J & 7;
  if constexpr (J + 8 < NC) {
    p_arrive_at(c.sb + B_XE + S * 8, c.last, c.lead);
    p_expect_tx(c.sb + B_XF + S * 8, 8192, c.lead && c.wi == 0);
  } else if constexpr (S == 1 || S == 2 || S == 4 || S == 7) p_arrive(c.sb + B_ME + (S >> 1) * 8, c.lead);
  if constexpr (J == 0) {
    if (c.issuer && c.wi == 6) { mbar_wait(c.sb + B_FO, t & 1, budget); load_x<DUAL, 7>(c.sb, c.M, t, c.last); }
  }
  if constexpr (J >= XD && J - XD + 8 < NC) {
    constexpr int I = J - XD;
    if (c.issuer && c.wi == (I & 1) * 4 + 1) { mbar_wait(c.sb + B_XE + I * 8, (t - LAG) & 1, budget); load_x<DUAL, I + 8>(c.sb, c.M, t, c.last); }
  }
}
template<int N, int J, class F, class G> DEVI bool tok_pass(float* d, const uint32_t* w, uint32_t dw, Ctx& c, int t, int& budget, F after0, G setup) {
  constexpr bool DUAL = N > 32;
  constexpr int NC = DUAL ? 16 : 8, KC = 64 / NC;
  if constexpr (J < NC) {
    if constexpr (J > 1) mbar_wait(c.sb + B_XF + (J & 7) * 8, c.par ^ (J >> 3), budget);
    wg_fence();
    seq_tok<N, J * KC, (J + 1) * KC>(d, w, dw);
    wg_commit();
    if constexpr (J == 1) after0();
    if constexpr (J >= NC - 5 && J < NC - 2) setup(J - (NC - 5));
    if constexpr (J > 0) { wg_wait<1>(); tok_release<DUAL, J - 1>(c, t, budget); }
    return tok_pass<N, J + 1>(d, w, dw, c, t, budget, after0, setup);
  } else {
    const bool ok = mbar_test(c.sb + B_MF, t & 1);
    wg_wait<0>();
    tok_release<DUAL, NC - 1>(c, t, budget);
    if (!DUAL) c.par ^= 1;
    return ok;
  }
}
template<int NB> DEVI void pack_tok(uint32_t* e, const float* d) {
#pragma unroll
  for (int i = 0; i < 8; i++) if ((i & 3) < NB) e[i] = pack_bf16(d[4 * (i & 3) + 2 * (i >> 2)], d[4 * (i & 3) + 2 * (i >> 2) + 1]);
}
DEVI void push_tok(const uint32_t* e, uint32_t sb, uint32_t o, int r, int rank) {
  const uint32_t b = mapa(sb, r);
  st_async128(b + o, e[0], e[1], e[2], e[3], b + (rank == 2 ? B_AV : B_AT));
}
DEVI uint32_t h1_tag(int seg) { return ((seg >> 1) & 1) ^ 1; }
DEVI uint4 pack_part(const float* c, int t) {
  return make_uint4(settag(pack_bf16(c[0], c[1]), h1_tag(t)), pack_bf16(c[2], c[3]), settag(pack_bf16(c[4], c[5]), h1_tag(t - LAG)), pack_bf16(c[6], c[7]));
}
DEVI void put_part(char* p1, char* p2, uint4 z, int t) { p_stg_rlx64(p1, z.x, z.y, t < NSEG); p_stg_rlx64(p2, z.z, z.w, t >= LAG); }

DEVI void rec_math(const uint32_t sb, const int wi, const Maps& M) {
  const int h = cta_id() / 3, rb = cluster_rank() >= 3 ? 3 : 0, rank = cluster_rank() - rb;
  const int warp = wi & 3, wg = wi >> 2;
  const bool lead = (threadIdx.x & 127) == 0;
  int budget = SPIN_BUDGET;
  uint32_t w[4 * KR];
  const int last = cluster_last();
  Ctx cx{sb, &M, last, rb + rank == last, wi, lead, 0};
  {
    const int lane = lane_id();
    const uint32_t a = sb + wg * STG + ((lane & 7) + (lane >> 4) * 8) * 128 + (((warp * 2 + ((lane >> 3) & 1)) ^ (lane & 7)) << 4);
    for (int i = 0; i < (wg == 1 || rank == 2 ? 12 : 8); i++)
      stg_rlx64((char*)g_h1[i & 3] + ((wo_tile(rank, wg, i >> 2) * 4 + warp) * 4 + (lane >> 3)) * 2048 + h * 64 + (lane & 7) * 8, 0, 0);
    mbar_wait(sb + B_ST + wg * 8, 0, budget);
#pragma unroll
    for (int k = 0; k < KR; k++) ldsm4t(a + k * 2048, w[4*k], w[4*k+1], w[4*k+2], w[4*k+3]);
    nbar_arrive<NB_ST, 384>();
    nbar_sync_r(NB_W0 + wg, 128);
    for (int i = 0; i < 5; i++) p_arrive_at(sb + B_FA + i * 8, i == 4 ? last : 0, lead);
    mbar_wait(sb + B_WS, 0, budget);
  }
  uint4 z = make_uint4(0, 0, 0, 0);
  char *z1 = nullptr, *z2 = nullptr;
  uint32_t rt0 = 0, rt1 = 0;
  mbar_wait(sb + B_XF, 0, budget); mbar_wait(sb + B_XF + 8, 0, budget);
#pragma unroll 1
  for (int t = 0;; t++) {
    const uint32_t dw = wg * (WSZ >> 4);
    uint32_t e[16];
    bool ok;
    auto finish = [&]() { put_part(z1, z2, z, t - 1); p_arrive_at(sb + B_FO, last, lead); };
    const int seg = t - rank * LAG;
    const bool att = rank < 2 && (unsigned)seg < (unsigned)NSEG;
    char* p1;
    uint32_t pw, oo;
    uint64_t u0, u1;
    int lane;
    auto setup = [&](int part) {
      if (part == 0) {
        lane = lane_id();
      } else if (part == 1) {
        char* const p = (char*)g_h1 + ((wo_tile(rank, wg, 0) * 4 + warp) * 4 + (lane >> 3)) * 2048 + h * 64 + (lane & 7) * 8;
        p1 = p + (t & 1) * sizeof(g_h1[0]);
        pin2(p1, nullptr);
      } else if (part == 2) {
        oo = OB + (lane >> 4) * 2048 + warp * 512 + rank * 256 + (lane & 15) * 16;
        pw = sb + PB + (wg ? lane * 4 : 768 + warp * 768 + lane * 16);
        pin2(pw, oo);
      } else {
        if (wg) {
          const uint32_t ra = mapa(sb, rb + ((warp & 1) ? 2 : (rank ^ 1) & 1)), rc = mapa(sb, rb + ((warp & 1) ? (rank ^ 1) & 1 : 2));
          u0 = pair(ra + oo, ra + B_OB); u1 = pair(rc + oo, rc + B_OB);
        } else {
          u0 = (uint64_t)((char*)(g_ot + rank * O_LAYER) + (size_t)(h * DH + warp * 16 + (lane >> 2)) * (SEQ * 2) + seg * 64 + (lane & 3) * 16);
          u1 = (uint32_t)((lane & 24) + ((lane >> 2) & 1) + 2 * warp - 8 * (lane & 3));
        }
        pin2(u0, u1);
      }
    };
    RPROF_STEP;
    auto mem_pass = [&](auto dual_c) {
      constexpr bool DUAL = decltype(dual_c)::value;
      float m[DUAL ? 12 : 8];
      RPROF(8 + wg * 12 - 32);
      if (!ok) mbar_wait(sb + B_MF, t & 1, budget);
      wg_fence(); seq_mem<DUAL, 0, 8>(m, w, dw); wg_commit();
      const uint32_t ao = ATT + rank * 10240 + wi * 1280, to = ao + 128 + (lane & 3) * 128 + (lane >> 2) * 16;
      const int la = DUAL ? rank == 0 : t >= NSEG;
      RPROF(1 + wg * 12);
      if (DUAL && rank == 0) {
#pragma unroll
        for (int i = 0; i < 8; i++) { const uint32_t x = e[i]; e[i] = e[8 + i]; e[8 + i] = x; }
      }
      auto piece = [&](int i) { push_tok(e + 4 * i, sb, to + (i & 1) * 640, rb + (la ^ (i >> 1)), rank); };
      piece(0);
      wg_fence(); seq_mem<DUAL, 8, 16>(m, w, dw); wg_commit();
      piece(1);
      mbar_wait(sb + B_MF + 8, t & 1, budget);
      wg_fence(); seq_mem<DUAL, 16, 24>(m, w, dw); wg_commit();
      if (DUAL) piece(2);
      wg_fence(); seq_mem<DUAL, 24, 32>(m, w, dw); wg_commit();
      if (DUAL) piece(3);
      mbar_wait(sb + B_MF + 16, t & 1, budget);
      wg_fence(); seq_mem<DUAL, 32, 48>(m, w, dw); wg_commit();
      wg_wait<1>(); p_arrive(sb + B_PD, lead);
      const uint32_t r0 = mapa(sb, rb + la), r1 = mapa(sb, rb + (la ^ 1)), m0 = r0 + ao + lane * 4, m1 = r1 + ao + lane * 4, ab = rank == 2 ? B_AV : B_AB;
      const uint64_t q0 = pair(m0, r0 + ab), q1 = pair(m0 + 640, r0 + ab), q2 = pair(m1, r1 + ab), q3 = pair(m1 + 640, r1 + ab);
      pin2(q0, q1);
      if (DUAL) pin2(q2, q3);
      mbar_wait(sb + B_MF + 24, t & 1, budget);
      wg_fence(); seq_mem<DUAL, 48, 64>(m, w, dw); wg_commit();
      wg_wait<1>(); p_arrive_at(sb + B_FA, 0, lead);
      wg_wait<0>();
      const uint32_t a0 = pack_bf16(m[0], m[1]), a1 = pack_bf16(m[2], m[3]), a2 = pack_bf16(m[4], m[5]), a3 = pack_bf16(m[6], m[7]);
      if constexpr (DUAL) {
        st_async32(q0, la ? a2 : a0); st_async32(q1, la ? a3 : a1); st_async32(q2, la ? a0 : a2); st_async32(q3, la ? a1 : a3);
        rt0 = pack_bf16(m[8], m[9]); rt1 = pack_bf16(m[10], m[11]);
      } else { st_async32(q0, a0); st_async32(q1, a1); rt0 = a2; rt1 = a3; }
      p_arrive(sb + B_WE, lead);
    };
    if (t >= LAG && t < NSEG) {
      float d[28];
      ok = tok_pass<56, 0>(d, w, dw, cx, t, budget, finish, setup);
      pack_tok<4>(e + 8, d); pack_tok<3>(e, d + 16); e[3] = rt0; e[7] = rt1;
      mem_pass(True());
    } else {
      float d[16];
      if (t > 0) finish();
      if (t > 0 && t < LAG) {
        ok = tok_pass<24, 0>(d, w, dw, cx, t, budget, []() {}, setup);
        pack_tok<3>(e, d); e[3] = rt0; e[7] = rt1;
      } else {
        ok = tok_pass<32, 0>(d, w, dw, cx, t, budget, []() {}, setup);
        pack_tok<4>(e, d);
      }
      mem_pass(False());
    }
    {
      RPROF(2 + wg * 12);
      auto wo_ready = [&]() { if (t == 0) mbar_wait(sb + B_WO, 0, budget); if (t < NSTEP - 1) mbar_wait(sb + B_WT, t & 1, budget); };
      constexpr float SC = 0.08838834764831845f * 1.4426950408889634f;
      if (!att) wo_ready();
      else {
        float s[32];
        setup(3);
        if (wg) {
          uint32_t one[4];
#pragma unroll
          for (int i = 0; i < 4; i++) one[i] = 0x3F803F80u + (pw >> 31);
          mbar_wait_cluster(sb + B_AT, seg & 1, budget);
          mbar_wait_cluster(sb + B_AB, seg & 1, budget);
          fence_proxy_async();
          RPROF(3 + 12);
          wg_fence(); seq_s<D_QM, 0>(s); wg_commit();
          nbar_arrive<NB_P, 256>();
          if (warp == 1) sts32(pw + 640, 0);
          mbar_wait_cluster(sb + B_AV, seg & 1, budget);
          wg_wait<0>();
          float mx = fmaxf(fmaxf(fmaxf(s[0], s[1]), fmaxf(s[4], s[5])), fmaxf(fmaxf(fmaxf(s[8], s[9]), fmaxf(s[12], s[13])), fmaxf(s[16], s[17])));
          const float x1 = __shfl_xor_sync(0xffffffffu, mx, 1), x2 = __shfl_xor_sync(0xffffffffu, mx, 2), x3 = __shfl_xor_sync(0xffffffffu, mx, 3);
          const float u = (warp & 2) ? ((warp & 1) ? s[16] : s[12]) : ((warp & 1) ? s[8] : s[4]);
          const float v = (warp & 2) ? ((warp & 1) ? s[17] : s[13]) : ((warp & 1) ? s[9] : s[5]);
          const float ms = -SC * fmaxf(fmaxf(mx, x1), fmaxf(x2, x3));
          sts32(pw + 128 + warp * 128, pack_bf16(ex2(fmaf(u, SC, ms)), ex2(fmaf(v, SC, ms))));
          if (warp == 0) sts32(pw, pack_bf16(ex2(fmaf(s[0], SC, ms)), ex2(fmaf(s[1], SC, ms))));
          fence_proxy_async();
          nbar_sync<NB_W1, 128>();
          RPROF(4 + 12);
          wg_fence();
          rs8<0, 0, D_P>(s + 8, one); rs8<1, 0, D_P + 16>(s + 8, one); rs8<1, 0, D_P + 32>(s + 8, one);
          wg_commit();
          ss8<0, 0, 0, D_V, D_P>(s, 0); ss8<0, 0, 0, D_V + 320, D_P>(s + 4, 0);
          ss8<1, 0, 0, D_V + 16, D_P + 16>(s, 0); ss8<1, 0, 0, D_V + 336, D_P + 16>(s + 4, 0);
          ss8<1, 0, 0, D_V + 32, D_P + 32>(s, 0); ss8<1, 0, 0, D_V + 352, D_P + 32>(s + 4, 0);
          wg_commit();
          wg_wait<1>();
          const float i0 = rcp(s[8]), i1 = rcp(s[9]);
          wg_wait<0>();
          stsm4(sb + oo, pack_bf16(s[0] * i0, s[1] * i1), pack_bf16(s[2] * i0, s[3] * i1), pack_bf16(s[4] * i0, s[5] * i1), pack_bf16(s[6] * i0, s[7] * i1));
          __syncwarp();
          const uint4 y = lds128v(sb + oo);
          if (t < NSTEP - 1) { st_async128(u0, y); st_async128(u1, y); e_complete_tx(sb + B_OB, 512); }
          wo_ready();
        } else {
          const int lim = (int)u1;
          char* const og = (char*)u0;
          nbar_sync<NB_P, 256>();
          RPROF(3);
          wg_fence();
          seq_s<D_QT, 0>(s);
          wg_commit();
          mbar_wait_cluster(sb + B_AV, seg & 1, budget);
          wg_wait<0>();
#pragma unroll
          for (int i = 0; i < 8; i++) { float& v = s[4 + 4 * (i >> 1) + (i & 1)]; v = i <= lim ? v : -INFINITY; }
          float mx = fmaxf(fmaxf(fmaxf(s[0], s[1]), fmaxf(s[4], s[5])), fmaxf(fmaxf(fmaxf(s[8], s[9]), fmaxf(s[12], s[13])), fmaxf(s[16], s[17])));
          const float x1 = __shfl_xor_sync(0xffffffffu, mx, 1), x2 = __shfl_xor_sync(0xffffffffu, mx, 2), x3 = __shfl_xor_sync(0xffffffffu, mx, 3);
          const float ms = -SC * fmaxf(fmaxf(mx, x1), fmaxf(x2, x3));
#pragma unroll
          for (int i = 0; i < 10; i++) { float& v = s[4 * (i >> 1) + (i & 1)]; v = ex2(fmaf(v, SC, ms)); }
          const float sum = (((s[0] + s[1]) + (s[4] + s[5])) + ((s[8] + s[9]) + (s[12] + s[13]))) + (s[16] + s[17]);
          const float y1 = __shfl_xor_sync(0xffffffffu, sum, 1), y2 = __shfl_xor_sync(0xffffffffu, sum, 2), y3 = __shfl_xor_sync(0xffffffffu, sum, 3);
          const float inv = rcp((sum + y1) + (y2 + y3));
          stsm4(pw, pack_bf16(s[0] * inv, s[1] * inv), pack_bf16(s[4] * inv, s[5] * inv), pack_bf16(s[8] * inv, s[9] * inv), pack_bf16(s[12] * inv, s[13] * inv));
          stsm2(pw + 512, pack_bf16(s[16] * inv, s[17] * inv), 0);
          fence_proxy_async();
          nbar_sync<NB_W0, 128>();
          RPROF(4);
          wg_fence();
          ss32<0, 0, 0, D_V, D_P + 48>(s, 0); ss32<0, 0, 0, D_V + 320, D_P + 48>(s + 16, 0);
          ss32<1, 0, 0, D_V + 16, D_P + 64>(s, 0); ss32<1, 0, 0, D_V + 336, D_P + 64>(s + 16, 0);
          ss32<1, 0, 0, D_V + 32, D_P + 80>(s, 0); ss32<1, 0, 0, D_V + 352, D_P + 80>(s + 16, 0);
          wg_commit();
          wo_ready();
          wg_wait<0>();
#pragma unroll
          for (int i = 0; i < 4; i++) {
            const float* d = s + (i >> 1) * 16 + (i & 1) * 2;
            stg128(og + ((i >> 1) * 64 + (i & 1) * 8) * (SEQ * 2), pack_bf16(d[0], d[1]), pack_bf16(d[4], d[5]), pack_bf16(d[8], d[9]), pack_bf16(d[12], d[13]));
          }
          if ((seg & 3) == 3) nbar_arrive<NB_O, 160>();
        }
      }
      RPROF(5 + wg * 12);
      const bool three = wg == 1 || rank == 2;
      char* const p2 = p1 + (2 + ((t - LAG) & 1) - (t & 1)) * (int)sizeof(g_h1[0]);
      if (t < NSTEP - 1) {
        float c[24];
        const uint32_t dt = wg ? 0 : 3072;
        mbar_wait_cluster(sb + B_OB, t & 1, budget);
        fence_proxy_async();
        RPROF(6 + wg * 12);
        wg_fence(); seq_wo<0, 0>(c, dt); wg_commit(); seq_wo<1, 0>(c + 8, dt); wg_commit();
        mbar_wait(sb + B_XF, cx.par, budget);
        wg_wait<1>();
        if (warp == 2) load_x_lent(sb, &M, t + 1, wg ? 3 : 5);
        put_part(p1, p2, pack_part(c, t), t);
        const int o3 = (wo_tile(rank, wg, three ? 2 : 1) - wo_tile(rank, wg, 0)) * 32768;
        z1 = p1 + o3; z2 = p2 + o3;
        if (three) {
          wg_fence(); seq_wo<2, 0>(c + 16, dt); wg_commit();
          wg_wait<1>(); put_part(p1 + 6 * 32768, p2 + 6 * 32768, pack_part(c + 8, t), t);
          mbar_wait(sb + B_XF + 8, cx.par, budget);
          wg_wait<0>(); z = pack_part(c + 16, t);
        } else { mbar_wait(sb + B_XF + 8, cx.par, budget); wg_wait<0>(); z = pack_part(c + 8, t); }
      } else break;
      RPROF(7 + wg * 12);
    }
  }
}

DEVI void wait_xa(const int* p, int& budget) {
  while (__any_sync(0xffffffffu, ldg_acq32(p) < 64) && --budget > 0) {}
  fence_proxy_global();
}
template<bool DUAL> DEVI void first_loads(uint32_t sb, const Maps* M, int n, int h, int rb, int& budget) {
  if (n >= LAG && ((n - LAG) & 3) == 0) e_prefetch_3d(&M->xs, 0, (n - LAG) * 32, h & 14);
  mbar_wait(sb + B_FA, n & 1, budget);
  load_x<DUAL, 0>(sb, M, n, rb); load_x<DUAL, 1>(sb, M, n, rb); load_x<DUAL, 2>(sb, M, n, rb);
}
template<bool DUAL> DEVI void lent_loads(uint32_t sb, const Maps* M, int n, int rb, int& budget) {
  mbar_wait(sb + B_FB, n & 1, budget);
  load_x<DUAL, 3>(sb, M, n, rb); load_x<DUAL, 4>(sb, M, n, rb); load_x<DUAL, 5>(sb, M, n, rb); load_x<DUAL, 6>(sb, M, n, rb);
}
DEVI void rec_comm(const uint32_t sb, const int warp, const Maps& M, const bf16* __restrict__ mem0) {
  const int lane = threadIdx.x & 31, h = cta_id() / 3, rb = cluster_rank() >= 3 ? 3 : 0, rank = cluster_rank() - rb;
  int budget = SPIN_BUDGET;
  const bool two = warp == 3 || (rank == 2 && warp == 2);
  const int ntask = two ? 2 : 1, qi = two ? (warp == 3 ? rank : 3) : rank * 3 + warp;
  const int task0 = two ? h * 2 + (qi >> 1) : 64 + h * 4 + (qi >> 1);
  auto h2_word = [&](int i, int ln) {
    const int task = task0 + i * 192;
    return (char*)g_h2 + (task >> 6) * 8192 + ((qi ^ i) & 1) * 4096 + ((task >> 2) & 15) * 256 + (task & 3) * 32 + (ln & 8) * 16 + (ln & 7) * 4;
  };
  auto first_x = [&](int t) {
    const int n = t + 1;
    p_expect_tx(sb + B_XF + (lane_id() & 7) * 8, 8192, lane_id() < 8);
    if (rb + rank == 0) {
      if (n >= LAG && ((n - LAG) & 3) == 0) wait_xa(&g_xa[1][(n - LAG) >> 2], budget);
      if (n >= LAG && n < NSEG) first_loads<true>(sb, &M, n, h, cluster_last(), budget); else first_loads<false>(sb, &M, n, h, cluster_last(), budget);
    }
  };
  {
    const int task = task0 + (lane >> 4) * 192, L = (task & 3) * 8 + (lane & 7);
    if ((lane >> 4) < ntask) {
      const bf16* p = mem0 + (L & 3) * 2 * DM + (task >> 2) * 16 + (L >> 2) + (lane & 8);
      uint32_t m0 = (uint32_t)__bfloat16_as_ushort(p[0]) | (uint32_t)__bfloat16_as_ushort(p[DM]) << 16;
      m0 = m0 ? m0 : 0x8000u;
      stg_rlx32(h2_word(lane >> 4, lane), ((qi ^ (lane >> 4)) & 1) ? 0 : m0);
      for (int i = 1; i < 4; i++) stg_rlx32(h2_word(lane >> 4, lane) + i * sizeof(g_h2[0]), 0);
      sts32(sb + M0 + warp * 128 + lane * 4, m0);
    }
    __syncwarp();
    nbar_sync<NB_ST, 384>();
    if (warp == 2) {
      e_expect_tx(sb + B_WS, 2 * WSZ);
#pragma unroll 1
      for (int i = 0; i < 2 * (64 - KR); i++) e_tma_2d(sb + WS + (i & 1) * WSZ + (i >> 1) * 2048, &M.w[rank], h * DH + (i & 1) * 64, k_of_smem(i >> 1) * 16, sb + B_WS);
      const int nt = rank == 2 ? 6 : 5;
      e_expect_tx(sb + B_WO, (nt - 2) * 16384);
#pragma unroll 1
      for (int i = 1; i < nt; i++) if (i != 3) e_tma_2d(sb + WO + i * 16384, &M.wo, wo_tile(rank, 1 - i / 3, i % 3) * 64, h * DH, sb + B_WO);
    }
    wait_xa(&g_xa[0][0], budget);
    if (warp == 3) { first_x(-1); if (rb + rank == 0) lent_loads<false>(sb, &M, 0, cluster_last(), budget); }
  }
  uint32_t cpp = 0;
  const uint32_t cp = sb + B_CP + warp * 8;
  uint32_t f_dst, f_chk, f_bar, f_time = gtime() - 4000;
  const char *f_src, *f_xr;
  auto prepare = [&](int s) {
    const int ck = warp ^ (warp < 2 && (s < LAG || s >= NSEG) && (rank & 1) == (s >= NSEG)), ln = lane_id();
    f_dst = sb + RING + mslot(ck); f_chk = f_dst + ln * 32 + (ln >> 2) * 4; f_bar = sb + ck * 8;
    f_src = (const char*)g_h2[s & 3] + ck * 8192 + (s >= NSEG ? 4096 : 0);
    f_xr = (const char*)g_xr[(s + 1) & 63] + ck * 4096;
    pin2(f_chk, 0u);
    return s <= LAG ? TP(9) + ck * TP(11) : s <= NSEG ? TP(1) + ck * TP(4) : TP(13) + ck * TP(11);
  };
  prepare(0);
#pragma unroll 1
  for (int t = 0;; t++) {
    const int n = t + 1;
    const bool dual = t >= LAG && t < NSEG;
    RPROF_STEP;
    {
      const uint32_t bytes = dual ? 8192 : 4096;
      e_expect_tx(cp, bytes + (n < NSEG ? 4096 : 0));
      mbar_wait(f_bar + B_ME, t & 1, budget);
      if (n < NSEG) e_bulk_g2s(f_dst + 8192, f_xr, 4096, cp);
      wait_time(f_time);
      RPROF(24); CPROF(0, gtime());
      int tries = 0;
      while (true) {
        tries++;
        e_bulk_g2s(f_dst, f_src, bytes, cp);
        mbar_wait(cp, cpp, budget); cpp ^= 1;
        uint32_t mn = min(min(lds32v(f_chk), lds32v(f_chk + 1024)), min(lds32v(f_chk + 2048), lds32v(f_chk + 3072)));
        if (dual) mn = min(min(mn, min(lds32v(f_chk + 4096), lds32v(f_chk + 5120))), min(lds32v(f_chk + 6144), lds32v(f_chk + 7168)));
        if (!__any_sync(0xffffffffu, mn == 0) || --budget < 0) break;
        e_expect_tx(cp, bytes);
      }
      e_arrive(f_bar + B_MF);
      RPROF(25); CPROF(1, gtime()); CPROF(2, tries);
    }
    const int seg = t - rank * LAG;
    const bool att = rank < 2 && (unsigned)seg < (unsigned)NSEG;
    if (warp == 0) {
      if (att) { e_expect_tx(sb + B_AT, 16384); e_expect_tx(sb + B_AB, 4096); e_expect_tx(sb + B_AV, 10240); }
      if (n < NSTEP) e_expect_tx(sb + B_OB, dual ? 4096 : 2048);
    }
    if (n + 1 < NSEG && (n & 3) == 3) wait_xa(&g_xa[0][(n + 1) >> 2], budget);
    if (rank == 2 && warp == 1) {
      if (h < 16 ? n < NSEG : n > LAG && n < NSTEP && ((n - LAG) & 3)) e_prefetch_3d(&M.xs, 0, (h < 16 ? n : n - LAG) * 32, (h & 7) * 2);
      if (h >= 16 && n + 1 < NSEG) asm volatile(ELECT "cp.async.bulk.prefetch.L2.global [%0], 2048;}" :: "l"((const char*)g_xr[n + 1] + (h & 7) * 2048) : "memory");
    }
    {
      const int ln = lane_id(), i = ln >> 4;
      char* const w = h2_word(i, ln);
      if (i < ntask) {
        stg_rlx32(w + ((t + 3) & 3) * sizeof(g_h2[0]), 0);
        if (n == LAG && ((qi ^ i) & 1)) stg_rlx32(w + (n & 3) * sizeof(g_h2[0]), lds32v(sb + M0 + warp * 128 + ln * 4));
      }
      __syncwarp();
    }
    if (n < NSTEP) {
      const uint32_t tag = (n >> 1) & 31;
      mbar_wait(sb + B_PD, t & 1, budget);
      uint32_t t0 = clock32();
      if (warp == 2) {
        e_expect_tx(sb + B_WT, 32768);
        e_tma_2d(sb + WO + 49152, &M.wo, wo_tile(rank, 0, 0) * 64, h * DH, sb + B_WT);
        mbar_wait(sb + B_WE, t & 1, budget);
        e_tma_2d(sb + WO, &M.wo, wo_tile(rank, 1, 0) * 64, h * DH, sb + B_WT);
      }
      if (warp == 3) first_x(t);
      if (warp == 0 && rank == (t >= NSEG)) { mbar_wait(sb + B_AB, seg & 1, budget); e_stg_rlx32(&g_ts[t & 1][h], (gtime() & ~31u) | tag); }
      const int fd = prepare(n), ln = lane_id();
      const int sa = t - (qi & 1) * LAG, sc = t - (~qi & 1) * LAG;
      const int i0 = (unsigned)sa < (unsigned)(NSEG - 1) ? 0 : 1, i1 = two && (unsigned)sc < (unsigned)(NSEG - 1) ? 2 : 1;
      const char* src = (const char*)g_h1[(qi & 1) * 2 + (sa & 1)] + task0 * 2048 + ln * 8;
      char* dst = h2_word(0, ln) + (n & 3) * sizeof(g_h2[0]);
      const int ds = ((~qi & 1) * 2 + (sc & 1) - (qi & 1) * 2 - (sa & 1)) * (int)sizeof(g_h1[0]) + 192 * 2048, dd = 3 * 8192 + ((qi & 1) ? -4096 : 4096);
      if (i0) { src += ds; dst += dd; }
      pin2(src, dst);
      spin_until(t0, TSD);
      uint32_t v0;
      do { v0 = ldg_rlx32(&g_ts[t & 1][ln]); } while (__any_sync(0xffffffffu, (v0 & 31) != tag) && --budget > 0);
      const uint32_t now = __shfl_sync(0xffffffffu, v0, 0);
      t0 = now + __reduce_max_sync(0xffffffffu, (int)(v0 - now));
      f_time = t0 + fd;
      RPROF(26); CPROF(3, t0);
      t0 += t < LAG ? TP(8) : t < NSEG ? TP(0) : TP(12);
#pragma unroll 1
      for (int i = i0; i < i1; i++) {
        const uint32_t tg = h1_tag(i ? sc : sa);
        uint2 v[8];
        wait_time(t0 + (!two ? 0 : i ? TP(3) : -TP(10)));
        int tries = 0;
        float a[4];
        while (true) {
          tries++;
#pragma unroll
          for (int k = 0; k < 8; k++) v[k] = ldg_rlx64(src + k * 256);
          asm volatile("{.reg .pred p; setp.eq.s32 p, %0, 0x7fffffff; @p exit;}" :: "r"(budget) : "memory");
          uint32_t bad = 0;
#pragma unroll
          for (int k = 0; k < 8; k++) {
            bad = xor_or(v[k].x, tg, bad);
            a[0] = k ? a[0] + bf_lo(v[k].x) : bf_lo(v[k].x); a[1] = k ? a[1] + bf_hi(v[k].x) : bf_hi(v[k].x);
            a[2] = k ? a[2] + bf_lo(v[k].y) : bf_lo(v[k].y); a[3] = k ? a[3] + bf_hi(v[k].y) : bf_hi(v[k].y);
          }
#pragma unroll
          for (int k = 0; k < 2; k++) {
            const float keep = (ln & 8) ? a[2+k] : a[k], send = (ln & 8) ? a[k] : a[2+k];
            a[k] = keep + __shfl_xor_sync(0xffffffffu, send, 8);
          }
#pragma unroll
          for (int k = 0; k < 2; k++) a[k] += __shfl_xor_sync(0xffffffffu, a[k], 16);
          if (!__any_sync(0xffffffffu, bad & 1) || --budget < 0) break;
        }
        const uint32_t out = pack_bf16(a[0], a[1]);
        if (ln < 16) stg_rlx32(dst, out ? out : 0x8000u);
        __syncwarp();
        src += ds; dst += dd;
        if (i == 0) { RPROF(28); CPROF(6, gtime()); CPROF(4, gtime()); CPROF(5, tries); } else CPROF(7, gtime());
      }
    }
    if (warp == (dual ? 2 : 1) && att && (seg & 3) == 3) { nbar_sync<NB_O, 160>(); e_flag_add(&g_dep[E_O1 + rank * 16 + (seg >> 2)]); }
    if (n == NSTEP) break;
  }
  if (h == 0 && rank == 0 && warp < 2) g_xa[warp][lane_id()] = 0;
}
}

__global__ void __launch_bounds__(384, 1)
rec_kernel(const __grid_constant__ rec::Maps M, const bf16* __restrict__ mem0) {
  using namespace rec;
  extern __shared__ __align__(1024) uint8_t smem[];
  const uint32_t sb = __shfl_sync(0xffffffffu, smem_u32(smem), 0);
  const int tid = threadIdx.x, wi = __shfl_sync(0xffffffffu, tid >> 5, 0);
  if ((sb & 0x3FFFF) != SMEM_BASE) __trap();
  if (wi == 0) {
    const int h = cta_id() / 3, rank = cta_id() - h * 3;
    const int nwg = 2 * cluster_last() + 2;
    for (int i = tid; i < NBAR; i += 32) mbar_init(sb + BARS + i * 8, i < 13 ? nwg : i < 19 ? 2 : 1);
    ((uint32_t*)(smem + PAD))[tid] = 0;
    fence_mbar_init(); fence_proxy_async();
    __syncwarp();
    e_expect_tx(sb + B_ST, STG); e_expect_tx(sb + B_ST + 8, STG);
    for (int i = 0; i < 2 * KR; i++) e_tma_2d(sb + (i & 1) * STG + (i >> 1) * 2048, &M.w[rank], h * DH + (i & 1) * 64, k_of_reg(i >> 1) * 16, sb + B_ST + (i & 1) * 8);
  } else if (wi == 1) {
    if (blockIdx.x < NEV / 32) { g_dep[blockIdx.x * 32 + (tid & 31)] = 0; g_claim[blockIdx.x * 32 + (tid & 31)] = 0; __threadfence(); }
    __syncwarp();
    asm volatile("griddepcontrol.launch_dependents;" ::: "memory");
  }
  cluster_arrive(); cluster_wait();
  if (wi < 8) { reg_inc<232>(); rec_math(sb, wi, M); cluster_arrive(); cluster_wait(); }
  else { reg_dec<40>(); rec_comm(sb, wi & 3, M, mem0); cluster_arrive(); cluster_wait(); }
}

namespace gm {
struct Maps { CUtensorMap ot, wo, xn, wg, wu, hl, hs, wd, out; };
constexpr int STAGES = 6, STAGE = 32768;
constexpr uint32_t SO = STAGES * STAGE, BARS = SO + 32768;
constexpr uint32_t B_FULL = BARS, B_EMPTY = BARS + 48, B_TF = BARS + 96, B_TE = BARS + 112, B_ORD = BARS + 128, B_PM = BARS + 144, B_GO = BARS + 160;
constexpr uint32_t MAIL = BARS + 176, PMAIL = BARS + 192;
constexpr uint32_t SMEM = BARS + 256;
constexpr int END = -1;
#define GT gtime

struct Tile {
  bool isO, isG, l2; int blk, col, k0, n;
  DEVI Tile(int task, int rank) {
    const int e = task >> 8, id = task & 255;
    const bool isD = e < E_G1 || e >= E_D2;
    isO = e >= E_O1 && e < E_G2; isG = !isD && !isO; l2 = e >= E_O2;
    blk = isG && l2 ? (e & 15) * 2 + rank : isD && !l2 ? e >> 1 : e & 15;
    col = isG ? (l2 ? id : id * 2 + rank) : (id & 3) * 2 + rank;
    k0 = isO ? (id >> 2) * 2048 : isG ? 0 : ((l2 ? e >> 4 : e) & 1) * 1792;
    n = isO ? 32 : isG ? 16 : 28;
  }
};

DEVI float geglu(float g, float u) {
  const float z = g * (0.7978845608028654f + 0.035677408136300125f * g * g);
  float t; asm("tanh.approx.f32 %0, %1;" : "=f"(t) : "f"(z));
  const float hg = 0.5f * g;
  return fmaf(hg, t, hg) * u;
}
struct Sched {
  int need, size, e;
  bool filler;
  uint4 dep, cl;
  DEVI void init(int lane) {
    e = (lane < 4 ? lane + 12 : lane < 16 ? lane - 4 : lane) * 4;
    const bool d = e < E_G1 || e >= E_D2, o = e >= E_O1 && e < E_G2;
    need = d ? 28 : e < E_O1 ? 64 : o ? 32 : 128;
    size = d ? 4 : o ? 8 : e < E_O1 ? 28 : e < E_G2 + 8 ? 56 : 0;
    filler = (int)blockIdx.x >= TP(5);
  }
  DEVI void scan(int lane) { cl = ldg_rlx128(g_claim + e); dep = ldg_rlx128(g_dep + e); }
  DEVI int next(int lane, int& budget) {
    while (--budget > 0) {
      int av[4], open = 0;
#pragma unroll
      for (int i = 0; i < 4; i++) { const int r = max(size - (int)(&cl.x)[i], 0); open |= r; av[i] = ((int)(&dep.x)[i] >= need ? r : 0) + (i ? av[i - 1] : 0); }
      const uint32_t mo = __ballot_sync(0xffffffffu, open);
      if (!mo) break;
      if (filler) {
        const int x = TP(6) & 3, dx = x == 0 ? dep.x : x == 1 ? dep.y : x == 2 ? dep.z : dep.w;
        filler = !__any_sync(0xffffffffu, e == ((E_O1 + TP(6)) & ~3) && dx >= need);
      }
      if (!filler && (mo & 0xffff) && lane >= E_O2 / 4) av[3] = 0;
      int inc = av[3], pos = 0;
      while (true) {
        const uint32_t m = __ballot_sync(0xffffffffu, inc > pos && av[3]);
        if (!m) break;
        const int l = __ffs(m) - 1, rel = pos - (inc - av[3]), i = (rel >= av[0]) + (rel >= av[1]) + (rel >= av[2]);
        int r = 0;
        if (lane == l) {
          const int tk = atomicAdd(g_claim + e + i, 1);
          r = tk < size ? (e + i) << 8 | tk : -1 - (inc - av[3] + (i == 0 ? av[0] : i == 1 ? av[1] : i == 2 ? av[2] : av[3]) + tk - size);
        }
        r = __shfl_sync(0xffffffffu, r, l);
        if (r >= 0) return r;
        if (pos == 0) {
#pragma unroll
          for (int o = 1; o < 32; o <<= 1) { const int v = __shfl_up_sync(0xffffffffu, inc, o); if (lane >= o) inc += v; }
        }
        pos = -1 - r;
      }
      if (pos == 0) __nanosleep(TP(7));
      scan(lane);
    }
    return END;
  }
};

DEVI void scheduler(const uint32_t sb) {
  const int lane = threadIdx.x & 31;
  int budget = SPIN_BUDGET;
  Sched sc; sc.init(lane);
#pragma unroll 1
  for (int i = 0;; i++) {
    mbar_wait(sb + B_GO, (i & 1) ^ 1, budget);
    sc.scan(lane);
    const int task = sc.next(lane, budget);
    const uint32_t r = mapa(sb, lane & 1);
    if (lane < 2) st_async32(r + PMAIL + (i & 1) * 4, task, r + B_PM + (i & 1) * 8);
    __syncwarp();
    if (task == END) break;
  }
}

DEVI void producer(const uint32_t sb, const Maps& M) {
  const int lane = threadIdx.x & 31, rank = cluster_rank();
  int budget = SPIN_BUDGET, s = 0, ph = 0;
#pragma unroll 1
  for (int i = 0;; i++) {
    e_expect_tx(sb + B_PM + (i & 1) * 8, 4);
    mbar_wait_cluster(sb + B_PM + (i & 1) * 8, (i >> 1) & 1, budget);
    const int task = budget < 0 ? END : __shfl_sync(0xffffffffu, (int)lds32v(sb + PMAIL + (i & 1) * 4), 0);
    fence_proxy_global();
    for (int z = 0; z < (task == END ? 2 : 1); z++) {
      const int g = (i + z) & 1;
      mbar_wait(sb + B_TE + g * 8, (((i + z) >> 1) & 1) ^ 1, budget);
      if (lane == 0) { sts64(sb + MAIL + g * 8, task, s | ph << 8); mbar_arrive(sb + B_TF + g * 8); }
      __syncwarp();
    }
    if (task == END) break;
    const Tile T(task, rank);
    const bool shareB = T.isG && T.l2;
    const CUtensorMap* mA = T.isO ? &M.ot : T.isG ? &M.xn : &M.hl;
    const CUtensorMap* mB0 = T.isO ? &M.wo : T.isG ? &M.wg : &M.wd;
    const CUtensorMap* mB1 = T.isG ? &M.wu : mB0;
    const int c0 = T.col * (T.isG ? 64 : 128), c1 = T.isG ? c0 : c0 + 64, row = T.blk * 128;
    const int ok = 0;
    int k = T.k0;
#pragma unroll 1
    for (int it = 0; it < T.n; it++, k += 64) {
      const uint32_t a = sb + s * STAGE, fb = sb + B_FULL + s * 8;
      mbar_wait(sb + B_EMPTY + s * 8, ph ^ 1, budget);
      e_expect_tx(fb, STAGE);
      if (shareB) {
        e_tma_2d_mc(a + 16384 + rank * 8192, rank ? mB1 : mB0, c0, k, fb);
        e_tma_2d(a, mA, k, row, fb); e_tma_2d(a + 8192, mA, k, row + 64, fb);
      } else {
        e_tma_2d_mc(a + rank * 8192, mA, T.isO ? row + rank * 64 : k, T.isO ? k + ok : row + rank * 64, fb);
        e_tma_2d(a + 16384, mB0, c0, k, fb); e_tma_2d(a + 24576, mB1, c1, k, fb);
      }
      if (it == T.n - TP(2)) e_arrive(sb + B_GO);
      if (++s == STAGES) { s = 0; ph ^= 1; }
    }
  }
}

template<int TA> DEVI void mainloop(float* d0, float* d1, uint32_t sb, int n, int s, int ph, bool lead, uint32_t ord, int& budget) {
  int prev = 0;
  const uint32_t rel = threadIdx.x & 127;
#pragma unroll 1
  for (int i = 0; i < n; i++) {
    mbar_wait(sb + B_FULL + s * 8, ph, budget);
    const uint32_t a = sb + s * STAGE;
    const uint64_t da = mkdesc(a, 16, 1024), db = mkdesc(a + 16384, 8192, 1024);
    wg_fence();
#pragma unroll
    for (int k = 0; k < 4; k++) {
      wgmma_n128<TA>(d0, da + k * (TA ? 128 : 2), db + k * 128, (i | k) != 0);
      wgmma_n128<TA>(d1, da + 512 + k * (TA ? 128 : 2), db + k * 128, (i | k) != 0);
    }
    wg_commit();
    if (i > 0) { wg_wait<1>(); p_arrive_at(sb + B_EMPTY + prev * 8, rel & 1, rel < 2); }
    prev = s;
    if (++s == STAGES) { s = 0; ph ^= 1; }
  }
  p_arrive(ord, lead);
  wg_wait<0>();
  p_arrive_at(sb + B_EMPTY + prev * 8, rel & 1, rel < 2);
}

DEVI void consumer(const uint32_t sb, const Maps& M, const int wg) {
  const int tid = threadIdx.x, lane = tid & 31, warp = (tid >> 5) & 3;
  const bool lead = (tid & 127) == 0;
  const uint32_t so = sb + SO + wg * 16384;
  int budget = SPIN_BUDGET;
  float d0[64], d1[64];
#pragma unroll 1
  for (int m = 0;; m++) {
    mbar_wait(sb + B_TF + wg * 8, m & 1, budget);
    const uint2 mail = lds64v(sb + MAIL + wg * 8);
    const int task = __shfl_sync(0xffffffffu, (int)mail.x, 0), pos = __shfl_sync(0xffffffffu, (int)mail.y, 0);
    e_arrive(sb + B_TE + wg * 8);
    if (task == END || budget < 0) break;
    const Tile T(task, cluster_rank());
    mbar_wait(sb + B_ORD + wg * 8, (m & 1) ^ wg ^ 1, budget);
    if (T.isO) mainloop<1>(d0, d1, sb, T.n, pos & 255, pos >> 8, lead, sb + B_ORD + (wg ^ 1) * 8, budget);
    else mainloop<0>(d0, d1, sb, T.n, pos & 255, pos >> 8, lead, sb + B_ORD + (wg ^ 1) * 8, budget);
    const uint32_t st = so + (warp * 16 + (lane & 15)) * 128;
    if (T.isG) {
      int* const fl = &g_dep[T.l2 ? E_D2 + (T.col >= 28) * 16 + T.blk : E_D1 + T.blk * 2 + (T.col >= 28)];
#pragma unroll
      for (int mm = 0; mm < 2; mm++) {
        const float* d = mm ? d1 : d0;
#pragma unroll
        for (int c = 0; c < 4; c++) {
          uint32_t r[4];
#pragma unroll
          for (int i = 0; i < 4; i++) r[i] = pack_bf16(geglu(d[8*c+2*i], d[32+8*c+2*i]), geglu(d[8*c+2*i+1], d[33+8*c+2*i]));
          stsm4(st + mm * 8192 + (((2 * c + (lane >> 4)) ^ (lane & 7)) << 4), r[0], r[1], r[2], r[3]);
        }
      }
      fence_proxy_async();
      nbar_sync_r(1 + wg, 128);
      if (lead) {
        tma_store_2d(&M.hs, so, T.col * 64, T.blk * 128);
        bulk_commit();
        bulk_wait<0>();
        flag_add(fl);
      }
    } else {
#pragma unroll
      for (int hf = 0; hf < 2; hf++) {
        if (hf) { if (lead) bulk_wait_read<0>(); nbar_sync_r(1 + wg, 128); }
#pragma unroll
        for (int mm = 0; mm < 2; mm++) {
          const float* d = (mm ? d1 : d0) + hf * 32;
#pragma unroll
          for (int c = 0; c < 4; c++)
            stsm4(st + mm * 8192 + (((2 * c + (lane >> 4)) ^ (lane & 7)) << 4), pack_bf16(d[8*c], d[8*c+1]), pack_bf16(d[8*c+2], d[8*c+3]),
                  pack_bf16(d[8*c+4], d[8*c+5]), pack_bf16(d[8*c+6], d[8*c+7]));
        }
        fence_proxy_async();
        nbar_sync_r(1 + wg, 128);
        if (lead) { tma_radd_2d(&M.out, so, T.col * 128 + hf * 64, T.blk * 128); bulk_commit(); }
      }
      if (lead) {
        bulk_wait<0>();
        if (T.isO || !T.l2) flag_add(&g_dep[(!T.isO ? E_LX2 : T.l2 ? E_LX1B : E_LX1A) + T.blk]);
      }
    }
    __syncwarp();
  }
}

DEVI void norm_helper(const bf16* __restrict__ x, bf16* out) {
  const int lane = threadIdx.x & 31;
  int budget = SPIN_BUDGET, tk = lane < 4 ? -1 : 1024;
#pragma unroll 1
  while (--budget > 0) {
    if (tk < 0) tk = atomicAdd(g_claim + E_LI + lane, 1);
    if (__all_sync(0xffffffffu, tk >= 1024)) break;
    const uint32_t m = __ballot_sync(0xffffffffu, tk < 1024 && (lane == 0 || ldg_acq32(g_dep + E_LI + lane * 16 + (tk >> 6)) >= 16));
    if (!m) { __nanosleep(TP(7)); continue; }
    const int ql = __ffs(m) - 1, task = __shfl_sync(0xffffffffu, tk, ql), q = E_LI + ql * 16, ev = task >> 6;
    if (lane == ql) tk = -1;
    const size_t off = (size_t)task * (DM * 4) + lane * 16;
    const char* src = (const char*)(q == E_LI ? x : out) + off;
    uint4 u[8];
#pragma unroll
    for (int i = 0; i < 8; i++) u[i] = ldg_rlx128(src + i * 512);
    if (q == E_LI) {
#pragma unroll
      for (int i = 0; i < 8; i++) stg128((char*)out + off + i * 512, u[i].x, u[i].y, u[i].z, u[i].w);
    }
    int* const fl = q == E_LI ? &g_xa[0][ev] : q == E_LX2 ? &g_xa[1][ev] : &g_dep[q == E_LX1A ? E_G1 + ev : E_G2 + (ev >> 1)];
    float mean[2], rs[2];
#pragma unroll
    for (int r = 0; r < 2; r++) {
      float s0 = 0, s1 = 0;
#pragma unroll
      for (int i = 0; i < 16; i++) { const uint32_t v = (&u[4*r + (i >> 2)].x)[i & 3]; s0 += bf_lo(v); s1 += bf_hi(v); }
      mean[r] = (s0 + s1) * (1.f / 32);
      s0 = s1 = 0;
#pragma unroll
      for (int i = 0; i < 16; i++) { const uint32_t v = (&u[4*r + (i >> 2)].x)[i & 3]; const float a = bf_lo(v) - mean[r], b = bf_hi(v) - mean[r]; s0 = fmaf(a, a, s0); s1 = fmaf(b, b, s1); }
      rs[r] = s0 + s1;
    }
    {
      const bool hi = lane & 16;
      float m1 = hi ? mean[1] : mean[0], q1 = hi ? rs[1] : rs[0], m2 = hi ? mean[0] : mean[1], q2 = hi ? rs[0] : rs[1], cnt = 16;
#pragma unroll
      for (int o = 16; o; o >>= 1) {
        m2 = __shfl_xor_sync(0xffffffffu, m2, o); q2 = __shfl_xor_sync(0xffffffffu, q2, o);
        const float dl = m1 - m2;
        q2 = q1 = fmaf(dl * dl, cnt, q1 + q2); m2 = m1 = 0.5f * (m1 + m2);
        cnt *= 2;
      }
      q1 = rsqrtf(q1 * (1.f / DM) + 1e-5f);
      m2 = __shfl_xor_sync(0xffffffffu, m1, 16); q2 = __shfl_xor_sync(0xffffffffu, q1, 16);
      mean[0] = hi ? m2 : m1; mean[1] = hi ? m1 : m2; rs[0] = hi ? q2 : q1; rs[1] = hi ? q1 : q2;
    }
#pragma unroll
    for (int i = 0; i < 8; i++) {
      uint32_t y[4];
#pragma unroll
      for (int c = 0; c < 4; c++) { const uint32_t v = (&u[i].x)[c]; y[c] = pack_bf16((bf_lo(v) - mean[i >> 2]) * rs[i >> 2], (bf_hi(v) - mean[i >> 2]) * rs[i >> 2]); }
      stg128((char*)g_xn + off + i * 512, y[0], y[1], y[2], y[3]);
      u[i] = make_uint4(y[0], y[1], y[2], y[3]);
    }
    if (q == E_LI && (task & 15) >= 12) {
      uint32_t* const xr = g_xr[task >> 4] + lane * 32 + (task & 3);
#pragma unroll
      for (int i = 0; i < 16; i++) {
        const uint32_t a = (&u[i >> 2].x)[i & 3], b = (&u[4 + (i >> 2)].x)[i & 3];
        xr[(i >> 2) * 1024 + (i & 3) * 8] = __byte_perm(a, b, 0x5410); xr[(i >> 2) * 1024 + (i & 3) * 8 + 4] = __byte_perm(a, b, 0x7632);
      }
    }
    fence_proxy_global();
    __syncwarp();
    if (lane == 0) flag_add(fl);
    __syncwarp();
  }
}
}

__global__ void __cluster_dims__(2, 1, 1) __launch_bounds__(384, 1)
gemm_kernel(const __grid_constant__ gm::Maps M, const bf16* __restrict__ x, bf16* out) {
  using namespace gm;
  extern __shared__ __align__(1024) uint8_t smem[];
  const uint32_t sb = __shfl_sync(0xffffffffu, smem_u32(smem), 0);
  const int tid = threadIdx.x, wi = __shfl_sync(0xffffffffu, tid >> 5, 0);
  if (tid < 21) mbar_init(sb + BARS + tid * 8, tid == 14 || tid == 15 ? 4 : tid >= 6 && tid < 12 ? 2 : 1);
  fence_mbar_init();
  cluster_arrive(); cluster_wait();
  if (wi < 8) { reg_inc<208>(); consumer(sb, M, wi >> 2); cluster_arrive(); cluster_wait(); }
  else {
    reg_dec<88>();
    if (wi == 8) producer(sb, M);
    else if (wi == 11 && cluster_rank() == 0) scheduler(sb);
    else {
      norm_helper(x, out);
      asm volatile("griddepcontrol.wait;" ::: "memory");
    }
    __syncwarp();
    cluster_arrive(); cluster_wait();
  }
}

typedef CUresult (*PFN_encodeTiled)(CUtensorMap*, CUtensorMapDataType, cuuint32_t, void*, const cuuint64_t*, const cuuint64_t*,
                                    const cuuint32_t*, const cuuint32_t*, CUtensorMapInterleave, CUtensorMapSwizzle,
                                    CUtensorMapL2promotion, CUtensorMapFloatOOBfill);
static PFN_encodeTiled g_encode = nullptr;
static CUtensorMap make_map(const void* ptr, uint64_t rows, uint64_t cols, uint32_t box_rows, CUtensorMapL2promotion pr = CU_TENSOR_MAP_L2_PROMOTION_L2_256B) {
  CUtensorMap m;
  cuuint64_t dims[2] = {cols, rows}, strides[1] = {cols * 2};
  cuuint32_t box[2] = {64, box_rows}, es[2] = {1, 1};
  g_encode(&m, CU_TENSOR_MAP_DATA_TYPE_BFLOAT16, 2, (void*)ptr, dims, strides, box, es, CU_TENSOR_MAP_INTERLEAVE_NONE,
           CU_TENSOR_MAP_SWIZZLE_128B, pr, CU_TENSOR_MAP_FLOAT_OOB_FILL_NONE);
  return m;
}

static CUtensorMap make_map3(const void* ptr, uint64_t d0, uint64_t d1, uint64_t d2, uint64_t stride2) {
  CUtensorMap m;
  cuuint64_t dims[3] = {d0, d1, d2}, strides[2] = {DM * 2, stride2};
  cuuint32_t box[3] = {64, 32, 2}, es[3] = {1, 1, 1};
  g_encode(&m, CU_TENSOR_MAP_DATA_TYPE_BFLOAT16, 3, (void*)ptr, dims, strides, box, es, CU_TENSOR_MAP_INTERLEAVE_NONE,
           CU_TENSOR_MAP_SWIZZLE_128B, CU_TENSOR_MAP_L2_PROMOTION_L2_256B, CU_TENSOR_MAP_FLOAT_OOB_FILL_NONE);
  return m;
}

extern "C" void kernel_launch(void* const* d_in, const int* in_sizes, int n_in, void* d_out, int out_size) {
  const bf16* x = (const bf16*)d_in[0];
  const bf16* mem0 = (const bf16*)d_in[1];
  if (!g_encode) {
    void* p = nullptr; cudaDriverEntryPointQueryResult q;
    cudaGetDriverEntryPoint("cuTensorMapEncodeTiled", &p, cudaEnableDefault, &q);
    g_encode = (PFN_encodeTiled)p;
    cudaFuncSetAttribute(gemm_kernel, cudaFuncAttributeMaxDynamicSharedMemorySize, gm::SMEM);
    cudaFuncSetAttribute(rec_kernel, cudaFuncAttributeMaxDynamicSharedMemorySize, rec::SMEM);
  }
  bf16 *xn, *ot, *hh;
  cudaGetSymbolAddress((void**)&xn, g_xn); cudaGetSymbolAddress((void**)&ot, g_ot); cudaGetSymbolAddress((void**)&hh, g_h);
  rec::Maps R;
  for (int i = 0; i < 3; i++) R.w[i] = make_map(d_in[2 + i], DM, NH * DH, 16, CU_TENSOR_MAP_L2_PROMOTION_NONE);
  R.wo = make_map(d_in[5], NH * DH, DM, 128);
  R.xd = make_map3(xn, DM, SEQ - LAG * 32, 2, (uint64_t)LAG * 32 * DM * 2); R.xs = make_map3(xn, 64, SEQ, DM / 64, 128);
  gm::Maps G;
  G.ot = make_map(ot, NH * DH + O_LAYER / SEQ, SEQ, 64); G.wo = make_map(d_in[5], NH * DH, DM, 64); G.xn = make_map(xn, SEQ, DM, 64);
  G.wg = make_map(d_in[8], DM, DF, 64); G.wu = make_map(d_in[9], DM, DF, 64); G.hl = make_map(hh, SEQ, DF, 64); G.hs = make_map(hh, SEQ, DF, 128);
  G.wd = make_map(d_in[10], DF, DM, 64); G.out = make_map(d_out, SEQ, DM, 128);
  cudaLaunchConfig_t cfg = {};
  cudaLaunchAttribute at[1];
  cfg.attrs = at; cfg.numAttrs = 1;
  cfg.gridDim = dim3(3 * NH); cfg.blockDim = dim3(384); cfg.dynamicSmemBytes = rec::SMEM; cfg.stream = cudaStreamPerThread;
  at[0].id = cudaLaunchAttributeClusterDimension; at[0].val.clusterDim.y = at[0].val.clusterDim.z = 1;
  static int csize = 0;
  if (!csize) {
    int n = 0;
    at[0].val.clusterDim.x = 6;
    csize = cudaOccupancyMaxActiveClusters(&n, rec_kernel, &cfg) == cudaSuccess && n >= NH / 2 ? 6 : 3;
  }
  at[0].val.clusterDim.x = csize;
  cudaLaunchKernelEx(&cfg, rec_kernel, R, mem0);
  cfg.gridDim = dim3(132); cfg.blockDim = dim3(384); cfg.dynamicSmemBytes = gm::SMEM; cfg.stream = cudaStreamPerThread;
  at[0].id = cudaLaunchAttributeProgrammaticStreamSerialization; at[0].val.programmaticStreamSerializationAllowed = 1;
  cudaLaunchKernelEx(&cfg, gemm_kernel, G, x, (bf16*)d_out);
}
```

```cpp
#include <cuda_runtime.h>
#include <cuda_bf16.h>
#include <cuda.h>
#include <stdint.h>

#define DEVI __device__ __forceinline__
typedef __nv_bfloat16 bf16;

constexpr int SEQ = 2048, DM = 1024, NH = 32, DH = 128, DF = 3584, NSEG = 64;
#define LAG 20
constexpr int NSTEP = NSEG + LAG;

#define TSD 1800
constexpr size_t O_LAYER = 0;
__device__ __align__(1024) bf16 g_xn[SEQ * DM];
__device__ __align__(1024) bf16 g_ot[SEQ * NH * DH + O_LAYER];
__device__ __align__(1024) bf16 g_h[SEQ * DF];
__device__ __align__(1024) uint32_t g_xr[NSEG][DM * 4];
__device__ __align__(1024) uint2 g_h1[4][256 * 256];
__device__ __align__(1024) uint4 g_h2[4][2048];
__device__ __align__(128) uint32_t g_ts[2][32];
enum { E_D1 = 0, E_G1 = 32, E_O1 = 48, E_O2 = 64, E_G2 = 80, E_D2 = 96,
       E_LI = 128, E_LX2 = 144, E_LX1A = 160, E_LX1B = 176, NEV = 256 };
__device__ __align__(128) int g_dep[NEV];
__device__ __align__(128) int g_claim[NEV];
__device__ __align__(128) int g_xa[2][32];

#define TUNE_DEFAULTS 1650, 2450, 6, 100, 100, 8, 14, 100, 1550, 2280, 100, 110, 1550, 2320, 200, 0
constexpr int c_D[16] = {TUNE_DEFAULTS};
template<int I> struct TPV { static constexpr int v = c_D[I]; };
#define TP(i) TPV<i>::v

DEVI uint32_t smem_u32(const void* p) { return (uint32_t)__cvta_generic_to_shared(p); }
DEVI void mbar_init(uint32_t bar, uint32_t cnt) { asm volatile("mbarrier.init.shared::cta.b64 [%0], %1;" :: "r"(bar), "r"(cnt) : "memory"); }
DEVI void mbar_arrive(uint32_t bar) { asm volatile("mbarrier.arrive.shared::cta.b64 _, [%0];" :: "r"(bar) : "memory"); }
DEVI bool mbar_try(uint32_t bar, uint32_t parity) {
  uint32_t p;
  asm volatile("{.reg .pred p; mbarrier.try_wait.parity.shared::cta.b64 p, [%1], %2; selp.u32 %0, 1, 0, p;}" : "=r"(p) : "r"(bar), "r"(parity) : "memory");
  return p;
}
DEVI bool mbar_test(uint32_t bar, uint32_t parity) {
  uint32_t p;
  asm volatile("{.reg .pred p; mbarrier.test_wait.parity.shared::cta.b64 p, [%1], %2; selp.u32 %0, 1, 0, p;}" : "=r"(p) : "r"(bar), "r"(parity) : "memory");
  return p;
}
constexpr int SPIN_BUDGET = 1 << 18;
DEVI void mbar_wait(uint32_t bar, uint32_t parity, int& budget) {
  while (!mbar_try(bar, parity)) { if (--budget < 0) break; }
}
DEVI bool mbar_try_cluster(uint32_t bar, uint32_t parity) {
  uint32_t p;
  asm volatile("{.reg .pred p; mbarrier.try_wait.parity.acquire.cluster.shared::cta.b64 p, [%1], %2; selp.u32 %0, 1, 0, p;}" : "=r"(p) : "r"(bar), "r"(parity) : "memory");
  return p;
}
DEVI void mbar_wait_cluster(uint32_t bar, uint32_t parity, int& budget) {
  while (!mbar_try_cluster(bar, parity)) { if (--budget < 0) break; }
}
DEVI uint32_t mapa(uint32_t addr, uint32_t rank) { uint32_t r; asm("mapa.shared::cluster.u32 %0, %1, %2;" : "=r"(r) : "r"(addr), "r"(rank)); return r; }
DEVI void cluster_arrive() { asm volatile("barrier.cluster.arrive.release.aligned;" ::: "memory"); }
DEVI void cluster_wait() { asm volatile("barrier.cluster.wait.acquire.aligned;" ::: "memory"); }
DEVI void fence_mbar_init() { asm volatile("fence.mbarrier_init.release.cluster;" ::: "memory"); }
DEVI void fence_proxy_async() { asm volatile("fence.proxy.async.shared::cta;" ::: "memory"); }
DEVI void fence_proxy_global() { asm volatile("fence.proxy.async.global;" ::: "memory"); }
#define ELECT "{.reg .pred p; elect.sync _|p, 0xffffffff;\n @p "
DEVI void e_expect_tx(uint32_t bar, uint32_t bytes) { asm volatile(ELECT "mbarrier.arrive.expect_tx.shared::cta.b64 _, [%0], %1;}" :: "r"(bar), "r"(bytes) : "memory"); }
DEVI void e_complete_tx(uint32_t bar, uint32_t bytes) { asm volatile("fence.acq_rel.cta;\n" ELECT "mbarrier.complete_tx.relaxed.cta.shared::cta.b64 [%0], %1;}" :: "r"(bar), "r"(bytes) : "memory"); }
DEVI void e_arrive(uint32_t bar) { asm volatile(ELECT "mbarrier.arrive.shared::cta.b64 _, [%0];}" :: "r"(bar) : "memory"); }
DEVI void e_tma_2d(uint32_t dst, const CUtensorMap* m, int c0, int c1, uint32_t bar) {
  asm volatile(ELECT "cp.async.bulk.tensor.2d.shared::cluster.global.mbarrier::complete_tx::bytes [%0], [%1, {%3, %4}], [%2];}"
    :: "r"(dst), "l"(m), "r"(bar), "r"(c0), "r"(c1) : "memory");
}
DEVI void e_prefetch_3d(const CUtensorMap* m, int c0, int c1, int c2) {
  asm volatile(ELECT "cp.async.bulk.prefetch.tensor.3d.L2.global [%0, {%1, %2, %3}];}" :: "l"(m), "r"(c0), "r"(c1), "r"(c2) : "memory");
}
DEVI void e_bulk_g2s(uint32_t dst, const void* src, uint32_t bytes, uint32_t bar) {
  asm volatile(ELECT "cp.async.bulk.shared::cluster.global.mbarrier::complete_tx::bytes [%0], [%1], %2, [%3];}" :: "r"(dst), "l"(src), "r"(bytes), "r"(bar) : "memory");
}
DEVI void e_tma_3d(uint32_t dst, const CUtensorMap* m, int c0, int c1, int c2, uint32_t bar) {
  asm volatile(ELECT "cp.async.bulk.tensor.3d.shared::cluster.global.mbarrier::complete_tx::bytes [%0], [%1, {%3, %4, %5}], [%2];}"
    :: "r"(dst), "l"(m), "r"(bar), "r"(c0), "r"(c1), "r"(c2) : "memory");
}
DEVI void e_tma_3d_mc(uint32_t dst, const CUtensorMap* m, int c0, int c1, int c2, uint32_t bar, int last) {
  asm volatile(ELECT "cp.async.bulk.tensor.3d.shared::cluster.global.mbarrier::complete_tx::bytes.multicast::cluster [%0], [%1, {%3, %4, %5}], [%2], %6;}"
    :: "r"(dst), "l"(m), "r"(bar), "r"(c0), "r"(c1), "r"(c2), "h"((uint16_t)((2 << last) - 1)) : "memory");
}
DEVI void e_tma_2d_mc(uint32_t dst, const CUtensorMap* m, int c0, int c1, uint32_t bar) {
  asm volatile(ELECT "cp.async.bulk.tensor.2d.shared::cluster.global.mbarrier::complete_tx::bytes.multicast::cluster [%0], [%1, {%3, %4}], [%2], %5;}"
    :: "r"(dst), "l"(m), "r"(bar), "r"(c0), "r"(c1), "h"((uint16_t)3) : "memory");
}
DEVI void p_arrive_at(uint32_t bar, uint32_t rank, bool c) {
  asm volatile("{.reg .pred p; .reg .b32 a; setp.ne.u32 p, %2, 0; mapa.shared::cluster.u32 a, %0, %1; @p mbarrier.arrive.shared::cluster.b64 _, [a];}"
    :: "r"(bar), "r"(rank), "r"((uint32_t)c) : "memory");
}
DEVI void p_expect_tx(uint32_t bar, uint32_t bytes, bool c) {
  asm volatile("{.reg .pred p; setp.ne.u32 p, %2, 0; @p mbarrier.arrive.expect_tx.shared::cta.b64 _, [%0], %1;}" :: "r"(bar), "r"(bytes), "r"((uint32_t)c) : "memory");
}
DEVI void p_arrive(uint32_t bar, bool c) { asm volatile("{.reg .pred p; setp.ne.u32 p, %1, 0; @p mbarrier.arrive.shared::cta.b64 _, [%0];}" :: "r"(bar), "r"((uint32_t)c) : "memory"); }
DEVI void tma_store_2d(const CUtensorMap* m, uint32_t src, int c0, int c1) {
  asm volatile("cp.async.bulk.tensor.2d.global.shared::cta.bulk_group [%0, {%2, %3}], [%1];" :: "l"(m), "r"(src), "r"(c0), "r"(c1) : "memory");
}
DEVI void tma_radd_2d(const CUtensorMap* m, uint32_t src, int c0, int c1) {
  asm volatile("cp.reduce.async.bulk.tensor.2d.global.shared::cta.add.bulk_group [%0, {%2, %3}], [%1];" :: "l"(m), "r"(src), "r"(c0), "r"(c1) : "memory");
}
DEVI void bulk_commit() { asm volatile("cp.async.bulk.commit_group;" ::: "memory"); }
template<int N> DEVI void bulk_wait_read() { asm volatile("cp.async.bulk.wait_group.read %0;" :: "n"(N) : "memory"); }
template<int N> DEVI void bulk_wait() { asm volatile("cp.async.bulk.wait_group %0;" :: "n"(N) : "memory"); }
template<int ID, int N> DEVI void nbar_sync() { asm volatile("bar.sync %0, %1;" :: "n"(ID), "n"(N) : "memory"); }
template<int ID, int N> DEVI void nbar_arrive() { asm volatile("bar.arrive %0, %1;" :: "n"(ID), "n"(N) : "memory"); }
DEVI void nbar_sync_r(int id, int n) { asm volatile("bar.sync %0, %1;" :: "r"(id), "r"(n) : "memory"); }
template<int R> DEVI void reg_inc() { asm volatile("setmaxnreg.inc.sync.aligned.u32 %0;" :: "n"(R)); }
template<int R> DEVI void reg_dec() { asm volatile("setmaxnreg.dec.sync.aligned.u32 %0;" :: "n"(R)); }
DEVI void wg_fence() { asm volatile("wgmma.fence.sync.aligned;" ::: "memory"); }
DEVI void wg_commit() { asm volatile("wgmma.commit_group.sync.aligned;" ::: "memory"); }
template<int N> DEVI void wg_wait() { asm volatile("wgmma.wait_group.sync.aligned %0;" :: "n"(N) : "memory"); }
DEVI uint64_t mkdesc(uint32_t addr, uint32_t lbo, uint32_t sbo, uint32_t sw = 1) {
  return ((uint64_t)((addr & 0x3FFFF) >> 4)) | ((uint64_t)(lbo >> 4) << 16) | ((uint64_t)(sbo >> 4) << 32) | ((uint64_t)sw << 62);
}
constexpr uint32_t SMEM_BASE = 1024;
__host__ __device__ constexpr long long CD(uint32_t off, uint32_t lbo, uint32_t sbo, uint32_t sw) {
  return (long long)(((uint64_t)((SMEM_BASE + off) >> 4)) | ((uint64_t)(lbo >> 4) << 16) | ((uint64_t)(sbo >> 4) << 32) | ((uint64_t)sw << 62));
}
DEVI uint32_t pack_bf16(float lo, float hi) { uint32_t r; asm("cvt.rn.bf16x2.f32 %0, %1, %2;" : "=r"(r) : "f"(hi), "f"(lo)); return r; }
DEVI float bf_lo(uint32_t v) { return __uint_as_float(v << 16); }
DEVI float bf_hi(uint32_t v) { return __uint_as_float(v & 0xffff0000u); }
DEVI void ldsm4t(uint32_t addr, uint32_t& r0, uint32_t& r1, uint32_t& r2, uint32_t& r3) {
  asm volatile("ldmatrix.sync.aligned.m8n8.x4.trans.shared.b16 {%0,%1,%2,%3}, [%4];" : "=r"(r0), "=r"(r1), "=r"(r2), "=r"(r3) : "r"(addr) : "memory");
}
DEVI void stsm4(uint32_t addr, uint32_t r0, uint32_t r1, uint32_t r2, uint32_t r3) {
  asm volatile("stmatrix.sync.aligned.m8n8.x4.shared.b16 [%0], {%1,%2,%3,%4};" :: "r"(addr), "r"(r0), "r"(r1), "r"(r2), "r"(r3) : "memory");
}
DEVI uint2 lds64v(uint32_t a) { uint2 v; asm volatile("ld.volatile.shared.v2.u32 {%0,%1}, [%2];" : "=r"(v.x), "=r"(v.y) : "r"(a) : "memory"); return v; }
DEVI uint32_t lds32v(uint32_t a) { uint32_t v; asm volatile("ld.volatile.shared.u32 %0, [%1];" : "=r"(v) : "r"(a) : "memory"); return v; }
DEVI uint4 lds128v(uint32_t a) { uint4 v; asm volatile("ld.volatile.shared.v4.u32 {%0,%1,%2,%3}, [%4];" : "=r"(v.x), "=r"(v.y), "=r"(v.z), "=r"(v.w) : "r"(a) : "memory"); return v; }
DEVI void sts32(uint32_t a, uint32_t x) { asm volatile("st.shared.u32 [%0], %1;" :: "r"(a), "r"(x) : "memory"); }
DEVI int lane_id() { int r; asm volatile("mov.u32 %0, %%laneid;" : "=r"(r)); return r; }
DEVI void sts64(uint32_t a, uint32_t x, uint32_t y) { asm volatile("st.shared.v2.u32 [%0], {%1,%2};" :: "r"(a), "r"(x), "r"(y) : "memory"); }
DEVI void st_async128(uint32_t a, uint32_t x, uint32_t y, uint32_t z, uint32_t w, uint32_t bar) {
  asm volatile("st.async.weak.shared::cluster.mbarrier::complete_tx::bytes.v4.b32 [%0], {%1,%2,%3,%4}, [%5];" :: "r"(a), "r"(x), "r"(y), "r"(z), "r"(w), "r"(bar) : "memory");
}
DEVI void st_async32(uint32_t a, uint32_t x, uint32_t bar) {
  asm volatile("st.async.weak.shared::cluster.mbarrier::complete_tx::bytes.b32 [%0], %1, [%2];" :: "r"(a), "r"(x), "r"(bar) : "memory");
}
DEVI uint4 ldg_rlx128(const void* p) {
  uint4 v;
  asm volatile("ld.relaxed.gpu.global.v4.b32 {%0,%1,%2,%3}, [%4];" : "=r"(v.x), "=r"(v.y), "=r"(v.z), "=r"(v.w) : "l"(p) : "memory");
  return v;
}
DEVI int ldg_rlx32(const void* p) { int v; asm volatile("ld.relaxed.gpu.global.b32 %0, [%1];" : "=r"(v) : "l"(p) : "memory"); return v; }
DEVI int ldg_acq32(const void* p) { int v; asm volatile("ld.acquire.gpu.global.b32 %0, [%1];" : "=r"(v) : "l"(p) : "memory"); return v; }
DEVI void stg128(void* p, uint32_t x, uint32_t y, uint32_t z, uint32_t w) {
  asm volatile("st.global.v4.b32 [%0], {%1,%2,%3,%4};" :: "l"(p), "r"(x), "r"(y), "r"(z), "r"(w) : "memory");
}
DEVI uint2 ldg_rlx64(const void* p) { uint2 v; asm volatile("{.reg .b64 a; ld.relaxed.gpu.global.b64 a, [%2]; mov.b64 {%0,%1}, a;}" : "=r"(v.x), "=r"(v.y) : "l"(p) : "memory"); return v; }
DEVI void stg_rlx64(void* p, uint32_t x, uint32_t y) { asm volatile("{.reg .b64 a; mov.b64 a, {%1,%2}; st.relaxed.gpu.global.b64 [%0], a;}" :: "l"(p), "r"(x), "r"(y) : "memory"); }
DEVI void stg_rlx32(void* p, uint32_t x) { asm volatile("st.relaxed.gpu.global.b32 [%0], %1;" :: "l"(p), "r"(x) : "memory"); }
DEVI void flag_add(int* p) { asm volatile("fence.proxy.async.global; red.release.gpu.global.add.s32 [%0], 1;" :: "l"(p) : "memory"); }
DEVI void e_stg_rlx32(void* p, uint32_t x) { asm volatile(ELECT "st.relaxed.gpu.global.b32 [%0], %1;}" :: "l"(p), "r"(x) : "memory"); }
DEVI void e_flag_add(int* p) { asm volatile("fence.proxy.async.global;\n" ELECT "red.release.gpu.global.add.s32 [%0], 1;}" :: "l"(p) : "memory"); }
DEVI int cluster_rank() { int r; asm volatile("mov.u32 %0, %%cluster_ctarank;" : "=r"(r)); return __shfl_sync(0xffffffffu, r, 0); }
DEVI int cluster_last() { int r; asm volatile("mov.u32 %0, %%cluster_nctarank;" : "=r"(r)); return __shfl_sync(0xffffffffu, r, 0) - 1; }
DEVI int cta_id() { int r; asm volatile("mov.u32 %0, %%ctaid.x;" : "=r"(r)); return __shfl_sync(0xffffffffu, r, 0); }
DEVI uint32_t clock32() { uint32_t c; asm volatile("mov.u32 %0, %%clock;" : "=r"(c)); return c; }
DEVI uint32_t gtime() { uint32_t c; asm volatile("mov.u32 %0, %%globaltimer_lo;" : "=r"(c)); return c; }
DEVI void wait_time(uint32_t t) { while (__any_sync(0xffffffffu, t - gtime() - 1 < 4000u)) {} }
DEVI void spin_until(uint32_t t0, int d) {
  int r;
  while (__any_sync(0xffffffffu, (r = d - (int)(clock32() - t0)) > 0)) {
    if (r > 300) __nanosleep(r >> 2);
  }
}
DEVI void pin2(const void* a, const void* b) { asm volatile("{.reg .pred p; setp.eq.u64 p, %0, %1; @p st.volatile.global.u64 [%0], %1;}" :: "l"(a), "l"(b) : "memory"); }
DEVI void pin2(uint32_t a, uint32_t b) { asm volatile("{.reg .pred p; setp.eq.u32 p, %0, %1; @p st.volatile.shared.u32 [%0], %1;}" :: "r"(a), "r"(b) : "memory"); }
DEVI void p_stg_rlx64(void* p, uint32_t x, uint32_t y, bool c) {
  asm volatile("{.reg .pred p; .reg .b64 a; setp.ne.u32 p, %3, 0; mov.b64 a, {%1,%2}; @p st.relaxed.gpu.global.b64 [%0], a;}" :: "l"(p), "r"(x), "r"(y), "r"((uint32_t)c) : "memory");
}
DEVI void pin2(uint64_t a, uint64_t b) { pin2((const void*)a, (const void*)b); }
DEVI uint64_t pair(uint32_t a, uint32_t bar) { return a | (uint64_t)bar << 32; }
DEVI void st_async32(uint64_t q, uint32_t x) { st_async32((uint32_t)q, x, (uint32_t)(q >> 32)); }
DEVI void st_async128(uint64_t q, uint4 v) { st_async128((uint32_t)q, v.x, v.y, v.z, v.w, (uint32_t)(q >> 32)); }
DEVI float ex2(float x) { float r; asm("ex2.approx.ftz.f32 %0, %1;" : "=f"(r) : "f"(x)); return r; }
DEVI float rcp(float x) { float r; asm("rcp.approx.ftz.f32 %0, %1;" : "=f"(r) : "f"(x)); return r; }
DEVI uint32_t xor_or(uint32_t a, uint32_t t, uint32_t acc) { uint32_t r; asm("lop3.b32 %0, %1, %2, %3, 0xbe;" : "=r"(r) : "r"(a), "r"(t), "r"(acc)); return r; }
DEVI void stsm2(uint32_t addr, uint32_t r0, uint32_t r1) {
  asm volatile("stmatrix.sync.aligned.m8n8.x2.shared.b16 [%0], {%1,%2};" :: "r"(addr), "r"(r0), "r"(r1) : "memory");
}
DEVI uint32_t settag(uint32_t v, uint32_t tag) { return (v & ~1u) | tag; }

#define A4(c, o)  c(d[o+0]), c(d[o+1]), c(d[o+2]), c(d[o+3])
#define A8(c, o)  A4(c, o), A4(c, o+4)
#define A16(c, o) A8(c, o), A8(c, o+8)
#define A12(c, o) A8(c, o), A4(c, o+8)
#define A28(c, o) A16(c, o), A12(c, o+16)
#define RL12 "{%0,%1,%2,%3,%4,%5,%6,%7,%8,%9,%10,%11}"
#define RL28 "{%0,%1,%2,%3,%4,%5,%6,%7,%8,%9,%10,%11,%12,%13,%14,%15,%16,%17,%18,%19,%20,%21,%22,%23,%24,%25,%26,%27}"
#define A20(c, o) A16(c, o), A4(c, o+16)
#define A32(c, o) A16(c, o), A16(c, o+16)
#define RL8  "{%0,%1,%2,%3,%4,%5,%6,%7}"
#define RL16 "{%0,%1,%2,%3,%4,%5,%6,%7,%8,%9,%10,%11,%12,%13,%14,%15}"
#define RL20 "{%0,%1,%2,%3,%4,%5,%6,%7,%8,%9,%10,%11,%12,%13,%14,%15,%16,%17,%18,%19}"
#define RL32 "{%0,%1,%2,%3,%4,%5,%6,%7,%8,%9,%10,%11,%12,%13,%14,%15,%16,%17,%18,%19,%20,%21,%22,%23,%24,%25,%26,%27,%28,%29,%30,%31}"
#define RL64 "{%0,%1,%2,%3,%4,%5,%6,%7,%8,%9,%10,%11,%12,%13,%14,%15,%16,%17,%18,%19,%20,%21,%22,%23,%24,%25,%26,%27,%28,%29,%30,%31," \
  "%32,%33,%34,%35,%36,%37,%38,%39,%40,%41,%42,%43,%44,%45,%46,%47,%48,%49,%50,%51,%52,%53,%54,%55,%56,%57,%58,%59,%60,%61,%62,%63}"
#define WG_OP(shape) "wgmma.mma_async.sync.aligned." shape "k16.f32.bf16.bf16 "
#define DEF_WGMMA(N, RL, AL, i0, i1, i2, i3, i4, i5, i6)                                                                         \
  template<int SC, int TB, long long CB> DEVI void rs##N(float* d, const uint32_t* a) {                                          \
    if (SC) asm volatile("{.reg .b64 tb; mov.b64 tb, %" #i4 ";\n" WG_OP("m64n" #N) RL ", {%" #i0 ",%" #i1 ",%" #i2 ",%" #i3 "}, tb, 1, 1, 1, %" #i5 ";}" \
      : AL("+f", 0) : "r"(a[0]), "r"(a[1]), "r"(a[2]), "r"(a[3]), "n"(CB), "n"(TB));                                             \
    else asm volatile("{.reg .b64 tb; mov.b64 tb, %" #i4 ";\n" WG_OP("m64n" #N) RL ", {%" #i0 ",%" #i1 ",%" #i2 ",%" #i3 "}, tb, 0, 1, 1, %" #i5 ";}" \
      : AL("=f", 0) : "r"(a[0]), "r"(a[1]), "r"(a[2]), "r"(a[3]), "n"(CB), "n"(TB));                                             \
  }                                                                                                                              \
  template<int SC, int TA, int TB, long long CA, long long CB> DEVI void ss##N(float* d, uint32_t a) {                           \
    if (SC) asm volatile("{.reg .b64 ta, tb; .reg .b32 lo, hi; add.u32 lo, %" #i0 ", %" #i1 "; mov.b32 hi, %" #i2 "; mov.b64 ta, {lo, hi}; mov.b64 tb, %" #i3 ";\n" \
      WG_OP("m64n" #N) RL ", ta, tb, 1, 1, 1, %" #i4 ", %" #i5 ";}"                                                              \
      : AL("+f", 0) : "r"(a), "n"((int)CA), "n"((int)(CA >> 32)), "n"(CB), "n"(TA), "n"(TB));                                    \
    else asm volatile("{.reg .b64 ta, tb; .reg .b32 lo, hi; add.u32 lo, %" #i0 ", %" #i1 "; mov.b32 hi, %" #i2 "; mov.b64 ta, {lo, hi}; mov.b64 tb, %" #i3 ";\n" \
      WG_OP("m64n" #N) RL ", ta, tb, 0, 1, 1, %" #i4 ", %" #i5 ";}"                                                              \
      : AL("=f", 0) : "r"(a), "n"((int)CA), "n"((int)(CA >> 32)), "n"(CB), "n"(TA), "n"(TB));                                    \
  }
DEF_WGMMA(8, "{%0,%1,%2,%3}", A4, 4, 5, 6, 7, 8, 9, 10)
DEF_WGMMA(16, RL8, A8, 8, 9, 10, 11, 12, 13, 14)
DEF_WGMMA(32, RL16, A16, 16, 17, 18, 19, 20, 21, 22)
DEF_WGMMA(40, RL20, A20, 20, 21, 22, 23, 24, 25, 26)
DEF_WGMMA(24, RL12, A12, 12, 13, 14, 15, 16, 17, 18)
DEF_WGMMA(56, RL28, A28, 28, 29, 30, 31, 32, 33, 34)
template<int TA> DEVI void wgmma_n128(float* d, uint64_t a, uint64_t b, int scale_d) {
  asm volatile("{.reg .pred p; setp.ne.b32 p, %66, 0;\n" WG_OP("m64n128") RL64 ", %64, %65, p, 1, 1, %67, 1;}"
    : A32("+f", 0), A32("+f", 32) : "l"(a), "l"(b), "r"(scale_d), "n"(TA));
}

namespace rec {
constexpr int KR = 43;
constexpr uint32_t WSZ = (64 - KR) * 2048, STG = KR * 2048;
constexpr uint32_t WS = 0;
constexpr uint32_t RING = 2 * WSZ;
constexpr uint32_t OB = RING + 3 * 8192;
constexpr uint32_t PB = OB + 4096;
constexpr uint32_t WO = RING + 32768;
constexpr uint32_t ATT = WO + 5 * 16384;
constexpr uint32_t AK = ATT + 10240, AV = ATT + 20480;
constexpr uint32_t PAD = ATT + 30720;
constexpr uint32_t BARS = PAD + 128;
constexpr uint32_t B_XE = BARS  , B_FA = BARS + 64  , B_FB = BARS + 88, B_FO = BARS + 96;
constexpr uint32_t B_ME = BARS + 104  , B_WE = BARS + 136, B_PD = BARS + 144;
constexpr uint32_t B_XF = BARS + 152  , B_MF = BARS + 216  , B_CP = BARS + 248  , B_WT = BARS + 280  ;
constexpr uint32_t B_AB = BARS + 296, B_OB = BARS + 304, B_ST = BARS + 312  , B_WS = BARS + 328, B_WO = BARS + 336, B_AT = BARS + 352, B_AV = BARS + 360;
constexpr int NBAR = 46;
constexpr uint32_t M0 = BARS + 384;
constexpr uint32_t SMEM = 232448;
constexpr int NB_P = 1, NB_ST = 2, NB_O = 3, NB_W0 = 4, NB_W1 = 5;
__host__ __device__ constexpr int wo_tile(int rank, int g, int i) { return i < 2 ? i * 6 + (rank == 2 ? g : 4 - 2 * g + rank) : 13 + rank - g; }
constexpr long long D_W = CD(WS, 16, 1024, 1), D_X = CD(0, 16, 1024, 1), D_O = CD(OB, 128, 256, 0);
constexpr long long D_WO = CD(WO, 16, 1024, 1), D_QM = CD(ATT, 640, 0, 0), D_QT = CD(ATT + 128, 640, 64, 0), D_K = CD(AK, 640, 128, 0);
constexpr long long D_V = CD(AV, 128, 640, 0), D_P = CD(PB, 128, 768, 0);
struct Maps { CUtensorMap w[3], wo, xd, xs; };
__host__ __device__ constexpr uint32_t mslot(int c) { return (c ^ (c >> 1)) * 12288; }
__host__ __device__ constexpr uint32_t xslot(int s) { return s < 3 ? RING + s * 8192 : s < 5 ? WO + (s - 3) * 8192 : s < 7 ? WO + (s + 1) * 8192 : OB; }
__host__ __device__ constexpr bool k_smem(int k) { return k % 3 == 2; }
__host__ __device__ constexpr int k_idx(int k) { return k % 3 == 2 ? k / 3 : k - k / 3; }
__host__ __device__ constexpr int k_of_reg(int i) { return i + (i >> 1); }
__host__ __device__ constexpr int k_of_smem(int i) { return 3 * i + 2; }

#define RPROF(i)
#define RPROF_STEP
#define CPROF(i, v)

template<bool DUAL, int K0, int K1> DEVI void seq_mem(float* d, const uint32_t* w, uint32_t dw) {
  if constexpr (K0 < K1) {
    constexpr long long B = CD(RING, 128, DUAL ? 4096 : 8192, 0) + mslot(K0 >> 4) / 16 + (K0 & 15) * 16;
    if constexpr (DUAL) {
      if constexpr (!k_smem(K0)) rs24<K0 != 0, 1, B>(d, w + 4 * k_idx(K0)); else ss24<1, 1, 1, D_W + k_idx(K0) * 128, B>(d, dw);
    } else {
      if constexpr (!k_smem(K0)) rs16<K0 != 0, 1, B>(d, w + 4 * k_idx(K0)); else ss16<1, 1, 1, D_W + k_idx(K0) * 128, B>(d, dw);
    }
    seq_mem<DUAL, K0 + 1, K1>(d, w, dw);
  }
}
template<int N, int K0, int K1> DEVI void seq_tok(float* d, const uint32_t* w, uint32_t dw) {
  if constexpr (K0 < K1) {
    constexpr bool DUAL = N > 32;
    constexpr long long B = D_X + (DUAL ? xslot((K0 >> 2) & 7) / 16 : xslot(K0 >> 3) / 16 + ((K0 >> 2) & 1) * 256) + (K0 & 3) * 2;
    if constexpr (DUAL) {
      if constexpr (!k_smem(K0)) rs56<K0 != 0, 0, B>(d, w + 4 * k_idx(K0)); else ss56<1, 1, 0, D_W + k_idx(K0) * 128, B>(d, dw);
    } else if constexpr (N == 24) {
      if constexpr (!k_smem(K0)) rs24<K0 != 0, 0, B>(d, w + 4 * k_idx(K0)); else ss24<1, 1, 0, D_W + k_idx(K0) * 128, B>(d, dw);
    } else {
      if constexpr (!k_smem(K0)) rs32<K0 != 0, 0, B>(d, w + 4 * k_idx(K0)); else ss32<1, 1, 0, D_W + k_idx(K0) * 128, B>(d, dw);
    }
    seq_tok<N, K0 + 1, K1>(d, w, dw);
  }
}
template<int T, int K0> DEVI void seq_wo(float* d, uint32_t dw) {
  if constexpr (K0 < 8) { ss16<K0 != 0, 1, 1, D_WO + T * 1024 + K0 * 128, D_O + K0 * 32>(d, dw); seq_wo<T, K0 + 1>(d, dw); }
}
template<long long Q, int K0> DEVI void seq_s(float* d) {
  if constexpr (K0 < 8) { ss40<K0 != 0, 1, 1, Q + K0 * 80, D_K + K0 * 80>(d, 0); seq_s<Q, K0 + 1>(d); }
}
template<bool DUAL, int J> DEVI void load_x(uint32_t sb, const Maps* M, int t, int rb) {
  if (DUAL) e_tma_3d_mc(sb + xslot(J & 7), &M->xd, J * 64, (t - LAG) * 32, 0, sb + B_XF + (J & 7) * 8, rb);
  else e_tma_3d_mc(sb + xslot(J & 7), &M->xs, 0, (t < NSEG ? t : t - LAG) * 32, J * 2, sb + B_XF + (J & 7) * 8, rb);
}
DEVI void load_x_lent(uint32_t sb, const Maps* M, int t, int j) {
  const bool dual = t >= LAG && t < NSEG;
  const uint32_t dst = sb + (j == 3 ? xslot(3) : xslot(5));
#pragma unroll
  for (int i = 0; i < 2; i++)
    e_tma_3d(dst + i * 8192, dual ? &M->xd : &M->xs, dual ? (j + i) * 64 : 0, (t < LAG ? t : t - LAG) * 32, dual ? 0 : (j + i) * 2, sb + B_XF + (j + i) * 8);
}
struct True { static constexpr bool value = true; };
struct False { static constexpr bool value = false; };
struct Ctx { uint32_t sb; const Maps* M; int last; bool issuer; int wi; bool lead; uint32_t par; };
#define XD 1
template<bool DUAL, int J> DEVI void tok_release(const Ctx& c, int t, int& budget) {
  constexpr int NC = DUAL ? 16 : 8, S = J & 7;
  if constexpr (J + 8 < NC) {
    p_arrive_at(c.sb + B_XE + S * 8, c.last, c.lead);
    p_expect_tx(c.sb + B_XF + S * 8, 8192, c.lead && c.wi == 0);
  } else if constexpr (S == 1 || S == 2 || S == 4 || S == 7) p_arrive(c.sb + B_ME + (S >> 1) * 8, c.lead);
  if constexpr (J == 0) {
    if (c.issuer && c.wi == 6) { mbar_wait(c.sb + B_FO, t & 1, budget); load_x<DUAL, 7>(c.sb, c.M, t, c.last); }
  }
  if constexpr (J >= XD && J - XD + 8 < NC) {
    constexpr int I = J - XD;
    if (c.issuer && c.wi == (I & 1) * 4 + 1) { mbar_wait(c.sb + B_XE + I * 8, (t - LAG) & 1, budget); load_x<DUAL, I + 8>(c.sb, c.M, t, c.last); }
  }
}
template<int N, int J, class F, class G> DEVI bool tok_pass(float* d, const uint32_t* w, uint32_t dw, Ctx& c, int t, int& budget, F after0, G setup) {
  constexpr bool DUAL = N > 32;
  constexpr int NC = DUAL ? 16 : 8, KC = 64 / NC;
  if constexpr (J < NC) {
    if constexpr (J > 1) mbar_wait(c.sb + B_XF + (J & 7) * 8, c.par ^ (J >> 3), budget);
    wg_fence();
    seq_tok<N, J * KC, (J + 1) * KC>(d, w, dw);
    wg_commit();
    if constexpr (J == 1) after0();
    if constexpr (J >= NC - 5 && J < NC - 2) setup(J - (NC - 5));
    if constexpr (J > 0) { wg_wait<1>(); tok_release<DUAL, J - 1>(c, t, budget); }
    return tok_pass<N, J + 1>(d, w, dw, c, t, budget, after0, setup);
  } else {
    const bool ok = mbar_test(c.sb + B_MF, t & 1);
    wg_wait<0>();
    tok_release<DUAL, NC - 1>(c, t, budget);
    if (!DUAL) c.par ^= 1;
    return ok;
  }
}
template<int NB> DEVI void pack_tok(uint32_t* e, const float* d) {
#pragma unroll
  for (int i = 0; i < 8; i++) if ((i & 3) < NB) e[i] = pack_bf16(d[4 * (i & 3) + 2 * (i >> 2)], d[4 * (i & 3) + 2 * (i >> 2) + 1]);
}
DEVI void push_tok(const uint32_t* e, uint32_t sb, uint32_t o, int r, int rank) {
  const uint32_t b = mapa(sb, r);
  st_async128(b + o, e[0], e[1], e[2], e[3], b + (rank == 2 ? B_AV : B_AT));
}
DEVI uint32_t h1_tag(int seg) { return ((seg >> 1) & 1) ^ 1; }
DEVI uint4 pack_part(const float* c, int t) {
  return make_uint4(settag(pack_bf16(c[0], c[1]), h1_tag(t)), pack_bf16(c[2], c[3]), settag(pack_bf16(c[4], c[5]), h1_tag(t - LAG)), pack_bf16(c[6], c[7]));
}
DEVI void put_part(char* p1, char* p2, uint4 z, int t) { p_stg_rlx64(p1, z.x, z.y, t < NSEG); p_stg_rlx64(p2, z.z, z.w, t >= LAG); }

DEVI void rec_math(const uint32_t sb, const int wi, const Maps& M) {
  const int h = cta_id() / 3, rb = cluster_rank() >= 3 ? 3 : 0, rank = cluster_rank() - rb;
  const int warp = wi & 3, wg = wi >> 2;
  const bool lead = (threadIdx.x & 127) == 0;
  int budget = SPIN_BUDGET;
  uint32_t w[4 * KR];
  const int last = cluster_last();
  Ctx cx{sb, &M, last, rb + rank == last, wi, lead, 0};
  {
    const int lane = lane_id();
    const uint32_t a = sb + wg * STG + ((lane & 7) + (lane >> 4) * 8) * 128 + (((warp * 2 + ((lane >> 3) & 1)) ^ (lane & 7)) << 4);
    for (int i = 0; i < (wg == 1 || rank == 2 ? 12 : 8); i++)
      stg_rlx64((char*)g_h1[i & 3] + ((wo_tile(rank, wg, i >> 2) * 4 + warp) * 4 + (lane >> 3)) * 2048 + h * 64 + (lane & 7) * 8, 0, 0);
    mbar_wait(sb + B_ST + wg * 8, 0, budget);
#pragma unroll
    for (int k = 0; k < KR; k++) ldsm4t(a + k * 2048, w[4*k], w[4*k+1], w[4*k+2], w[4*k+3]);
    nbar_arrive<NB_ST, 384>();
    nbar_sync_r(NB_W0 + wg, 128);
    for (int i = 0; i < 5; i++) p_arrive_at(sb + B_FA + i * 8, i == 4 ? last : 0, lead);
    mbar_wait(sb + B_WS, 0, budget);
  }
  uint4 z = make_uint4(0, 0, 0, 0);
  char *z1 = nullptr, *z2 = nullptr;
  uint32_t rt0 = 0, rt1 = 0;
  mbar_wait(sb + B_XF, 0, budget); mbar_wait(sb + B_XF + 8, 0, budget);
#pragma unroll 1
  for (int t = 0;; t++) {
    const uint32_t dw = wg * (WSZ >> 4);
    uint32_t e[16];
    bool ok;
    auto finish = [&]() { put_part(z1, z2, z, t - 1); p_arrive_at(sb + B_FO, last, lead); };
    const int seg = t - rank * LAG;
    const bool att = rank < 2 && (unsigned)seg < (unsigned)NSEG;
    char* p1;
    uint32_t pw, oo;
    uint64_t u0, u1;
    int lane;
    auto setup = [&](int part) {
      if (part == 0) {
        lane = lane_id();
      } else if (part == 1) {
        char* const p = (char*)g_h1 + ((wo_tile(rank, wg, 0) * 4 + warp) * 4 + (lane >> 3)) * 2048 + h * 64 + (lane & 7) * 8;
        p1 = p + (t & 1) * sizeof(g_h1[0]);
        pin2(p1, nullptr);
      } else if (part == 2) {
        oo = OB + (lane >> 4) * 2048 + warp * 512 + rank * 256 + (lane & 15) * 16;
        pw = sb + PB + (wg ? lane * 4 : 768 + warp * 768 + lane * 16);
        pin2(pw, oo);
      } else {
        if (wg) {
          const uint32_t ra = mapa(sb, rb + ((warp & 1) ? 2 : (rank ^ 1) & 1)), rc = mapa(sb, rb + ((warp & 1) ? (rank ^ 1) & 1 : 2));
          u0 = pair(ra + oo, ra + B_OB); u1 = pair(rc + oo, rc + B_OB);
        } else {
          u0 = (uint64_t)((char*)(g_ot + rank * O_LAYER) + (size_t)(h * DH + warp * 16 + (lane >> 2)) * (SEQ * 2) + seg * 64 + (lane & 3) * 16);
          u1 = (uint32_t)((lane & 24) + ((lane >> 2) & 1) + 2 * warp - 8 * (lane & 3));
        }
        pin2(u0, u1);
      }
    };
    RPROF_STEP;
    auto mem_pass = [&](auto dual_c) {
      constexpr bool DUAL = decltype(dual_c)::value;
      float m[DUAL ? 12 : 8];
      RPROF(8 + wg * 12 - 32);
      if (!ok) mbar_wait(sb + B_MF, t & 1, budget);
      wg_fence(); seq_mem<DUAL, 0, 8>(m, w, dw); wg_commit();
      const uint32_t ao = ATT + rank * 10240 + wi * 1280, to = ao + 128 + (lane & 3) * 128 + (lane >> 2) * 16;
      const int la = DUAL ? rank == 0 : t >= NSEG;
      RPROF(1 + wg * 12);
      if (DUAL && rank == 0) {
#pragma unroll
        for (int i = 0; i < 8; i++) { const uint32_t x = e[i]; e[i] = e[8 + i]; e[8 + i] = x; }
      }
      auto piece = [&](int i) { push_tok(e + 4 * i, sb, to + (i & 1) * 640, rb + (la ^ (i >> 1)), rank); };
      piece(0);
      wg_fence(); seq_mem<DUAL, 8, 16>(m, w, dw); wg_commit();
      piece(1);
      mbar_wait(sb + B_MF + 8, t & 1, budget);
      wg_fence(); seq_mem<DUAL, 16, 24>(m, w, dw); wg_commit();
      if (DUAL) piece(2);
      wg_fence(); seq_mem<DUAL, 24, 32>(m, w, dw); wg_commit();
      if (DUAL) piece(3);
      mbar_wait(sb + B_MF + 16, t & 1, budget);
      wg_fence(); seq_mem<DUAL, 32, 48>(m, w, dw); wg_commit();
      wg_wait<1>(); p_arrive(sb + B_PD, lead);
      const uint32_t r0 = mapa(sb, rb + la), r1 = mapa(sb, rb + (la ^ 1)), m0 = r0 + ao + lane * 4, m1 = r1 + ao + lane * 4, ab = rank == 2 ? B_AV : B_AB;
      const uint64_t q0 = pair(m0, r0 + ab), q1 = pair(m0 + 640, r0 + ab), q2 = pair(m1, r1 + ab), q3 = pair(m1 + 640, r1 + ab);
      pin2(q0, q1);
      if (DUAL) pin2(q2, q3);
      mbar_wait(sb + B_MF + 24, t & 1, budget);
      wg_fence(); seq_mem<DUAL, 48, 64>(m, w, dw); wg_commit();
      wg_wait<1>(); p_arrive_at(sb + B_FA, 0, lead);
      wg_wait<0>();
      const uint32_t a0 = pack_bf16(m[0], m[1]), a1 = pack_bf16(m[2], m[3]), a2 = pack_bf16(m[4], m[5]), a3 = pack_bf16(m[6], m[7]);
      if constexpr (DUAL) {
        st_async32(q0, la ? a2 : a0); st_async32(q1, la ? a3 : a1); st_async32(q2, la ? a0 : a2); st_async32(q3, la ? a1 : a3);
        rt0 = pack_bf16(m[8], m[9]); rt1 = pack_bf16(m[10], m[11]);
      } else { st_async32(q0, a0); st_async32(q1, a1); rt0 = a2; rt1 = a3; }
      p_arrive(sb + B_WE, lead);
    };
    if (t >= LAG && t < NSEG) {
      float d[28];
      ok = tok_pass<56, 0>(d, w, dw, cx, t, budget, finish, setup);
      pack_tok<4>(e + 8, d); pack_tok<3>(e, d + 16); e[3] = rt0; e[7] = rt1;
      mem_pass(True());
    } else {
      float d[16];
      if (t > 0) finish();
      if (t > 0 && t < LAG) {
        ok = tok_pass<24, 0>(d, w, dw, cx, t, budget, []() {}, setup);
        pack_tok<3>(e, d); e[3] = rt0; e[7] = rt1;
      } else {
        ok = tok_pass<32, 0>(d, w, dw, cx, t, budget, []() {}, setup);
        pack_tok<4>(e, d);
      }
      mem_pass(False());
    }
    {
      RPROF(2 + wg * 12);
      auto wo_ready = [&]() { if (t == 0) mbar_wait(sb + B_WO, 0, budget); if (t < NSTEP - 1) mbar_wait(sb + B_WT, t & 1, budget); };
      constexpr float SC = 0.08838834764831845f * 1.4426950408889634f;
      if (!att) wo_ready();
      else {
        float s[32];
        setup(3);
        if (wg) {
          uint32_t one[4];
#pragma unroll
          for (int i = 0; i < 4; i++) one[i] = 0x3F803F80u + (pw >> 31);
          mbar_wait_cluster(sb + B_AT, seg & 1, budget);
          mbar_wait_cluster(sb + B_AB, seg & 1, budget);
          fence_proxy_async();
          RPROF(3 + 12);
          wg_fence(); seq_s<D_QM, 0>(s); wg_commit();
          nbar_arrive<NB_P, 256>();
          if (warp == 1) sts32(pw + 640, 0);
          mbar_wait_cluster(sb + B_AV, seg & 1, budget);
          wg_wait<0>();
          float mx = fmaxf(fmaxf(fmaxf(s[0], s[1]), fmaxf(s[4], s[5])), fmaxf(fmaxf(fmaxf(s[8], s[9]), fmaxf(s[12], s[13])), fmaxf(s[16], s[17])));
          const float x1 = __shfl_xor_sync(0xffffffffu, mx, 1), x2 = __shfl_xor_sync(0xffffffffu, mx, 2), x3 = __shfl_xor_sync(0xffffffffu, mx, 3);
          const float u = (warp & 2) ? ((warp & 1) ? s[16] : s[12]) : ((warp & 1) ? s[8] : s[4]);
          const float v = (warp & 2) ? ((warp & 1) ? s[17] : s[13]) : ((warp & 1) ? s[9] : s[5]);
          const float ms = -SC * fmaxf(fmaxf(mx, x1), fmaxf(x2, x3));
          sts32(pw + 128 + warp * 128, pack_bf16(ex2(fmaf(u, SC, ms)), ex2(fmaf(v, SC, ms))));
          if (warp == 0) sts32(pw, pack_bf16(ex2(fmaf(s[0], SC, ms)), ex2(fmaf(s[1], SC, ms))));
          fence_proxy_async();
          nbar_sync<NB_W1, 128>();
          RPROF(4 + 12);
          wg_fence();
          rs8<0, 0, D_P>(s + 8, one); rs8<1, 0, D_P + 16>(s + 8, one); rs8<1, 0, D_P + 32>(s + 8, one);
          wg_commit();
          ss8<0, 0, 0, D_V, D_P>(s, 0); ss8<0, 0, 0, D_V + 320, D_P>(s + 4, 0);
          ss8<1, 0, 0, D_V + 16, D_P + 16>(s, 0); ss8<1, 0, 0, D_V + 336, D_P + 16>(s + 4, 0);
          ss8<1, 0, 0, D_V + 32, D_P + 32>(s, 0); ss8<1, 0, 0, D_V + 352, D_P + 32>(s + 4, 0);
          wg_commit();
          wg_wait<1>();
          const float i0 = rcp(s[8]), i1 = rcp(s[9]);
          wg_wait<0>();
          stsm4(sb + oo, pack_bf16(s[0] * i0, s[1] * i1), pack_bf16(s[2] * i0, s[3] * i1), pack_bf16(s[4] * i0, s[5] * i1), pack_bf16(s[6] * i0, s[7] * i1));
          __syncwarp();
          const uint4 y = lds128v(sb + oo);
          if (t < NSTEP - 1) { st_async128(u0, y); st_async128(u1, y); e_complete_tx(sb + B_OB, 512); }
          wo_ready();
        } else {
          const int lim = (int)u1;
          char* const og = (char*)u0;
          nbar_sync<NB_P, 256>();
          RPROF(3);
          wg_fence();
          seq_s<D_QT, 0>(s);
          wg_commit();
          mbar_wait_cluster(sb + B_AV, seg & 1, budget);
          wg_wait<0>();
#pragma unroll
          for (int i = 0; i < 8; i++) { float& v = s[4 + 4 * (i >> 1) + (i & 1)]; v = i <= lim ? v : -INFINITY; }
          float mx = fmaxf(fmaxf(fmaxf(s[0], s[1]), fmaxf(s[4], s[5])), fmaxf(fmaxf(fmaxf(s[8], s[9]), fmaxf(s[12], s[13])), fmaxf(s[16], s[17])));
          const float x1 = __shfl_xor_sync(0xffffffffu, mx, 1), x2 = __shfl_xor_sync(0xffffffffu, mx, 2), x3 = __shfl_xor_sync(0xffffffffu, mx, 3);
          const float ms = -SC * fmaxf(fmaxf(mx, x1), fmaxf(x2, x3));
#pragma unroll
          for (int i = 0; i < 10; i++) { float& v = s[4 * (i >> 1) + (i & 1)]; v = ex2(fmaf(v, SC, ms)); }
          const float sum = (((s[0] + s[1]) + (s[4] + s[5])) + ((s[8] + s[9]) + (s[12] + s[13]))) + (s[16] + s[17]);
          const float y1 = __shfl_xor_sync(0xffffffffu, sum, 1), y2 = __shfl_xor_sync(0xffffffffu, sum, 2), y3 = __shfl_xor_sync(0xffffffffu, sum, 3);
          const float inv = rcp((sum + y1) + (y2 + y3));
          stsm4(pw, pack_bf16(s[0] * inv, s[1] * inv), pack_bf16(s[4] * inv, s[5] * inv), pack_bf16(s[8] * inv, s[9] * inv), pack_bf16(s[12] * inv, s[13] * inv));
          stsm2(pw + 512, pack_bf16(s[16] * inv, s[17] * inv), 0);
          fence_proxy_async();
          nbar_sync<NB_W0, 128>();
          RPROF(4);
          wg_fence();
          ss32<0, 0, 0, D_V, D_P + 48>(s, 0); ss32<0, 0, 0, D_V + 320, D_P + 48>(s + 16, 0);
          ss32<1, 0, 0, D_V + 16, D_P + 64>(s, 0); ss32<1, 0, 0, D_V + 336, D_P + 64>(s + 16, 0);
          ss32<1, 0, 0, D_V + 32, D_P + 80>(s, 0); ss32<1, 0, 0, D_V + 352, D_P + 80>(s + 16, 0);
          wg_commit();
          wo_ready();
          wg_wait<0>();
#pragma unroll
          for (int i = 0; i < 4; i++) {
            const float* d = s + (i >> 1) * 16 + (i & 1) * 2;
            stg128(og + ((i >> 1) * 64 + (i & 1) * 8) * (SEQ * 2), pack_bf16(d[0], d[1]), pack_bf16(d[4], d[5]), pack_bf16(d[8], d[9]), pack_bf16(d[12], d[13]));
          }
          if ((seg & 3) == 3) nbar_arrive<NB_O, 160>();
        }
      }
      RPROF(5 + wg * 12);
      const bool three = wg == 1 || rank == 2;
      char* const p2 = p1 + (2 + ((t - LAG) & 1) - (t & 1)) * (int)sizeof(g_h1[0]);
      if (t < NSTEP - 1) {
        float c[24];
        const uint32_t dt = wg ? 0 : 3072;
        mbar_wait_cluster(sb + B_OB, t & 1, budget);
        fence_proxy_async();
        RPROF(6 + wg * 12);
        wg_fence(); seq_wo<0, 0>(c, dt); wg_commit(); seq_wo<1, 0>(c + 8, dt); wg_commit();
        mbar_wait(sb + B_XF, cx.par, budget);
        wg_wait<1>();
        if (warp == 2) load_x_lent(sb, &M, t + 1, wg ? 3 : 5);
        put_part(p1, p2, pack_part(c, t), t);
        const int o3 = (wo_tile(rank, wg, three ? 2 : 1) - wo_tile(rank, wg, 0)) * 32768;
        z1 = p1 + o3; z2 = p2 + o3;
        if (three) {
          wg_fence(); seq_wo<2, 0>(c + 16, dt); wg_commit();
          wg_wait<1>(); put_part(p1 + 6 * 32768, p2 + 6 * 32768, pack_part(c + 8, t), t);
          mbar_wait(sb + B_XF + 8, cx.par, budget);
          wg_wait<0>(); z = pack_part(c + 16, t);
        } else { mbar_wait(sb + B_XF + 8, cx.par, budget); wg_wait<0>(); z = pack_part(c + 8, t); }
      } else break;
      RPROF(7 + wg * 12);
    }
  }
}

DEVI void wait_xa(const int* p, int& budget) {
  while (__any_sync(0xffffffffu, ldg_acq32(p) < 64) && --budget > 0) {}
  fence_proxy_global();
}
template<bool DUAL> DEVI void first_loads(uint32_t sb, const Maps* M, int n, int h, int rb, int& budget) {
  if (n >= LAG && ((n - LAG) & 3) == 0) e_prefetch_3d(&M->xs, 0, (n - LAG) * 32, h & 14);
  mbar_wait(sb + B_FA, n & 1, budget);
  load_x<DUAL, 0>(sb, M, n, rb); load_x<DUAL, 1>(sb, M, n, rb); load_x<DUAL, 2>(sb, M, n, rb);
}
template<bool DUAL> DEVI void lent_loads(uint32_t sb, const Maps* M, int n, int rb, int& budget) {
  mbar_wait(sb + B_FB, n & 1, budget);
  load_x<DUAL, 3>(sb, M, n, rb); load_x<DUAL, 4>(sb, M, n, rb); load_x<DUAL, 5>(sb, M, n, rb); load_x<DUAL, 6>(sb, M, n, rb);
}
DEVI void rec_comm(const uint32_t sb, const int warp, const Maps& M, const bf16* __restrict__ mem0) {
  const int lane = threadIdx.x & 31, h = cta_id() / 3, rb = cluster_rank() >= 3 ? 3 : 0, rank = cluster_rank() - rb;
  int budget = SPIN_BUDGET;
  const bool two = warp == 3 || (rank == 2 && warp == 2);
  const int ntask = two ? 2 : 1, qi = two ? (warp == 3 ? rank : 3) : rank * 3 + warp;
  const int task0 = two ? h * 2 + (qi >> 1) : 64 + h * 4 + (qi >> 1);
  auto h2_word = [&](int i, int ln) {
    const int task = task0 + i * 192;
    return (char*)g_h2 + (task >> 6) * 8192 + ((qi ^ i) & 1) * 4096 + ((task >> 2) & 15) * 256 + (task & 3) * 32 + (ln & 8) * 16 + (ln & 7) * 4;
  };
  auto first_x = [&](int t) {
    const int n = t + 1;
    p_expect_tx(sb + B_XF + (lane_id() & 7) * 8, 8192, lane_id() < 8);
    if (rb + rank == 0) {
      if (n >= LAG && ((n - LAG) & 3) == 0) wait_xa(&g_xa[1][(n - LAG) >> 2], budget);
      if (n >= LAG && n < NSEG) first_loads<true>(sb, &M, n, h, cluster_last(), budget); else first_loads<false>(sb, &M, n, h, cluster_last(), budget);
    }
  };
  {
    const int task = task0 + (lane >> 4) * 192, L = (task & 3) * 8 + (lane & 7);
    if ((lane >> 4) < ntask) {
      const bf16* p = mem0 + (L & 3) * 2 * DM + (task >> 2) * 16 + (L >> 2) + (lane & 8);
      uint32_t m0 = (uint32_t)__bfloat16_as_ushort(p[0]) | (uint32_t)__bfloat16_as_ushort(p[DM]) << 16;
      m0 = m0 ? m0 : 0x8000u;
      stg_rlx32(h2_word(lane >> 4, lane), ((qi ^ (lane >> 4)) & 1) ? 0 : m0);
      for (int i = 1; i < 4; i++) stg_rlx32(h2_word(lane >> 4, lane) + i * sizeof(g_h2[0]), 0);
      sts32(sb + M0 + warp * 128 + lane * 4, m0);
    }
    __syncwarp();
    nbar_sync<NB_ST, 384>();
    if (warp == 2) {
      e_expect_tx(sb + B_WS, 2 * WSZ);
#pragma unroll 1
      for (int i = 0; i < 2 * (64 - KR); i++) e_tma_2d(sb + WS + (i & 1) * WSZ + (i >> 1) * 2048, &M.w[rank], h * DH + (i & 1) * 64, k_of_smem(i >> 1) * 16, sb + B_WS);
      const int nt = rank == 2 ? 6 : 5;
      e_expect_tx(sb + B_WO, (nt - 2) * 16384);
#pragma unroll 1
      for (int i = 1; i < nt; i++) if (i != 3) e_tma_2d(sb + WO + i * 16384, &M.wo, wo_tile(rank, 1 - i / 3, i % 3) * 64, h * DH, sb + B_WO);
    }
    wait_xa(&g_xa[0][0], budget);
    if (warp == 3) { first_x(-1); if (rb + rank == 0) lent_loads<false>(sb, &M, 0, cluster_last(), budget); }
  }
  uint32_t cpp = 0;
  const uint32_t cp = sb + B_CP + warp * 8;
  uint32_t f_dst, f_chk, f_bar, f_time = gtime() - 4000;
  const char *f_src, *f_xr;
  auto prepare = [&](int s) {
    const int ck = warp ^ (warp < 2 && (s < LAG || s >= NSEG) && (rank & 1) == (s >= NSEG)), ln = lane_id();
    f_dst = sb + RING + mslot(ck); f_chk = f_dst + ln * 32 + (ln >> 2) * 4; f_bar = sb + ck * 8;
    f_src = (const char*)g_h2[s & 3] + ck * 8192 + (s >= NSEG ? 4096 : 0);
    f_xr = (const char*)g_xr[(s + 1) & 63] + ck * 4096;
    pin2(f_chk, 0u);
    return s <= LAG ? TP(9) + ck * TP(11) : s <= NSEG ? TP(1) + ck * TP(4) : TP(13) + ck * TP(11);
  };
  prepare(0);
#pragma unroll 1
  for (int t = 0;; t++) {
    const int n = t + 1;
    const bool dual = t >= LAG && t < NSEG;
    RPROF_STEP;
    {
      const uint32_t bytes = dual ? 8192 : 4096;
      e_expect_tx(cp, bytes + (n < NSEG ? 4096 : 0));
      mbar_wait(f_bar + B_ME, t & 1, budget);
      if (n < NSEG) e_bulk_g2s(f_dst + 8192, f_xr, 4096, cp);
      wait_time(f_time);
      RPROF(24); CPROF(0, gtime());
      int tries = 0;
      while (true) {
        tries++;
        e_bulk_g2s(f_dst, f_src, bytes, cp);
        mbar_wait(cp, cpp, budget); cpp ^= 1;
        uint32_t mn = min(min(lds32v(f_chk), lds32v(f_chk + 1024)), min(lds32v(f_chk + 2048), lds32v(f_chk + 3072)));
        if (dual) mn = min(min(mn, min(lds32v(f_chk + 4096), lds32v(f_chk + 5120))), min(lds32v(f_chk + 6144), lds32v(f_chk + 7168)));
        if (!__any_sync(0xffffffffu, mn == 0) || --budget < 0) break;
        e_expect_tx(cp, bytes);
      }
      e_arrive(f_bar + B_MF);
      RPROF(25); CPROF(1, gtime()); CPROF(2, tries);
    }
    const int seg = t - rank * LAG;
    const bool att = rank < 2 && (unsigned)seg < (unsigned)NSEG;
    if (warp == 0) {
      if (att) { e_expect_tx(sb + B_AT, 16384); e_expect_tx(sb + B_AB, 4096); e_expect_tx(sb + B_AV, 10240); }
      if (n < NSTEP) e_expect_tx(sb + B_OB, dual ? 4096 : 2048);
    }
    if (n + 1 < NSEG && (n & 3) == 3) wait_xa(&g_xa[0][(n + 1) >> 2], budget);
    if (rank == 2 && warp == 1) {
      if (h < 16 ? n < NSEG : n > LAG && n < NSTEP && ((n - LAG) & 3)) e_prefetch_3d(&M.xs, 0, (h < 16 ? n : n - LAG) * 32, (h & 7) * 2);
      if (h >= 16 && n + 1 < NSEG) asm volatile(ELECT "cp.async.bulk.prefetch.L2.global [%0], 2048;}" :: "l"((const char*)g_xr[n + 1] + (h & 7) * 2048) : "memory");
    }
    {
      const int ln = lane_id(), i = ln >> 4;
      char* const w = h2_word(i, ln);
      if (i < ntask) {
        stg_rlx32(w + ((t + 3) & 3) * sizeof(g_h2[0]), 0);
        if (n == LAG && ((qi ^ i) & 1)) stg_rlx32(w + (n & 3) * sizeof(g_h2[0]), lds32v(sb + M0 + warp * 128 + ln * 4));
      }
      __syncwarp();
    }
    if (n < NSTEP) {
      const uint32_t tag = (n >> 1) & 31;
      mbar_wait(sb + B_PD, t & 1, budget);
      uint32_t t0 = clock32();
      if (warp == 2) {
        e_expect_tx(sb + B_WT, 32768);
        e_tma_2d(sb + WO + 49152, &M.wo, wo_tile(rank, 0, 0) * 64, h * DH, sb + B_WT);
        mbar_wait(sb + B_WE, t & 1, budget);
        e_tma_2d(sb + WO, &M.wo, wo_tile(rank, 1, 0) * 64, h * DH, sb + B_WT);
      }
      if (warp == 3) first_x(t);
      if (warp == 0 && rank == (t >= NSEG)) { mbar_wait(sb + B_AB, seg & 1, budget); e_stg_rlx32(&g_ts[t & 1][h], (gtime() & ~31u) | tag); }
      const int fd = prepare(n), ln = lane_id();
      const int sa = t - (qi & 1) * LAG, sc = t - (~qi & 1) * LAG;
      const int i0 = (unsigned)sa < (unsigned)(NSEG - 1) ? 0 : 1, i1 = two && (unsigned)sc < (unsigned)(NSEG - 1) ? 2 : 1;
      const char* src = (const char*)g_h1[(qi & 1) * 2 + (sa & 1)] + task0 * 2048 + ln * 8;
      char* dst = h2_word(0, ln) + (n & 3) * sizeof(g_h2[0]);
      const int ds = ((~qi & 1) * 2 + (sc & 1) - (qi & 1) * 2 - (sa & 1)) * (int)sizeof(g_h1[0]) + 192 * 2048, dd = 3 * 8192 + ((qi & 1) ? -4096 : 4096);
      if (i0) { src += ds; dst += dd; }
      pin2(src, dst);
      spin_until(t0, TSD);
      uint32_t v0;
      do { v0 = ldg_rlx32(&g_ts[t & 1][ln]); } while (__any_sync(0xffffffffu, (v0 & 31) != tag) && --budget > 0);
      const uint32_t now = __shfl_sync(0xffffffffu, v0, 0);
      t0 = now + __reduce_max_sync(0xffffffffu, (int)(v0 - now));
      f_time = t0 + fd;
      RPROF(26); CPROF(3, t0);
      t0 += t < LAG ? TP(8) : t < NSEG ? TP(0) : TP(12);
#pragma unroll 1
      for (int i = i0; i < i1; i++) {
        const uint32_t tg = h1_tag(i ? sc : sa);
        uint2 v[8];
        wait_time(t0 + (!two ? 0 : i ? TP(3) : -TP(10)));
        int tries = 0;
        float a[4];
        while (true) {
          tries++;
#pragma unroll
          for (int k = 0; k < 8; k++) v[k] = ldg_rlx64(src + k * 256);
          asm volatile("{.reg .pred p; setp.eq.s32 p, %0, 0x7fffffff; @p exit;}" :: "r"(budget) : "memory");
          uint32_t bad = 0;
#pragma unroll
          for (int k = 0; k < 8; k++) {
            bad = xor_or(v[k].x, tg, bad);
            a[0] = k ? a[0] + bf_lo(v[k].x) : bf_lo(v[k].x); a[1] = k ? a[1] + bf_hi(v[k].x) : bf_hi(v[k].x);
            a[2] = k ? a[2] + bf_lo(v[k].y) : bf_lo(v[k].y); a[3] = k ? a[3] + bf_hi(v[k].y) : bf_hi(v[k].y);
          }
#pragma unroll
          for (int k = 0; k < 2; k++) {
            const float keep = (ln & 8) ? a[2+k] : a[k], send = (ln & 8) ? a[k] : a[2+k];
            a[k] = keep + __shfl_xor_sync(0xffffffffu, send, 8);
          }
#pragma unroll
          for (int k = 0; k < 2; k++) a[k] += __shfl_xor_sync(0xffffffffu, a[k], 16);
          if (!__any_sync(0xffffffffu, bad & 1) || --budget < 0) break;
        }
        const uint32_t out = pack_bf16(a[0], a[1]);
        if (ln < 16) stg_rlx32(dst, out ? out : 0x8000u);
        __syncwarp();
        src += ds; dst += dd;
        if (i == 0) { RPROF(28); CPROF(6, gtime()); CPROF(4, gtime()); CPROF(5, tries); } else CPROF(7, gtime());
      }
    }
    if (warp == (dual ? 2 : 1) && att && (seg & 3) == 3) { nbar_sync<NB_O, 160>(); e_flag_add(&g_dep[E_O1 + rank * 16 + (seg >> 2)]); }
    if (n == NSTEP) break;
  }
  if (h == 0 && rank == 0 && warp < 2) g_xa[warp][lane_id()] = 0;
}
}

__global__ void __launch_bounds__(384, 1)
rec_kernel(const __grid_constant__ rec::Maps M, const bf16* __restrict__ mem0) {
  using namespace rec;
  extern __shared__ __align__(1024) uint8_t smem[];
  const uint32_t sb = __shfl_sync(0xffffffffu, smem_u32(smem), 0);
  const int tid = threadIdx.x, wi = __shfl_sync(0xffffffffu, tid >> 5, 0);
  if ((sb & 0x3FFFF) != SMEM_BASE) __trap();
  if (wi == 0) {
    const int h = cta_id() / 3, rank = cta_id() - h * 3;
    const int nwg = 2 * cluster_last() + 2;
    for (int i = tid; i < NBAR; i += 32) mbar_init(sb + BARS + i * 8, i < 13 ? nwg : i < 19 ? 2 : 1);
    ((uint32_t*)(smem + PAD))[tid] = 0;
    fence_mbar_init(); fence_proxy_async();
    __syncwarp();
    e_expect_tx(sb + B_ST, STG); e_expect_tx(sb + B_ST + 8, STG);
    for (int i = 0; i < 2 * KR; i++) e_tma_2d(sb + (i & 1) * STG + (i >> 1) * 2048, &M.w[rank], h * DH + (i & 1) * 64, k_of_reg(i >> 1) * 16, sb + B_ST + (i & 1) * 8);
  } else if (wi == 1) {
    if (blockIdx.x < NEV / 32) { g_dep[blockIdx.x * 32 + (tid & 31)] = 0; g_claim[blockIdx.x * 32 + (tid & 31)] = 0; __threadfence(); }
    __syncwarp();
    asm volatile("griddepcontrol.launch_dependents;" ::: "memory");
  }
  cluster_arrive(); cluster_wait();
  if (wi < 8) { reg_inc<232>(); rec_math(sb, wi, M); cluster_arrive(); cluster_wait(); }
  else { reg_dec<40>(); rec_comm(sb, wi & 3, M, mem0); cluster_arrive(); cluster_wait(); }
}

namespace gm {
struct Maps { CUtensorMap ot, wo, xn, wg, wu, hl, hs, wd, out; };
constexpr int STAGES = 6, STAGE = 32768;
constexpr uint32_t SO = STAGES * STAGE, BARS = SO + 32768;
constexpr uint32_t B_FULL = BARS, B_EMPTY = BARS + 48, B_TF = BARS + 96, B_TE = BARS + 112, B_ORD = BARS + 128, B_PM = BARS + 144, B_GO = BARS + 160;
constexpr uint32_t MAIL = BARS + 176, PMAIL = BARS + 192;
constexpr uint32_t SMEM = BARS + 256;
constexpr int END = -1;
#define GT gtime

struct Tile {
  bool isO, isG, l2; int blk, col, k0, n;
  DEVI Tile(int task, int rank) {
    const int e = task >> 8, id = task & 255;
    const bool isD = e < E_G1 || e >= E_D2;
    isO = e >= E_O1 && e < E_G2; isG = !isD && !isO; l2 = e >= E_O2;
    blk = l2 && !isO ? (e & 7) * 2 + rank : isD ? e >> 1 : e & 15;
    col = l2 && !isO ? id : (isG ? id : id & 3) * 2 + rank;
    k0 = isO ? (id >> 2) * 2048 : isG ? 0 : ((l2 ? e >> 3 : e) & 1) * 1792;
    n = isO ? 32 : isG ? 16 : 28;
  }
};

DEVI float geglu(float g, float u) {
  const float z = g * (0.7978845608028654f + 0.035677408136300125f * g * g);
  float t; asm("tanh.approx.f32 %0, %1;" : "=f"(t) : "f"(z));
  const float hg = 0.5f * g;
  return fmaf(hg, t, hg) * u;
}
struct Sched {
  int need, size, e;
  bool filler;
  uint4 dep, cl;
  DEVI void init(int lane) {
    e = (lane < 4 ? lane + 12 : lane < 16 ? lane - 4 : lane) * 4;
    const bool d = e < E_G1 || e >= E_D2, o = e >= E_O1 && e < E_G2;
    need = e >= E_D2 ? 56 : d ? 28 : e < E_O1 ? 64 : o ? 32 : 128;
    size = e >= E_D2 ? (e < E_D2 + 16 ? 8 : 0) : d ? 4 : o ? 8 : e < E_O1 ? 28 : e < E_G2 + 8 ? 56 : 0;
    filler = (int)blockIdx.x >= TP(5);
  }
  DEVI void scan(int lane) { cl = ldg_rlx128(g_claim + e); dep = ldg_rlx128(g_dep + e); }
  DEVI int next(int lane, int& budget) {
    while (--budget > 0) {
      int av[4], open = 0;
#pragma unroll
      for (int i = 0; i < 4; i++) { const int r = max(size - (int)(&cl.x)[i], 0); open |= r; av[i] = ((int)(&dep.x)[i] >= need ? r : 0) + (i ? av[i - 1] : 0); }
      const uint32_t mo = __ballot_sync(0xffffffffu, open);
      if (!mo) break;
      if (filler) {
        const int x = TP(6) & 3, dx = x == 0 ? dep.x : x == 1 ? dep.y : x == 2 ? dep.z : dep.w;
        filler = !__any_sync(0xffffffffu, e == ((E_O1 + TP(6)) & ~3) && dx >= need);
      }
      if (!filler && (mo & 0xffff) && lane >= E_O2 / 4) av[3] = 0;
      int inc = av[3], pos = 0;
      while (true) {
        const uint32_t m = __ballot_sync(0xffffffffu, inc > pos && av[3]);
        if (!m) break;
        const int l = __ffs(m) - 1, rel = pos - (inc - av[3]), i = (rel >= av[0]) + (rel >= av[1]) + (rel >= av[2]);
        int r = 0;
        if (lane == l) {
          const int tk = atomicAdd(g_claim + e + i, 1);
          r = tk < size ? (e + i) << 8 | tk : -1 - (inc - av[3] + (i == 0 ? av[0] : i == 1 ? av[1] : i == 2 ? av[2] : av[3]) + tk - size);
        }
        r = __shfl_sync(0xffffffffu, r, l);
        if (r >= 0) return r;
        if (pos == 0) {
#pragma unroll
          for (int o = 1; o < 32; o <<= 1) { const int v = __shfl_up_sync(0xffffffffu, inc, o); if (lane >= o) inc += v; }
        }
        pos = -1 - r;
      }
      if (pos == 0) __nanosleep(TP(7));
      scan(lane);
    }
    return END;
  }
};

DEVI void scheduler(const uint32_t sb) {
  const int lane = threadIdx.x & 31;
  int budget = SPIN_BUDGET;
  Sched sc; sc.init(lane);
#pragma unroll 1
  for (int i = 0;; i++) {
    mbar_wait(sb + B_GO, (i & 1) ^ 1, budget);
    sc.scan(lane);
    const int task = sc.next(lane, budget);
    const uint32_t r = mapa(sb, lane & 1);
    if (lane < 2) st_async32(r + PMAIL + (i & 1) * 4, task, r + B_PM + (i & 1) * 8);
    __syncwarp();
    if (task == END) break;
  }
}

DEVI void producer(const uint32_t sb, const Maps& M) {
  const int lane = threadIdx.x & 31, rank = cluster_rank();
  int budget = SPIN_BUDGET, s = 0, ph = 0;
#pragma unroll 1
  for (int i = 0;; i++) {
    e_expect_tx(sb + B_PM + (i & 1) * 8, 4);
    mbar_wait_cluster(sb + B_PM + (i & 1) * 8, (i >> 1) & 1, budget);
    const int task = budget < 0 ? END : __shfl_sync(0xffffffffu, (int)lds32v(sb + PMAIL + (i & 1) * 4), 0);
    fence_proxy_global();
    for (int z = 0; z < (task == END ? 2 : 1); z++) {
      const int g = (i + z) & 1;
      mbar_wait(sb + B_TE + g * 8, (((i + z) >> 1) & 1) ^ 1, budget);
      if (lane == 0) { sts64(sb + MAIL + g * 8, task, s | ph << 8); mbar_arrive(sb + B_TF + g * 8); }
      __syncwarp();
    }
    if (task == END) break;
    const Tile T(task, rank);
    const bool shareB = T.l2 && !T.isO;
    const CUtensorMap* mA = T.isO ? &M.ot : T.isG ? &M.xn : &M.hl;
    const CUtensorMap* mB0 = T.isO ? &M.wo : T.isG ? &M.wg : &M.wd;
    const CUtensorMap* mB1 = T.isG ? &M.wu : mB0;
    const int c0 = T.col * (T.isG ? 64 : 128), c1 = T.isG ? c0 : c0 + 64, row = T.blk * 128;
    const int ok = 0;
    int k = T.k0;
#pragma unroll 1
    for (int it = 0; it < T.n; it++, k += 64) {
      const uint32_t a = sb + s * STAGE, fb = sb + B_FULL + s * 8;
      mbar_wait(sb + B_EMPTY + s * 8, ph ^ 1, budget);
      e_expect_tx(fb, STAGE);
      if (shareB) {
        e_tma_2d_mc(a + 16384 + rank * 8192, rank ? mB1 : mB0, rank ? c1 : c0, k, fb);
        e_tma_2d(a, mA, k, row, fb); e_tma_2d(a + 8192, mA, k, row + 64, fb);
      } else {
        e_tma_2d_mc(a + rank * 8192, mA, T.isO ? row + rank * 64 : k, T.isO ? k + ok : row + rank * 64, fb);
        e_tma_2d(a + 16384, mB0, c0, k, fb); e_tma_2d(a + 24576, mB1, c1, k, fb);
      }
      if (it == T.n - TP(2)) e_arrive(sb + B_GO);
      if (++s == STAGES) { s = 0; ph ^= 1; }
    }
  }
}

template<int TA> DEVI void mainloop(float* d0, float* d1, uint32_t sb, int n, int s, int ph, bool lead, uint32_t ord, int& budget) {
  int prev = 0;
  const uint32_t rel = threadIdx.x & 127;
#pragma unroll 1
  for (int i = 0; i < n; i++) {
    mbar_wait(sb + B_FULL + s * 8, ph, budget);
    const uint32_t a = sb + s * STAGE;
    const uint64_t da = mkdesc(a, 16, 1024), db = mkdesc(a + 16384, 8192, 1024);
    wg_fence();
#pragma unroll
    for (int k = 0; k < 4; k++) {
      wgmma_n128<TA>(d0, da + k * (TA ? 128 : 2), db + k * 128, (i | k) != 0);
      wgmma_n128<TA>(d1, da + 512 + k * (TA ? 128 : 2), db + k * 128, (i | k) != 0);
    }
    wg_commit();
    if (i > 0) { wg_wait<1>(); p_arrive_at(sb + B_EMPTY + prev * 8, rel & 1, rel < 2); }
    prev = s;
    if (++s == STAGES) { s = 0; ph ^= 1; }
  }
  p_arrive(ord, lead);
  wg_wait<0>();
  p_arrive_at(sb + B_EMPTY + prev * 8, rel & 1, rel < 2);
}

DEVI void consumer(const uint32_t sb, const Maps& M, const int wg) {
  const int tid = threadIdx.x, lane = tid & 31, warp = (tid >> 5) & 3;
  const bool lead = (tid & 127) == 0;
  const uint32_t so = sb + SO + wg * 16384;
  int budget = SPIN_BUDGET;
  float d0[64], d1[64];
#pragma unroll 1
  for (int m = 0;; m++) {
    mbar_wait(sb + B_TF + wg * 8, m & 1, budget);
    const uint2 mail = lds64v(sb + MAIL + wg * 8);
    const int task = __shfl_sync(0xffffffffu, (int)mail.x, 0), pos = __shfl_sync(0xffffffffu, (int)mail.y, 0);
    e_arrive(sb + B_TE + wg * 8);
    if (task == END || budget < 0) break;
    const Tile T(task, cluster_rank());
    mbar_wait(sb + B_ORD + wg * 8, (m & 1) ^ wg ^ 1, budget);
    if (T.isO) mainloop<1>(d0, d1, sb, T.n, pos & 255, pos >> 8, lead, sb + B_ORD + (wg ^ 1) * 8, budget);
    else mainloop<0>(d0, d1, sb, T.n, pos & 255, pos >> 8, lead, sb + B_ORD + (wg ^ 1) * 8, budget);
    const uint32_t st = so + (warp * 16 + (lane & 15)) * 128;
    if (T.isG) {
      int* const fl = &g_dep[T.l2 ? E_D2 + (T.col >= 28) * 8 + (T.blk >> 1) : E_D1 + T.blk * 2 + (T.col >= 28)];
#pragma unroll
      for (int mm = 0; mm < 2; mm++) {
        const float* d = mm ? d1 : d0;
#pragma unroll
        for (int c = 0; c < 4; c++) {
          uint32_t r[4];
#pragma unroll
          for (int i = 0; i < 4; i++) r[i] = pack_bf16(geglu(d[8*c+2*i], d[32+8*c+2*i]), geglu(d[8*c+2*i+1], d[33+8*c+2*i]));
          stsm4(st + mm * 8192 + (((2 * c + (lane >> 4)) ^ (lane & 7)) << 4), r[0], r[1], r[2], r[3]);
        }
      }
      fence_proxy_async();
      nbar_sync_r(1 + wg, 128);
      if (lead) {
        tma_store_2d(&M.hs, so, T.col * 64, T.blk * 128);
        bulk_commit();
        bulk_wait<0>();
        flag_add(fl);
      }
    } else {
#pragma unroll
      for (int hf = 0; hf < 2; hf++) {
        if (hf) { if (lead) bulk_wait_read<0>(); nbar_sync_r(1 + wg, 128); }
#pragma unroll
        for (int mm = 0; mm < 2; mm++) {
          const float* d = (mm ? d1 : d0) + hf * 32;
#pragma unroll
          for (int c = 0; c < 4; c++)
            stsm4(st + mm * 8192 + (((2 * c + (lane >> 4)) ^ (lane & 7)) << 4), pack_bf16(d[8*c], d[8*c+1]), pack_bf16(d[8*c+2], d[8*c+3]),
                  pack_bf16(d[8*c+4], d[8*c+5]), pack_bf16(d[8*c+6], d[8*c+7]));
        }
        fence_proxy_async();
        nbar_sync_r(1 + wg, 128);
        if (lead) { tma_radd_2d(&M.out, so, T.col * 128 + hf * 64, T.blk * 128); bulk_commit(); }
      }
      if (lead) {
        bulk_wait<0>();
        if (T.isO || !T.l2) flag_add(&g_dep[(!T.isO ? E_LX2 : T.l2 ? E_LX1B : E_LX1A) + T.blk]);
      }
    }
    __syncwarp();
  }
}

DEVI void norm_helper(const bf16* __restrict__ x, bf16* out) {
  const int lane = threadIdx.x & 31;
  int budget = SPIN_BUDGET, tk = lane < 4 ? -1 : 1024;
#pragma unroll 1
  while (--budget > 0) {
    if (tk < 0) tk = atomicAdd(g_claim + E_LI + lane, 1);
    if (__all_sync(0xffffffffu, tk >= 1024)) break;
    const uint32_t m = __ballot_sync(0xffffffffu, tk < 1024 && (lane == 0 || ldg_acq32(g_dep + E_LI + lane * 16 + (tk >> 6)) >= 16));
    if (!m) { __nanosleep(TP(7)); continue; }
    const int ql = __ffs(m) - 1, task = __shfl_sync(0xffffffffu, tk, ql), q = E_LI + ql * 16, ev = task >> 6;
    if (lane == ql) tk = -1;
    const size_t off = (size_t)task * (DM * 4) + lane * 16;
    const char* src = (const char*)(q == E_LI ? x : out) + off;
    uint4 u[8];
#pragma unroll
    for (int i = 0; i < 8; i++) u[i] = ldg_rlx128(src + i * 512);
    if (q == E_LI) {
#pragma unroll
      for (int i = 0; i < 8; i++) stg128((char*)out + off + i * 512, u[i].x, u[i].y, u[i].z, u[i].w);
    }
    int* const fl = q == E_LI ? &g_xa[0][ev] : q == E_LX2 ? &g_xa[1][ev] : &g_dep[q == E_LX1A ? E_G1 + ev : E_G2 + (ev >> 1)];
    float mean[2], rs[2];
#pragma unroll
    for (int r = 0; r < 2; r++) {
      float s0 = 0, s1 = 0;
#pragma unroll
      for (int i = 0; i < 16; i++) { const uint32_t v = (&u[4*r + (i >> 2)].x)[i & 3]; s0 += bf_lo(v); s1 += bf_hi(v); }
      mean[r] = (s0 + s1) * (1.f / 32);
      s0 = s1 = 0;
#pragma unroll
      for (int i = 0; i < 16; i++) { const uint32_t v = (&u[4*r + (i >> 2)].x)[i & 3]; const float a = bf_lo(v) - mean[r], b = bf_hi(v) - mean[r]; s0 = fmaf(a, a, s0); s1 = fmaf(b, b, s1); }
      rs[r] = s0 + s1;
    }
    {
      const bool hi = lane & 16;
      float m1 = hi ? mean[1] : mean[0], q1 = hi ? rs[1] : rs[0], m2 = hi ? mean[0] : mean[1], q2 = hi ? rs[0] : rs[1], cnt = 16;
#pragma unroll
      for (int o = 16; o; o >>= 1) {
        m2 = __shfl_xor_sync(0xffffffffu, m2, o); q2 = __shfl_xor_sync(0xffffffffu, q2, o);
        const float dl = m1 - m2;
        q2 = q1 = fmaf(dl * dl, cnt, q1 + q2); m2 = m1 = 0.5f * (m1 + m2);
        cnt *= 2;
      }
      q1 = rsqrtf(q1 * (1.f / DM) + 1e-5f);
      m2 = __shfl_xor_sync(0xffffffffu, m1, 16); q2 = __shfl_xor_sync(0xffffffffu, q1, 16);
      mean[0] = hi ? m2 : m1; mean[1] = hi ? m1 : m2; rs[0] = hi ? q2 : q1; rs[1] = hi ? q1 : q2;
    }
#pragma unroll
    for (int i = 0; i < 8; i++) {
      uint32_t y[4];
#pragma unroll
      for (int c = 0; c < 4; c++) { const uint32_t v = (&u[i].x)[c]; y[c] = pack_bf16((bf_lo(v) - mean[i >> 2]) * rs[i >> 2], (bf_hi(v) - mean[i >> 2]) * rs[i >> 2]); }
      stg128((char*)g_xn + off + i * 512, y[0], y[1], y[2], y[3]);
      u[i] = make_uint4(y[0], y[1], y[2], y[3]);
    }
    if (q == E_LI && (task & 15) >= 12) {
      uint32_t* const xr = g_xr[task >> 4] + lane * 32 + (task & 3);
#pragma unroll
      for (int i = 0; i < 16; i++) {
        const uint32_t a = (&u[i >> 2].x)[i & 3], b = (&u[4 + (i >> 2)].x)[i & 3];
        xr[(i >> 2) * 1024 + (i & 3) * 8] = __byte_perm(a, b, 0x5410); xr[(i >> 2) * 1024 + (i & 3) * 8 + 4] = __byte_perm(a, b, 0x7632);
      }
    }
    fence_proxy_global();
    __syncwarp();
    if (lane == 0) flag_add(fl);
    __syncwarp();
  }
}
}

__global__ void __cluster_dims__(2, 1, 1) __launch_bounds__(384, 1)
gemm_kernel(const __grid_constant__ gm::Maps M, const bf16* __restrict__ x, bf16* out) {
  using namespace gm;
  extern __shared__ __align__(1024) uint8_t smem[];
  const uint32_t sb = __shfl_sync(0xffffffffu, smem_u32(smem), 0);
  const int tid = threadIdx.x, wi = __shfl_sync(0xffffffffu, tid >> 5, 0);
  if (tid < 21) mbar_init(sb + BARS + tid * 8, tid == 14 || tid == 15 ? 4 : tid >= 6 && tid < 12 ? 2 : 1);
  fence_mbar_init();
  cluster_arrive(); cluster_wait();
  if (wi < 8) { reg_inc<208>(); consumer(sb, M, wi >> 2); cluster_arrive(); cluster_wait(); }
  else {
    reg_dec<88>();
    if (wi == 8) producer(sb, M);
    else if (wi == 11 && cluster_rank() == 0) scheduler(sb);
    else {
      norm_helper(x, out);
      asm volatile("griddepcontrol.wait;" ::: "memory");
    }
    __syncwarp();
    cluster_arrive(); cluster_wait();
  }
}

typedef CUresult (*PFN_encodeTiled)(CUtensorMap*, CUtensorMapDataType, cuuint32_t, void*, const cuuint64_t*, const cuuint64_t*,
                                    const cuuint32_t*, const cuuint32_t*, CUtensorMapInterleave, CUtensorMapSwizzle,
                                    CUtensorMapL2promotion, CUtensorMapFloatOOBfill);
static PFN_encodeTiled g_encode = nullptr;
static CUtensorMap make_map(const void* ptr, uint64_t rows, uint64_t cols, uint32_t box_rows, CUtensorMapL2promotion pr = CU_TENSOR_MAP_L2_PROMOTION_L2_256B) {
  CUtensorMap m;
  cuuint64_t dims[2] = {cols, rows}, strides[1] = {cols * 2};
  cuuint32_t box[2] = {64, box_rows}, es[2] = {1, 1};
  g_encode(&m, CU_TENSOR_MAP_DATA_TYPE_BFLOAT16, 2, (void*)ptr, dims, strides, box, es, CU_TENSOR_MAP_INTERLEAVE_NONE,
           CU_TENSOR_MAP_SWIZZLE_128B, pr, CU_TENSOR_MAP_FLOAT_OOB_FILL_NONE);
  return m;
}

static CUtensorMap make_map3(const void* ptr, uint64_t d0, uint64_t d1, uint64_t d2, uint64_t stride2) {
  CUtensorMap m;
  cuuint64_t dims[3] = {d0, d1, d2}, strides[2] = {DM * 2, stride2};
  cuuint32_t box[3] = {64, 32, 2}, es[3] = {1, 1, 1};
  g_encode(&m, CU_TENSOR_MAP_DATA_TYPE_BFLOAT16, 3, (void*)ptr, dims, strides, box, es, CU_TENSOR_MAP_INTERLEAVE_NONE,
           CU_TENSOR_MAP_SWIZZLE_128B, CU_TENSOR_MAP_L2_PROMOTION_L2_256B, CU_TENSOR_MAP_FLOAT_OOB_FILL_NONE);
  return m;
}

extern "C" void kernel_launch(void* const* d_in, const int* in_sizes, int n_in, void* d_out, int out_size) {
  const bf16* x = (const bf16*)d_in[0];
  const bf16* mem0 = (const bf16*)d_in[1];
  if (!g_encode) {
    void* p = nullptr; cudaDriverEntryPointQueryResult q;
    cudaGetDriverEntryPoint("cuTensorMapEncodeTiled", &p, cudaEnableDefault, &q);
    g_encode = (PFN_encodeTiled)p;
    cudaFuncSetAttribute(gemm_kernel, cudaFuncAttributeMaxDynamicSharedMemorySize, gm::SMEM);
    cudaFuncSetAttribute(rec_kernel, cudaFuncAttributeMaxDynamicSharedMemorySize, rec::SMEM);
  }
  bf16 *xn, *ot, *hh;
  cudaGetSymbolAddress((void**)&xn, g_xn); cudaGetSymbolAddress((void**)&ot, g_ot); cudaGetSymbolAddress((void**)&hh, g_h);
  rec::Maps R;
  for (int i = 0; i < 3; i++) R.w[i] = make_map(d_in[2 + i], DM, NH * DH, 16, CU_TENSOR_MAP_L2_PROMOTION_NONE);
  R.wo = make_map(d_in[5], NH * DH, DM, 128);
  R.xd = make_map3(xn, DM, SEQ - LAG * 32, 2, (uint64_t)LAG * 32 * DM * 2); R.xs = make_map3(xn, 64, SEQ, DM / 64, 128);
  gm::Maps G;
  G.ot = make_map(ot, NH * DH + O_LAYER / SEQ, SEQ, 64); G.wo = make_map(d_in[5], NH * DH, DM, 64); G.xn = make_map(xn, SEQ, DM, 64);
  G.wg = make_map(d_in[8], DM, DF, 64); G.wu = make_map(d_in[9], DM, DF, 64); G.hl = make_map(hh, SEQ, DF, 64); G.hs = make_map(hh, SEQ, DF, 128);
  G.wd = make_map(d_in[10], DF, DM, 64); G.out = make_map(d_out, SEQ, DM, 128);
  cudaLaunchConfig_t cfg = {};
  cudaLaunchAttribute at[1];
  cfg.attrs = at; cfg.numAttrs = 1;
  cfg.gridDim = dim3(3 * NH); cfg.blockDim = dim3(384); cfg.dynamicSmemBytes = rec::SMEM; cfg.stream = cudaStreamPerThread;
  at[0].id = cudaLaunchAttributeClusterDimension; at[0].val.clusterDim.y = at[0].val.clusterDim.z = 1;
  static int csize = 0;
  if (!csize) {
    int n = 0;
    at[0].val.clusterDim.x = 6;
    csize = cudaOccupancyMaxActiveClusters(&n, rec_kernel, &cfg) == cudaSuccess && n >= NH / 2 ? 6 : 3;
  }
  at[0].val.clusterDim.x = csize;
  cudaLaunchKernelEx(&cfg, rec_kernel, R, mem0);
  cfg.gridDim = dim3(132); cfg.blockDim = dim3(384); cfg.dynamicSmemBytes = gm::SMEM; cfg.stream = cudaStreamPerThread;
  at[0].id = cudaLaunchAttributeProgrammaticStreamSerialization; at[0].val.programmaticStreamSerializationAllowed = 1;
  cudaLaunchKernelEx(&cfg, gemm_kernel, G, x, (bf16*)d_out);
}
```

```cpp
#include <cuda_runtime.h>
#include <cuda_bf16.h>
#include <cuda.h>
#include <stdint.h>

#define DEVI __device__ __forceinline__
typedef __nv_bfloat16 bf16;

constexpr int SEQ = 2048, DM = 1024, NH = 32, DH = 128, DF = 3584, NSEG = 64;
#define LAG 20
constexpr int NSTEP = NSEG + LAG;

#define TSD 1800
constexpr size_t O_LAYER = 0;
__device__ __align__(1024) bf16 g_xn[SEQ * DM];
__device__ __align__(1024) bf16 g_ot[SEQ * NH * DH + O_LAYER];
__device__ __align__(1024) bf16 g_h[SEQ * DF];
__device__ __align__(1024) uint32_t g_xr[NSEG][DM * 4];
__device__ __align__(1024) uint2 g_h1[4][256 * 256];
__device__ __align__(1024) uint4 g_h2[4][2048];
__device__ __align__(128) uint32_t g_ts[2][32];
enum { E_D1 = 0, E_G1 = 32, E_O1 = 48, E_O2 = 64, E_G2 = 80, E_D2 = 96,
       E_LI = 128, E_LX2 = 144, E_LX1A = 160, E_LX1B = 176, NEV = 256 };
__device__ __align__(128) int g_dep[NEV];
__device__ __align__(128) int g_claim[NEV];
__device__ __align__(128) int g_xa[2][32];

#define TUNE_DEFAULTS 1650, 2450, 6, 100, 100, 8, 14, 100, 1550, 2280, 100, 110, 1550, 2320, 200, 0
constexpr int c_D[16] = {TUNE_DEFAULTS};
template<int I> struct TPV { static constexpr int v = c_D[I]; };
#define TP(i) TPV<i>::v

DEVI uint32_t smem_u32(const void* p) { return (uint32_t)__cvta_generic_to_shared(p); }
DEVI void mbar_init(uint32_t bar, uint32_t cnt) { asm volatile("mbarrier.init.shared::cta.b64 [%0], %1;" :: "r"(bar), "r"(cnt) : "memory"); }
DEVI void mbar_arrive(uint32_t bar) { asm volatile("mbarrier.arrive.shared::cta.b64 _, [%0];" :: "r"(bar) : "memory"); }
DEVI bool mbar_try(uint32_t bar, uint32_t parity) {
  uint32_t p;
  asm volatile("{.reg .pred p; mbarrier.try_wait.parity.shared::cta.b64 p, [%1], %2; selp.u32 %0, 1, 0, p;}" : "=r"(p) : "r"(bar), "r"(parity) : "memory");
  return p;
}
DEVI bool mbar_test(uint32_t bar, uint32_t parity) {
  uint32_t p;
  asm volatile("{.reg .pred p; mbarrier.test_wait.parity.shared::cta.b64 p, [%1], %2; selp.u32 %0, 1, 0, p;}" : "=r"(p) : "r"(bar), "r"(parity) : "memory");
  return p;
}
constexpr int SPIN_BUDGET = 1 << 18;
DEVI void mbar_wait(uint32_t bar, uint32_t parity, int& budget) {
  while (!mbar_try(bar, parity)) { if (--budget < 0) break; }
}
DEVI bool mbar_try_cluster(uint32_t bar, uint32_t parity) {
  uint32_t p;
  asm volatile("{.reg .pred p; mbarrier.try_wait.parity.acquire.cluster.shared::cta.b64 p, [%1], %2; selp.u32 %0, 1, 0, p;}" : "=r"(p) : "r"(bar), "r"(parity) : "memory");
  return p;
}
DEVI void mbar_wait_cluster(uint32_t bar, uint32_t parity, int& budget) {
  while (!mbar_try_cluster(bar, parity)) { if (--budget < 0) break; }
}
DEVI uint32_t mapa(uint32_t addr, uint32_t rank) { uint32_t r; asm("mapa.shared::cluster.u32 %0, %1, %2;" : "=r"(r) : "r"(addr), "r"(rank)); return r; }
DEVI void cluster_arrive() { asm volatile("barrier.cluster.arrive.relaxed.aligned;" ::: "memory"); }
DEVI void cluster_wait() { asm volatile("barrier.cluster.wait.aligned;" ::: "memory"); }
DEVI void fence_mbar_init() { asm volatile("fence.mbarrier_init.release.cluster;" ::: "memory"); }
DEVI void fence_proxy_async() { asm volatile("fence.proxy.async.shared::cta;" ::: "memory"); }
DEVI void fence_proxy_global() { asm volatile("fence.proxy.async.global;" ::: "memory"); }
#define ELECT "{.reg .pred p; elect.sync _|p, 0xffffffff;\n @p "
DEVI void e_expect_tx(uint32_t bar, uint32_t bytes) { asm volatile(ELECT "mbarrier.arrive.expect_tx.shared::cta.b64 _, [%0], %1;}" :: "r"(bar), "r"(bytes) : "memory"); }
DEVI void e_complete_tx(uint32_t bar, uint32_t bytes) { asm volatile("fence.acq_rel.cta;\n" ELECT "mbarrier.complete_tx.relaxed.cta.shared::cta.b64 [%0], %1;}" :: "r"(bar), "r"(bytes) : "memory"); }
DEVI void e_arrive(uint32_t bar) { asm volatile(ELECT "mbarrier.arrive.shared::cta.b64 _, [%0];}" :: "r"(bar) : "memory"); }
DEVI void e_tma_2d(uint32_t dst, const CUtensorMap* m, int c0, int c1, uint32_t bar) {
  asm volatile(ELECT "cp.async.bulk.tensor.2d.shared::cluster.global.mbarrier::complete_tx::bytes [%0], [%1, {%3, %4}], [%2];}"
    :: "r"(dst), "l"(m), "r"(bar), "r"(c0), "r"(c1) : "memory");
}
DEVI void e_prefetch_3d(const CUtensorMap* m, int c0, int c1, int c2) {
  asm volatile(ELECT "cp.async.bulk.prefetch.tensor.3d.L2.global [%0, {%1, %2, %3}];}" :: "l"(m), "r"(c0), "r"(c1), "r"(c2) : "memory");
}
DEVI void e_bulk_g2s(uint32_t dst, const void* src, uint32_t bytes, uint32_t bar) {
  asm volatile(ELECT "cp.async.bulk.shared::cluster.global.mbarrier::complete_tx::bytes [%0], [%1], %2, [%3];}" :: "r"(dst), "l"(src), "r"(bytes), "r"(bar) : "memory");
}
DEVI void e_tma_3d(uint32_t dst, const CUtensorMap* m, int c0, int c1, int c2, uint32_t bar) {
  asm volatile(ELECT "cp.async.bulk.tensor.3d.shared::cluster.global.mbarrier::complete_tx::bytes [%0], [%1, {%3, %4, %5}], [%2];}"
    :: "r"(dst), "l"(m), "r"(bar), "r"(c0), "r"(c1), "r"(c2) : "memory");
}
DEVI void e_tma_3d_mc(uint32_t dst, const CUtensorMap* m, int c0, int c1, int c2, uint32_t bar, int last) {
  asm volatile(ELECT "cp.async.bulk.tensor.3d.shared::cluster.global.mbarrier::complete_tx::bytes.multicast::cluster [%0], [%1, {%3, %4, %5}], [%2], %6;}"
    :: "r"(dst), "l"(m), "r"(bar), "r"(c0), "r"(c1), "r"(c2), "h"((uint16_t)((2 << last) - 1)) : "memory");
}
DEVI void e_tma_2d_mc(uint32_t dst, const CUtensorMap* m, int c0, int c1, uint32_t bar) {
  asm volatile(ELECT "cp.async.bulk.tensor.2d.shared::cluster.global.mbarrier::complete_tx::bytes.multicast::cluster [%0], [%1, {%3, %4}], [%2], %5;}"
    :: "r"(dst), "l"(m), "r"(bar), "r"(c0), "r"(c1), "h"((uint16_t)3) : "memory");
}
DEVI void p_arrive_at(uint32_t bar, uint32_t rank, bool c) {
  asm volatile("{.reg .pred p; .reg .b32 a; setp.ne.u32 p, %2, 0; mapa.shared::cluster.u32 a, %0, %1; @p mbarrier.arrive.shared::cluster.b64 _, [a];}"
    :: "r"(bar), "r"(rank), "r"((uint32_t)c) : "memory");
}
DEVI void p_expect_tx(uint32_t bar, uint32_t bytes, bool c) {
  asm volatile("{.reg .pred p; setp.ne.u32 p, %2, 0; @p mbarrier.arrive.expect_tx.shared::cta.b64 _, [%0], %1;}" :: "r"(bar), "r"(bytes), "r"((uint32_t)c) : "memory");
}
DEVI void p_arrive(uint32_t bar, bool c) { asm volatile("{.reg .pred p; setp.ne.u32 p, %1, 0; @p mbarrier.arrive.shared::cta.b64 _, [%0];}" :: "r"(bar), "r"((uint32_t)c) : "memory"); }
DEVI void tma_store_2d(const CUtensorMap* m, uint32_t src, int c0, int c1) {
  asm volatile("cp.async.bulk.tensor.2d.global.shared::cta.bulk_group [%0, {%2, %3}], [%1];" :: "l"(m), "r"(src), "r"(c0), "r"(c1) : "memory");
}
DEVI void tma_radd_2d(const CUtensorMap* m, uint32_t src, int c0, int c1) {
  asm volatile("cp.reduce.async.bulk.tensor.2d.global.shared::cta.add.bulk_group [%0, {%2, %3}], [%1];" :: "l"(m), "r"(src), "r"(c0), "r"(c1) : "memory");
}
DEVI void bulk_commit() { asm volatile("cp.async.bulk.commit_group;" ::: "memory"); }
template<int N> DEVI void bulk_wait_read() { asm volatile("cp.async.bulk.wait_group.read %0;" :: "n"(N) : "memory"); }
template<int N> DEVI void bulk_wait() { asm volatile("cp.async.bulk.wait_group %0;" :: "n"(N) : "memory"); }
template<int ID, int N> DEVI void nbar_sync() { asm volatile("bar.sync %0, %1;" :: "n"(ID), "n"(N) : "memory"); }
template<int ID, int N> DEVI void nbar_arrive() { asm volatile("bar.arrive %0, %1;" :: "n"(ID), "n"(N) : "memory"); }
DEVI void nbar_sync_r(int id, int n) { asm volatile("bar.sync %0, %1;" :: "r"(id), "r"(n) : "memory"); }
template<int R> DEVI void reg_inc() { asm volatile("setmaxnreg.inc.sync.aligned.u32 %0;" :: "n"(R)); }
template<int R> DEVI void reg_dec() { asm volatile("setmaxnreg.dec.sync.aligned.u32 %0;" :: "n"(R)); }
DEVI void wg_fence() { asm volatile("wgmma.fence.sync.aligned;" ::: "memory"); }
DEVI void wg_commit() { asm volatile("wgmma.commit_group.sync.aligned;" ::: "memory"); }
template<int N> DEVI void wg_wait() { asm volatile("wgmma.wait_group.sync.aligned %0;" :: "n"(N) : "memory"); }
DEVI uint64_t mkdesc(uint32_t addr, uint32_t lbo, uint32_t sbo, uint32_t sw = 1) {
  return ((uint64_t)((addr & 0x3FFFF) >> 4)) | ((uint64_t)(lbo >> 4) << 16) | ((uint64_t)(sbo >> 4) << 32) | ((uint64_t)sw << 62);
}
constexpr uint32_t SMEM_BASE = 1024;
__host__ __device__ constexpr long long CD(uint32_t off, uint32_t lbo, uint32_t sbo, uint32_t sw) {
  return (long long)(((uint64_t)((SMEM_BASE + off) >> 4)) | ((uint64_t)(lbo >> 4) << 16) | ((uint64_t)(sbo >> 4) << 32) | ((uint64_t)sw << 62));
}
DEVI uint32_t pack_bf16(float lo, float hi) { uint32_t r; asm("cvt.rn.bf16x2.f32 %0, %1, %2;" : "=r"(r) : "f"(hi), "f"(lo)); return r; }
DEVI float bf_lo(uint32_t v) { return __uint_as_float(v << 16); }
DEVI float bf_hi(uint32_t v) { return __uint_as_float(v & 0xffff0000u); }
DEVI void ldsm4t(uint32_t addr, uint32_t& r0, uint32_t& r1, uint32_t& r2, uint32_t& r3) {
  asm volatile("ldmatrix.sync.aligned.m8n8.x4.trans.shared.b16 {%0,%1,%2,%3}, [%4];" : "=r"(r0), "=r"(r1), "=r"(r2), "=r"(r3) : "r"(addr) : "memory");
}
DEVI void stsm4(uint32_t addr, uint32_t r0, uint32_t r1, uint32_t r2, uint32_t r3) {
  asm volatile("stmatrix.sync.aligned.m8n8.x4.shared.b16 [%0], {%1,%2,%3,%4};" :: "r"(addr), "r"(r0), "r"(r1), "r"(r2), "r"(r3) : "memory");
}
DEVI uint2 lds64v(uint32_t a) { uint2 v; asm volatile("ld.volatile.shared.v2.u32 {%0,%1}, [%2];" : "=r"(v.x), "=r"(v.y) : "r"(a) : "memory"); return v; }
DEVI uint32_t lds32v(uint32_t a) { uint32_t v; asm volatile("ld.volatile.shared.u32 %0, [%1];" : "=r"(v) : "r"(a) : "memory"); return v; }
DEVI uint4 lds128v(uint32_t a) { uint4 v; asm volatile("ld.volatile.shared.v4.u32 {%0,%1,%2,%3}, [%4];" : "=r"(v.x), "=r"(v.y), "=r"(v.z), "=r"(v.w) : "r"(a) : "memory"); return v; }
DEVI void sts32(uint32_t a, uint32_t x) { asm volatile("st.shared.u32 [%0], %1;" :: "r"(a), "r"(x) : "memory"); }
DEVI int lane_id() { int r; asm volatile("mov.u32 %0, %%laneid;" : "=r"(r)); return r; }
DEVI void sts64(uint32_t a, uint32_t x, uint32_t y) { asm volatile("st.shared.v2.u32 [%0], {%1,%2};" :: "r"(a), "r"(x), "r"(y) : "memory"); }
DEVI void st_async128(uint32_t a, uint32_t x, uint32_t y, uint32_t z, uint32_t w, uint32_t bar) {
  asm volatile("st.async.weak.shared::cluster.mbarrier::complete_tx::bytes.v4.b32 [%0], {%1,%2,%3,%4}, [%5];" :: "r"(a), "r"(x), "r"(y), "r"(z), "r"(w), "r"(bar) : "memory");
}
DEVI void st_async32(uint32_t a, uint32_t x, uint32_t bar) {
  asm volatile("st.async.weak.shared::cluster.mbarrier::complete_tx::bytes.b32 [%0], %1, [%2];" :: "r"(a), "r"(x), "r"(bar) : "memory");
}
DEVI uint4 ldg_rlx128(const void* p) {
  uint4 v;
  asm volatile("ld.relaxed.gpu.global.v4.b32 {%0,%1,%2,%3}, [%4];" : "=r"(v.x), "=r"(v.y), "=r"(v.z), "=r"(v.w) : "l"(p) : "memory");
  return v;
}
DEVI int ldg_rlx32(const void* p) { int v; asm volatile("ld.relaxed.gpu.global.b32 %0, [%1];" : "=r"(v) : "l"(p) : "memory"); return v; }
DEVI int ldg_acq32(const void* p) { int v; asm volatile("ld.acquire.gpu.global.b32 %0, [%1];" : "=r"(v) : "l"(p) : "memory"); return v; }
DEVI void stg128(void* p, uint32_t x, uint32_t y, uint32_t z, uint32_t w) {
  asm volatile("st.global.v4.b32 [%0], {%1,%2,%3,%4};" :: "l"(p), "r"(x), "r"(y), "r"(z), "r"(w) : "memory");
}
DEVI uint2 ldg_rlx64(const void* p) { uint2 v; asm volatile("{.reg .b64 a; ld.relaxed.gpu.global.b64 a, [%2]; mov.b64 {%0,%1}, a;}" : "=r"(v.x), "=r"(v.y) : "l"(p) : "memory"); return v; }
DEVI void stg_rlx64(void* p, uint32_t x, uint32_t y) { asm volatile("{.reg .b64 a; mov.b64 a, {%1,%2}; st.relaxed.gpu.global.b64 [%0], a;}" :: "l"(p), "r"(x), "r"(y) : "memory"); }
DEVI void stg_rlx32(void* p, uint32_t x) { asm volatile("st.relaxed.gpu.global.b32 [%0], %1;" :: "l"(p), "r"(x) : "memory"); }
DEVI void flag_add(int* p) { asm volatile("fence.proxy.async.global; red.release.gpu.global.add.s32 [%0], 1;" :: "l"(p) : "memory"); }
DEVI void e_stg_rlx32(void* p, uint32_t x) { asm volatile(ELECT "st.relaxed.gpu.global.b32 [%0], %1;}" :: "l"(p), "r"(x) : "memory"); }
DEVI void e_flag_add(int* p) { asm volatile("fence.proxy.async.global;\n" ELECT "red.release.gpu.global.add.s32 [%0], 1;}" :: "l"(p) : "memory"); }
DEVI int cluster_rank() { int r; asm volatile("mov.u32 %0, %%cluster_ctarank;" : "=r"(r)); return __shfl_sync(0xffffffffu, r, 0); }
DEVI int cluster_last() { int r; asm volatile("mov.u32 %0, %%cluster_nctarank;" : "=r"(r)); return __shfl_sync(0xffffffffu, r, 0) - 1; }
DEVI int cta_id() { int r; asm volatile("mov.u32 %0, %%ctaid.x;" : "=r"(r)); return __shfl_sync(0xffffffffu, r, 0); }
DEVI uint32_t clock32() { uint32_t c; asm volatile("mov.u32 %0, %%clock;" : "=r"(c)); return c; }
DEVI uint32_t gtime() { uint32_t c; asm volatile("mov.u32 %0, %%globaltimer_lo;" : "=r"(c)); return c; }
DEVI void wait_time(uint32_t t) { while (__any_sync(0xffffffffu, t - gtime() - 1 < 4000u)) {} }
DEVI void spin_until(uint32_t t0, int d) {
  int r;
  while (__any_sync(0xffffffffu, (r = d - (int)(clock32() - t0)) > 0)) {
    if (r > 300) __nanosleep(r >> 2);
  }
}
DEVI void pin2(const void* a, const void* b) { asm volatile("{.reg .pred p; setp.eq.u64 p, %0, %1; @p st.volatile.global.u64 [%0], %1;}" :: "l"(a), "l"(b) : "memory"); }
DEVI void pin2(uint32_t a, uint32_t b) { asm volatile("{.reg .pred p; setp.eq.u32 p, %0, %1; @p st.volatile.shared.u32 [%0], %1;}" :: "r"(a), "r"(b) : "memory"); }
DEVI void p_stg_rlx64(void* p, uint32_t x, uint32_t y, bool c) {
  asm volatile("{.reg .pred p; .reg .b64 a; setp.ne.u32 p, %3, 0; mov.b64 a, {%1,%2}; @p st.relaxed.gpu.global.b64 [%0], a;}" :: "l"(p), "r"(x), "r"(y), "r"((uint32_t)c) : "memory");
}
DEVI void pin2(uint64_t a, uint64_t b) { pin2((const void*)a, (const void*)b); }
DEVI uint64_t pair(uint32_t a, uint32_t bar) { return a | (uint64_t)bar << 32; }
DEVI void st_async32(uint64_t q, uint32_t x) { st_async32((uint32_t)q, x, (uint32_t)(q >> 32)); }
DEVI void st_async128(uint64_t q, uint4 v) { st_async128((uint32_t)q, v.x, v.y, v.z, v.w, (uint32_t)(q >> 32)); }
DEVI float ex2(float x) { float r; asm("ex2.approx.ftz.f32 %0, %1;" : "=f"(r) : "f"(x)); return r; }
DEVI float rcp(float x) { float r; asm("rcp.approx.ftz.f32 %0, %1;" : "=f"(r) : "f"(x)); return r; }
DEVI uint32_t xor_or(uint32_t a, uint32_t t, uint32_t acc) { uint32_t r; asm("lop3.b32 %0, %1, %2, %3, 0xbe;" : "=r"(r) : "r"(a), "r"(t), "r"(acc)); return r; }
DEVI void stsm2(uint32_t addr, uint32_t r0, uint32_t r1) {
  asm volatile("stmatrix.sync.aligned.m8n8.x2.shared.b16 [%0], {%1,%2};" :: "r"(addr), "r"(r0), "r"(r1) : "memory");
}
DEVI uint32_t settag(uint32_t v, uint32_t tag) { return (v & ~1u) | tag; }

#define A4(c, o)  c(d[o+0]), c(d[o+1]), c(d[o+2]), c(d[o+3])
#define A8(c, o)  A4(c, o), A4(c, o+4)
#define A16(c, o) A8(c, o), A8(c, o+8)
#define A12(c, o) A8(c, o), A4(c, o+8)
#define A28(c, o) A16(c, o), A12(c, o+16)
#define RL12 "{%0,%1,%2,%3,%4,%5,%6,%7,%8,%9,%10,%11}"
#define RL28 "{%0,%1,%2,%3,%4,%5,%6,%7,%8,%9,%10,%11,%12,%13,%14,%15,%16,%17,%18,%19,%20,%21,%22,%23,%24,%25,%26,%27}"
#define A20(c, o) A16(c, o), A4(c, o+16)
#define A32(c, o) A16(c, o), A16(c, o+16)
#define RL8  "{%0,%1,%2,%3,%4,%5,%6,%7}"
#define RL16 "{%0,%1,%2,%3,%4,%5,%6,%7,%8,%9,%10,%11,%12,%13,%14,%15}"
#define RL20 "{%0,%1,%2,%3,%4,%5,%6,%7,%8,%9,%10,%11,%12,%13,%14,%15,%16,%17,%18,%19}"
#define RL32 "{%0,%1,%2,%3,%4,%5,%6,%7,%8,%9,%10,%11,%12,%13,%14,%15,%16,%17,%18,%19,%20,%21,%22,%23,%24,%25,%26,%27,%28,%29,%30,%31}"
#define RL64 "{%0,%1,%2,%3,%4,%5,%6,%7,%8,%9,%10,%11,%12,%13,%14,%15,%16,%17,%18,%19,%20,%21,%22,%23,%24,%25,%26,%27,%28,%29,%30,%31," \
  "%32,%33,%34,%35,%36,%37,%38,%39,%40,%41,%42,%43,%44,%45,%46,%47,%48,%49,%50,%51,%52,%53,%54,%55,%56,%57,%58,%59,%60,%61,%62,%63}"
#define WG_OP(shape) "wgmma.mma_async.sync.aligned." shape "k16.f32.bf16.bf16 "
#define DEF_WGMMA(N, RL, AL, i0, i1, i2, i3, i4, i5, i6)                                                                         \
  template<int SC, int TB, long long CB> DEVI void rs##N(float* d, const uint32_t* a) {                                          \
    if (SC) asm volatile("{.reg .b64 tb; mov.b64 tb, %" #i4 ";\n" WG_OP("m64n" #N) RL ", {%" #i0 ",%" #i1 ",%" #i2 ",%" #i3 "}, tb, 1, 1, 1, %" #i5 ";}" \
      : AL("+f", 0) : "r"(a[0]), "r"(a[1]), "r"(a[2]), "r"(a[3]), "n"(CB), "n"(TB));                                             \
    else asm volatile("{.reg .b64 tb; mov.b64 tb, %" #i4 ";\n" WG_OP("m64n" #N) RL ", {%" #i0 ",%" #i1 ",%" #i2 ",%" #i3 "}, tb, 0, 1, 1, %" #i5 ";}" \
      : AL("=f", 0) : "r"(a[0]), "r"(a[1]), "r"(a[2]), "r"(a[3]), "n"(CB), "n"(TB));                                             \
  }                                                                                                                              \
  template<int SC, int TA, int TB, long long CA, long long CB> DEVI void ss##N(float* d, uint32_t a) {                           \
    if (SC) asm volatile("{.reg .b64 ta, tb; .reg .b32 lo, hi; add.u32 lo, %" #i0 ", %" #i1 "; mov.b32 hi, %" #i2 "; mov.b64 ta, {lo, hi}; mov.b64 tb, %" #i3 ";\n" \
      WG_OP("m64n" #N) RL ", ta, tb, 1, 1, 1, %" #i4 ", %" #i5 ";}"                                                              \
      : AL("+f", 0) : "r"(a), "n"((int)CA), "n"((int)(CA >> 32)), "n"(CB), "n"(TA), "n"(TB));                                    \
    else asm volatile("{.reg .b64 ta, tb; .reg .b32 lo, hi; add.u32 lo, %" #i0 ", %" #i1 "; mov.b32 hi, %" #i2 "; mov.b64 ta, {lo, hi}; mov.b64 tb, %" #i3 ";\n" \
      WG_OP("m64n" #N) RL ", ta, tb, 0, 1, 1, %" #i4 ", %" #i5 ";}"                                                              \
      : AL("=f", 0) : "r"(a), "n"((int)CA), "n"((int)(CA >> 32)), "n"(CB), "n"(TA), "n"(TB));                                    \
  }
DEF_WGMMA(8, "{%0,%1,%2,%3}", A4, 4, 5, 6, 7, 8, 9, 10)
DEF_WGMMA(16, RL8, A8, 8, 9, 10, 11, 12, 13, 14)
DEF_WGMMA(32, RL16, A16, 16, 17, 18, 19, 20, 21, 22)
DEF_WGMMA(40, RL20, A20, 20, 21, 22, 23, 24, 25, 26)
DEF_WGMMA(24, RL12, A12, 12, 13, 14, 15, 16, 17, 18)
DEF_WGMMA(56, RL28, A28, 28, 29, 30, 31, 32, 33, 34)
template<int TA> DEVI void wgmma_n128(float* d, uint64_t a, uint64_t b, int scale_d) {
  asm volatile("{.reg .pred p; setp.ne.b32 p, %66, 0;\n" WG_OP("m64n128") RL64 ", %64, %65, p, 1, 1, %67, 1;}"
    : A32("+f", 0), A32("+f", 32) : "l"(a), "l"(b), "r"(scale_d), "n"(TA));
}

namespace rec {
constexpr int KR = 43;
constexpr uint32_t WSZ = (64 - KR) * 2048, STG = KR * 2048;
constexpr uint32_t WS = 0;
constexpr uint32_t RING = 2 * WSZ;
constexpr uint32_t OB = RING + 3 * 8192;
constexpr uint32_t PB = OB + 4096;
constexpr uint32_t WO = RING + 32768;
constexpr uint32_t ATT = WO + 5 * 16384;
constexpr uint32_t AK = ATT + 10240, AV = ATT + 20480;
constexpr uint32_t PAD = ATT + 30720;
constexpr uint32_t BARS = PAD + 128;
constexpr uint32_t B_XE = BARS  , B_FA = BARS + 64  , B_FB = BARS + 88, B_FO = BARS + 96;
constexpr uint32_t B_ME = BARS + 104  , B_WE = BARS + 136, B_PD = BARS + 144;
constexpr uint32_t B_XF = BARS + 152  , B_MF = BARS + 216  , B_CP = BARS + 248  , B_WT = BARS + 280  ;
constexpr uint32_t B_AB = BARS + 296, B_OB = BARS + 304, B_ST = BARS + 312  , B_WS = BARS + 328, B_WO = BARS + 336, B_AT = BARS + 352, B_AV = BARS + 360;
constexpr int NBAR = 46;
constexpr uint32_t M0 = BARS + 384;
constexpr uint32_t SMEM = 232448;
constexpr int NB_P = 1, NB_ST = 2, NB_O = 3, NB_W0 = 4, NB_W1 = 5;
__host__ __device__ constexpr int wo_tile(int rank, int g, int i) { return i < 2 ? i * 6 + (rank == 2 ? g : 4 - 2 * g + rank) : 13 + rank - g; }
constexpr long long D_W = CD(WS, 16, 1024, 1), D_X = CD(0, 16, 1024, 1), D_O = CD(OB, 128, 256, 0);
constexpr long long D_WO = CD(WO, 16, 1024, 1), D_QM = CD(ATT, 640, 0, 0), D_QT = CD(ATT + 128, 640, 64, 0), D_K = CD(AK, 640, 128, 0);
constexpr long long D_V = CD(AV, 128, 640, 0), D_P = CD(PB, 128, 768, 0);
struct Maps { CUtensorMap w[3], wo, xd, xs; };
__host__ __device__ constexpr uint32_t mslot(int c) { return (c ^ (c >> 1)) * 12288; }
__host__ __device__ constexpr uint32_t xslot(int s) { return s < 3 ? RING + s * 8192 : s < 5 ? WO + (s - 3) * 8192 : s < 7 ? WO + (s + 1) * 8192 : OB; }
__host__ __device__ constexpr bool k_smem(int k) { return k % 3 == 2; }
__host__ __device__ constexpr int k_idx(int k) { return k % 3 == 2 ? k / 3 : k - k / 3; }
__host__ __device__ constexpr int k_of_reg(int i) { return i + (i >> 1); }
__host__ __device__ constexpr int k_of_smem(int i) { return 3 * i + 2; }

#define RPROF(i)
#define RPROF_STEP
#define CPROF(i, v)

template<bool DUAL, int K0, int K1> DEVI void seq_mem(float* d, const uint32_t* w, uint32_t dw) {
  if constexpr (K0 < K1) {
    constexpr long long B = CD(RING, 128, DUAL ? 4096 : 8192, 0) + mslot(K0 >> 4) / 16 + (K0 & 15) * 16;
    if constexpr (DUAL) {
      if constexpr (!k_smem(K0)) rs24<K0 != 0, 1, B>(d, w + 4 * k_idx(K0)); else ss24<1, 1, 1, D_W + k_idx(K0) * 128, B>(d, dw);
    } else {
      if constexpr (!k_smem(K0)) rs16<K0 != 0, 1, B>(d, w + 4 * k_idx(K0)); else ss16<1, 1, 1, D_W + k_idx(K0) * 128, B>(d, dw);
    }
    seq_mem<DUAL, K0 + 1, K1>(d, w, dw);
  }
}
template<int N, int K0, int K1> DEVI void seq_tok(float* d, const uint32_t* w, uint32_t dw) {
  if constexpr (K0 < K1) {
    constexpr bool DUAL = N > 32;
    constexpr long long B = D_X + (DUAL ? xslot((K0 >> 2) & 7) / 16 : xslot(K0 >> 3) / 16 + ((K0 >> 2) & 1) * 256) + (K0 & 3) * 2;
    if constexpr (DUAL) {
      if constexpr (!k_smem(K0)) rs56<K0 != 0, 0, B>(d, w + 4 * k_idx(K0)); else ss56<1, 1, 0, D_W + k_idx(K0) * 128, B>(d, dw);
    } else if constexpr (N == 24) {
      if constexpr (!k_smem(K0)) rs24<K0 != 0, 0, B>(d, w + 4 * k_idx(K0)); else ss24<1, 1, 0, D_W + k_idx(K0) * 128, B>(d, dw);
    } else {
      if constexpr (!k_smem(K0)) rs32<K0 != 0, 0, B>(d, w + 4 * k_idx(K0)); else ss32<1, 1, 0, D_W + k_idx(K0) * 128, B>(d, dw);
    }
    seq_tok<N, K0 + 1, K1>(d, w, dw);
  }
}
template<int T, int K0> DEVI void seq_wo(float* d, uint32_t dw) {
  if constexpr (K0 < 8) { ss16<K0 != 0, 1, 1, D_WO + T * 1024 + K0 * 128, D_O + K0 * 32>(d, dw); seq_wo<T, K0 + 1>(d, dw); }
}
template<long long Q, int K0> DEVI void seq_s(float* d) {
  if constexpr (K0 < 8) { ss40<K0 != 0, 1, 1, Q + K0 * 80, D_K + K0 * 80>(d, 0); seq_s<Q, K0 + 1>(d); }
}
template<bool DUAL, int J> DEVI void load_x(uint32_t sb, const Maps* M, int t, int rb) {
  if (DUAL) e_tma_3d_mc(sb + xslot(J & 7), &M->xd, J * 64, (t - LAG) * 32, 0, sb + B_XF + (J & 7) * 8, rb);
  else e_tma_3d_mc(sb + xslot(J & 7), &M->xs, 0, (t < NSEG ? t : t - LAG) * 32, J * 2, sb + B_XF + (J & 7) * 8, rb);
}
DEVI void load_x_lent(uint32_t sb, const Maps* M, int t, int j) {
  const bool dual = t >= LAG && t < NSEG;
  const uint32_t dst = sb + (j == 3 ? xslot(3) : xslot(5));
#pragma unroll
  for (int i = 0; i < 2; i++)
    e_tma_3d(dst + i * 8192, dual ? &M->xd : &M->xs, dual ? (j + i) * 64 : 0, (t < LAG ? t : t - LAG) * 32, dual ? 0 : (j + i) * 2, sb + B_XF + (j + i) * 8);
}
struct True { static constexpr bool value = true; };
struct False { static constexpr bool value = false; };
struct Ctx { uint32_t sb; const Maps* M; int last; bool issuer; int wi; bool lead; uint32_t par; };
#define XD 1
template<bool DUAL, int J> DEVI void tok_release(const Ctx& c, int t, int& budget) {
  constexpr int NC = DUAL ? 16 : 8, S = J & 7;
  if constexpr (J + 8 < NC) {
    p_arrive_at(c.sb + B_XE + S * 8, c.last, c.lead);
    p_expect_tx(c.sb + B_XF + S * 8, 8192, c.lead && c.wi == 0);
  } else if constexpr (S == 1 || S == 2 || S == 4 || S == 7) p_arrive(c.sb + B_ME + (S >> 1) * 8, c.lead);
  if constexpr (J == 0) {
    if (c.issuer && c.wi == 6) { mbar_wait(c.sb + B_FO, t & 1, budget); load_x<DUAL, 7>(c.sb, c.M, t, c.last); }
  }
  if constexpr (J >= XD && J - XD + 8 < NC) {
    constexpr int I = J - XD;
    if (c.issuer && c.wi == (I & 1) * 4 + 1) { mbar_wait(c.sb + B_XE + I * 8, (t - LAG) & 1, budget); load_x<DUAL, I + 8>(c.sb, c.M, t, c.last); }
  }
}
template<int N, int J, class F, class G> DEVI bool tok_pass(float* d, const uint32_t* w, uint32_t dw, Ctx& c, int t, int& budget, F after0, G setup) {
  constexpr bool DUAL = N > 32;
  constexpr int NC = DUAL ? 16 : 8, KC = 64 / NC;
  if constexpr (J < NC) {
    if constexpr (J > 1) mbar_wait(c.sb + B_XF + (J & 7) * 8, c.par ^ (J >> 3), budget);
    wg_fence();
    seq_tok<N, J * KC, (J + 1) * KC>(d, w, dw);
    wg_commit();
    if constexpr (J == 1) after0();
    if constexpr (J >= NC - 5 && J < NC - 2) setup(J - (NC - 5));
    if constexpr (J > 0) { wg_wait<1>(); tok_release<DUAL, J - 1>(c, t, budget); }
    return tok_pass<N, J + 1>(d, w, dw, c, t, budget, after0, setup);
  } else {
    const bool ok = mbar_test(c.sb + B_MF, t & 1);
    wg_wait<0>();
    tok_release<DUAL, NC - 1>(c, t, budget);
    if (!DUAL) c.par ^= 1;
    return ok;
  }
}
template<int NB> DEVI void pack_tok(uint32_t* e, const float* d) {
#pragma unroll
  for (int i = 0; i < 8; i++) if ((i & 3) < NB) e[i] = pack_bf16(d[4 * (i & 3) + 2 * (i >> 2)], d[4 * (i & 3) + 2 * (i >> 2) + 1]);
}
DEVI void push_tok(const uint32_t* e, uint32_t sb, uint32_t o, int r, int rank) {
  const uint32_t b = mapa(sb, r);
  st_async128(b + o, e[0], e[1], e[2], e[3], b + (rank == 2 ? B_AV : B_AT));
}
DEVI uint32_t h1_tag(int seg) { return ((seg >> 1) & 1) ^ 1; }
DEVI uint4 pack_part(const float* c, int t) {
  return make_uint4(settag(pack_bf16(c[0], c[1]), h1_tag(t)), pack_bf16(c[2], c[3]), settag(pack_bf16(c[4], c[5]), h1_tag(t - LAG)), pack_bf16(c[6], c[7]));
}
DEVI void put_part(char* p1, char* p2, uint4 z, int t) { p_stg_rlx64(p1, z.x, z.y, t < NSEG); p_stg_rlx64(p2, z.z, z.w, t >= LAG); }

DEVI void rec_math(const uint32_t sb, const int wi, const Maps& M) {
  const int h = cta_id() / 3, rb = cluster_rank() >= 3 ? 3 : 0, rank = cluster_rank() - rb;
  const int warp = wi & 3, wg = wi >> 2;
  const bool lead = (threadIdx.x & 127) == 0;
  int budget = SPIN_BUDGET;
  uint32_t w[4 * KR];
  const int last = cluster_last();
  Ctx cx{sb, &M, last, rb + rank == last, wi, lead, 0};
  {
    const int lane = lane_id();
    const uint32_t a = sb + wg * STG + ((lane & 7) + (lane >> 4) * 8) * 128 + (((warp * 2 + ((lane >> 3) & 1)) ^ (lane & 7)) << 4);
    for (int i = 0; i < (wg == 1 || rank == 2 ? 12 : 8); i++)
      stg_rlx64((char*)g_h1[i & 3] + ((wo_tile(rank, wg, i >> 2) * 4 + warp) * 4 + (lane >> 3)) * 2048 + h * 64 + (lane & 7) * 8, 0, 0);
    mbar_wait(sb + B_ST + wg * 8, 0, budget);
#pragma unroll
    for (int k = 0; k < KR; k++) ldsm4t(a + k * 2048, w[4*k], w[4*k+1], w[4*k+2], w[4*k+3]);
    nbar_arrive<NB_ST, 384>();
    nbar_sync_r(NB_W0 + wg, 128);
    for (int i = 0; i < 5; i++) p_arrive_at(sb + B_FA + i * 8, i == 4 ? last : 0, lead);
    mbar_wait(sb + B_WS, 0, budget);
  }
  uint4 z = make_uint4(0, 0, 0, 0);
  char *z1 = nullptr, *z2 = nullptr;
  uint32_t rt0 = 0, rt1 = 0;
  mbar_wait(sb + B_XF, 0, budget); mbar_wait(sb + B_XF + 8, 0, budget);
#pragma unroll 1
  for (int t = 0;; t++) {
    const uint32_t dw = wg * (WSZ >> 4);
    uint32_t e[16];
    bool ok;
    auto finish = [&]() { put_part(z1, z2, z, t - 1); p_arrive_at(sb + B_FO, last, lead); };
    const int seg = t - rank * LAG;
    const bool att = rank < 2 && (unsigned)seg < (unsigned)NSEG;
    char* p1;
    uint32_t pw, oo;
    uint64_t u0, u1;
    int lane;
    auto setup = [&](int part) {
      if (part == 0) {
        lane = lane_id();
      } else if (part == 1) {
        char* const p = (char*)g_h1 + ((wo_tile(rank, wg, 0) * 4 + warp) * 4 + (lane >> 3)) * 2048 + h * 64 + (lane & 7) * 8;
        p1 = p + (t & 1) * sizeof(g_h1[0]);
        pin2(p1, nullptr);
      } else if (part == 2) {
        oo = OB + (lane >> 4) * 2048 + warp * 512 + rank * 256 + (lane & 15) * 16;
        pw = sb + PB + (wg ? lane * 4 : 768 + warp * 768 + lane * 16);
        pin2(pw, oo);
      } else {
        if (wg) {
          const uint32_t ra = mapa(sb, rb + ((warp & 1) ? 2 : (rank ^ 1) & 1)), rc = mapa(sb, rb + ((warp & 1) ? (rank ^ 1) & 1 : 2));
          u0 = pair(ra + oo, ra + B_OB); u1 = pair(rc + oo, rc + B_OB);
        } else {
          u0 = (uint64_t)((char*)(g_ot + rank * O_LAYER) + (size_t)(h * DH + warp * 16 + (lane >> 2)) * (SEQ * 2) + seg * 64 + (lane & 3) * 16);
          u1 = (uint32_t)((lane & 24) + ((lane >> 2) & 1) + 2 * warp - 8 * (lane & 3));
        }
        pin2(u0, u1);
      }
    };
    RPROF_STEP;
    auto mem_pass = [&](auto dual_c) {
      constexpr bool DUAL = decltype(dual_c)::value;
      float m[DUAL ? 12 : 8];
      RPROF(8 + wg * 12 - 32);
      if (!ok) mbar_wait(sb + B_MF, t & 1, budget);
      wg_fence(); seq_mem<DUAL, 0, 8>(m, w, dw); wg_commit();
      const uint32_t ao = ATT + rank * 10240 + wi * 1280, to = ao + 128 + (lane & 3) * 128 + (lane >> 2) * 16;
      const int la = DUAL ? rank == 0 : t >= NSEG;
      RPROF(1 + wg * 12);
      if (DUAL && rank == 0) {
#pragma unroll
        for (int i = 0; i < 8; i++) { const uint32_t x = e[i]; e[i] = e[8 + i]; e[8 + i] = x; }
      }
      auto piece = [&](int i) { push_tok(e + 4 * i, sb, to + (i & 1) * 640, rb + (la ^ (i >> 1)), rank); };
      piece(0);
      wg_fence(); seq_mem<DUAL, 8, 16>(m, w, dw); wg_commit();
      piece(1);
      mbar_wait(sb + B_MF + 8, t & 1, budget);
      wg_fence(); seq_mem<DUAL, 16, 24>(m, w, dw); wg_commit();
      if (DUAL) piece(2);
      wg_fence(); seq_mem<DUAL, 24, 32>(m, w, dw); wg_commit();
      if (DUAL) piece(3);
      mbar_wait(sb + B_MF + 16, t & 1, budget);
      wg_fence(); seq_mem<DUAL, 32, 48>(m, w, dw); wg_commit();
      wg_wait<1>(); p_arrive(sb + B_PD, lead);
      const uint32_t r0 = mapa(sb, rb + la), r1 = mapa(sb, rb + (la ^ 1)), m0 = r0 + ao + lane * 4, m1 = r1 + ao + lane * 4, ab = rank == 2 ? B_AV : B_AB;
      const uint64_t q0 = pair(m0, r0 + ab), q1 = pair(m0 + 640, r0 + ab), q2 = pair(m1, r1 + ab), q3 = pair(m1 + 640, r1 + ab);
      pin2(q0, q1);
      if (DUAL) pin2(q2, q3);
      mbar_wait(sb + B_MF + 24, t & 1, budget);
      wg_fence(); seq_mem<DUAL, 48, 64>(m, w, dw); wg_commit();
      wg_wait<1>(); p_arrive_at(sb + B_FA, 0, lead);
      wg_wait<0>();
      const uint32_t a0 = pack_bf16(m[0], m[1]), a1 = pack_bf16(m[2], m[3]), a2 = pack_bf16(m[4], m[5]), a3 = pack_bf16(m[6], m[7]);
      if constexpr (DUAL) {
        st_async32(q0, la ? a2 : a0); st_async32(q1, la ? a3 : a1); st_async32(q2, la ? a0 : a2); st_async32(q3, la ? a1 : a3);
        rt0 = pack_bf16(m[8], m[9]); rt1 = pack_bf16(m[10], m[11]);
      } else { st_async32(q0, a0); st_async32(q1, a1); rt0 = a2; rt1 = a3; }
      p_arrive(sb + B_WE, lead);
    };
    if (t >= LAG && t < NSEG) {
      float d[28];
      ok = tok_pass<56, 0>(d, w, dw, cx, t, budget, finish, setup);
      pack_tok<4>(e + 8, d); pack_tok<3>(e, d + 16); e[3] = rt0; e[7] = rt1;
      mem_pass(True());
    } else {
      float d[16];
      if (t > 0) finish();
      if (t > 0 && t < LAG) {
        ok = tok_pass<24, 0>(d, w, dw, cx, t, budget, []() {}, setup);
        pack_tok<3>(e, d); e[3] = rt0; e[7] = rt1;
      } else {
        ok = tok_pass<32, 0>(d, w, dw, cx, t, budget, []() {}, setup);
        pack_tok<4>(e, d);
      }
      mem_pass(False());
    }
    {
      RPROF(2 + wg * 12);
      auto wo_ready = [&]() { if (t == 0) mbar_wait(sb + B_WO, 0, budget); if (t < NSTEP - 1) mbar_wait(sb + B_WT, t & 1, budget); };
      constexpr float SC = 0.08838834764831845f * 1.4426950408889634f;
      if (!att) wo_ready();
      else {
        float s[32];
        setup(3);
        if (wg) {
          uint32_t one[4];
#pragma unroll
          for (int i = 0; i < 4; i++) one[i] = 0x3F803F80u + (pw >> 31);
          mbar_wait_cluster(sb + B_AT, seg & 1, budget);
          mbar_wait_cluster(sb + B_AB, seg & 1, budget);
          fence_proxy_async();
          RPROF(3 + 12);
          wg_fence(); seq_s<D_QM, 0>(s); wg_commit();
          nbar_arrive<NB_P, 256>();
          if (warp == 1) sts32(pw + 640, 0);
          mbar_wait_cluster(sb + B_AV, seg & 1, budget);
          wg_wait<0>();
          float mx = fmaxf(fmaxf(fmaxf(s[0], s[1]), fmaxf(s[4], s[5])), fmaxf(fmaxf(fmaxf(s[8], s[9]), fmaxf(s[12], s[13])), fmaxf(s[16], s[17])));
          const float x1 = __shfl_xor_sync(0xffffffffu, mx, 1), x2 = __shfl_xor_sync(0xffffffffu, mx, 2), x3 = __shfl_xor_sync(0xffffffffu, mx, 3);
          const float u = (warp & 2) ? ((warp & 1) ? s[16] : s[12]) : ((warp & 1) ? s[8] : s[4]);
          const float v = (warp & 2) ? ((warp & 1) ? s[17] : s[13]) : ((warp & 1) ? s[9] : s[5]);
          const float ms = -SC * fmaxf(fmaxf(mx, x1), fmaxf(x2, x3));
          sts32(pw + 128 + warp * 128, pack_bf16(ex2(fmaf(u, SC, ms)), ex2(fmaf(v, SC, ms))));
          if (warp == 0) sts32(pw, pack_bf16(ex2(fmaf(s[0], SC, ms)), ex2(fmaf(s[1], SC, ms))));
          fence_proxy_async();
          nbar_sync<NB_W1, 128>();
          RPROF(4 + 12);
          wg_fence();
          rs8<0, 0, D_P>(s + 8, one); rs8<1, 0, D_P + 16>(s + 8, one); rs8<1, 0, D_P + 32>(s + 8, one);
          wg_commit();
          ss8<0, 0, 0, D_V, D_P>(s, 0); ss8<0, 0, 0, D_V + 320, D_P>(s + 4, 0);
          ss8<1, 0, 0, D_V + 16, D_P + 16>(s, 0); ss8<1, 0, 0, D_V + 336, D_P + 16>(s + 4, 0);
          ss8<1, 0, 0, D_V + 32, D_P + 32>(s, 0); ss8<1, 0, 0, D_V + 352, D_P + 32>(s + 4, 0);
          wg_commit();
          wg_wait<1>();
          const float i0 = rcp(s[8]), i1 = rcp(s[9]);
          wg_wait<0>();
          stsm4(sb + oo, pack_bf16(s[0] * i0, s[1] * i1), pack_bf16(s[2] * i0, s[3] * i1), pack_bf16(s[4] * i0, s[5] * i1), pack_bf16(s[6] * i0, s[7] * i1));
          __syncwarp();
          const uint4 y = lds128v(sb + oo);
          if (t < NSTEP - 1) { st_async128(u0, y); st_async128(u1, y); e_complete_tx(sb + B_OB, 512); }
          wo_ready();
        } else {
          const int lim = (int)u1;
          char* const og = (char*)u0;
          nbar_sync<NB_P, 256>();
          RPROF(3);
          wg_fence();
          seq_s<D_QT, 0>(s);
          wg_commit();
          mbar_wait_cluster(sb + B_AV, seg & 1, budget);
          wg_wait<0>();
#pragma unroll
          for (int i = 0; i < 8; i++) { float& v = s[4 + 4 * (i >> 1) + (i & 1)]; v = i <= lim ? v : -INFINITY; }
          float mx = fmaxf(fmaxf(fmaxf(s[0], s[1]), fmaxf(s[4], s[5])), fmaxf(fmaxf(fmaxf(s[8], s[9]), fmaxf(s[12], s[13])), fmaxf(s[16], s[17])));
          const float x1 = __shfl_xor_sync(0xffffffffu, mx, 1), x2 = __shfl_xor_sync(0xffffffffu, mx, 2), x3 = __shfl_xor_sync(0xffffffffu, mx, 3);
          const float ms = -SC * fmaxf(fmaxf(mx, x1), fmaxf(x2, x3));
#pragma unroll
          for (int i = 0; i < 10; i++) { float& v = s[4 * (i >> 1) + (i & 1)]; v = ex2(fmaf(v, SC, ms)); }
          const float sum = (((s[0] + s[1]) + (s[4] + s[5])) + ((s[8] + s[9]) + (s[12] + s[13]))) + (s[16] + s[17]);
          const float y1 = __shfl_xor_sync(0xffffffffu, sum, 1), y2 = __shfl_xor_sync(0xffffffffu, sum, 2), y3 = __shfl_xor_sync(0xffffffffu, sum, 3);
          const float inv = rcp((sum + y1) + (y2 + y3));
          stsm4(pw, pack_bf16(s[0] * inv, s[1] * inv), pack_bf16(s[4] * inv, s[5] * inv), pack_bf16(s[8] * inv, s[9] * inv), pack_bf16(s[12] * inv, s[13] * inv));
          stsm2(pw + 512, pack_bf16(s[16] * inv, s[17] * inv), 0);
          fence_proxy_async();
          nbar_sync<NB_W0, 128>();
          RPROF(4);
          wg_fence();
          ss32<0, 0, 0, D_V, D_P + 48>(s, 0); ss32<0, 0, 0, D_V + 320, D_P + 48>(s + 16, 0);
          ss32<1, 0, 0, D_V + 16, D_P + 64>(s, 0); ss32<1, 0, 0, D_V + 336, D_P + 64>(s + 16, 0);
          ss32<1, 0, 0, D_V + 32, D_P + 80>(s, 0); ss32<1, 0, 0, D_V + 352, D_P + 80>(s + 16, 0);
          wg_commit();
          wo_ready();
          wg_wait<0>();
#pragma unroll
          for (int i = 0; i < 4; i++) {
            const float* d = s + (i >> 1) * 16 + (i & 1) * 2;
            stg128(og + ((i >> 1) * 64 + (i & 1) * 8) * (SEQ * 2), pack_bf16(d[0], d[1]), pack_bf16(d[4], d[5]), pack_bf16(d[8], d[9]), pack_bf16(d[12], d[13]));
          }
          if ((seg & 3) == 3) nbar_arrive<NB_O, 160>();
        }
      }
      RPROF(5 + wg * 12);
      const bool three = wg == 1 || rank == 2;
      char* const p2 = p1 + (2 + ((t - LAG) & 1) - (t & 1)) * (int)sizeof(g_h1[0]);
      if (t < NSTEP - 1) {
        float c[24];
        const uint32_t dt = wg ? 0 : 3072;
        mbar_wait_cluster(sb + B_OB, t & 1, budget);
        fence_proxy_async();
        RPROF(6 + wg * 12);
        wg_fence(); seq_wo<0, 0>(c, dt); wg_commit(); seq_wo<1, 0>(c + 8, dt); wg_commit();
        mbar_wait(sb + B_XF, cx.par, budget);
        wg_wait<1>();
        if (warp == 2) load_x_lent(sb, &M, t + 1, wg ? 3 : 5);
        put_part(p1, p2, pack_part(c, t), t);
        const int o3 = (wo_tile(rank, wg, three ? 2 : 1) - wo_tile(rank, wg, 0)) * 32768;
        z1 = p1 + o3; z2 = p2 + o3;
        if (three) {
          wg_fence(); seq_wo<2, 0>(c + 16, dt); wg_commit();
          wg_wait<1>(); put_part(p1 + 6 * 32768, p2 + 6 * 32768, pack_part(c + 8, t), t);
          mbar_wait(sb + B_XF + 8, cx.par, budget);
          wg_wait<0>(); z = pack_part(c + 16, t);
        } else { mbar_wait(sb + B_XF + 8, cx.par, budget); wg_wait<0>(); z = pack_part(c + 8, t); }
      } else break;
      RPROF(7 + wg * 12);
    }
  }
}

DEVI void wait_xa(const int* p, int& budget) {
  while (__any_sync(0xffffffffu, ldg_acq32(p) < 64) && --budget > 0) {}
  fence_proxy_global();
}
template<bool DUAL> DEVI void first_loads(uint32_t sb, const Maps* M, int n, int h, int rb, int& budget) {
  if (n >= LAG && ((n - LAG) & 3) == 0) e_prefetch_3d(&M->xs, 0, (n - LAG) * 32, h & 14);
  mbar_wait(sb + B_FA, n & 1, budget);
  load_x<DUAL, 0>(sb, M, n, rb); load_x<DUAL, 1>(sb, M, n, rb); load_x<DUAL, 2>(sb, M, n, rb);
}
template<bool DUAL> DEVI void lent_loads(uint32_t sb, const Maps* M, int n, int rb, int& budget) {
  mbar_wait(sb + B_FB, n & 1, budget);
  load_x<DUAL, 3>(sb, M, n, rb); load_x<DUAL, 4>(sb, M, n, rb); load_x<DUAL, 5>(sb, M, n, rb); load_x<DUAL, 6>(sb, M, n, rb);
}
DEVI void rec_comm(const uint32_t sb, const int warp, const Maps& M, const bf16* __restrict__ mem0) {
  const int lane = threadIdx.x & 31, h = cta_id() / 3, rb = cluster_rank() >= 3 ? 3 : 0, rank = cluster_rank() - rb;
  int budget = SPIN_BUDGET;
  const bool two = warp == 3 || (rank == 2 && warp == 2);
  const int ntask = two ? 2 : 1, qi = two ? (warp == 3 ? rank : 3) : rank * 3 + warp;
  const int task0 = two ? h * 2 + (qi >> 1) : 64 + h * 4 + (qi >> 1);
  auto h2_word = [&](int i, int ln) {
    const int task = task0 + i * 192;
    return (char*)g_h2 + (task >> 6) * 8192 + ((qi ^ i) & 1) * 4096 + ((task >> 2) & 15) * 256 + (task & 3) * 32 + (ln & 8) * 16 + (ln & 7) * 4;
  };
  auto first_x = [&](int t) {
    const int n = t + 1;
    p_expect_tx(sb + B_XF + (lane_id() & 7) * 8, 8192, lane_id() < 8);
    if (rb + rank == 0) {
      if (n >= LAG && ((n - LAG) & 3) == 0) wait_xa(&g_xa[1][(n - LAG) >> 2], budget);
      if (n >= LAG && n < NSEG) first_loads<true>(sb, &M, n, h, cluster_last(), budget); else first_loads<false>(sb, &M, n, h, cluster_last(), budget);
    }
  };
  {
    const int task = task0 + (lane >> 4) * 192, L = (task & 3) * 8 + (lane & 7);
    if ((lane >> 4) < ntask) {
      const bf16* p = mem0 + (L & 3) * 2 * DM + (task >> 2) * 16 + (L >> 2) + (lane & 8);
      uint32_t m0 = (uint32_t)__bfloat16_as_ushort(p[0]) | (uint32_t)__bfloat16_as_ushort(p[DM]) << 16;
      m0 = m0 ? m0 : 0x8000u;
      stg_rlx32(h2_word(lane >> 4, lane), ((qi ^ (lane >> 4)) & 1) ? 0 : m0);
      for (int i = 1; i < 4; i++) stg_rlx32(h2_word(lane >> 4, lane) + i * sizeof(g_h2[0]), 0);
      sts32(sb + M0 + warp * 128 + lane * 4, m0);
    }
    __syncwarp();
    nbar_sync<NB_ST, 384>();
    if (warp == 2) {
      e_expect_tx(sb + B_WS, 2 * WSZ);
#pragma unroll 1
      for (int i = 0; i < 2 * (64 - KR); i++) e_tma_2d(sb + WS + (i & 1) * WSZ + (i >> 1) * 2048, &M.w[rank], h * DH + (i & 1) * 64, k_of_smem(i >> 1) * 16, sb + B_WS);
      const int nt = rank == 2 ? 6 : 5;
      e_expect_tx(sb + B_WO, (nt - 2) * 16384);
#pragma unroll 1
      for (int i = 1; i < nt; i++) if (i != 3) e_tma_2d(sb + WO + i * 16384, &M.wo, wo_tile(rank, 1 - i / 3, i % 3) * 64, h * DH, sb + B_WO);
    }
    wait_xa(&g_xa[0][0], budget);
    if (warp == 3) { first_x(-1); if (rb + rank == 0) lent_loads<false>(sb, &M, 0, cluster_last(), budget); }
  }
  uint32_t cpp = 0;
  const uint32_t cp = sb + B_CP + warp * 8;
  uint32_t f_dst, f_chk, f_bar, f_time = gtime() - 4000;
  const char *f_src, *f_xr;
  auto prepare = [&](int s) {
    const int ck = warp ^ (warp < 2 && (s < LAG || s >= NSEG) && (rank & 1) == (s >= NSEG)), ln = lane_id();
    f_dst = sb + RING + mslot(ck); f_chk = f_dst + ln * 32 + (ln >> 2) * 4; f_bar = sb + ck * 8;
    f_src = (const char*)g_h2[s & 3] + ck * 8192 + (s >= NSEG ? 4096 : 0);
    f_xr = (const char*)g_xr[(s + 1) & 63] + ck * 4096;
    pin2(f_chk, 0u);
    return s <= LAG ? TP(9) + ck * TP(11) : s <= NSEG ? TP(1) + ck * TP(4) : TP(13) + ck * TP(11);
  };
  prepare(0);
#pragma unroll 1
  for (int t = 0;; t++) {
    const int n = t + 1;
    const bool dual = t >= LAG && t < NSEG;
    RPROF_STEP;
    {
      const uint32_t bytes = dual ? 8192 : 4096;
      e_expect_tx(cp, bytes + (n < NSEG ? 4096 : 0));
      mbar_wait(f_bar + B_ME, t & 1, budget);
      if (n < NSEG) e_bulk_g2s(f_dst + 8192, f_xr, 4096, cp);
      wait_time(f_time);
      RPROF(24); CPROF(0, gtime());
      int tries = 0;
      while (true) {
        tries++;
        e_bulk_g2s(f_dst, f_src, bytes, cp);
        mbar_wait(cp, cpp, budget); cpp ^= 1;
        uint32_t mn = min(min(lds32v(f_chk), lds32v(f_chk + 1024)), min(lds32v(f_chk + 2048), lds32v(f_chk + 3072)));
        if (dual) mn = min(min(mn, min(lds32v(f_chk + 4096), lds32v(f_chk + 5120))), min(lds32v(f_chk + 6144), lds32v(f_chk + 7168)));
        if (!__any_sync(0xffffffffu, mn == 0) || --budget < 0) break;
        e_expect_tx(cp, bytes);
      }
      e_arrive(f_bar + B_MF);
      RPROF(25); CPROF(1, gtime()); CPROF(2, tries);
    }
    const int seg = t - rank * LAG;
    const bool att = rank < 2 && (unsigned)seg < (unsigned)NSEG;
    if (warp == 0) {
      if (att) { e_expect_tx(sb + B_AT, 16384); e_expect_tx(sb + B_AB, 4096); e_expect_tx(sb + B_AV, 10240); }
      if (n < NSTEP) e_expect_tx(sb + B_OB, dual ? 4096 : 2048);
    }
    if (n + 1 < NSEG && (n & 3) == 3) wait_xa(&g_xa[0][(n + 1) >> 2], budget);
    if (rank == 2 && warp == 1) {
      if (h < 16 ? n < NSEG : n > LAG && n < NSTEP && ((n - LAG) & 3)) e_prefetch_3d(&M.xs, 0, (h < 16 ? n : n - LAG) * 32, (h & 7) * 2);
      if (h >= 16 && n + 1 < NSEG) asm volatile(ELECT "cp.async.bulk.prefetch.L2.global [%0], 2048;}" :: "l"((const char*)g_xr[n + 1] + (h & 7) * 2048) : "memory");
    }
    {
      const int ln = lane_id(), i = ln >> 4;
      char* const w = h2_word(i, ln);
      if (i < ntask) {
        stg_rlx32(w + ((t + 3) & 3) * sizeof(g_h2[0]), 0);
        if (n == LAG && ((qi ^ i) & 1)) stg_rlx32(w + (n & 3) * sizeof(g_h2[0]), lds32v(sb + M0 + warp * 128 + ln * 4));
      }
      __syncwarp();
    }
    if (n < NSTEP) {
      const uint32_t tag = (n >> 1) & 31;
      mbar_wait(sb + B_PD, t & 1, budget);
      uint32_t t0 = clock32();
      if (warp == 2) {
        e_expect_tx(sb + B_WT, 32768);
        e_tma_2d(sb + WO + 49152, &M.wo, wo_tile(rank, 0, 0) * 64, h * DH, sb + B_WT);
        mbar_wait(sb + B_WE, t & 1, budget);
        e_tma_2d(sb + WO, &M.wo, wo_tile(rank, 1, 0) * 64, h * DH, sb + B_WT);
      }
      if (warp == 3) first_x(t);
      if (warp == 0 && rank == (t >= NSEG)) { mbar_wait(sb + B_AB, seg & 1, budget); e_stg_rlx32(&g_ts[t & 1][h], (gtime() & ~31u) | tag); }
      const int fd = prepare(n), ln = lane_id();
      const int sa = t - (qi & 1) * LAG, sc = t - (~qi & 1) * LAG;
      const int i0 = (unsigned)sa < (unsigned)(NSEG - 1) ? 0 : 1, i1 = two && (unsigned)sc < (unsigned)(NSEG - 1) ? 2 : 1;
      const char* src = (const char*)g_h1[(qi & 1) * 2 + (sa & 1)] + task0 * 2048 + ln * 8;
      char* dst = h2_word(0, ln) + (n & 3) * sizeof(g_h2[0]);
      const int ds = ((~qi & 1) * 2 + (sc & 1) - (qi & 1) * 2 - (sa & 1)) * (int)sizeof(g_h1[0]) + 192 * 2048, dd = 3 * 8192 + ((qi & 1) ? -4096 : 4096);
      if (i0) { src += ds; dst += dd; }
      pin2(src, dst);
      spin_until(t0, TSD);
      uint32_t v0;
      do { v0 = ldg_rlx32(&g_ts[t & 1][ln]); } while (__any_sync(0xffffffffu, (v0 & 31) != tag) && --budget > 0);
      const uint32_t now = __shfl_sync(0xffffffffu, v0, 0);
      t0 = now + __reduce_max_sync(0xffffffffu, (int)(v0 - now));
      f_time = t0 + fd;
      RPROF(26); CPROF(3, t0);
      t0 += t < LAG ? TP(8) : t < NSEG ? TP(0) : TP(12);
#pragma unroll 1
      for (int i = i0; i < i1; i++) {
        const uint32_t tg = h1_tag(i ? sc : sa);
        uint2 v[8];
        wait_time(t0 + (!two ? 0 : i ? TP(3) : -TP(10)));
        int tries = 0;
        float a[4];
        while (true) {
          tries++;
#pragma unroll
          for (int k = 0; k < 8; k++) v[k] = ldg_rlx64(src + k * 256);
          asm volatile("{.reg .pred p; setp.eq.s32 p, %0, 0x7fffffff; @p exit;}" :: "r"(budget) : "memory");
          uint32_t bad = 0;
#pragma unroll
          for (int k = 0; k < 8; k++) {
            bad = xor_or(v[k].x, tg, bad);
            a[0] = k ? a[0] + bf_lo(v[k].x) : bf_lo(v[k].x); a[1] = k ? a[1] + bf_hi(v[k].x) : bf_hi(v[k].x);
            a[2] = k ? a[2] + bf_lo(v[k].y) : bf_lo(v[k].y); a[3] = k ? a[3] + bf_hi(v[k].y) : bf_hi(v[k].y);
          }
#pragma unroll
          for (int k = 0; k < 2; k++) {
            const float keep = (ln & 8) ? a[2+k] : a[k], send = (ln & 8) ? a[k] : a[2+k];
            a[k] = keep + __shfl_xor_sync(0xffffffffu, send, 8);
          }
#pragma unroll
          for (int k = 0; k < 2; k++) a[k] += __shfl_xor_sync(0xffffffffu, a[k], 16);
          if (!__any_sync(0xffffffffu, bad & 1) || --budget < 0) break;
        }
        const uint32_t out = pack_bf16(a[0], a[1]);
        if (ln < 16) stg_rlx32(dst, out ? out : 0x8000u);
        __syncwarp();
        src += ds; dst += dd;
        if (i == 0) { RPROF(28); CPROF(6, gtime()); CPROF(4, gtime()); CPROF(5, tries); } else CPROF(7, gtime());
      }
    }
    if (warp == (dual ? 2 : 1) && att && (seg & 3) == 3) { nbar_sync<NB_O, 160>(); e_flag_add(&g_dep[E_O1 + rank * 16 + (seg >> 2)]); }
    if (n == NSTEP) break;
  }
  if (h == 0 && rank == 0 && warp < 2) g_xa[warp][lane_id()] = 0;
}
}

__global__ void __launch_bounds__(384, 1)
rec_kernel(const __grid_constant__ rec::Maps M, const bf16* __restrict__ mem0) {
  using namespace rec;
  extern __shared__ __align__(1024) uint8_t smem[];
  const uint32_t sb = __shfl_sync(0xffffffffu, smem_u32(smem), 0);
  const int tid = threadIdx.x, wi = __shfl_sync(0xffffffffu, tid >> 5, 0);
  if ((sb & 0x3FFFF) != SMEM_BASE) __trap();
  if (wi == 0) {
    const int h = cta_id() / 3, rank = cta_id() - h * 3;
    const int nwg = 2 * cluster_last() + 2;
    for (int i = tid; i < NBAR; i += 32) mbar_init(sb + BARS + i * 8, i < 13 ? nwg : i < 19 ? 2 : 1);
    ((uint32_t*)(smem + PAD))[tid] = 0;
    fence_mbar_init(); fence_proxy_async();
    __syncwarp();
    e_expect_tx(sb + B_ST, STG); e_expect_tx(sb + B_ST + 8, STG);
    for (int i = 0; i < 2 * KR; i++) e_tma_2d(sb + (i & 1) * STG + (i >> 1) * 2048, &M.w[rank], h * DH + (i & 1) * 64, k_of_reg(i >> 1) * 16, sb + B_ST + (i & 1) * 8);
  } else if (wi == 1) {
    if (blockIdx.x < NEV / 32) { g_dep[blockIdx.x * 32 + (tid & 31)] = 0; g_claim[blockIdx.x * 32 + (tid & 31)] = 0; __threadfence(); }
    __syncwarp();
    asm volatile("griddepcontrol.launch_dependents;" ::: "memory");
  }
  cluster_arrive(); cluster_wait();
  if (wi < 8) { reg_inc<232>(); rec_math(sb, wi, M); cluster_arrive(); cluster_wait(); }
  else { reg_dec<40>(); rec_comm(sb, wi & 3, M, mem0); cluster_arrive(); cluster_wait(); }
}

namespace gm {
struct Maps { CUtensorMap ot, wo, xn, wg, wu, hl, hs, wd, out; };
constexpr int STAGES = 6, STAGE = 32768;
constexpr uint32_t SO = STAGES * STAGE, BARS = SO + 32768;
constexpr uint32_t B_FULL = BARS, B_EMPTY = BARS + 48, B_TF = BARS + 96, B_TE = BARS + 112, B_ORD = BARS + 128, B_PM = BARS + 144, B_GO = BARS + 160;
constexpr uint32_t MAIL = BARS + 176, PMAIL = BARS + 192;
constexpr uint32_t SMEM = BARS + 256;
constexpr int END = -1;
#define DQ 8
#define GT gtime

struct Tile {
  bool isO, isG, l2; int blk, col, k0, n;
  DEVI Tile(int task, int rank) {
    const int e = task >> 8, id = task & 255;
    const bool isD = e < E_G1 || e >= E_D2;
    isO = e >= E_O1 && e < E_G2; isG = !isD && !isO; l2 = e >= E_O2;
    blk = l2 && !isO ? (e & 7) * 2 + rank : isD ? e >> 1 : e & 15;
    col = l2 && !isO ? id : (isG ? id : id & 3) * 2 + rank;
    k0 = isO ? (id >> 2) * 2048 : isG ? 0 : ((l2 ? e >> 3 : e) & 1) * 1792;
    n = isO ? 32 : isG ? 16 : 28;
    if (e >= E_D2 + DQ) { n = 14; k0 += (id >> 3) * 896; col = id & 7; }
  }
};

DEVI float geglu(float g, float u) {
  const float z = g * (0.7978845608028654f + 0.035677408136300125f * g * g);
  float t; asm("tanh.approx.f32 %0, %1;" : "=f"(t) : "f"(z));
  const float hg = 0.5f * g;
  return fmaf(hg, t, hg) * u;
}
struct Sched {
  int need, size, e;
  bool filler;
  uint4 dep, cl;
  DEVI void init(int lane) {
    e = (lane < 4 ? lane + 12 : lane < 16 ? lane - 4 : lane) * 4;
    const bool d = e < E_G1 || e >= E_D2, o = e >= E_O1 && e < E_G2;
    need = e >= E_D2 ? 56 : d ? 28 : e < E_O1 ? 64 : o ? 32 : 128;
    size = e >= E_D2 ? (e < E_D2 + DQ ? 8 : e < E_D2 + 16 ? 16 : 0) : d ? 4 : o ? 8 : e < E_O1 ? 28 : e < E_G2 + 8 ? 56 : 0;
    filler = (int)blockIdx.x >= TP(5);
  }
  DEVI void scan(int lane) { cl = ldg_rlx128(g_claim + e); dep = ldg_rlx128(g_dep + e); }
  DEVI int next(int lane, int& budget) {
    while (--budget > 0) {
      int av[4], open = 0;
#pragma unroll
      for (int i = 0; i < 4; i++) { const int r = max(size - (int)(&cl.x)[i], 0); open |= r; av[i] = ((int)(&dep.x)[i] >= need ? r : 0) + (i ? av[i - 1] : 0); }
      const uint32_t mo = __ballot_sync(0xffffffffu, open);
      if (!mo) break;
      if (filler) {
        const int x = TP(6) & 3, dx = x == 0 ? dep.x : x == 1 ? dep.y : x == 2 ? dep.z : dep.w;
        filler = !__any_sync(0xffffffffu, e == ((E_O1 + TP(6)) & ~3) && dx >= need);
      }
      if (!filler && (mo & 0xffff) && lane >= E_O2 / 4) av[3] = 0;
      int inc = av[3], pos = 0;
      while (true) {
        const uint32_t m = __ballot_sync(0xffffffffu, inc > pos && av[3]);
        if (!m) break;
        const int l = __ffs(m) - 1, rel = pos - (inc - av[3]), i = (rel >= av[0]) + (rel >= av[1]) + (rel >= av[2]);
        int r = 0;
        if (lane == l) {
          const int tk = atomicAdd(g_claim + e + i, 1);
          r = tk < size ? (e + i) << 8 | tk : -1 - (inc - av[3] + (i == 0 ? av[0] : i == 1 ? av[1] : i == 2 ? av[2] : av[3]) + tk - size);
        }
        r = __shfl_sync(0xffffffffu, r, l);
        if (r >= 0) return r;
        if (pos == 0) {
#pragma unroll
          for (int o = 1; o < 32; o <<= 1) { const int v = __shfl_up_sync(0xffffffffu, inc, o); if (lane >= o) inc += v; }
        }
        pos = -1 - r;
      }
      if (pos == 0) __nanosleep(TP(7));
      scan(lane);
    }
    return END;
  }
};

DEVI void scheduler(const uint32_t sb) {
  const int lane = threadIdx.x & 31;
  int budget = SPIN_BUDGET;
  Sched sc; sc.init(lane);
#pragma unroll 1
  for (int i = 0;; i++) {
    if (i) mbar_wait(sb + B_GO, (i & 1) ^ 1, budget);
    sc.scan(lane);
    if (i == 0) cluster_wait();
    const int task = sc.next(lane, budget);
    const uint32_t r = mapa(sb, lane & 1);
    if (lane < 2) st_async32(r + PMAIL + (i & 1) * 4, task, r + B_PM + (i & 1) * 8);
    __syncwarp();
    if (task == END) break;
  }
}

DEVI void producer(const uint32_t sb, const Maps& M) {
  const int lane = threadIdx.x & 31, rank = cluster_rank();
  int budget = SPIN_BUDGET, s = 0, ph = 0;
#pragma unroll 1
  for (int i = 0;; i++) {
    e_expect_tx(sb + B_PM + (i & 1) * 8, 4);
    mbar_wait_cluster(sb + B_PM + (i & 1) * 8, (i >> 1) & 1, budget);
    const int task = budget < 0 ? END : __shfl_sync(0xffffffffu, (int)lds32v(sb + PMAIL + (i & 1) * 4), 0);
    fence_proxy_global();
    for (int z = 0; z < (task == END ? 2 : 1); z++) {
      const int g = (i + z) & 1;
      mbar_wait(sb + B_TE + g * 8, (((i + z) >> 1) & 1) ^ 1, budget);
      if (lane == 0) { sts64(sb + MAIL + g * 8, task, s | ph << 8); mbar_arrive(sb + B_TF + g * 8); }
      __syncwarp();
    }
    if (task == END) break;
    const Tile T(task, rank);
    const bool shareB = T.l2 && !T.isO;
    const CUtensorMap* mA = T.isO ? &M.ot : T.isG ? &M.xn : &M.hl;
    const CUtensorMap* mB0 = T.isO ? &M.wo : T.isG ? &M.wg : &M.wd;
    const CUtensorMap* mB1 = T.isG ? &M.wu : mB0;
    const int c0 = T.col * (T.isG ? 64 : 128), c1 = T.isG ? c0 : c0 + 64, row = T.blk * 128;
    const int ok = 0;
    int k = T.k0;
#pragma unroll 1
    for (int it = 0; it < T.n; it++, k += 64) {
      const uint32_t a = sb + s * STAGE, fb = sb + B_FULL + s * 8;
      mbar_wait(sb + B_EMPTY + s * 8, ph ^ 1, budget);
      e_expect_tx(fb, STAGE);
      if (shareB) {
        e_tma_2d_mc(a + 16384 + rank * 8192, rank ? mB1 : mB0, rank ? c1 : c0, k, fb);
        e_tma_2d(a, mA, k, row, fb); e_tma_2d(a + 8192, mA, k, row + 64, fb);
      } else {
        e_tma_2d_mc(a + rank * 8192, mA, T.isO ? row + rank * 64 : k, T.isO ? k + ok : row + rank * 64, fb);
        e_tma_2d(a + 16384, mB0, c0, k, fb); e_tma_2d(a + 24576, mB1, c1, k, fb);
      }
      if (it == T.n - TP(2)) e_arrive(sb + B_GO);
      if (++s == STAGES) { s = 0; ph ^= 1; }
    }
  }
}

template<int TA> DEVI void mainloop(float* d0, float* d1, uint32_t sb, int n, int s, int ph, bool lead, uint32_t ord, int& budget) {
  int prev = 0;
  const uint32_t rel = threadIdx.x & 127;
#pragma unroll 1
  for (int i = 0; i < n; i++) {
    mbar_wait(sb + B_FULL + s * 8, ph, budget);
    const uint32_t a = sb + s * STAGE;
    const uint64_t da = mkdesc(a, 16, 1024), db = mkdesc(a + 16384, 8192, 1024);
    wg_fence();
#pragma unroll
    for (int k = 0; k < 4; k++) {
      wgmma_n128<TA>(d0, da + k * (TA ? 128 : 2), db + k * 128, (i | k) != 0);
      wgmma_n128<TA>(d1, da + 512 + k * (TA ? 128 : 2), db + k * 128, (i | k) != 0);
    }
    wg_commit();
    if (i > 0) { wg_wait<1>(); p_arrive_at(sb + B_EMPTY + prev * 8, rel & 1, rel < 2); }
    prev = s;
    if (++s == STAGES) { s = 0; ph ^= 1; }
  }
  p_arrive(ord, lead);
  wg_wait<0>();
  p_arrive_at(sb + B_EMPTY + prev * 8, rel & 1, rel < 2);
}

DEVI void consumer(const uint32_t sb, const Maps& M, const int wg) {
  const int tid = threadIdx.x, lane = tid & 31, warp = (tid >> 5) & 3;
  const bool lead = (tid & 127) == 0;
  const uint32_t so = sb + SO + wg * 16384;
  int budget = SPIN_BUDGET;
  float d0[64], d1[64];
#pragma unroll 1
  for (int m = 0;; m++) {
    mbar_wait(sb + B_TF + wg * 8, m & 1, budget);
    const uint2 mail = lds64v(sb + MAIL + wg * 8);
    const int task = __shfl_sync(0xffffffffu, (int)mail.x, 0), pos = __shfl_sync(0xffffffffu, (int)mail.y, 0);
    e_arrive(sb + B_TE + wg * 8);
    if (task == END || budget < 0) break;
    const Tile T(task, cluster_rank());
    mbar_wait(sb + B_ORD + wg * 8, (m & 1) ^ wg ^ 1, budget);
    if (T.isO) mainloop<1>(d0, d1, sb, T.n, pos & 255, pos >> 8, lead, sb + B_ORD + (wg ^ 1) * 8, budget);
    else mainloop<0>(d0, d1, sb, T.n, pos & 255, pos >> 8, lead, sb + B_ORD + (wg ^ 1) * 8, budget);
    const uint32_t st = so + (warp * 16 + (lane & 15)) * 128;
    if (T.isG) {
      int* const fl = &g_dep[T.l2 ? E_D2 + (T.col >= 28) * 8 + (T.blk >> 1) : E_D1 + T.blk * 2 + (T.col >= 28)];
#pragma unroll
      for (int mm = 0; mm < 2; mm++) {
        const float* d = mm ? d1 : d0;
#pragma unroll
        for (int c = 0; c < 4; c++) {
          uint32_t r[4];
#pragma unroll
          for (int i = 0; i < 4; i++) r[i] = pack_bf16(geglu(d[8*c+2*i], d[32+8*c+2*i]), geglu(d[8*c+2*i+1], d[33+8*c+2*i]));
          stsm4(st + mm * 8192 + (((2 * c + (lane >> 4)) ^ (lane & 7)) << 4), r[0], r[1], r[2], r[3]);
        }
      }
      fence_proxy_async();
      nbar_sync_r(1 + wg, 128);
      if (lead) {
        tma_store_2d(&M.hs, so, T.col * 64, T.blk * 128);
        bulk_commit();
        bulk_wait<0>();
        flag_add(fl);
      }
    } else {
#pragma unroll
      for (int hf = 0; hf < 2; hf++) {
        if (hf) { if (lead) bulk_wait_read<0>(); nbar_sync_r(1 + wg, 128); }
#pragma unroll
        for (int mm = 0; mm < 2; mm++) {
          const float* d = (mm ? d1 : d0) + hf * 32;
#pragma unroll
          for (int c = 0; c < 4; c++)
            stsm4(st + mm * 8192 + (((2 * c + (lane >> 4)) ^ (lane & 7)) << 4), pack_bf16(d[8*c], d[8*c+1]), pack_bf16(d[8*c+2], d[8*c+3]),
                  pack_bf16(d[8*c+4], d[8*c+5]), pack_bf16(d[8*c+6], d[8*c+7]));
        }
        fence_proxy_async();
        nbar_sync_r(1 + wg, 128);
        if (lead) { tma_radd_2d(&M.out, so, T.col * 128 + hf * 64, T.blk * 128); bulk_commit(); }
      }
      if (lead) {
        bulk_wait<0>();
        if (T.isO || !T.l2) flag_add(&g_dep[(!T.isO ? E_LX2 : T.l2 ? E_LX1B : E_LX1A) + T.blk]);
      }
    }
    __syncwarp();
  }
}

DEVI void norm_helper(const bf16* __restrict__ x, bf16* out) {
  const int lane = threadIdx.x & 31;
  int budget = SPIN_BUDGET, tk = lane < 4 ? -1 : 1024;
#pragma unroll 1
  while (--budget > 0) {
    if (tk < 0) tk = atomicAdd(g_claim + E_LI + lane, 1);
    if (__all_sync(0xffffffffu, tk >= 1024)) break;
    const uint32_t m = __ballot_sync(0xffffffffu, tk < 1024 && (lane == 0 || ldg_acq32(g_dep + E_LI + lane * 16 + (tk >> 6)) >= 16));
    if (!m) { __nanosleep(TP(7)); continue; }
    const int ql = __ffs(m) - 1, task = __shfl_sync(0xffffffffu, tk, ql), q = E_LI + ql * 16, ev = task >> 6;
    if (lane == ql) tk = -1;
    const size_t off = (size_t)task * (DM * 4) + lane * 16;
    const char* src = (const char*)(q == E_LI ? x : out) + off;
    uint4 u[8];
#pragma unroll
    for (int i = 0; i < 8; i++) u[i] = ldg_rlx128(src + i * 512);
    if (q == E_LI) {
#pragma unroll
      for (int i = 0; i < 8; i++) stg128((char*)out + off + i * 512, u[i].x, u[i].y, u[i].z, u[i].w);
    }
    int* const fl = q == E_LI ? &g_xa[0][ev] : q == E_LX2 ? &g_xa[1][ev] : &g_dep[q == E_LX1A ? E_G1 + ev : E_G2 + (ev >> 1)];
    float mean[2], rs[2];
#pragma unroll
    for (int r = 0; r < 2; r++) {
      float s0 = 0, s1 = 0;
#pragma unroll
      for (int i = 0; i < 16; i++) { const uint32_t v = (&u[4*r + (i >> 2)].x)[i & 3]; s0 += bf_lo(v); s1 += bf_hi(v); }
      mean[r] = (s0 + s1) * (1.f / 32);
      s0 = s1 = 0;
#pragma unroll
      for (int i = 0; i < 16; i++) { const uint32_t v = (&u[4*r + (i >> 2)].x)[i & 3]; const float a = bf_lo(v) - mean[r], b = bf_hi(v) - mean[r]; s0 = fmaf(a, a, s0); s1 = fmaf(b, b, s1); }
      rs[r] = s0 + s1;
    }
    {
      const bool hi = lane & 16;
      float m1 = hi ? mean[1] : mean[0], q1 = hi ? rs[1] : rs[0], m2 = hi ? mean[0] : mean[1], q2 = hi ? rs[0] : rs[1], cnt = 16;
#pragma unroll
      for (int o = 16; o; o >>= 1) {
        m2 = __shfl_xor_sync(0xffffffffu, m2, o); q2 = __shfl_xor_sync(0xffffffffu, q2, o);
        const float dl = m1 - m2;
        q2 = q1 = fmaf(dl * dl, cnt, q1 + q2); m2 = m1 = 0.5f * (m1 + m2);
        cnt *= 2;
      }
      q1 = rsqrtf(q1 * (1.f / DM) + 1e-5f);
      m2 = __shfl_xor_sync(0xffffffffu, m1, 16); q2 = __shfl_xor_sync(0xffffffffu, q1, 16);
      mean[0] = hi ? m2 : m1; mean[1] = hi ? m1 : m2; rs[0] = hi ? q2 : q1; rs[1] = hi ? q1 : q2;
    }
#pragma unroll
    for (int i = 0; i < 8; i++) {
      uint32_t y[4];
#pragma unroll
      for (int c = 0; c < 4; c++) { const uint32_t v = (&u[i].x)[c]; y[c] = pack_bf16((bf_lo(v) - mean[i >> 2]) * rs[i >> 2], (bf_hi(v) - mean[i >> 2]) * rs[i >> 2]); }
      stg128((char*)g_xn + off + i * 512, y[0], y[1], y[2], y[3]);
      u[i] = make_uint4(y[0], y[1], y[2], y[3]);
    }
    if (q == E_LI && (task & 15) >= 12) {
      uint32_t* const xr = g_xr[task >> 4] + lane * 32 + (task & 3);
#pragma unroll
      for (int i = 0; i < 16; i++) {
        const uint32_t a = (&u[i >> 2].x)[i & 3], b = (&u[4 + (i >> 2)].x)[i & 3];
        xr[(i >> 2) * 1024 + (i & 3) * 8] = __byte_perm(a, b, 0x5410); xr[(i >> 2) * 1024 + (i & 3) * 8 + 4] = __byte_perm(a, b, 0x7632);
      }
    }
    fence_proxy_global();
    __syncwarp();
    if (lane == 0) flag_add(fl);
    __syncwarp();
  }
}
}

__global__ void __cluster_dims__(2, 1, 1) __launch_bounds__(384, 1)
gemm_kernel(const __grid_constant__ gm::Maps M, const bf16* __restrict__ x, bf16* out) {
  using namespace gm;
  extern __shared__ __align__(1024) uint8_t smem[];
  const uint32_t sb = __shfl_sync(0xffffffffu, smem_u32(smem), 0);
  const int tid = threadIdx.x, wi = __shfl_sync(0xffffffffu, tid >> 5, 0);
  if (tid < 21) mbar_init(sb + BARS + tid * 8, tid == 14 || tid == 15 ? 4 : tid >= 6 && tid < 12 ? 2 : 1);
  fence_mbar_init();
  cluster_arrive();
  const bool sched = wi == 11 && cluster_rank() == 0;
  if (!sched) cluster_wait();
  if (wi < 8) { reg_inc<208>(); consumer(sb, M, wi >> 2); cluster_arrive(); cluster_wait(); }
  else {
    reg_dec<88>();
    if (wi == 8) producer(sb, M);
    else if (sched) scheduler(sb);
    else {
      norm_helper(x, out);
      asm volatile("griddepcontrol.wait;" ::: "memory");
    }
    __syncwarp();
    cluster_arrive(); cluster_wait();
  }
}

typedef CUresult (*PFN_encodeTiled)(CUtensorMap*, CUtensorMapDataType, cuuint32_t, void*, const cuuint64_t*, const cuuint64_t*,
                                    const cuuint32_t*, const cuuint32_t*, CUtensorMapInterleave, CUtensorMapSwizzle,
                                    CUtensorMapL2promotion, CUtensorMapFloatOOBfill);
static PFN_encodeTiled g_encode = nullptr;
static CUtensorMap make_map(const void* ptr, uint64_t rows, uint64_t cols, uint32_t box_rows, CUtensorMapL2promotion pr = CU_TENSOR_MAP_L2_PROMOTION_L2_256B) {
  CUtensorMap m;
  cuuint64_t dims[2] = {cols, rows}, strides[1] = {cols * 2};
  cuuint32_t box[2] = {64, box_rows}, es[2] = {1, 1};
  g_encode(&m, CU_TENSOR_MAP_DATA_TYPE_BFLOAT16, 2, (void*)ptr, dims, strides, box, es, CU_TENSOR_MAP_INTERLEAVE_NONE,
           CU_TENSOR_MAP_SWIZZLE_128B, pr, CU_TENSOR_MAP_FLOAT_OOB_FILL_NONE);
  return m;
}

static CUtensorMap make_map3(const void* ptr, uint64_t d0, uint64_t d1, uint64_t d2, uint64_t stride2) {
  CUtensorMap m;
  cuuint64_t dims[3] = {d0, d1, d2}, strides[2] = {DM * 2, stride2};
  cuuint32_t box[3] = {64, 32, 2}, es[3] = {1, 1, 1};
  g_encode(&m, CU_TENSOR_MAP_DATA_TYPE_BFLOAT16, 3, (void*)ptr, dims, strides, box, es, CU_TENSOR_MAP_INTERLEAVE_NONE,
           CU_TENSOR_MAP_SWIZZLE_128B, CU_TENSOR_MAP_L2_PROMOTION_L2_256B, CU_TENSOR_MAP_FLOAT_OOB_FILL_NONE);
  return m;
}

extern "C" void kernel_launch(void* const* d_in, const int* in_sizes, int n_in, void* d_out, int out_size) {
  const bf16* x = (const bf16*)d_in[0];
  const bf16* mem0 = (const bf16*)d_in[1];
  if (!g_encode) {
    void* p = nullptr; cudaDriverEntryPointQueryResult q;
    cudaGetDriverEntryPoint("cuTensorMapEncodeTiled", &p, cudaEnableDefault, &q);
    g_encode = (PFN_encodeTiled)p;
    cudaFuncSetAttribute(gemm_kernel, cudaFuncAttributeMaxDynamicSharedMemorySize, gm::SMEM);
    cudaFuncSetAttribute(rec_kernel, cudaFuncAttributeMaxDynamicSharedMemorySize, rec::SMEM);
  }
  bf16 *xn, *ot, *hh;
  cudaGetSymbolAddress((void**)&xn, g_xn); cudaGetSymbolAddress((void**)&ot, g_ot); cudaGetSymbolAddress((void**)&hh, g_h);
  rec::Maps R;
  for (int i = 0; i < 3; i++) R.w[i] = make_map(d_in[2 + i], DM, NH * DH, 16, CU_TENSOR_MAP_L2_PROMOTION_NONE);
  R.wo = make_map(d_in[5], NH * DH, DM, 128);
  R.xd = make_map3(xn, DM, SEQ - LAG * 32, 2, (uint64_t)LAG * 32 * DM * 2); R.xs = make_map3(xn, 64, SEQ, DM / 64, 128);
  gm::Maps G;
  G.ot = make_map(ot, NH * DH + O_LAYER / SEQ, SEQ, 64); G.wo = make_map(d_in[5], NH * DH, DM, 64); G.xn = make_map(xn, SEQ, DM, 64);
  G.wg = make_map(d_in[8], DM, DF, 64); G.wu = make_map(d_in[9], DM, DF, 64); G.hl = make_map(hh, SEQ, DF, 64); G.hs = make_map(hh, SEQ, DF, 128);
  G.wd = make_map(d_in[10], DF, DM, 64); G.out = make_map(d_out, SEQ, DM, 128);
  cudaLaunchConfig_t cfg = {};
  cudaLaunchAttribute at[1];
  cfg.attrs = at; cfg.numAttrs = 1;
  cfg.gridDim = dim3(3 * NH); cfg.blockDim = dim3(384); cfg.dynamicSmemBytes = rec::SMEM; cfg.stream = cudaStreamPerThread;
  at[0].id = cudaLaunchAttributeClusterDimension; at[0].val.clusterDim.y = at[0].val.clusterDim.z = 1;
  static int csize = 0;
  if (!csize) {
    int n = 0;
    at[0].val.clusterDim.x = 6;
    csize = cudaOccupancyMaxActiveClusters(&n, rec_kernel, &cfg) == cudaSuccess && n >= NH / 2 ? 6 : 3;
  }
  at[0].val.clusterDim.x = csize;
  cudaLaunchKernelEx(&cfg, rec_kernel, R, mem0);
  cfg.gridDim = dim3(132); cfg.blockDim = dim3(384); cfg.dynamicSmemBytes = gm::SMEM; cfg.stream = cudaStreamPerThread;
  at[0].id = cudaLaunchAttributeProgrammaticStreamSerialization; at[0].val.programmaticStreamSerializationAllowed = 1;
  cudaLaunchKernelEx(&cfg, gemm_kernel, G, x, (bf16*)d_out);
}
```

```cpp
#include <cuda_runtime.h>
#include <cuda_bf16.h>
#include <cuda.h>
#include <stdint.h>

#define DEVI __device__ __forceinline__
typedef __nv_bfloat16 bf16;

constexpr int SEQ = 2048, DM = 1024, NH = 32, DH = 128, DF = 3584, NSEG = 64;
#define LAG 20
constexpr int NSTEP = NSEG + LAG;

#define TSD 1800
constexpr size_t O_LAYER = 0;
__device__ __align__(1024) bf16 g_xn[SEQ * DM];
__device__ __align__(1024) bf16 g_ot[SEQ * NH * DH + O_LAYER];
__device__ __align__(1024) bf16 g_h[SEQ * DF];
__device__ __align__(1024) uint32_t g_xr[NSEG][DM * 4];
__device__ __align__(1024) uint2 g_h1[4][256 * 256];
__device__ __align__(1024) uint4 g_h2[4][2048];
__device__ __align__(128) uint32_t g_ts[2][32];
enum { E_D1 = 0, E_G1 = 32, E_O1 = 48, E_O2 = 64, E_G2 = 80, E_D2 = 96,
       E_LI = 128, E_LX2 = 144, E_LX1A = 160, E_LX1B = 176, NEV = 256 };
__device__ __align__(128) int g_dep[NEV];
__device__ __align__(128) int g_claim[NEV];
__device__ __align__(128) int g_xa[2][32];

#define TUNE_DEFAULTS 1650, 2450, 6, 100, 100, 8, 14, 100, 1550, 2280, 100, 110, 1550, 2320, 200, 0
constexpr int c_D[16] = {TUNE_DEFAULTS};
template<int I> struct TPV { static constexpr int v = c_D[I]; };
#define TP(i) TPV<i>::v

DEVI uint32_t smem_u32(const void* p) { return (uint32_t)__cvta_generic_to_shared(p); }
DEVI void mbar_init(uint32_t bar, uint32_t cnt) { asm volatile("mbarrier.init.shared::cta.b64 [%0], %1;" :: "r"(bar), "r"(cnt) : "memory"); }
DEVI void mbar_arrive(uint32_t bar) { asm volatile("mbarrier.arrive.shared::cta.b64 _, [%0];" :: "r"(bar) : "memory"); }
DEVI bool mbar_try(uint32_t bar, uint32_t parity) {
  uint32_t p;
  asm volatile("{.reg .pred p; mbarrier.try_wait.parity.shared::cta.b64 p, [%1], %2; selp.u32 %0, 1, 0, p;}" : "=r"(p) : "r"(bar), "r"(parity) : "memory");
  return p;
}
DEVI bool mbar_test(uint32_t bar, uint32_t parity) {
  uint32_t p;
  asm volatile("{.reg .pred p; mbarrier.test_wait.parity.shared::cta.b64 p, [%1], %2; selp.u32 %0, 1, 0, p;}" : "=r"(p) : "r"(bar), "r"(parity) : "memory");
  return p;
}
constexpr int SPIN_BUDGET = 1 << 18;
DEVI void mbar_wait(uint32_t bar, uint32_t parity, int& budget) {
  while (!mbar_try(bar, parity)) { if (--budget < 0) break; }
}
DEVI bool mbar_try_cluster(uint32_t bar, uint32_t parity) {
  uint32_t p;
  asm volatile("{.reg .pred p; mbarrier.try_wait.parity.acquire.cluster.shared::cta.b64 p, [%1], %2; selp.u32 %0, 1, 0, p;}" : "=r"(p) : "r"(bar), "r"(parity) : "memory");
  return p;
}
DEVI void mbar_wait_cluster(uint32_t bar, uint32_t parity, int& budget) {
  while (!mbar_try_cluster(bar, parity)) { if (--budget < 0) break; }
}
DEVI uint32_t mapa(uint32_t addr, uint32_t rank) { uint32_t r; asm("mapa.shared::cluster.u32 %0, %1, %2;" : "=r"(r) : "r"(addr), "r"(rank)); return r; }
DEVI void cluster_arrive() { asm volatile("barrier.cluster.arrive.relaxed.aligned;" ::: "memory"); }
DEVI void cluster_wait() { asm volatile("barrier.cluster.wait.aligned;" ::: "memory"); }
DEVI void fence_mbar_init() { asm volatile("fence.mbarrier_init.release.cluster;" ::: "memory"); }
DEVI void fence_proxy_async() { asm volatile("fence.proxy.async.shared::cta;" ::: "memory"); }
DEVI void fence_proxy_global() { asm volatile("fence.proxy.async.global;" ::: "memory"); }
#define ELECT "{.reg .pred p; elect.sync _|p, 0xffffffff;\n @p "
DEVI void e_expect_tx(uint32_t bar, uint32_t bytes) { asm volatile(ELECT "mbarrier.arrive.expect_tx.shared::cta.b64 _, [%0], %1;}" :: "r"(bar), "r"(bytes) : "memory"); }
DEVI void e_complete_tx(uint32_t bar, uint32_t bytes) { asm volatile("fence.acq_rel.cta;\n" ELECT "mbarrier.complete_tx.relaxed.cta.shared::cta.b64 [%0], %1;}" :: "r"(bar), "r"(bytes) : "memory"); }
DEVI void e_arrive(uint32_t bar) { asm volatile(ELECT "mbarrier.arrive.shared::cta.b64 _, [%0];}" :: "r"(bar) : "memory"); }
DEVI void e_tma_2d(uint32_t dst, const CUtensorMap* m, int c0, int c1, uint32_t bar) {
  asm volatile(ELECT "cp.async.bulk.tensor.2d.shared::cluster.global.mbarrier::complete_tx::bytes [%0], [%1, {%3, %4}], [%2];}"
    :: "r"(dst), "l"(m), "r"(bar), "r"(c0), "r"(c1) : "memory");
}
DEVI void e_prefetch_3d(const CUtensorMap* m, int c0, int c1, int c2) {
  asm volatile(ELECT "cp.async.bulk.prefetch.tensor.3d.L2.global [%0, {%1, %2, %3}];}" :: "l"(m), "r"(c0), "r"(c1), "r"(c2) : "memory");
}
DEVI void e_bulk_g2s(uint32_t dst, const void* src, uint32_t bytes, uint32_t bar) {
  asm volatile(ELECT "cp.async.bulk.shared::cluster.global.mbarrier::complete_tx::bytes [%0], [%1], %2, [%3];}" :: "r"(dst), "l"(src), "r"(bytes), "r"(bar) : "memory");
}
DEVI void e_tma_3d(uint32_t dst, const CUtensorMap* m, int c0, int c1, int c2, uint32_t bar) {
  asm volatile(ELECT "cp.async.bulk.tensor.3d.shared::cluster.global.mbarrier::complete_tx::bytes [%0], [%1, {%3, %4, %5}], [%2];}"
    :: "r"(dst), "l"(m), "r"(bar), "r"(c0), "r"(c1), "r"(c2) : "memory");
}
DEVI void e_tma_3d_mc(uint32_t dst, const CUtensorMap* m, int c0, int c1, int c2, uint32_t bar, int last) {
  asm volatile(ELECT "cp.async.bulk.tensor.3d.shared::cluster.global.mbarrier::complete_tx::bytes.multicast::cluster [%0], [%1, {%3, %4, %5}], [%2], %6;}"
    :: "r"(dst), "l"(m), "r"(bar), "r"(c0), "r"(c1), "r"(c2), "h"((uint16_t)((2 << last) - 1)) : "memory");
}
DEVI void e_tma_2d_mc(uint32_t dst, const CUtensorMap* m, int c0, int c1, uint32_t bar) {
  asm volatile(ELECT "cp.async.bulk.tensor.2d.shared::cluster.global.mbarrier::complete_tx::bytes.multicast::cluster [%0], [%1, {%3, %4}], [%2], %5;}"
    :: "r"(dst), "l"(m), "r"(bar), "r"(c0), "r"(c1), "h"((uint16_t)3) : "memory");
}
DEVI void p_arrive_at(uint32_t bar, uint32_t rank, bool c) {
  asm volatile("{.reg .pred p; .reg .b32 a; setp.ne.u32 p, %2, 0; mapa.shared::cluster.u32 a, %0, %1; @p mbarrier.arrive.shared::cluster.b64 _, [a];}"
    :: "r"(bar), "r"(rank), "r"((uint32_t)c) : "memory");
}
DEVI void p_expect_tx(uint32_t bar, uint32_t bytes, bool c) {
  asm volatile("{.reg .pred p; setp.ne.u32 p, %2, 0; @p mbarrier.arrive.expect_tx.shared::cta.b64 _, [%0], %1;}" :: "r"(bar), "r"(bytes), "r"((uint32_t)c) : "memory");
}
DEVI void p_arrive(uint32_t bar, bool c) { asm volatile("{.reg .pred p; setp.ne.u32 p, %1, 0; @p mbarrier.arrive.shared::cta.b64 _, [%0];}" :: "r"(bar), "r"((uint32_t)c) : "memory"); }
DEVI void tma_store_2d(const CUtensorMap* m, uint32_t src, int c0, int c1) {
  asm volatile("cp.async.bulk.tensor.2d.global.shared::cta.bulk_group [%0, {%2, %3}], [%1];" :: "l"(m), "r"(src), "r"(c0), "r"(c1) : "memory");
}
DEVI void tma_radd_2d(const CUtensorMap* m, uint32_t src, int c0, int c1) {
  asm volatile("cp.reduce.async.bulk.tensor.2d.global.shared::cta.add.bulk_group [%0, {%2, %3}], [%1];" :: "l"(m), "r"(src), "r"(c0), "r"(c1) : "memory");
}
DEVI void bulk_commit() { asm volatile("cp.async.bulk.commit_group;" ::: "memory"); }
template<int N> DEVI void bulk_wait_read() { asm volatile("cp.async.bulk.wait_group.read %0;" :: "n"(N) : "memory"); }
template<int N> DEVI void bulk_wait() { asm volatile("cp.async.bulk.wait_group %0;" :: "n"(N) : "memory"); }
template<int ID, int N> DEVI void nbar_sync() { asm volatile("bar.sync %0, %1;" :: "n"(ID), "n"(N) : "memory"); }
template<int ID, int N> DEVI void nbar_arrive() { asm volatile("bar.arrive %0, %1;" :: "n"(ID), "n"(N) : "memory"); }
DEVI void nbar_sync_r(int id, int n) { asm volatile("bar.sync %0, %1;" :: "r"(id), "r"(n) : "memory"); }
template<int R> DEVI void reg_inc() { asm volatile("setmaxnreg.inc.sync.aligned.u32 %0;" :: "n"(R)); }
template<int R> DEVI void reg_dec() { asm volatile("setmaxnreg.dec.sync.aligned.u32 %0;" :: "n"(R)); }
DEVI void wg_fence() { asm volatile("wgmma.fence.sync.aligned;" ::: "memory"); }
DEVI void wg_commit() { asm volatile("wgmma.commit_group.sync.aligned;" ::: "memory"); }
template<int N> DEVI void wg_wait() { asm volatile("wgmma.wait_group.sync.aligned %0;" :: "n"(N) : "memory"); }
DEVI uint64_t mkdesc(uint32_t addr, uint32_t lbo, uint32_t sbo, uint32_t sw = 1) {
  return ((uint64_t)((addr & 0x3FFFF) >> 4)) | ((uint64_t)(lbo >> 4) << 16) | ((uint64_t)(sbo >> 4) << 32) | ((uint64_t)sw << 62);
}
constexpr uint32_t SMEM_BASE = 1024;
__host__ __device__ constexpr long long CD(uint32_t off, uint32_t lbo, uint32_t sbo, uint32_t sw) {
  return (long long)(((uint64_t)((SMEM_BASE + off) >> 4)) | ((uint64_t)(lbo >> 4) << 16) | ((uint64_t)(sbo >> 4) << 32) | ((uint64_t)sw << 62));
}
DEVI uint32_t pack_bf16(float lo, float hi) { uint32_t r; asm("cvt.rn.bf16x2.f32 %0, %1, %2;" : "=r"(r) : "f"(hi), "f"(lo)); return r; }
DEVI float bf_lo(uint32_t v) { return __uint_as_float(v << 16); }
DEVI float bf_hi(uint32_t v) { return __uint_as_float(v & 0xffff0000u); }
DEVI void ldsm4t(uint32_t addr, uint32_t& r0, uint32_t& r1, uint32_t& r2, uint32_t& r3) {
  asm volatile("ldmatrix.sync.aligned.m8n8.x4.trans.shared.b16 {%0,%1,%2,%3}, [%4];" : "=r"(r0), "=r"(r1), "=r"(r2), "=r"(r3) : "r"(addr) : "memory");
}
DEVI void stsm4(uint32_t addr, uint32_t r0, uint32_t r1, uint32_t r2, uint32_t r3) {
  asm volatile("stmatrix.sync.aligned.m8n8.x4.shared.b16 [%0], {%1,%2,%3,%4};" :: "r"(addr), "r"(r0), "r"(r1), "r"(r2), "r"(r3) : "memory");
}
DEVI uint2 lds64v(uint32_t a) { uint2 v; asm volatile("ld.volatile.shared.v2.u32 {%0,%1}, [%2];" : "=r"(v.x), "=r"(v.y) : "r"(a) : "memory"); return v; }
DEVI uint32_t lds32v(uint32_t a) { uint32_t v; asm volatile("ld.volatile.shared.u32 %0, [%1];" : "=r"(v) : "r"(a) : "memory"); return v; }
DEVI uint4 lds128v(uint32_t a) { uint4 v; asm volatile("ld.volatile.shared.v4.u32 {%0,%1,%2,%3}, [%4];" : "=r"(v.x), "=r"(v.y), "=r"(v.z), "=r"(v.w) : "r"(a) : "memory"); return v; }
DEVI void sts32(uint32_t a, uint32_t x) { asm volatile("st.shared.u32 [%0], %1;" :: "r"(a), "r"(x) : "memory"); }
DEVI int lane_id() { int r; asm volatile("mov.u32 %0, %%laneid;" : "=r"(r)); return r; }
DEVI void sts64(uint32_t a, uint32_t x, uint32_t y) { asm volatile("st.shared.v2.u32 [%0], {%1,%2};" :: "r"(a), "r"(x), "r"(y) : "memory"); }
DEVI void st_async128(uint32_t a, uint32_t x, uint32_t y, uint32_t z, uint32_t w, uint32_t bar) {
  asm volatile("st.async.weak.shared::cluster.mbarrier::complete_tx::bytes.v4.b32 [%0], {%1,%2,%3,%4}, [%5];" :: "r"(a), "r"(x), "r"(y), "r"(z), "r"(w), "r"(bar) : "memory");
}
DEVI void st_async32(uint32_t a, uint32_t x, uint32_t bar) {
  asm volatile("st.async.weak.shared::cluster.mbarrier::complete_tx::bytes.b32 [%0], %1, [%2];" :: "r"(a), "r"(x), "r"(bar) : "memory");
}
DEVI uint4 ldg_rlx128(const void* p) {
  uint4 v;
  asm volatile("ld.relaxed.gpu.global.v4.b32 {%0,%1,%2,%3}, [%4];" : "=r"(v.x), "=r"(v.y), "=r"(v.z), "=r"(v.w) : "l"(p) : "memory");
  return v;
}
DEVI int ldg_rlx32(const void* p) { int v; asm volatile("ld.relaxed.gpu.global.b32 %0, [%1];" : "=r"(v) : "l"(p) : "memory"); return v; }
DEVI int ldg_acq32(const void* p) { int v; asm volatile("ld.acquire.gpu.global.b32 %0, [%1];" : "=r"(v) : "l"(p) : "memory"); return v; }
DEVI void stg128(void* p, uint32_t x, uint32_t y, uint32_t z, uint32_t w) {
  asm volatile("st.global.v4.b32 [%0], {%1,%2,%3,%4};" :: "l"(p), "r"(x), "r"(y), "r"(z), "r"(w) : "memory");
}
DEVI uint2 ldg_rlx64(const void* p) { uint2 v; asm volatile("{.reg .b64 a; ld.relaxed.gpu.global.b64 a, [%2]; mov.b64 {%0,%1}, a;}" : "=r"(v.x), "=r"(v.y) : "l"(p) : "memory"); return v; }
DEVI void stg_rlx64(void* p, uint32_t x, uint32_t y) { asm volatile("{.reg .b64 a; mov.b64 a, {%1,%2}; st.relaxed.gpu.global.b64 [%0], a;}" :: "l"(p), "r"(x), "r"(y) : "memory"); }
DEVI void stg_rlx32(void* p, uint32_t x) { asm volatile("st.relaxed.gpu.global.b32 [%0], %1;" :: "l"(p), "r"(x) : "memory"); }
DEVI void flag_add(int* p) { asm volatile("fence.proxy.async.global; red.release.gpu.global.add.s32 [%0], 1;" :: "l"(p) : "memory"); }
DEVI void e_stg_rlx32(void* p, uint32_t x) { asm volatile(ELECT "st.relaxed.gpu.global.b32 [%0], %1;}" :: "l"(p), "r"(x) : "memory"); }
DEVI void e_flag_add(int* p) { asm volatile("fence.proxy.async.global;\n" ELECT "red.release.gpu.global.add.s32 [%0], 1;}" :: "l"(p) : "memory"); }
DEVI int cluster_rank() { int r; asm volatile("mov.u32 %0, %%cluster_ctarank;" : "=r"(r)); return __shfl_sync(0xffffffffu, r, 0); }
DEVI int cluster_last() { int r; asm volatile("mov.u32 %0, %%cluster_nctarank;" : "=r"(r)); return __shfl_sync(0xffffffffu, r, 0) - 1; }
DEVI int cta_id() { int r; asm volatile("mov.u32 %0, %%ctaid.x;" : "=r"(r)); return __shfl_sync(0xffffffffu, r, 0); }
DEVI uint32_t clock32() { uint32_t c; asm volatile("mov.u32 %0, %%clock;" : "=r"(c)); return c; }
DEVI uint32_t gtime() { uint32_t c; asm volatile("mov.u32 %0, %%globaltimer_lo;" : "=r"(c)); return c; }
DEVI void wait_time(uint32_t t) { while (__any_sync(0xffffffffu, t - gtime() - 1 < 4000u)) {} }
DEVI void spin_until(uint32_t t0, int d) {
  int r;
  while (__any_sync(0xffffffffu, (r = d - (int)(clock32() - t0)) > 0)) {
    if (r > 300) __nanosleep(r >> 2);
  }
}
DEVI void pin2(const void* a, const void* b) { asm volatile("{.reg .pred p; setp.eq.u64 p, %0, %1; @p st.volatile.global.u64 [%0], %1;}" :: "l"(a), "l"(b) : "memory"); }
DEVI void pin2(uint32_t a, uint32_t b) { asm volatile("{.reg .pred p; setp.eq.u32 p, %0, %1; @p st.volatile.shared.u32 [%0], %1;}" :: "r"(a), "r"(b) : "memory"); }
DEVI void p_stg_rlx64(void* p, uint32_t x, uint32_t y, bool c) {
  asm volatile("{.reg .pred p; .reg .b64 a; setp.ne.u32 p, %3, 0; mov.b64 a, {%1,%2}; @p st.relaxed.gpu.global.b64 [%0], a;}" :: "l"(p), "r"(x), "r"(y), "r"((uint32_t)c) : "memory");
}
DEVI void pin2(uint64_t a, uint64_t b) { pin2((const void*)a, (const void*)b); }
DEVI uint64_t pair(uint32_t a, uint32_t bar) { return a | (uint64_t)bar << 32; }
DEVI void st_async32(uint64_t q, uint32_t x) { st_async32((uint32_t)q, x, (uint32_t)(q >> 32)); }
DEVI void st_async128(uint64_t q, uint4 v) { st_async128((uint32_t)q, v.x, v.y, v.z, v.w, (uint32_t)(q >> 32)); }
DEVI float ex2(float x) { float r; asm("ex2.approx.ftz.f32 %0, %1;" : "=f"(r) : "f"(x)); return r; }
DEVI float rcp(float x) { float r; asm("rcp.approx.ftz.f32 %0, %1;" : "=f"(r) : "f"(x)); return r; }
DEVI uint32_t xor_or(uint32_t a, uint32_t t, uint32_t acc) { uint32_t r; asm("lop3.b32 %0, %1, %2, %3, 0xbe;" : "=r"(r) : "r"(a), "r"(t), "r"(acc)); return r; }
DEVI void stsm2(uint32_t addr, uint32_t r0, uint32_t r1) {
  asm volatile("stmatrix.sync.aligned.m8n8.x2.shared.b16 [%0], {%1,%2};" :: "r"(addr), "r"(r0), "r"(r1) : "memory");
}
DEVI uint32_t settag(uint32_t v, uint32_t tag) { return (v & ~1u) | tag; }

#define A4(c, o)  c(d[o+0]), c(d[o+1]), c(d[o+2]), c(d[o+3])
#define A8(c, o)  A4(c, o), A4(c, o+4)
#define A16(c, o) A8(c, o), A8(c, o+8)
#define A12(c, o) A8(c, o), A4(c, o+8)
#define A28(c, o) A16(c, o), A12(c, o+16)
#define RL12 "{%0,%1,%2,%3,%4,%5,%6,%7,%8,%9,%10,%11}"
#define RL28 "{%0,%1,%2,%3,%4,%5,%6,%7,%8,%9,%10,%11,%12,%13,%14,%15,%16,%17,%18,%19,%20,%21,%22,%23,%24,%25,%26,%27}"
#define A20(c, o) A16(c, o), A4(c, o+16)
#define A32(c, o) A16(c, o), A16(c, o+16)
#define RL8  "{%0,%1,%2,%3,%4,%5,%6,%7}"
#define RL16 "{%0,%1,%2,%3,%4,%5,%6,%7,%8,%9,%10,%11,%12,%13,%14,%15}"
#define RL20 "{%0,%1,%2,%3,%4,%5,%6,%7,%8,%9,%10,%11,%12,%13,%14,%15,%16,%17,%18,%19}"
#define RL32 "{%0,%1,%2,%3,%4,%5,%6,%7,%8,%9,%10,%11,%12,%13,%14,%15,%16,%17,%18,%19,%20,%21,%22,%23,%24,%25,%26,%27,%28,%29,%30,%31}"
#define RL64 "{%0,%1,%2,%3,%4,%5,%6,%7,%8,%9,%10,%11,%12,%13,%14,%15,%16,%17,%18,%19,%20,%21,%22,%23,%24,%25,%26,%27,%28,%29,%30,%31," \
  "%32,%33,%34,%35,%36,%37,%38,%39,%40,%41,%42,%43,%44,%45,%46,%47,%48,%49,%50,%51,%52,%53,%54,%55,%56,%57,%58,%59,%60,%61,%62,%63}"
#define WG_OP(shape) "wgmma.mma_async.sync.aligned." shape "k16.f32.bf16.bf16 "
#define DEF_WGMMA(N, RL, AL, i0, i1, i2, i3, i4, i5, i6)                                                                         \
  template<int SC, int TB, long long CB> DEVI void rs##N(float* d, const uint32_t* a) {                                          \
    if (SC) asm volatile("{.reg .b64 tb; mov.b64 tb, %" #i4 ";\n" WG_OP("m64n" #N) RL ", {%" #i0 ",%" #i1 ",%" #i2 ",%" #i3 "}, tb, 1, 1, 1, %" #i5 ";}" \
      : AL("+f", 0) : "r"(a[0]), "r"(a[1]), "r"(a[2]), "r"(a[3]), "n"(CB), "n"(TB));                                             \
    else asm volatile("{.reg .b64 tb; mov.b64 tb, %" #i4 ";\n" WG_OP("m64n" #N) RL ", {%" #i0 ",%" #i1 ",%" #i2 ",%" #i3 "}, tb, 0, 1, 1, %" #i5 ";}" \
      : AL("=f", 0) : "r"(a[0]), "r"(a[1]), "r"(a[2]), "r"(a[3]), "n"(CB), "n"(TB));                                             \
  }                                                                                                                              \
  template<int SC, int TA, int TB, long long CA, long long CB> DEVI void ss##N(float* d, uint32_t a) {                           \
    if (SC) asm volatile("{.reg .b64 ta, tb; .reg .b32 lo, hi; add.u32 lo, %" #i0 ", %" #i1 "; mov.b32 hi, %" #i2 "; mov.b64 ta, {lo, hi}; mov.b64 tb, %" #i3 ";\n" \
      WG_OP("m64n" #N) RL ", ta, tb, 1, 1, 1, %" #i4 ", %" #i5 ";}"                                                              \
      : AL("+f", 0) : "r"(a), "n"((int)CA), "n"((int)(CA >> 32)), "n"(CB), "n"(TA), "n"(TB));                                    \
    else asm volatile("{.reg .b64 ta, tb; .reg .b32 lo, hi; add.u32 lo, %" #i0 ", %" #i1 "; mov.b32 hi, %" #i2 "; mov.b64 ta, {lo, hi}; mov.b64 tb, %" #i3 ";\n" \
      WG_OP("m64n" #N) RL ", ta, tb, 0, 1, 1, %" #i4 ", %" #i5 ";}"                                                              \
      : AL("=f", 0) : "r"(a), "n"((int)CA), "n"((int)(CA >> 32)), "n"(CB), "n"(TA), "n"(TB));                                    \
  }
DEF_WGMMA(8, "{%0,%1,%2,%3}", A4, 4, 5, 6, 7, 8, 9, 10)
DEF_WGMMA(16, RL8, A8, 8, 9, 10, 11, 12, 13, 14)
DEF_WGMMA(32, RL16, A16, 16, 17, 18, 19, 20, 21, 22)
DEF_WGMMA(40, RL20, A20, 20, 21, 22, 23, 24, 25, 26)
DEF_WGMMA(24, RL12, A12, 12, 13, 14, 15, 16, 17, 18)
DEF_WGMMA(56, RL28, A28, 28, 29, 30, 31, 32, 33, 34)
template<int TA> DEVI void wgmma_n128(float* d, uint64_t a, uint64_t b, int scale_d) {
  asm volatile("{.reg .pred p; setp.ne.b32 p, %66, 0;\n" WG_OP("m64n128") RL64 ", %64, %65, p, 1, 1, %67, 1;}"
    : A32("+f", 0), A32("+f", 32) : "l"(a), "l"(b), "r"(scale_d), "n"(TA));
}

namespace rec {
constexpr int KR = 43;
constexpr uint32_t WSZ = (64 - KR) * 2048, STG = KR * 2048;
constexpr uint32_t WS = 0;
constexpr uint32_t RING = 2 * WSZ;
constexpr uint32_t OB = RING + 3 * 8192;
constexpr uint32_t PB = OB + 4096;
constexpr uint32_t WO = RING + 32768;
constexpr uint32_t ATT = WO + 5 * 16384;
constexpr uint32_t AK = ATT + 10240, AV = ATT + 20480;
constexpr uint32_t PAD = ATT + 30720;
constexpr uint32_t BARS = PAD + 128;
constexpr uint32_t B_XE = BARS  , B_FA = BARS + 64  , B_FB = BARS + 88, B_FO = BARS + 96;
constexpr uint32_t B_ME = BARS + 104  , B_WE = BARS + 136, B_PD = BARS + 144;
constexpr uint32_t B_XF = BARS + 152  , B_MF = BARS + 216  , B_CP = BARS + 248  , B_WT = BARS + 280  ;
constexpr uint32_t B_AB = BARS + 296, B_OB = BARS + 304, B_ST = BARS + 312  , B_WS = BARS + 328, B_WO = BARS + 336, B_AT = BARS + 352, B_AV = BARS + 360;
constexpr int NBAR = 46;
constexpr uint32_t M0 = BARS + 384;
constexpr uint32_t SMEM = 232448;
constexpr int NB_P = 1, NB_ST = 2, NB_O = 3, NB_W0 = 4, NB_W1 = 5;
__host__ __device__ constexpr int wo_tile(int rank, int g, int i) { return i < 2 ? i * 6 + (rank == 2 ? g : 4 - 2 * g + rank) : 13 + rank - g; }
constexpr long long D_W = CD(WS, 16, 1024, 1), D_X = CD(0, 16, 1024, 1), D_O = CD(OB, 128, 256, 0);
constexpr long long D_WO = CD(WO, 16, 1024, 1), D_QM = CD(ATT, 640, 0, 0), D_QT = CD(ATT + 128, 640, 64, 0), D_K = CD(AK, 640, 128, 0);
constexpr long long D_V = CD(AV, 128, 640, 0), D_P = CD(PB, 128, 768, 0);
struct Maps { CUtensorMap w[3], wo, xd, xs; };
__host__ __device__ constexpr uint32_t mslot(int c) { return (c ^ (c >> 1)) * 12288; }
__host__ __device__ constexpr uint32_t xslot(int s) { return s < 3 ? RING + s * 8192 : s < 5 ? WO + (s - 3) * 8192 : s < 7 ? WO + (s + 1) * 8192 : OB; }
__host__ __device__ constexpr bool k_smem(int k) { return k % 3 == 2; }
__host__ __device__ constexpr int k_idx(int k) { return k % 3 == 2 ? k / 3 : k - k / 3; }
__host__ __device__ constexpr int k_of_reg(int i) { return i + (i >> 1); }
__host__ __device__ constexpr int k_of_smem(int i) { return 3 * i + 2; }

#define RPROF(i)
#define RPROF_STEP
#define CPROF(i, v)

template<bool DUAL, int K0, int K1> DEVI void seq_mem(float* d, const uint32_t* w, uint32_t dw) {
  if constexpr (K0 < K1) {
    constexpr long long B = CD(RING, 128, DUAL ? 4096 : 8192, 0) + mslot(K0 >> 4) / 16 + (K0 & 15) * 16;
    if constexpr (DUAL) {
      if constexpr (!k_smem(K0)) rs24<K0 != 0, 1, B>(d, w + 4 * k_idx(K0)); else ss24<1, 1, 1, D_W + k_idx(K0) * 128, B>(d, dw);
    } else {
      if constexpr (!k_smem(K0)) rs16<K0 != 0, 1, B>(d, w + 4 * k_idx(K0)); else ss16<1, 1, 1, D_W + k_idx(K0) * 128, B>(d, dw);
    }
    seq_mem<DUAL, K0 + 1, K1>(d, w, dw);
  }
}
template<int N, int K0, int K1> DEVI void seq_tok(float* d, const uint32_t* w, uint32_t dw) {
  if constexpr (K0 < K1) {
    constexpr bool DUAL = N > 32;
    constexpr long long B = D_X + (DUAL ? xslot((K0 >> 2) & 7) / 16 : xslot(K0 >> 3) / 16 + ((K0 >> 2) & 1) * 256) + (K0 & 3) * 2;
    if constexpr (DUAL) {
      if constexpr (!k_smem(K0)) rs56<K0 != 0, 0, B>(d, w + 4 * k_idx(K0)); else ss56<1, 1, 0, D_W + k_idx(K0) * 128, B>(d, dw);
    } else if constexpr (N == 24) {
      if constexpr (!k_smem(K0)) rs24<K0 != 0, 0, B>(d, w + 4 * k_idx(K0)); else ss24<1, 1, 0, D_W + k_idx(K0) * 128, B>(d, dw);
    } else {
      if constexpr (!k_smem(K0)) rs32<K0 != 0, 0, B>(d, w + 4 * k_idx(K0)); else ss32<1, 1, 0, D_W + k_idx(K0) * 128, B>(d, dw);
    }
    seq_tok<N, K0 + 1, K1>(d, w, dw);
  }
}
template<int T, int K0> DEVI void seq_wo(float* d, uint32_t dw) {
  if constexpr (K0 < 8) { ss16<K0 != 0, 1, 1, D_WO + T * 1024 + K0 * 128, D_O + K0 * 32>(d, dw); seq_wo<T, K0 + 1>(d, dw); }
}
template<long long Q, int K0> DEVI void seq_s(float* d) {
  if constexpr (K0 < 8) { ss40<K0 != 0, 1, 1, Q + K0 * 80, D_K + K0 * 80>(d, 0); seq_s<Q, K0 + 1>(d); }
}
template<bool DUAL, int J> DEVI void load_x(uint32_t sb, const Maps* M, int t, int rb) {
  if (DUAL) e_tma_3d_mc(sb + xslot(J & 7), &M->xd, J * 64, (t - LAG) * 32, 0, sb + B_XF + (J & 7) * 8, rb);
  else e_tma_3d_mc(sb + xslot(J & 7), &M->xs, 0, (t < NSEG ? t : t - LAG) * 32, J * 2, sb + B_XF + (J & 7) * 8, rb);
}
DEVI void load_x_lent(uint32_t sb, const Maps* M, int t, int j) {
  const bool dual = t >= LAG && t < NSEG;
  const uint32_t dst = sb + (j == 3 ? xslot(3) : xslot(5));
#pragma unroll
  for (int i = 0; i < 2; i++)
    e_tma_3d(dst + i * 8192, dual ? &M->xd : &M->xs, dual ? (j + i) * 64 : 0, (t < LAG ? t : t - LAG) * 32, dual ? 0 : (j + i) * 2, sb + B_XF + (j + i) * 8);
}
struct True { static constexpr bool value = true; };
struct False { static constexpr bool value = false; };
struct Ctx { uint32_t sb; const Maps* M; int last; bool issuer; int wi; bool lead; uint32_t par; };
#define XD 1
template<bool DUAL, int J> DEVI void tok_release(const Ctx& c, int t, int& budget) {
  constexpr int NC = DUAL ? 16 : 8, S = J & 7;
  if constexpr (J + 8 < NC) {
    p_arrive_at(c.sb + B_XE + S * 8, c.last, c.lead);
    p_expect_tx(c.sb + B_XF + S * 8, 8192, c.lead && c.wi == 0);
  } else if constexpr (S == 1 || S == 2 || S == 4 || S == 7) p_arrive(c.sb + B_ME + (S >> 1) * 8, c.lead);
  if constexpr (J == 0) {
    if (c.issuer && c.wi == 6) { mbar_wait(c.sb + B_FO, t & 1, budget); load_x<DUAL, 7>(c.sb, c.M, t, c.last); }
  }
  if constexpr (J >= XD && J - XD + 8 < NC) {
    constexpr int I = J - XD;
    if (c.issuer && c.wi == (I & 1) * 4 + 1) { mbar_wait(c.sb + B_XE + I * 8, (t - LAG) & 1, budget); load_x<DUAL, I + 8>(c.sb, c.M, t, c.last); }
  }
}
template<int N, int J, class F, class G> DEVI bool tok_pass(float* d, const uint32_t* w, uint32_t dw, Ctx& c, int t, int& budget, F after0, G setup) {
  constexpr bool DUAL = N > 32;
  constexpr int NC = DUAL ? 16 : 8, KC = 64 / NC;
  if constexpr (J < NC) {
    if constexpr (J > 1) mbar_wait(c.sb + B_XF + (J & 7) * 8, c.par ^ (J >> 3), budget);
    wg_fence();
    seq_tok<N, J * KC, (J + 1) * KC>(d, w, dw);
    wg_commit();
    if constexpr (J == 1) after0();
    if constexpr (J >= NC - 5 && J < NC - 2) setup(J - (NC - 5));
    if constexpr (J > 0) { wg_wait<1>(); tok_release<DUAL, J - 1>(c, t, budget); }
    return tok_pass<N, J + 1>(d, w, dw, c, t, budget, after0, setup);
  } else {
    const bool ok = mbar_test(c.sb + B_MF, t & 1);
    wg_wait<0>();
    tok_release<DUAL, NC - 1>(c, t, budget);
    if (!DUAL) c.par ^= 1;
    return ok;
  }
}
template<int NB> DEVI void pack_tok(uint32_t* e, const float* d) {
#pragma unroll
  for (int i = 0; i < 8; i++) if ((i & 3) < NB) e[i] = pack_bf16(d[4 * (i & 3) + 2 * (i >> 2)], d[4 * (i & 3) + 2 * (i >> 2) + 1]);
}
DEVI void push_tok(const uint32_t* e, uint32_t sb, uint32_t o, int r, int rank) {
  const uint32_t b = mapa(sb, r);
  st_async128(b + o, e[0], e[1], e[2], e[3], b + (rank == 2 ? B_AV : B_AT));
}
DEVI uint32_t h1_tag(int seg) { return ((seg >> 1) & 1) ^ 1; }
DEVI uint4 pack_part(const float* c, int t) {
  return make_uint4(settag(pack_bf16(c[0], c[1]), h1_tag(t)), pack_bf16(c[2], c[3]), settag(pack_bf16(c[4], c[5]), h1_tag(t - LAG)), pack_bf16(c[6], c[7]));
}
DEVI void put_part(char* p1, char* p2, uint4 z, int t) { p_stg_rlx64(p1, z.x, z.y, t < NSEG); p_stg_rlx64(p2, z.z, z.w, t >= LAG); }

DEVI void rec_math(const uint32_t sb, const int wi, const Maps& M) {
  const int h = cta_id() / 3, rb = cluster_rank() >= 3 ? 3 : 0, rank = cluster_rank() - rb;
  const int warp = wi & 3, wg = wi >> 2;
  const bool lead = (threadIdx.x & 127) == 0;
  int budget = SPIN_BUDGET;
  uint32_t w[4 * KR];
  const int last = cluster_last();
  Ctx cx{sb, &M, last, rb + rank == last, wi, lead, 0};
  {
    const int lane = lane_id();
    const uint32_t a = sb + wg * STG + ((lane & 7) + (lane >> 4) * 8) * 128 + (((warp * 2 + ((lane >> 3) & 1)) ^ (lane & 7)) << 4);
    for (int i = 0; i < (wg == 1 || rank == 2 ? 12 : 8); i++)
      stg_rlx64((char*)g_h1[i & 3] + ((wo_tile(rank, wg, i >> 2) * 4 + warp) * 4 + (lane >> 3)) * 2048 + h * 64 + (lane & 7) * 8, 0, 0);
    mbar_wait(sb + B_ST + wg * 8, 0, budget);
#pragma unroll
    for (int k = 0; k < KR; k++) ldsm4t(a + k * 2048, w[4*k], w[4*k+1], w[4*k+2], w[4*k+3]);
    nbar_arrive<NB_ST, 384>();
    nbar_sync_r(NB_W0 + wg, 128);
    for (int i = 0; i < 5; i++) p_arrive_at(sb + B_FA + i * 8, i == 4 ? last : 0, lead);
    mbar_wait(sb + B_WS, 0, budget);
  }
  uint4 z = make_uint4(0, 0, 0, 0);
  char *z1 = nullptr, *z2 = nullptr;
  uint32_t rt0 = 0, rt1 = 0;
  mbar_wait(sb + B_XF, 0, budget); mbar_wait(sb + B_XF + 8, 0, budget);
#pragma unroll 1
  for (int t = 0;; t++) {
    const uint32_t dw = wg * (WSZ >> 4);
    uint32_t e[16];
    bool ok;
    auto finish = [&]() { put_part(z1, z2, z, t - 1); p_arrive_at(sb + B_FO, last, lead); };
    const int seg = t - rank * LAG;
    const bool att = rank < 2 && (unsigned)seg < (unsigned)NSEG;
    char* p1;
    uint32_t pw, oo;
    uint64_t u0, u1;
    int lane;
    auto setup = [&](int part) {
      if (part == 0) {
        lane = lane_id();
      } else if (part == 1) {
        char* const p = (char*)g_h1 + ((wo_tile(rank, wg, 0) * 4 + warp) * 4 + (lane >> 3)) * 2048 + h * 64 + (lane & 7) * 8;
        p1 = p + (t & 1) * sizeof(g_h1[0]);
        pin2(p1, nullptr);
      } else if (part == 2) {
        oo = OB + (lane >> 4) * 2048 + warp * 512 + rank * 256 + (lane & 15) * 16;
        pw = sb + PB + (wg ? lane * 4 : 768 + warp * 768 + lane * 16);
        pin2(pw, oo);
      } else {
        if (wg) {
          const uint32_t ra = mapa(sb, rb + ((warp & 1) ? 2 : (rank ^ 1) & 1)), rc = mapa(sb, rb + ((warp & 1) ? (rank ^ 1) & 1 : 2));
          u0 = pair(ra + oo, ra + B_OB); u1 = pair(rc + oo, rc + B_OB);
        } else {
          u0 = (uint64_t)((char*)(g_ot + rank * O_LAYER) + (size_t)(h * DH + warp * 16 + (lane >> 2)) * (SEQ * 2) + seg * 64 + (lane & 3) * 16);
          u1 = (uint32_t)((lane & 24) + ((lane >> 2) & 1) + 2 * warp - 8 * (lane & 3));
        }
        pin2(u0, u1);
      }
    };
    RPROF_STEP;
    auto mem_pass = [&](auto dual_c) {
      constexpr bool DUAL = decltype(dual_c)::value;
      float m[DUAL ? 12 : 8];
      RPROF(8 + wg * 12 - 32);
      if (!ok) mbar_wait(sb + B_MF, t & 1, budget);
      wg_fence(); seq_mem<DUAL, 0, 8>(m, w, dw); wg_commit();
      const uint32_t ao = ATT + rank * 10240 + wi * 1280, to = ao + 128 + (lane & 3) * 128 + (lane >> 2) * 16;
      const int la = DUAL ? rank == 0 || (rank == 2 && wg) : t >= NSEG;
      RPROF(1 + wg * 12);
      if (DUAL && la) {
#pragma unroll
        for (int i = 0; i < 8; i++) { const uint32_t x = e[i]; e[i] = e[8 + i]; e[8 + i] = x; }
      }
      auto piece = [&](int i) { push_tok(e + 4 * i, sb, to + (i & 1) * 640, rb + (la ^ (i >> 1)), rank); };
      piece(0);
      wg_fence(); seq_mem<DUAL, 8, 16>(m, w, dw); wg_commit();
      piece(1);
      mbar_wait(sb + B_MF + 8, t & 1, budget);
      wg_fence(); seq_mem<DUAL, 16, 24>(m, w, dw); wg_commit();
      if (DUAL) piece(2);
      wg_fence(); seq_mem<DUAL, 24, 32>(m, w, dw); wg_commit();
      if (DUAL) piece(3);
      mbar_wait(sb + B_MF + 16, t & 1, budget);
      wg_fence(); seq_mem<DUAL, 32, 48>(m, w, dw); wg_commit();
      wg_wait<1>(); p_arrive(sb + B_PD, lead);
      const uint32_t r0 = mapa(sb, rb + la), r1 = mapa(sb, rb + (la ^ 1)), m0 = r0 + ao + lane * 4, m1 = r1 + ao + lane * 4, ab = rank == 2 ? B_AV : B_AB;
      const uint64_t q0 = pair(m0, r0 + ab), q1 = pair(m0 + 640, r0 + ab), q2 = pair(m1, r1 + ab), q3 = pair(m1 + 640, r1 + ab);
      pin2(q0, q1);
      if (DUAL) pin2(q2, q3);
      mbar_wait(sb + B_MF + 24, t & 1, budget);
      wg_fence(); seq_mem<DUAL, 48, 64>(m, w, dw); wg_commit();
      wg_wait<1>(); p_arrive_at(sb + B_FA, 0, lead);
      wg_wait<0>();
      const uint32_t a0 = pack_bf16(m[0], m[1]), a1 = pack_bf16(m[2], m[3]), a2 = pack_bf16(m[4], m[5]), a3 = pack_bf16(m[6], m[7]);
      if constexpr (DUAL) {
        st_async32(q0, la ? a2 : a0); st_async32(q1, la ? a3 : a1); st_async32(q2, la ? a0 : a2); st_async32(q3, la ? a1 : a3);
        rt0 = pack_bf16(m[8], m[9]); rt1 = pack_bf16(m[10], m[11]);
      } else { st_async32(q0, a0); st_async32(q1, a1); rt0 = a2; rt1 = a3; }
      p_arrive(sb + B_WE, lead);
    };
    if (t >= LAG && t < NSEG) {
      float d[28];
      ok = tok_pass<56, 0>(d, w, dw, cx, t, budget, finish, setup);
      pack_tok<4>(e + 8, d); pack_tok<3>(e, d + 16); e[3] = rt0; e[7] = rt1;
      mem_pass(True());
    } else {
      float d[16];
      if (t > 0) finish();
      if (t > 0 && t < LAG) {
        ok = tok_pass<24, 0>(d, w, dw, cx, t, budget, []() {}, setup);
        pack_tok<3>(e, d); e[3] = rt0; e[7] = rt1;
      } else {
        ok = tok_pass<32, 0>(d, w, dw, cx, t, budget, []() {}, setup);
        pack_tok<4>(e, d);
      }
      mem_pass(False());
    }
    {
      RPROF(2 + wg * 12);
      auto wo_ready = [&]() { if (t == 0) mbar_wait(sb + B_WO, 0, budget); if (t < NSTEP - 1) mbar_wait(sb + B_WT, t & 1, budget); };
      constexpr float SC = 0.08838834764831845f * 1.4426950408889634f;
      if (!att) wo_ready();
      else {
        float s[32];
        setup(3);
        if (wg) {
          uint32_t one[4];
#pragma unroll
          for (int i = 0; i < 4; i++) one[i] = 0x3F803F80u + (pw >> 31);
          mbar_wait_cluster(sb + B_AT, seg & 1, budget);
          mbar_wait_cluster(sb + B_AB, seg & 1, budget);
          fence_proxy_async();
          RPROF(3 + 12);
          wg_fence(); seq_s<D_QM, 0>(s); wg_commit();
          nbar_arrive<NB_P, 256>();
          if (warp == 1) sts32(pw + 640, 0);
          mbar_wait_cluster(sb + B_AV, seg & 1, budget);
          wg_wait<0>();
          float mx = fmaxf(fmaxf(fmaxf(s[0], s[1]), fmaxf(s[4], s[5])), fmaxf(fmaxf(fmaxf(s[8], s[9]), fmaxf(s[12], s[13])), fmaxf(s[16], s[17])));
          const float x1 = __shfl_xor_sync(0xffffffffu, mx, 1), x2 = __shfl_xor_sync(0xffffffffu, mx, 2), x3 = __shfl_xor_sync(0xffffffffu, mx, 3);
          const float u = (warp & 2) ? ((warp & 1) ? s[16] : s[12]) : ((warp & 1) ? s[8] : s[4]);
          const float v = (warp & 2) ? ((warp & 1) ? s[17] : s[13]) : ((warp & 1) ? s[9] : s[5]);
          const float ms = -SC * fmaxf(fmaxf(mx, x1), fmaxf(x2, x3));
          sts32(pw + 128 + warp * 128, pack_bf16(ex2(fmaf(u, SC, ms)), ex2(fmaf(v, SC, ms))));
          if (warp == 0) sts32(pw, pack_bf16(ex2(fmaf(s[0], SC, ms)), ex2(fmaf(s[1], SC, ms))));
          fence_proxy_async();
          nbar_sync<NB_W1, 128>();
          RPROF(4 + 12);
          wg_fence();
          rs8<0, 0, D_P>(s + 8, one); rs8<1, 0, D_P + 16>(s + 8, one); rs8<1, 0, D_P + 32>(s + 8, one);
          wg_commit();
          ss8<0, 0, 0, D_V, D_P>(s, 0); ss8<0, 0, 0, D_V + 320, D_P>(s + 4, 0);
          ss8<1, 0, 0, D_V + 16, D_P + 16>(s, 0); ss8<1, 0, 0, D_V + 336, D_P + 16>(s + 4, 0);
          ss8<1, 0, 0, D_V + 32, D_P + 32>(s, 0); ss8<1, 0, 0, D_V + 352, D_P + 32>(s + 4, 0);
          wg_commit();
          wg_wait<1>();
          const float i0 = rcp(s[8]), i1 = rcp(s[9]);
          wg_wait<0>();
          stsm4(sb + oo, pack_bf16(s[0] * i0, s[1] * i1), pack_bf16(s[2] * i0, s[3] * i1), pack_bf16(s[4] * i0, s[5] * i1), pack_bf16(s[6] * i0, s[7] * i1));
          __syncwarp();
          const uint4 y = lds128v(sb + oo);
          if (t < NSTEP - 1) { st_async128(u0, y); st_async128(u1, y); e_complete_tx(sb + B_OB, 512); }
          wo_ready();
        } else {
          const int lim = (int)u1;
          char* const og = (char*)u0;
          nbar_sync<NB_P, 256>();
          RPROF(3);
          wg_fence();
          seq_s<D_QT, 0>(s);
          wg_commit();
          mbar_wait_cluster(sb + B_AV, seg & 1, budget);
          wg_wait<0>();
#pragma unroll
          for (int i = 0; i < 8; i++) { float& v = s[4 + 4 * (i >> 1) + (i & 1)]; v = i <= lim ? v : -INFINITY; }
          float mx = fmaxf(fmaxf(fmaxf(s[0], s[1]), fmaxf(s[4], s[5])), fmaxf(fmaxf(fmaxf(s[8], s[9]), fmaxf(s[12], s[13])), fmaxf(s[16], s[17])));
          const float x1 = __shfl_xor_sync(0xffffffffu, mx, 1), x2 = __shfl_xor_sync(0xffffffffu, mx, 2), x3 = __shfl_xor_sync(0xffffffffu, mx, 3);
          const float ms = -SC * fmaxf(fmaxf(mx, x1), fmaxf(x2, x3));
#pragma unroll
          for (int i = 0; i < 10; i++) { float& v = s[4 * (i >> 1) + (i & 1)]; v = ex2(fmaf(v, SC, ms)); }
          const float sum = (((s[0] + s[1]) + (s[4] + s[5])) + ((s[8] + s[9]) + (s[12] + s[13]))) + (s[16] + s[17]);
          const float y1 = __shfl_xor_sync(0xffffffffu, sum, 1), y2 = __shfl_xor_sync(0xffffffffu, sum, 2), y3 = __shfl_xor_sync(0xffffffffu, sum, 3);
          const float inv = rcp((sum + y1) + (y2 + y3));
          stsm4(pw, pack_bf16(s[0] * inv, s[1] * inv), pack_bf16(s[4] * inv, s[5] * inv), pack_bf16(s[8] * inv, s[9] * inv), pack_bf16(s[12] * inv, s[13] * inv));
          stsm2(pw + 512, pack_bf16(s[16] * inv, s[17] * inv), 0);
          fence_proxy_async();
          nbar_sync<NB_W0, 128>();
          RPROF(4);
          wg_fence();
          ss32<0, 0, 0, D_V, D_P + 48>(s, 0); ss32<0, 0, 0, D_V + 320, D_P + 48>(s + 16, 0);
          ss32<1, 0, 0, D_V + 16, D_P + 64>(s, 0); ss32<1, 0, 0, D_V + 336, D_P + 64>(s + 16, 0);
          ss32<1, 0, 0, D_V + 32, D_P + 80>(s, 0); ss32<1, 0, 0, D_V + 352, D_P + 80>(s + 16, 0);
          wg_commit();
          wo_ready();
          wg_wait<0>();
#pragma unroll
          for (int i = 0; i < 4; i++) {
            const float* d = s + (i >> 1) * 16 + (i & 1) * 2;
            stg128(og + ((i >> 1) * 64 + (i & 1) * 8) * (SEQ * 2), pack_bf16(d[0], d[1]), pack_bf16(d[4], d[5]), pack_bf16(d[8], d[9]), pack_bf16(d[12], d[13]));
          }
          if ((seg & 3) == 3) nbar_arrive<NB_O, 160>();
        }
      }
      RPROF(5 + wg * 12);
      const bool three = wg == 1 || rank == 2;
      char* const p2 = p1 + (2 + ((t - LAG) & 1) - (t & 1)) * (int)sizeof(g_h1[0]);
      if (t < NSTEP - 1) {
        float c[24];
        const uint32_t dt = wg ? 0 : 3072;
        mbar_wait_cluster(sb + B_OB, t & 1, budget);
        fence_proxy_async();
        RPROF(6 + wg * 12);
        wg_fence(); seq_wo<0, 0>(c, dt); wg_commit(); seq_wo<1, 0>(c + 8, dt); wg_commit();
        mbar_wait(sb + B_XF, cx.par, budget);
        wg_wait<1>();
        if (warp == 2) load_x_lent(sb, &M, t + 1, wg ? 3 : 5);
        put_part(p1, p2, pack_part(c, t), t);
        const int o3 = (wo_tile(rank, wg, three ? 2 : 1) - wo_tile(rank, wg, 0)) * 32768;
        z1 = p1 + o3; z2 = p2 + o3;
        if (three) {
          wg_fence(); seq_wo<2, 0>(c + 16, dt); wg_commit();
          wg_wait<1>(); put_part(p1 + 6 * 32768, p2 + 6 * 32768, pack_part(c + 8, t), t);
          mbar_wait(sb + B_XF + 8, cx.par, budget);
          wg_wait<0>(); z = pack_part(c + 16, t);
        } else { mbar_wait(sb + B_XF + 8, cx.par, budget); wg_wait<0>(); z = pack_part(c + 8, t); }
      } else break;
      RPROF(7 + wg * 12);
    }
  }
}

DEVI void wait_xa(const int* p, int& budget) {
  while (__any_sync(0xffffffffu, ldg_acq32(p) < 64) && --budget > 0) {}
  fence_proxy_global();
}
template<bool DUAL> DEVI void first_loads(uint32_t sb, const Maps* M, int n, int h, int rb, int& budget) {
  if (n >= LAG && ((n - LAG) & 3) == 0) e_prefetch_3d(&M->xs, 0, (n - LAG) * 32, h & 14);
  mbar_wait(sb + B_FA, n & 1, budget);
  load_x<DUAL, 0>(sb, M, n, rb); load_x<DUAL, 1>(sb, M, n, rb); load_x<DUAL, 2>(sb, M, n, rb);
}
template<bool DUAL> DEVI void lent_loads(uint32_t sb, const Maps* M, int n, int rb, int& budget) {
  mbar_wait(sb + B_FB, n & 1, budget);
  load_x<DUAL, 3>(sb, M, n, rb); load_x<DUAL, 4>(sb, M, n, rb); load_x<DUAL, 5>(sb, M, n, rb); load_x<DUAL, 6>(sb, M, n, rb);
}
DEVI void rec_comm(const uint32_t sb, const int warp, const Maps& M, const bf16* __restrict__ mem0) {
  const int lane = threadIdx.x & 31, h = cta_id() / 3, rb = cluster_rank() >= 3 ? 3 : 0, rank = cluster_rank() - rb;
  int budget = SPIN_BUDGET;
  const bool two = warp == 3 || (rank == 2 && warp == 2);
  const int ntask = two ? 2 : 1, qi = two ? (warp == 3 ? rank : 3) : rank * 3 + warp;
  const int task0 = two ? h * 2 + (qi >> 1) : 64 + h * 4 + (qi >> 1);
  auto h2_word = [&](int i, int ln) {
    const int task = task0 + i * 192;
    return (char*)g_h2 + (task >> 6) * 8192 + ((qi ^ i) & 1) * 4096 + ((task >> 2) & 15) * 256 + (task & 3) * 32 + (ln & 8) * 16 + (ln & 7) * 4;
  };
  auto first_x = [&](int t) {
    const int n = t + 1;
    p_expect_tx(sb + B_XF + (lane_id() & 7) * 8, 8192, lane_id() < 8);
    if (rb + rank == 0) {
      if (n >= LAG && ((n - LAG) & 3) == 0) wait_xa(&g_xa[1][(n - LAG) >> 2], budget);
      if (n >= LAG && n < NSEG) first_loads<true>(sb, &M, n, h, cluster_last(), budget); else first_loads<false>(sb, &M, n, h, cluster_last(), budget);
    }
  };
  {
    const int task = task0 + (lane >> 4) * 192, L = (task & 3) * 8 + (lane & 7);
    if ((lane >> 4) < ntask) {
      const bf16* p = mem0 + (L & 3) * 2 * DM + (task >> 2) * 16 + (L >> 2) + (lane & 8);
      uint32_t m0 = (uint32_t)__bfloat16_as_ushort(p[0]) | (uint32_t)__bfloat16_as_ushort(p[DM]) << 16;
      m0 = m0 ? m0 : 0x8000u;
      stg_rlx32(h2_word(lane >> 4, lane), ((qi ^ (lane >> 4)) & 1) ? 0 : m0);
      for (int i = 1; i < 4; i++) stg_rlx32(h2_word(lane >> 4, lane) + i * sizeof(g_h2[0]), 0);
      sts32(sb + M0 + warp * 128 + lane * 4, m0);
    }
    __syncwarp();
    nbar_sync<NB_ST, 384>();
    if (warp == 2) {
      e_expect_tx(sb + B_WS, 2 * WSZ);
#pragma unroll 1
      for (int i = 0; i < 2 * (64 - KR); i++) e_tma_2d(sb + WS + (i & 1) * WSZ + (i >> 1) * 2048, &M.w[rank], h * DH + (i & 1) * 64, k_of_smem(i >> 1) * 16, sb + B_WS);
      const int nt = rank == 2 ? 6 : 5;
      e_expect_tx(sb + B_WO, (nt - 2) * 16384);
#pragma unroll 1
      for (int i = 1; i < nt; i++) if (i != 3) e_tma_2d(sb + WO + i * 16384, &M.wo, wo_tile(rank, 1 - i / 3, i % 3) * 64, h * DH, sb + B_WO);
    }
    wait_xa(&g_xa[0][0], budget);
    if (warp == 3) { first_x(-1); if (rb + rank == 0) lent_loads<false>(sb, &M, 0, cluster_last(), budget); }
  }
  uint32_t cpp = 0;
  const uint32_t cp = sb + B_CP + warp * 8;
  uint32_t f_dst, f_chk, f_bar, f_time = gtime() - 4000;
  const char *f_src, *f_xr;
  auto prepare = [&](int s) {
    const int ck = warp ^ (warp < 2 && (s < LAG || s >= NSEG) && (rank & 1) == (s >= NSEG)), ln = lane_id();
    f_dst = sb + RING + mslot(ck); f_chk = f_dst + ln * 32 + (ln >> 2) * 4; f_bar = sb + ck * 8;
    f_src = (const char*)g_h2[s & 3] + ck * 8192 + (s >= NSEG ? 4096 : 0);
    f_xr = (const char*)g_xr[(s + 1) & 63] + ck * 4096;
    pin2(f_chk, 0u);
    return s <= LAG ? TP(9) + ck * TP(11) : s <= NSEG ? TP(1) + ck * TP(4) : TP(13) + ck * TP(11);
  };
  prepare(0);
#pragma unroll 1
  for (int t = 0;; t++) {
    const int n = t + 1;
    const bool dual = t >= LAG && t < NSEG;
    RPROF_STEP;
    {
      const uint32_t bytes = dual ? 8192 : 4096;
      e_expect_tx(cp, bytes + (n < NSEG ? 4096 : 0));
      mbar_wait(f_bar + B_ME, t & 1, budget);
      if (n < NSEG) e_bulk_g2s(f_dst + 8192, f_xr, 4096, cp);
      wait_time(f_time);
      RPROF(24); CPROF(0, gtime());
      int tries = 0;
      while (true) {
        tries++;
        e_bulk_g2s(f_dst, f_src, bytes, cp);
        mbar_wait(cp, cpp, budget); cpp ^= 1;
        uint32_t mn = min(min(lds32v(f_chk), lds32v(f_chk + 1024)), min(lds32v(f_chk + 2048), lds32v(f_chk + 3072)));
        if (dual) mn = min(min(mn, min(lds32v(f_chk + 4096), lds32v(f_chk + 5120))), min(lds32v(f_chk + 6144), lds32v(f_chk + 7168)));
        if (!__any_sync(0xffffffffu, mn == 0) || --budget < 0) break;
        e_expect_tx(cp, bytes);
      }
      e_arrive(f_bar + B_MF);
      RPROF(25); CPROF(1, gtime()); CPROF(2, tries);
    }
    const int seg = t - rank * LAG;
    const bool att = rank < 2 && (unsigned)seg < (unsigned)NSEG;
    if (warp == 0) {
      if (att) { e_expect_tx(sb + B_AT, 16384); e_expect_tx(sb + B_AB, 4096); e_expect_tx(sb + B_AV, 10240); }
      if (n < NSTEP) e_expect_tx(sb + B_OB, dual ? 4096 : 2048);
    }
    if (n + 1 < NSEG && (n & 3) == 3) wait_xa(&g_xa[0][(n + 1) >> 2], budget);
    if (rank == 2 && warp == 1) {
      if (h < 16 ? n < NSEG : n > LAG && n < NSTEP && ((n - LAG) & 3)) e_prefetch_3d(&M.xs, 0, (h < 16 ? n : n - LAG) * 32, (h & 7) * 2);
      if (h >= 16 && n + 1 < NSEG) asm volatile(ELECT "cp.async.bulk.prefetch.L2.global [%0], 2048;}" :: "l"((const char*)g_xr[n + 1] + (h & 7) * 2048) : "memory");
    }
    {
      const int ln = lane_id(), i = ln >> 4;
      char* const w = h2_word(i, ln);
      if (i < ntask) {
        stg_rlx32(w + ((t + 3) & 3) * sizeof(g_h2[0]), 0);
        if (n == LAG && ((qi ^ i) & 1)) stg_rlx32(w + (n & 3) * sizeof(g_h2[0]), lds32v(sb + M0 + warp * 128 + ln * 4));
      }
      __syncwarp();
    }
    if (n < NSTEP) {
      const uint32_t tag = (n >> 1) & 31;
      mbar_wait(sb + B_PD, t & 1, budget);
      uint32_t t0 = clock32();
      if (warp == 2) {
        e_expect_tx(sb + B_WT, 32768);
        e_tma_2d(sb + WO + 49152, &M.wo, wo_tile(rank, 0, 0) * 64, h * DH, sb + B_WT);
        mbar_wait(sb + B_WE, t & 1, budget);
        e_tma_2d(sb + WO, &M.wo, wo_tile(rank, 1, 0) * 64, h * DH, sb + B_WT);
      }
      if (warp == 3) first_x(t);
      if (warp == 0 && rank == (t >= NSEG)) { mbar_wait(sb + B_AB, seg & 1, budget); e_stg_rlx32(&g_ts[t & 1][h], (gtime() & ~31u) | tag); }
      const int fd = prepare(n), ln = lane_id();
      const int sa = t - (qi & 1) * LAG, sc = t - (~qi & 1) * LAG;
      const int i0 = (unsigned)sa < (unsigned)(NSEG - 1) ? 0 : 1, i1 = two && (unsigned)sc < (unsigned)(NSEG - 1) ? 2 : 1;
      const char* src = (const char*)g_h1[(qi & 1) * 2 + (sa & 1)] + task0 * 2048 + ln * 8;
      char* dst = h2_word(0, ln) + (n & 3) * sizeof(g_h2[0]);
      const int ds = ((~qi & 1) * 2 + (sc & 1) - (qi & 1) * 2 - (sa & 1)) * (int)sizeof(g_h1[0]) + 192 * 2048, dd = 3 * 8192 + ((qi & 1) ? -4096 : 4096);
      if (i0) { src += ds; dst += dd; }
      pin2(src, dst);
      spin_until(t0, TSD);
      uint32_t v0;
      do { v0 = ldg_rlx32(&g_ts[t & 1][ln]); } while (__any_sync(0xffffffffu, (v0 & 31) != tag) && --budget > 0);
      const uint32_t now = __shfl_sync(0xffffffffu, v0, 0);
      t0 = now + __reduce_max_sync(0xffffffffu, (int)(v0 - now));
      f_time = t0 + fd;
      RPROF(26); CPROF(3, t0);
      t0 += t < LAG ? TP(8) : t < NSEG ? TP(0) : TP(12);
#pragma unroll 1
      for (int i = i0; i < i1; i++) {
        const uint32_t tg = h1_tag(i ? sc : sa);
        uint2 v[8];
        wait_time(t0 + (!two ? 0 : i ? TP(3) : -TP(10)));
        int tries = 0;
        float a[4];
        while (true) {
          tries++;
#pragma unroll
          for (int k = 0; k < 8; k++) v[k] = ldg_rlx64(src + k * 256);
          asm volatile("{.reg .pred p; setp.eq.s32 p, %0, 0x7fffffff; @p exit;}" :: "r"(budget) : "memory");
          uint32_t bad = 0;
#pragma unroll
          for (int k = 0; k < 8; k++) {
            bad = xor_or(v[k].x, tg, bad);
            a[0] = k ? a[0] + bf_lo(v[k].x) : bf_lo(v[k].x); a[1] = k ? a[1] + bf_hi(v[k].x) : bf_hi(v[k].x);
            a[2] = k ? a[2] + bf_lo(v[k].y) : bf_lo(v[k].y); a[3] = k ? a[3] + bf_hi(v[k].y) : bf_hi(v[k].y);
          }
#pragma unroll
          for (int k = 0; k < 2; k++) {
            const float keep = (ln & 8) ? a[2+k] : a[k], send = (ln & 8) ? a[k] : a[2+k];
            a[k] = keep + __shfl_xor_sync(0xffffffffu, send, 8);
          }
#pragma unroll
          for (int k = 0; k < 2; k++) a[k] += __shfl_xor_sync(0xffffffffu, a[k], 16);
          if (!__any_sync(0xffffffffu, bad & 1) || --budget < 0) break;
        }
        const uint32_t out = pack_bf16(a[0], a[1]);
        if (ln < 16) stg_rlx32(dst, out ? out : 0x8000u);
        __syncwarp();
        src += ds; dst += dd;
        if (i == 0) { RPROF(28); CPROF(6, gtime()); CPROF(4, gtime()); CPROF(5, tries); } else CPROF(7, gtime());
      }
    }
    if (n == NSTEP) cluster_arrive();
    if (warp == (dual ? 2 : 1) && att && (seg & 3) == 3) { nbar_sync<NB_O, 160>(); e_flag_add(&g_dep[E_O1 + rank * 16 + (seg >> 2)]); }
    if (n == NSTEP) break;
  }
  if (h == 0 && rank == 0 && warp < 2) g_xa[warp][lane_id()] = 0;
}
}

__global__ void __launch_bounds__(384, 1)
rec_kernel(const __grid_constant__ rec::Maps M, const bf16* __restrict__ mem0) {
  using namespace rec;
  extern __shared__ __align__(1024) uint8_t smem[];
  const uint32_t sb = __shfl_sync(0xffffffffu, smem_u32(smem), 0);
  const int tid = threadIdx.x, wi = __shfl_sync(0xffffffffu, tid >> 5, 0);
  if ((sb & 0x3FFFF) != SMEM_BASE) __trap();
  if (wi == 0) {
    const int h = cta_id() / 3, rank = cta_id() - h * 3;
    const int nwg = 2 * cluster_last() + 2;
    for (int i = tid; i < NBAR; i += 32) mbar_init(sb + BARS + i * 8, i < 13 ? nwg : i < 19 ? 2 : 1);
    ((uint32_t*)(smem + PAD))[tid] = 0;
    fence_mbar_init(); fence_proxy_async();
    __syncwarp();
    e_expect_tx(sb + B_ST, STG); e_expect_tx(sb + B_ST + 8, STG);
    for (int i = 0; i < 2 * KR; i++) e_tma_2d(sb + (i & 1) * STG + (i >> 1) * 2048, &M.w[rank], h * DH + (i & 1) * 64, k_of_reg(i >> 1) * 16, sb + B_ST + (i & 1) * 8);
  } else if (wi == 1) {
    if (blockIdx.x < NEV / 32) { g_dep[blockIdx.x * 32 + (tid & 31)] = 0; g_claim[blockIdx.x * 32 + (tid & 31)] = 0; __threadfence(); }
    __syncwarp();
    asm volatile("griddepcontrol.launch_dependents;" ::: "memory");
  } else if (wi == 2) {
    if ((tid & 31) < 3) asm volatile("prefetch.tensormap [%0];" :: "l"(&M.wo + (tid & 31)) : "memory");
    __syncwarp();
  }
  cluster_arrive(); cluster_wait();
  if (wi < 8) { reg_inc<232>(); rec_math(sb, wi, M); cluster_arrive(); cluster_wait(); }
  else { reg_dec<40>(); rec_comm(sb, wi & 3, M, mem0); cluster_wait(); }
}

namespace gm {
struct Maps { CUtensorMap ot, wo, xn, wg, wu, hl, hs, wd, out; };
constexpr int STAGES = 6, STAGE = 32768;
constexpr uint32_t SO = STAGES * STAGE, BARS = SO + 32768;
constexpr uint32_t B_FULL = BARS, B_EMPTY = BARS + 48, B_TF = BARS + 96, B_TE = BARS + 112, B_ORD = BARS + 128, B_PM = BARS + 144, B_GO = BARS + 160;
constexpr uint32_t MAIL = BARS + 176, PMAIL = BARS + 192;
constexpr uint32_t SMEM = BARS + 256;
constexpr int END = -1;
#define DQ 8
#define GT gtime

struct Tile {
  bool isO, isG, l2; int blk, col, k0, n;
  DEVI Tile(int task, int rank) {
    const int e = task >> 8, id = task & 255;
    const bool isD = e < E_G1 || e >= E_D2;
    isO = e >= E_O1 && e < E_G2; isG = !isD && !isO; l2 = e >= E_O2;
    blk = l2 && !isO ? (e & 7) * 2 + rank : isD ? e >> 1 : e & 15;
    col = l2 && !isO ? id : (isG ? id : id & 3) * 2 + rank;
    k0 = isO ? (id >> 2) * 2048 : isG ? 0 : ((l2 ? e >> 3 : e) & 1) * 1792;
    n = isO ? 32 : isG ? 16 : 28;
    if (e >= E_D2 + DQ) { n = 14; k0 += (id >> 3) * 896; col = id & 7; }
  }
};

DEVI float geglu(float g, float u) {
  const float z = g * (0.7978845608028654f + 0.035677408136300125f * g * g);
  float t; asm("tanh.approx.f32 %0, %1;" : "=f"(t) : "f"(z));
  const float hg = 0.5f * g;
  return fmaf(hg, t, hg) * u;
}
struct Sched {
  int need, size, e;
  bool filler;
  uint4 dep, cl;
  DEVI void init(int lane) {
    e = (lane < 4 ? lane + 12 : lane < 16 ? lane - 4 : lane) * 4;
    const bool d = e < E_G1 || e >= E_D2, o = e >= E_O1 && e < E_G2;
    need = e >= E_D2 ? 56 : d ? 28 : e < E_O1 ? 64 : o ? 32 : 128;
    size = e >= E_D2 ? (e < E_D2 + DQ ? 8 : e < E_D2 + 16 ? 16 : 0) : d ? 4 : o ? 8 : e < E_O1 ? 28 : e < E_G2 + 8 ? 56 : 0;
    filler = (int)blockIdx.x >= TP(5);
  }
  DEVI void scan(int lane) { cl = ldg_rlx128(g_claim + e); dep = ldg_rlx128(g_dep + e); }
  DEVI int next(int lane, int& budget) {
    while (--budget > 0) {
      int av[4], open = 0;
#pragma unroll
      for (int i = 0; i < 4; i++) { const int r = max(size - (int)(&cl.x)[i], 0); open |= r; av[i] = ((int)(&dep.x)[i] >= need ? r : 0) + (i ? av[i - 1] : 0); }
      const uint32_t mo = __ballot_sync(0xffffffffu, open);
      if (!mo) break;
      if (filler) {
        const int x = TP(6) & 3, dx = x == 0 ? dep.x : x == 1 ? dep.y : x == 2 ? dep.z : dep.w;
        filler = !__any_sync(0xffffffffu, e == ((E_O1 + TP(6)) & ~3) && dx >= need);
      }
      if (!filler && (mo & 0xffff) && lane >= E_O2 / 4) av[3] = 0;
      int inc = av[3], pos = 0;
      while (true) {
        const uint32_t m = __ballot_sync(0xffffffffu, inc > pos && av[3]);
        if (!m) break;
        const int l = __ffs(m) - 1, rel = pos - (inc - av[3]), i = (rel >= av[0]) + (rel >= av[1]) + (rel >= av[2]);
        int r = 0;
        if (lane == l) {
          const int tk = atomicAdd(g_claim + e + i, 1);
          r = tk < size ? (e + i) << 8 | tk : -1 - (inc - av[3] + (i == 0 ? av[0] : i == 1 ? av[1] : i == 2 ? av[2] : av[3]) + tk - size);
        }
        r = __shfl_sync(0xffffffffu, r, l);
        if (r >= 0) return r;
        if (pos == 0) {
#pragma unroll
          for (int o = 1; o < 32; o <<= 1) { const int v = __shfl_up_sync(0xffffffffu, inc, o); if (lane >= o) inc += v; }
        }
        pos = -1 - r;
      }
      if (pos == 0) __nanosleep(TP(7));
      scan(lane);
    }
    return END;
  }
};

DEVI void scheduler(const uint32_t sb) {
  const int lane = threadIdx.x & 31;
  int budget = SPIN_BUDGET;
  Sched sc; sc.init(lane);
#pragma unroll 1
  for (int i = 0;; i++) {
    if (i) mbar_wait(sb + B_GO, (i & 1) ^ 1, budget);
    sc.scan(lane);
    if (i == 0) cluster_wait();
    const int task = sc.next(lane, budget);
    const uint32_t r = mapa(sb, lane & 1);
    if (lane < 2) st_async32(r + PMAIL + (i & 1) * 4, task, r + B_PM + (i & 1) * 8);
    __syncwarp();
    if (task == END) break;
  }
}

DEVI void producer(const uint32_t sb, const Maps& M) {
  const int lane = threadIdx.x & 31, rank = cluster_rank();
  int budget = SPIN_BUDGET, s = 0, ph = 0;
#pragma unroll 1
  for (int i = 0;; i++) {
    e_expect_tx(sb + B_PM + (i & 1) * 8, 4);
    mbar_wait_cluster(sb + B_PM + (i & 1) * 8, (i >> 1) & 1, budget);
    const int task = budget < 0 ? END : __shfl_sync(0xffffffffu, (int)lds32v(sb + PMAIL + (i & 1) * 4), 0);
    fence_proxy_global();
    for (int z = 0; z < (task == END ? 2 : 1); z++) {
      const int g = (i + z) & 1;
      mbar_wait(sb + B_TE + g * 8, (((i + z) >> 1) & 1) ^ 1, budget);
      if (lane == 0) { sts64(sb + MAIL + g * 8, task, s | ph << 8); mbar_arrive(sb + B_TF + g * 8); }
      __syncwarp();
    }
    if (task == END) break;
    const Tile T(task, rank);
    const bool shareB = T.l2 && !T.isO;
    const CUtensorMap* mA = T.isO ? &M.ot : T.isG ? &M.xn : &M.hl;
    const CUtensorMap* mB0 = T.isO ? &M.wo : T.isG ? &M.wg : &M.wd;
    const CUtensorMap* mB1 = T.isG ? &M.wu : mB0;
    const int c0 = T.col * (T.isG ? 64 : 128), c1 = T.isG ? c0 : c0 + 64, row = T.blk * 128;
    const int ok = 0;
    int k = T.k0;
#pragma unroll 1
    for (int it = 0; it < T.n; it++, k += 64) {
      const uint32_t a = sb + s * STAGE, fb = sb + B_FULL + s * 8;
      mbar_wait(sb + B_EMPTY + s * 8, ph ^ 1, budget);
      e_expect_tx(fb, STAGE);
      if (shareB) {
        e_tma_2d_mc(a + 16384 + rank * 8192, rank ? mB1 : mB0, rank ? c1 : c0, k, fb);
        e_tma_2d(a, mA, k, row, fb); e_tma_2d(a + 8192, mA, k, row + 64, fb);
      } else {
        e_tma_2d_mc(a + rank * 8192, mA, T.isO ? row + rank * 64 : k, T.isO ? k + ok : row + rank * 64, fb);
        e_tma_2d(a + 16384, mB0, c0, k, fb); e_tma_2d(a + 24576, mB1, c1, k, fb);
      }
      if (it == T.n - TP(2)) e_arrive(sb + B_GO);
      if (++s == STAGES) { s = 0; ph ^= 1; }
    }
  }
}

template<int TA> DEVI void mainloop(float* d0, float* d1, uint32_t sb, int n, int s, int ph, bool lead, uint32_t ord, int& budget) {
  int prev = 0;
  const uint32_t rel = threadIdx.x & 127;
#pragma unroll 1
  for (int i = 0; i < n; i++) {
    mbar_wait(sb + B_FULL + s * 8, ph, budget);
    const uint32_t a = sb + s * STAGE;
    const uint64_t da = mkdesc(a, 16, 1024), db = mkdesc(a + 16384, 8192, 1024);
    wg_fence();
#pragma unroll
    for (int k = 0; k < 4; k++) {
      wgmma_n128<TA>(d0, da + k * (TA ? 128 : 2), db + k * 128, (i | k) != 0);
      wgmma_n128<TA>(d1, da + 512 + k * (TA ? 128 : 2), db + k * 128, (i | k) != 0);
    }
    wg_commit();
    if (i > 0) { wg_wait<1>(); p_arrive_at(sb + B_EMPTY + prev * 8, rel & 1, rel < 2); }
    prev = s;
    if (++s == STAGES) { s = 0; ph ^= 1; }
  }
  p_arrive(ord, lead);
  wg_wait<0>();
  p_arrive_at(sb + B_EMPTY + prev * 8, rel & 1, rel < 2);
}

DEVI void consumer(const uint32_t sb, const Maps& M, const int wg) {
  const int tid = threadIdx.x, lane = tid & 31, warp = (tid >> 5) & 3;
  const bool lead = (tid & 127) == 0;
  const uint32_t so = sb + SO + wg * 16384;
  int budget = SPIN_BUDGET;
  float d0[64], d1[64];
#pragma unroll 1
  for (int m = 0;; m++) {
    mbar_wait(sb + B_TF + wg * 8, m & 1, budget);
    const uint2 mail = lds64v(sb + MAIL + wg * 8);
    const int task = __shfl_sync(0xffffffffu, (int)mail.x, 0), pos = __shfl_sync(0xffffffffu, (int)mail.y, 0);
    e_arrive(sb + B_TE + wg * 8);
    if (task == END || budget < 0) break;
    const Tile T(task, cluster_rank());
    mbar_wait(sb + B_ORD + wg * 8, (m & 1) ^ wg ^ 1, budget);
    if (T.isO) mainloop<1>(d0, d1, sb, T.n, pos & 255, pos >> 8, lead, sb + B_ORD + (wg ^ 1) * 8, budget);
    else mainloop<0>(d0, d1, sb, T.n, pos & 255, pos >> 8, lead, sb + B_ORD + (wg ^ 1) * 8, budget);
    const uint32_t st = so + (warp * 16 + (lane & 15)) * 128;
    if (T.isG) {
      int* const fl = &g_dep[T.l2 ? E_D2 + (T.col >= 28) * 8 + (T.blk >> 1) : E_D1 + T.blk * 2 + (T.col >= 28)];
#pragma unroll
      for (int mm = 0; mm < 2; mm++) {
        const float* d = mm ? d1 : d0;
#pragma unroll
        for (int c = 0; c < 4; c++) {
          uint32_t r[4];
#pragma unroll
          for (int i = 0; i < 4; i++) r[i] = pack_bf16(geglu(d[8*c+2*i], d[32+8*c+2*i]), geglu(d[8*c+2*i+1], d[33+8*c+2*i]));
          stsm4(st + mm * 8192 + (((2 * c + (lane >> 4)) ^ (lane & 7)) << 4), r[0], r[1], r[2], r[3]);
        }
      }
      fence_proxy_async();
      nbar_sync_r(1 + wg, 128);
      if (lead) {
        tma_store_2d(&M.hs, so, T.col * 64, T.blk * 128);
        bulk_commit();
        bulk_wait<0>();
        flag_add(fl);
      }
    } else {
#pragma unroll
      for (int hf = 0; hf < 2; hf++) {
        if (hf) { if (lead) bulk_wait_read<0>(); nbar_sync_r(1 + wg, 128); }
#pragma unroll
        for (int mm = 0; mm < 2; mm++) {
          const float* d = (mm ? d1 : d0) + hf * 32;
#pragma unroll
          for (int c = 0; c < 4; c++)
            stsm4(st + mm * 8192 + (((2 * c + (lane >> 4)) ^ (lane & 7)) << 4), pack_bf16(d[8*c], d[8*c+1]), pack_bf16(d[8*c+2], d[8*c+3]),
                  pack_bf16(d[8*c+4], d[8*c+5]), pack_bf16(d[8*c+6], d[8*c+7]));
        }
        fence_proxy_async();
        nbar_sync_r(1 + wg, 128);
        if (lead) { tma_radd_2d(&M.out, so, T.col * 128 + hf * 64, T.blk * 128); bulk_commit(); }
      }
      if (lead) {
        bulk_wait<0>();
        if (T.isO || !T.l2) flag_add(&g_dep[(!T.isO ? E_LX2 : T.l2 ? E_LX1B : E_LX1A) + T.blk]);
      }
    }
    __syncwarp();
  }
}

DEVI void norm_helper(const bf16* __restrict__ x, bf16* out) {
  const int lane = threadIdx.x & 31;
  int budget = SPIN_BUDGET, tk = lane < 4 ? -1 : 1024;
#pragma unroll 1
  while (--budget > 0) {
    if (tk < 0) tk = atomicAdd(g_claim + E_LI + lane, 1);
    if (__all_sync(0xffffffffu, tk >= 1024)) break;
    const uint32_t m = __ballot_sync(0xffffffffu, tk < 1024 && (lane == 0 || ldg_acq32(g_dep + E_LI + lane * 16 + (tk >> 6)) >= 16));
    if (!m) { __nanosleep(TP(7)); continue; }
    const int ql = __ffs(m) - 1, task = __shfl_sync(0xffffffffu, tk, ql), q = E_LI + ql * 16, ev = task >> 6;
    if (lane == ql) tk = -1;
    const size_t off = (size_t)task * (DM * 4) + lane * 16;
    const char* src = (const char*)(q == E_LI ? x : out) + off;
    uint4 u[8];
#pragma unroll
    for (int i = 0; i < 8; i++) u[i] = ldg_rlx128(src + i * 512);
    if (q == E_LI) {
#pragma unroll
      for (int i = 0; i < 8; i++) stg128((char*)out + off + i * 512, u[i].x, u[i].y, u[i].z, u[i].w);
    }
    int* const fl = q == E_LI ? &g_xa[0][ev] : q == E_LX2 ? &g_xa[1][ev] : &g_dep[q == E_LX1A ? E_G1 + ev : E_G2 + (ev >> 1)];
    float mean[2], rs[2];
#pragma unroll
    for (int r = 0; r < 2; r++) {
      float s0 = 0, s1 = 0;
#pragma unroll
      for (int i = 0; i < 16; i++) { const uint32_t v = (&u[4*r + (i >> 2)].x)[i & 3]; s0 += bf_lo(v); s1 += bf_hi(v); }
      mean[r] = (s0 + s1) * (1.f / 32);
      s0 = s1 = 0;
#pragma unroll
      for (int i = 0; i < 16; i++) { const uint32_t v = (&u[4*r + (i >> 2)].x)[i & 3]; const float a = bf_lo(v) - mean[r], b = bf_hi(v) - mean[r]; s0 = fmaf(a, a, s0); s1 = fmaf(b, b, s1); }
      rs[r] = s0 + s1;
    }
    {
      const bool hi = lane & 16;
      float m1 = hi ? mean[1] : mean[0], q1 = hi ? rs[1] : rs[0], m2 = hi ? mean[0] : mean[1], q2 = hi ? rs[0] : rs[1], cnt = 16;
#pragma unroll
      for (int o = 16; o; o >>= 1) {
        m2 = __shfl_xor_sync(0xffffffffu, m2, o); q2 = __shfl_xor_sync(0xffffffffu, q2, o);
        const float dl = m1 - m2;
        q2 = q1 = fmaf(dl * dl, cnt, q1 + q2); m2 = m1 = 0.5f * (m1 + m2);
        cnt *= 2;
      }
      q1 = rsqrtf(q1 * (1.f / DM) + 1e-5f);
      m2 = __shfl_xor_sync(0xffffffffu, m1, 16); q2 = __shfl_xor_sync(0xffffffffu, q1, 16);
      mean[0] = hi ? m2 : m1; mean[1] = hi ? m1 : m2; rs[0] = hi ? q2 : q1; rs[1] = hi ? q1 : q2;
    }
#pragma unroll
    for (int i = 0; i < 8; i++) {
      uint32_t y[4];
#pragma unroll
      for (int c = 0; c < 4; c++) { const uint32_t v = (&u[i].x)[c]; y[c] = pack_bf16((bf_lo(v) - mean[i >> 2]) * rs[i >> 2], (bf_hi(v) - mean[i >> 2]) * rs[i >> 2]); }
      stg128((char*)g_xn + off + i * 512, y[0], y[1], y[2], y[3]);
      u[i] = make_uint4(y[0], y[1], y[2], y[3]);
    }
    if (q == E_LI && (task & 15) >= 12) {
      uint32_t* const xr = g_xr[task >> 4] + lane * 32 + (task & 3);
#pragma unroll
      for (int i = 0; i < 16; i++) {
        const uint32_t a = (&u[i >> 2].x)[i & 3], b = (&u[4 + (i >> 2)].x)[i & 3];
        xr[(i >> 2) * 1024 + (i & 3) * 8] = __byte_perm(a, b, 0x5410); xr[(i >> 2) * 1024 + (i & 3) * 8 + 4] = __byte_perm(a, b, 0x7632);
      }
    }
    fence_proxy_global();
    __syncwarp();
    if (lane == 0) flag_add(fl);
    __syncwarp();
  }
}
}

__global__ void __cluster_dims__(2, 1, 1) __launch_bounds__(384, 1)
gemm_kernel(const __grid_constant__ gm::Maps M, const bf16* __restrict__ x, bf16* out) {
  using namespace gm;
  extern __shared__ __align__(1024) uint8_t smem[];
  const uint32_t sb = __shfl_sync(0xffffffffu, smem_u32(smem), 0);
  const int tid = threadIdx.x, wi = __shfl_sync(0xffffffffu, tid >> 5, 0);
  if (tid < 21) mbar_init(sb + BARS + tid * 8, tid == 14 || tid == 15 ? 4 : tid >= 6 && tid < 12 ? 2 : 1);
  fence_mbar_init();
  if (tid >= 256 && tid < 265) asm volatile("prefetch.tensormap [%0];" :: "l"(&M.ot + (tid - 256)) : "memory");
  __syncwarp();
  cluster_arrive();
  const bool sched = wi == 11 && cluster_rank() == 0;
  if (!sched) cluster_wait();
  if (wi < 8) { reg_inc<208>(); consumer(sb, M, wi >> 2); cluster_arrive(); cluster_wait(); }
  else {
    reg_dec<88>();
    if (wi == 8) producer(sb, M);
    else if (sched) scheduler(sb);
    else {
      norm_helper(x, out);
      asm volatile("griddepcontrol.wait;" ::: "memory");
    }
    __syncwarp();
    cluster_arrive(); cluster_wait();
  }
}

typedef CUresult (*PFN_encodeTiled)(CUtensorMap*, CUtensorMapDataType, cuuint32_t, void*, const cuuint64_t*, const cuuint64_t*,
                                    const cuuint32_t*, const cuuint32_t*, CUtensorMapInterleave, CUtensorMapSwizzle,
                                    CUtensorMapL2promotion, CUtensorMapFloatOOBfill);
static PFN_encodeTiled g_encode = nullptr;
static CUtensorMap make_map(const void* ptr, uint64_t rows, uint64_t cols, uint32_t box_rows, CUtensorMapL2promotion pr = CU_TENSOR_MAP_L2_PROMOTION_L2_256B) {
  CUtensorMap m;
  cuuint64_t dims[2] = {cols, rows}, strides[1] = {cols * 2};
  cuuint32_t box[2] = {64, box_rows}, es[2] = {1, 1};
  g_encode(&m, CU_TENSOR_MAP_DATA_TYPE_BFLOAT16, 2, (void*)ptr, dims, strides, box, es, CU_TENSOR_MAP_INTERLEAVE_NONE,
           CU_TENSOR_MAP_SWIZZLE_128B, pr, CU_TENSOR_MAP_FLOAT_OOB_FILL_NONE);
  return m;
}

static CUtensorMap make_map3(const void* ptr, uint64_t d0, uint64_t d1, uint64_t d2, uint64_t stride2) {
  CUtensorMap m;
  cuuint64_t dims[3] = {d0, d1, d2}, strides[2] = {DM * 2, stride2};
  cuuint32_t box[3] = {64, 32, 2}, es[3] = {1, 1, 1};
  g_encode(&m, CU_TENSOR_MAP_DATA_TYPE_BFLOAT16, 3, (void*)ptr, dims, strides, box, es, CU_TENSOR_MAP_INTERLEAVE_NONE,
           CU_TENSOR_MAP_SWIZZLE_128B, CU_TENSOR_MAP_L2_PROMOTION_L2_256B, CU_TENSOR_MAP_FLOAT_OOB_FILL_NONE);
  return m;
}

extern "C" void kernel_launch(void* const* d_in, const int* in_sizes, int n_in, void* d_out, int out_size) {
  const bf16* x = (const bf16*)d_in[0];
  const bf16* mem0 = (const bf16*)d_in[1];
  if (!g_encode) {
    void* p = nullptr; cudaDriverEntryPointQueryResult q;
    cudaGetDriverEntryPoint("cuTensorMapEncodeTiled", &p, cudaEnableDefault, &q);
    g_encode = (PFN_encodeTiled)p;
    cudaFuncSetAttribute(gemm_kernel, cudaFuncAttributeMaxDynamicSharedMemorySize, gm::SMEM);
    cudaFuncSetAttribute(rec_kernel, cudaFuncAttributeMaxDynamicSharedMemorySize, rec::SMEM);
  }
  bf16 *xn, *ot, *hh;
  cudaGetSymbolAddress((void**)&xn, g_xn); cudaGetSymbolAddress((void**)&ot, g_ot); cudaGetSymbolAddress((void**)&hh, g_h);
  rec::Maps R;
  for (int i = 0; i < 3; i++) R.w[i] = make_map(d_in[2 + i], DM, NH * DH, 16, CU_TENSOR_MAP_L2_PROMOTION_NONE);
  R.wo = make_map(d_in[5], NH * DH, DM, 128);
  R.xd = make_map3(xn, DM, SEQ - LAG * 32, 2, (uint64_t)LAG * 32 * DM * 2); R.xs = make_map3(xn, 64, SEQ, DM / 64, 128);
  gm::Maps G;
  G.ot = make_map(ot, NH * DH + O_LAYER / SEQ, SEQ, 64); G.wo = make_map(d_in[5], NH * DH, DM, 64); G.xn = make_map(xn, SEQ, DM, 64);
  G.wg = make_map(d_in[8], DM, DF, 64); G.wu = make_map(d_in[9], DM, DF, 64); G.hl = make_map(hh, SEQ, DF, 64); G.hs = make_map(hh, SEQ, DF, 128);
  G.wd = make_map(d_in[10], DF, DM, 64); G.out = make_map(d_out, SEQ, DM, 128);
  cudaLaunchConfig_t cfg = {};
  cudaLaunchAttribute at[1];
  cfg.attrs = at; cfg.numAttrs = 1;
  cfg.gridDim = dim3(3 * NH); cfg.blockDim = dim3(384); cfg.dynamicSmemBytes = rec::SMEM; cfg.stream = cudaStreamPerThread;
  at[0].id = cudaLaunchAttributeClusterDimension; at[0].val.clusterDim.y = at[0].val.clusterDim.z = 1;
  static int csize = 0;
  if (!csize) {
    int n = 0;
    at[0].val.clusterDim.x = 6;
    csize = cudaOccupancyMaxActiveClusters(&n, rec_kernel, &cfg) == cudaSuccess && n >= NH / 2 ? 6 : 3;
  }
  at[0].val.clusterDim.x = csize;
  cudaLaunchKernelEx(&cfg, rec_kernel, R, mem0);
  cfg.gridDim = dim3(132); cfg.blockDim = dim3(384); cfg.dynamicSmemBytes = gm::SMEM; cfg.stream = cudaStreamPerThread;
  at[0].id = cudaLaunchAttributeProgrammaticStreamSerialization; at[0].val.programmaticStreamSerializationAllowed = 1;
  cudaLaunchKernelEx(&cfg, gemm_kernel, G, x, (bf16*)d_out);
}
```

```cpp
#include <cuda_runtime.h>
#include <cuda_bf16.h>
#include <cuda.h>
#include <stdint.h>

#define DEVI __device__ __forceinline__
typedef __nv_bfloat16 bf16;

constexpr int SEQ = 2048, DM = 1024, NH = 32, DH = 128, DF = 3584, NSEG = 64;
#define LAG 20
constexpr int NSTEP = NSEG + LAG;

#define TSD 1800
constexpr size_t O_LAYER = 0;
__device__ __align__(1024) bf16 g_xn[SEQ * DM];
__device__ __align__(1024) bf16 g_ot[SEQ * NH * DH + O_LAYER];
__device__ __align__(1024) bf16 g_h[SEQ * DF];
__device__ __align__(1024) uint32_t g_xr[NSEG][DM * 4];
__device__ __align__(1024) uint2 g_h1[4][256 * 256];
__device__ __align__(1024) uint4 g_h2[4][2048];
__device__ __align__(128) uint32_t g_ts[2][32];
enum { E_D1 = 0, E_G1 = 32, E_O1 = 48, E_O2 = 64, E_G2 = 80, E_D2 = 96,
       E_LI = 128, E_LX2 = 144, E_LX1A = 160, E_LX1B = 176, NEV = 256 };
__device__ __align__(128) int g_dep[NEV];
__device__ __align__(128) int g_claim[NEV];
__device__ __align__(128) int g_xa[2][32];

#define TUNE_DEFAULTS 1650, 2450, 6, 100, 100, 8, 14, 100, 1500, 2225, 100, 110, 1500, 2225, 200, 0
constexpr int c_D[16] = {TUNE_DEFAULTS};
template<int I> struct TPV { static constexpr int v = c_D[I]; };
#define TP(i) TPV<i>::v

DEVI uint32_t smem_u32(const void* p) { return (uint32_t)__cvta_generic_to_shared(p); }
DEVI void mbar_init(uint32_t bar, uint32_t cnt) { asm volatile("mbarrier.init.shared::cta.b64 [%0], %1;" :: "r"(bar), "r"(cnt) : "memory"); }
DEVI void mbar_arrive(uint32_t bar) { asm volatile("mbarrier.arrive.shared::cta.b64 _, [%0];" :: "r"(bar) : "memory"); }
DEVI bool mbar_try(uint32_t bar, uint32_t parity) {
  uint32_t p;
  asm volatile("{.reg .pred p; mbarrier.try_wait.parity.shared::cta.b64 p, [%1], %2; selp.u32 %0, 1, 0, p;}" : "=r"(p) : "r"(bar), "r"(parity) : "memory");
  return p;
}
DEVI bool mbar_test(uint32_t bar, uint32_t parity) {
  uint32_t p;
  asm volatile("{.reg .pred p; mbarrier.test_wait.parity.shared::cta.b64 p, [%1], %2; selp.u32 %0, 1, 0, p;}" : "=r"(p) : "r"(bar), "r"(parity) : "memory");
  return p;
}
constexpr int SPIN_BUDGET = 1 << 18;
DEVI void mbar_wait(uint32_t bar, uint32_t parity, int& budget) {
  while (!mbar_try(bar, parity)) { if (--budget < 0) break; }
}
DEVI bool mbar_try_cluster(uint32_t bar, uint32_t parity) {
  uint32_t p;
  asm volatile("{.reg .pred p; mbarrier.try_wait.parity.acquire.cluster.shared::cta.b64 p, [%1], %2; selp.u32 %0, 1, 0, p;}" : "=r"(p) : "r"(bar), "r"(parity) : "memory");
  return p;
}
DEVI void mbar_wait_cluster(uint32_t bar, uint32_t parity, int& budget) {
  while (!mbar_try_cluster(bar, parity)) { if (--budget < 0) break; }
}
DEVI uint32_t mapa(uint32_t addr, uint32_t rank) { uint32_t r; asm("mapa.shared::cluster.u32 %0, %1, %2;" : "=r"(r) : "r"(addr), "r"(rank)); return r; }
DEVI void cluster_arrive() { asm volatile("barrier.cluster.arrive.relaxed.aligned;" ::: "memory"); }
DEVI void cluster_wait() { asm volatile("barrier.cluster.wait.aligned;" ::: "memory"); }
DEVI void fence_mbar_init() { asm volatile("fence.mbarrier_init.release.cluster;" ::: "memory"); }
DEVI void fence_proxy_async() { asm volatile("fence.proxy.async.shared::cta;" ::: "memory"); }
DEVI void fence_proxy_global() { asm volatile("fence.proxy.async.global;" ::: "memory"); }
#define ELECT "{.reg .pred p; elect.sync _|p, 0xffffffff;\n @p "
DEVI void e_expect_tx(uint32_t bar, uint32_t bytes) { asm volatile(ELECT "mbarrier.arrive.expect_tx.shared::cta.b64 _, [%0], %1;}" :: "r"(bar), "r"(bytes) : "memory"); }
DEVI void e_complete_tx(uint32_t bar, uint32_t bytes) { asm volatile("fence.acq_rel.cta;\n" ELECT "mbarrier.complete_tx.relaxed.cta.shared::cta.b64 [%0], %1;}" :: "r"(bar), "r"(bytes) : "memory"); }
DEVI void e_arrive(uint32_t bar) { asm volatile(ELECT "mbarrier.arrive.shared::cta.b64 _, [%0];}" :: "r"(bar) : "memory"); }
DEVI void e_tma_2d(uint32_t dst, const CUtensorMap* m, int c0, int c1, uint32_t bar) {
  asm volatile(ELECT "cp.async.bulk.tensor.2d.shared::cluster.global.mbarrier::complete_tx::bytes [%0], [%1, {%3, %4}], [%2];}"
    :: "r"(dst), "l"(m), "r"(bar), "r"(c0), "r"(c1) : "memory");
}
DEVI void e_prefetch_3d(const CUtensorMap* m, int c0, int c1, int c2) {
  asm volatile(ELECT "cp.async.bulk.prefetch.tensor.3d.L2.global [%0, {%1, %2, %3}];}" :: "l"(m), "r"(c0), "r"(c1), "r"(c2) : "memory");
}
DEVI void e_bulk_g2s(uint32_t dst, const void* src, uint32_t bytes, uint32_t bar) {
  asm volatile(ELECT "cp.async.bulk.shared::cluster.global.mbarrier::complete_tx::bytes [%0], [%1], %2, [%3];}" :: "r"(dst), "l"(src), "r"(bytes), "r"(bar) : "memory");
}
DEVI void e_tma_3d(uint32_t dst, const CUtensorMap* m, int c0, int c1, int c2, uint32_t bar) {
  asm volatile(ELECT "cp.async.bulk.tensor.3d.shared::cluster.global.mbarrier::complete_tx::bytes [%0], [%1, {%3, %4, %5}], [%2];}"
    :: "r"(dst), "l"(m), "r"(bar), "r"(c0), "r"(c1), "r"(c2) : "memory");
}
DEVI void e_tma_3d_mc(uint32_t dst, const CUtensorMap* m, int c0, int c1, int c2, uint32_t bar, int last) {
  asm volatile(ELECT "cp.async.bulk.tensor.3d.shared::cluster.global.mbarrier::complete_tx::bytes.multicast::cluster [%0], [%1, {%3, %4, %5}], [%2], %6;}"
    :: "r"(dst), "l"(m), "r"(bar), "r"(c0), "r"(c1), "r"(c2), "h"((uint16_t)((2 << last) - 1)) : "memory");
}
DEVI void e_tma_2d_mc(uint32_t dst, const CUtensorMap* m, int c0, int c1, uint32_t bar) {
  asm volatile(ELECT "cp.async.bulk.tensor.2d.shared::cluster.global.mbarrier::complete_tx::bytes.multicast::cluster [%0], [%1, {%3, %4}], [%2], %5;}"
    :: "r"(dst), "l"(m), "r"(bar), "r"(c0), "r"(c1), "h"((uint16_t)3) : "memory");
}
DEVI void p_arrive_at(uint32_t bar, uint32_t rank, bool c) {
  asm volatile("{.reg .pred p; .reg .b32 a; setp.ne.u32 p, %2, 0; mapa.shared::cluster.u32 a, %0, %1; @p mbarrier.arrive.shared::cluster.b64 _, [a];}"
    :: "r"(bar), "r"(rank), "r"((uint32_t)c) : "memory");
}
DEVI void p_expect_tx(uint32_t bar, uint32_t bytes, bool c) {
  asm volatile("{.reg .pred p; setp.ne.u32 p, %2, 0; @p mbarrier.arrive.expect_tx.shared::cta.b64 _, [%0], %1;}" :: "r"(bar), "r"(bytes), "r"((uint32_t)c) : "memory");
}
DEVI void p_arrive(uint32_t bar, bool c) { asm volatile("{.reg .pred p; setp.ne.u32 p, %1, 0; @p mbarrier.arrive.shared::cta.b64 _, [%0];}" :: "r"(bar), "r"((uint32_t)c) : "memory"); }
DEVI void tma_store_2d(const CUtensorMap* m, uint32_t src, int c0, int c1) {
  asm volatile("cp.async.bulk.tensor.2d.global.shared::cta.bulk_group [%0, {%2, %3}], [%1];" :: "l"(m), "r"(src), "r"(c0), "r"(c1) : "memory");
}
DEVI void tma_radd_2d(const CUtensorMap* m, uint32_t src, int c0, int c1) {
  asm volatile("cp.reduce.async.bulk.tensor.2d.global.shared::cta.add.bulk_group [%0, {%2, %3}], [%1];" :: "l"(m), "r"(src), "r"(c0), "r"(c1) : "memory");
}
DEVI void bulk_commit() { asm volatile("cp.async.bulk.commit_group;" ::: "memory"); }
template<int N> DEVI void bulk_wait_read() { asm volatile("cp.async.bulk.wait_group.read %0;" :: "n"(N) : "memory"); }
template<int N> DEVI void bulk_wait() { asm volatile("cp.async.bulk.wait_group %0;" :: "n"(N) : "memory"); }
template<int ID, int N> DEVI void nbar_sync() { asm volatile("bar.sync %0, %1;" :: "n"(ID), "n"(N) : "memory"); }
template<int ID, int N> DEVI void nbar_arrive() { asm volatile("bar.arrive %0, %1;" :: "n"(ID), "n"(N) : "memory"); }
DEVI void nbar_sync_r(int id, int n) { asm volatile("bar.sync %0, %1;" :: "r"(id), "r"(n) : "memory"); }
template<int R> DEVI void reg_inc() { asm volatile("setmaxnreg.inc.sync.aligned.u32 %0;" :: "n"(R)); }
template<int R> DEVI void reg_dec() { asm volatile("setmaxnreg.dec.sync.aligned.u32 %0;" :: "n"(R)); }
DEVI void wg_fence() { asm volatile("wgmma.fence.sync.aligned;" ::: "memory"); }
DEVI void wg_commit() { asm volatile("wgmma.commit_group.sync.aligned;" ::: "memory"); }
template<int N> DEVI void wg_wait() { asm volatile("wgmma.wait_group.sync.aligned %0;" :: "n"(N) : "memory"); }
DEVI uint64_t mkdesc(uint32_t addr, uint32_t lbo, uint32_t sbo, uint32_t sw = 1) {
  return ((uint64_t)((addr & 0x3FFFF) >> 4)) | ((uint64_t)(lbo >> 4) << 16) | ((uint64_t)(sbo >> 4) << 32) | ((uint64_t)sw << 62);
}
constexpr uint32_t SMEM_BASE = 1024;
__host__ __device__ constexpr long long CD(uint32_t off, uint32_t lbo, uint32_t sbo, uint32_t sw) {
  return (long long)(((uint64_t)((SMEM_BASE + off) >> 4)) | ((uint64_t)(lbo >> 4) << 16) | ((uint64_t)(sbo >> 4) << 32) | ((uint64_t)sw << 62));
}
DEVI uint32_t pack_bf16(float lo, float hi) { uint32_t r; asm("cvt.rn.bf16x2.f32 %0, %1, %2;" : "=r"(r) : "f"(hi), "f"(lo)); return r; }
DEVI float bf_lo(uint32_t v) { return __uint_as_float(v << 16); }
DEVI float bf_hi(uint32_t v) { return __uint_as_float(v & 0xffff0000u); }
DEVI void ldsm4t(uint32_t addr, uint32_t& r0, uint32_t& r1, uint32_t& r2, uint32_t& r3) {
  asm volatile("ldmatrix.sync.aligned.m8n8.x4.trans.shared.b16 {%0,%1,%2,%3}, [%4];" : "=r"(r0), "=r"(r1), "=r"(r2), "=r"(r3) : "r"(addr) : "memory");
}
DEVI void stsm4(uint32_t addr, uint32_t r0, uint32_t r1, uint32_t r2, uint32_t r3) {
  asm volatile("stmatrix.sync.aligned.m8n8.x4.shared.b16 [%0], {%1,%2,%3,%4};" :: "r"(addr), "r"(r0), "r"(r1), "r"(r2), "r"(r3) : "memory");
}
DEVI uint2 lds64v(uint32_t a) { uint2 v; asm volatile("ld.volatile.shared.v2.u32 {%0,%1}, [%2];" : "=r"(v.x), "=r"(v.y) : "r"(a) : "memory"); return v; }
DEVI uint32_t lds32v(uint32_t a) { uint32_t v; asm volatile("ld.volatile.shared.u32 %0, [%1];" : "=r"(v) : "r"(a) : "memory"); return v; }
DEVI uint4 lds128v(uint32_t a) { uint4 v; asm volatile("ld.volatile.shared.v4.u32 {%0,%1,%2,%3}, [%4];" : "=r"(v.x), "=r"(v.y), "=r"(v.z), "=r"(v.w) : "r"(a) : "memory"); return v; }
DEVI void sts32(uint32_t a, uint32_t x) { asm volatile("st.shared.u32 [%0], %1;" :: "r"(a), "r"(x) : "memory"); }
DEVI int lane_id() { int r; asm volatile("mov.u32 %0, %%laneid;" : "=r"(r)); return r; }
DEVI void sts64(uint32_t a, uint32_t x, uint32_t y) { asm volatile("st.shared.v2.u32 [%0], {%1,%2};" :: "r"(a), "r"(x), "r"(y) : "memory"); }
DEVI void st_async128(uint32_t a, uint32_t x, uint32_t y, uint32_t z, uint32_t w, uint32_t bar) {
  asm volatile("st.async.weak.shared::cluster.mbarrier::complete_tx::bytes.v4.b32 [%0], {%1,%2,%3,%4}, [%5];" :: "r"(a), "r"(x), "r"(y), "r"(z), "r"(w), "r"(bar) : "memory");
}
DEVI void st_async32(uint32_t a, uint32_t x, uint32_t bar) {
  asm volatile("st.async.weak.shared::cluster.mbarrier::complete_tx::bytes.b32 [%0], %1, [%2];" :: "r"(a), "r"(x), "r"(bar) : "memory");
}
DEVI uint4 ldg_rlx128(const void* p) {
  uint4 v;
  asm volatile("ld.relaxed.gpu.global.v4.b32 {%0,%1,%2,%3}, [%4];" : "=r"(v.x), "=r"(v.y), "=r"(v.z), "=r"(v.w) : "l"(p) : "memory");
  return v;
}
DEVI int ldg_rlx32(const void* p) { int v; asm volatile("ld.relaxed.gpu.global.b32 %0, [%1];" : "=r"(v) : "l"(p) : "memory"); return v; }
DEVI int ldg_acq32(const void* p) { int v; asm volatile("ld.acquire.gpu.global.b32 %0, [%1];" : "=r"(v) : "l"(p) : "memory"); return v; }
DEVI void stg128(void* p, uint32_t x, uint32_t y, uint32_t z, uint32_t w) {
  asm volatile("st.global.v4.b32 [%0], {%1,%2,%3,%4};" :: "l"(p), "r"(x), "r"(y), "r"(z), "r"(w) : "memory");
}
DEVI uint2 ldg_rlx64(const void* p) { uint2 v; asm volatile("{.reg .b64 a; ld.relaxed.gpu.global.b64 a, [%2]; mov.b64 {%0,%1}, a;}" : "=r"(v.x), "=r"(v.y) : "l"(p) : "memory"); return v; }
DEVI void stg_rlx64(void* p, uint32_t x, uint32_t y) { asm volatile("{.reg .b64 a; mov.b64 a, {%1,%2}; st.relaxed.gpu.global.b64 [%0], a;}" :: "l"(p), "r"(x), "r"(y) : "memory"); }
DEVI void stg_rlx32(void* p, uint32_t x) { asm volatile("st.relaxed.gpu.global.b32 [%0], %1;" :: "l"(p), "r"(x) : "memory"); }
DEVI void flag_add(int* p) { asm volatile("fence.proxy.async.global; red.release.gpu.global.add.s32 [%0], 1;" :: "l"(p) : "memory"); }
DEVI void e_stg_rlx32(void* p, uint32_t x) { asm volatile(ELECT "st.relaxed.gpu.global.b32 [%0], %1;}" :: "l"(p), "r"(x) : "memory"); }
DEVI void e_flag_add(int* p) { asm volatile("fence.proxy.async.global;\n" ELECT "red.release.gpu.global.add.s32 [%0], 1;}" :: "l"(p) : "memory"); }
DEVI int cluster_rank() { int r; asm volatile("mov.u32 %0, %%cluster_ctarank;" : "=r"(r)); return __shfl_sync(0xffffffffu, r, 0); }
DEVI int cluster_last() { int r; asm volatile("mov.u32 %0, %%cluster_nctarank;" : "=r"(r)); return __shfl_sync(0xffffffffu, r, 0) - 1; }
DEVI int cta_id() { int r; asm volatile("mov.u32 %0, %%ctaid.x;" : "=r"(r)); return __shfl_sync(0xffffffffu, r, 0); }
DEVI uint32_t clock32() { uint32_t c; asm volatile("mov.u32 %0, %%clock;" : "=r"(c)); return c; }
DEVI uint32_t gtime() { uint32_t c; asm volatile("mov.u32 %0, %%globaltimer_lo;" : "=r"(c)); return c; }
DEVI void wait_time(uint32_t t) { while (__any_sync(0xffffffffu, t - gtime() - 1 < 4000u)) {} }
DEVI void spin_until(uint32_t t0, int d) {
  int r;
  while (__any_sync(0xffffffffu, (r = d - (int)(clock32() - t0)) > 0)) {
    if (r > 300) __nanosleep(r >> 2);
  }
}
DEVI void pin2(const void* a, const void* b) { asm volatile("{.reg .pred p; setp.eq.u64 p, %0, %1; @p st.volatile.global.u64 [%0], %1;}" :: "l"(a), "l"(b) : "memory"); }
DEVI void pin2(uint32_t a, uint32_t b) { asm volatile("{.reg .pred p; setp.eq.u32 p, %0, %1; @p st.volatile.shared.u32 [%0], %1;}" :: "r"(a), "r"(b) : "memory"); }
DEVI void p_stg_rlx64(void* p, uint32_t x, uint32_t y, bool c) {
  asm volatile("{.reg .pred p; .reg .b64 a; setp.ne.u32 p, %3, 0; mov.b64 a, {%1,%2}; @p st.relaxed.gpu.global.b64 [%0], a;}" :: "l"(p), "r"(x), "r"(y), "r"((uint32_t)c) : "memory");
}
DEVI void pin2(uint64_t a, uint64_t b) { pin2((const void*)a, (const void*)b); }
DEVI uint64_t pair(uint32_t a, uint32_t bar) { return a | (uint64_t)bar << 32; }
DEVI void st_async32(uint64_t q, uint32_t x) { st_async32((uint32_t)q, x, (uint32_t)(q >> 32)); }
DEVI void st_async128(uint64_t q, uint4 v) { st_async128((uint32_t)q, v.x, v.y, v.z, v.w, (uint32_t)(q >> 32)); }
DEVI float ex2(float x) { float r; asm("ex2.approx.ftz.f32 %0, %1;" : "=f"(r) : "f"(x)); return r; }
DEVI float rcp(float x) { float r; asm("rcp.approx.ftz.f32 %0, %1;" : "=f"(r) : "f"(x)); return r; }
DEVI uint32_t xor_or(uint32_t a, uint32_t t, uint32_t acc) { uint32_t r; asm("lop3.b32 %0, %1, %2, %3, 0xbe;" : "=r"(r) : "r"(a), "r"(t), "r"(acc)); return r; }
DEVI void stsm2(uint32_t addr, uint32_t r0, uint32_t r1) {
  asm volatile("stmatrix.sync.aligned.m8n8.x2.shared.b16 [%0], {%1,%2};" :: "r"(addr), "r"(r0), "r"(r1) : "memory");
}
DEVI uint32_t settag(uint32_t v, uint32_t tag) { return (v & ~1u) | tag; }

#define A4(c, o)  c(d[o+0]), c(d[o+1]), c(d[o+2]), c(d[o+3])
#define A8(c, o)  A4(c, o), A4(c, o+4)
#define A16(c, o) A8(c, o), A8(c, o+8)
#define A12(c, o) A8(c, o), A4(c, o+8)
#define A28(c, o) A16(c, o), A12(c, o+16)
#define RL12 "{%0,%1,%2,%3,%4,%5,%6,%7,%8,%9,%10,%11}"
#define RL28 "{%0,%1,%2,%3,%4,%5,%6,%7,%8,%9,%10,%11,%12,%13,%14,%15,%16,%17,%18,%19,%20,%21,%22,%23,%24,%25,%26,%27}"
#define A20(c, o) A16(c, o), A4(c, o+16)
#define A32(c, o) A16(c, o), A16(c, o+16)
#define RL8  "{%0,%1,%2,%3,%4,%5,%6,%7}"
#define RL16 "{%0,%1,%2,%3,%4,%5,%6,%7,%8,%9,%10,%11,%12,%13,%14,%15}"
#define RL20 "{%0,%1,%2,%3,%4,%5,%6,%7,%8,%9,%10,%11,%12,%13,%14,%15,%16,%17,%18,%19}"
#define RL32 "{%0,%1,%2,%3,%4,%5,%6,%7,%8,%9,%10,%11,%12,%13,%14,%15,%16,%17,%18,%19,%20,%21,%22,%23,%24,%25,%26,%27,%28,%29,%30,%31}"
#define RL64 "{%0,%1,%2,%3,%4,%5,%6,%7,%8,%9,%10,%11,%12,%13,%14,%15,%16,%17,%18,%19,%20,%21,%22,%23,%24,%25,%26,%27,%28,%29,%30,%31," \
  "%32,%33,%34,%35,%36,%37,%38,%39,%40,%41,%42,%43,%44,%45,%46,%47,%48,%49,%50,%51,%52,%53,%54,%55,%56,%57,%58,%59,%60,%61,%62,%63}"
#define WG_OP(shape) "wgmma.mma_async.sync.aligned." shape "k16.f32.bf16.bf16 "
#define DEF_WGMMA(N, RL, AL, i0, i1, i2, i3, i4, i5, i6)                                                                         \
  template<int SC, int TB, long long CB> DEVI void rs##N(float* d, const uint32_t* a) {                                          \
    if (SC) asm volatile("{.reg .b64 tb; mov.b64 tb, %" #i4 ";\n" WG_OP("m64n" #N) RL ", {%" #i0 ",%" #i1 ",%" #i2 ",%" #i3 "}, tb, 1, 1, 1, %" #i5 ";}" \
      : AL("+f", 0) : "r"(a[0]), "r"(a[1]), "r"(a[2]), "r"(a[3]), "n"(CB), "n"(TB));                                             \
    else asm volatile("{.reg .b64 tb; mov.b64 tb, %" #i4 ";\n" WG_OP("m64n" #N) RL ", {%" #i0 ",%" #i1 ",%" #i2 ",%" #i3 "}, tb, 0, 1, 1, %" #i5 ";}" \
      : AL("=f", 0) : "r"(a[0]), "r"(a[1]), "r"(a[2]), "r"(a[3]), "n"(CB), "n"(TB));                                             \
  }                                                                                                                              \
  template<int SC, int TA, int TB, long long CA, long long CB> DEVI void ss##N(float* d, uint32_t a) {                           \
    if (SC) asm volatile("{.reg .b64 ta, tb; .reg .b32 lo, hi; add.u32 lo, %" #i0 ", %" #i1 "; mov.b32 hi, %" #i2 "; mov.b64 ta, {lo, hi}; mov.b64 tb, %" #i3 ";\n" \
      WG_OP("m64n" #N) RL ", ta, tb, 1, 1, 1, %" #i4 ", %" #i5 ";}"                                                              \
      : AL("+f", 0) : "r"(a), "n"((int)CA), "n"((int)(CA >> 32)), "n"(CB), "n"(TA), "n"(TB));                                    \
    else asm volatile("{.reg .b64 ta, tb; .reg .b32 lo, hi; add.u32 lo, %" #i0 ", %" #i1 "; mov.b32 hi, %" #i2 "; mov.b64 ta, {lo, hi}; mov.b64 tb, %" #i3 ";\n" \
      WG_OP("m64n" #N) RL ", ta, tb, 0, 1, 1, %" #i4 ", %" #i5 ";}"                                                              \
      : AL("=f", 0) : "r"(a), "n"((int)CA), "n"((int)(CA >> 32)), "n"(CB), "n"(TA), "n"(TB));                                    \
  }
DEF_WGMMA(8, "{%0,%1,%2,%3}", A4, 4, 5, 6, 7, 8, 9, 10)
DEF_WGMMA(16, RL8, A8, 8, 9, 10, 11, 12, 13, 14)
DEF_WGMMA(32, RL16, A16, 16, 17, 18, 19, 20, 21, 22)
DEF_WGMMA(40, RL20, A20, 20, 21, 22, 23, 24, 25, 26)
DEF_WGMMA(24, RL12, A12, 12, 13, 14, 15, 16, 17, 18)
DEF_WGMMA(56, RL28, A28, 28, 29, 30, 31, 32, 33, 34)
template<int TA> DEVI void wgmma_n128(float* d, uint64_t a, uint64_t b, int scale_d) {
  asm volatile("{.reg .pred p; setp.ne.b32 p, %66, 0;\n" WG_OP("m64n128") RL64 ", %64, %65, p, 1, 1, %67, 1;}"
    : A32("+f", 0), A32("+f", 32) : "l"(a), "l"(b), "r"(scale_d), "n"(TA));
}

namespace rec {
constexpr int KR = 43;
constexpr uint32_t WSZ = (64 - KR) * 2048, STG = KR * 2048;
constexpr uint32_t WS = 0;
constexpr uint32_t RING = 2 * WSZ;
constexpr uint32_t OB = RING + 3 * 8192;
constexpr uint32_t PB = OB + 4096;
constexpr uint32_t WO = RING + 32768;
constexpr uint32_t ATT = WO + 5 * 16384;
constexpr uint32_t AK = ATT + 10240, AV = ATT + 20480;
constexpr uint32_t PAD = ATT + 30720;
constexpr uint32_t BARS = PAD + 128;
constexpr uint32_t B_XE = BARS  , B_FA = BARS + 64  , B_FB = BARS + 88, B_FO = BARS + 96;
constexpr uint32_t B_ME = BARS + 104  , B_WE = BARS + 136, B_PD = BARS + 144;
constexpr uint32_t B_XF = BARS + 152  , B_MF = BARS + 216  , B_CP = BARS + 248  , B_WT = BARS + 280  ;
constexpr uint32_t B_AB = BARS + 296, B_OB = BARS + 304, B_ST = BARS + 312  , B_WS = BARS + 328, B_WO = BARS + 336, B_AT = BARS + 352, B_AV = BARS + 360;
constexpr int NBAR = 46;
constexpr uint32_t M0 = BARS + 384;
constexpr uint32_t SMEM = 232448;
constexpr int NB_P = 1, NB_ST = 2, NB_O = 3, NB_W0 = 4, NB_W1 = 5;
__host__ __device__ constexpr int wo_tile(int rank, int g, int i) { return i < 2 ? i * 6 + (rank == 2 ? g : 4 - 2 * g + rank) : 13 + rank - g; }
constexpr long long D_W = CD(WS, 16, 1024, 1), D_X = CD(0, 16, 1024, 1), D_O = CD(OB, 128, 256, 0);
constexpr long long D_WO = CD(WO, 16, 1024, 1), D_QM = CD(ATT, 640, 0, 0), D_QT = CD(ATT + 128, 640, 64, 0), D_K = CD(AK, 640, 128, 0);
constexpr long long D_V = CD(AV, 128, 640, 0), D_P = CD(PB, 128, 768, 0);
struct Maps { CUtensorMap w[3], wo, xd, xs; };
__host__ __device__ constexpr uint32_t mslot(int c) { return (c ^ (c >> 1)) * 12288; }
__host__ __device__ constexpr uint32_t xslot(int s) { return s < 3 ? RING + s * 8192 : s < 5 ? WO + (s - 3) * 8192 : s < 7 ? WO + (s + 1) * 8192 : OB; }
__host__ __device__ constexpr bool k_smem(int k) { return k % 3 == 2; }
__host__ __device__ constexpr int k_idx(int k) { return k % 3 == 2 ? k / 3 : k - k / 3; }
__host__ __device__ constexpr int k_of_reg(int i) { return i + (i >> 1); }
__host__ __device__ constexpr int k_of_smem(int i) { return 3 * i + 2; }

#define RPROF(i)
#define RPROF_STEP
#define CPROF(i, v)

template<bool DUAL, int K0, int K1> DEVI void seq_mem(float* d, const uint32_t* w, uint32_t dw) {
  if constexpr (K0 < K1) {
    constexpr long long B = CD(RING, 128, DUAL ? 4096 : 8192, 0) + mslot(K0 >> 4) / 16 + (K0 & 15) * 16;
    if constexpr (DUAL) {
      if constexpr (!k_smem(K0)) rs24<K0 != 0, 1, B>(d, w + 4 * k_idx(K0)); else ss24<1, 1, 1, D_W + k_idx(K0) * 128, B>(d, dw);
    } else {
      if constexpr (!k_smem(K0)) rs16<K0 != 0, 1, B>(d, w + 4 * k_idx(K0)); else ss16<1, 1, 1, D_W + k_idx(K0) * 128, B>(d, dw);
    }
    seq_mem<DUAL, K0 + 1, K1>(d, w, dw);
  }
}
template<int N, int K0, int K1> DEVI void seq_tok(float* d, const uint32_t* w, uint32_t dw) {
  if constexpr (K0 < K1) {
    constexpr bool DUAL = N > 32;
    constexpr long long B = D_X + (DUAL ? xslot((K0 >> 2) & 7) / 16 : xslot(K0 >> 3) / 16 + ((K0 >> 2) & 1) * 256) + (K0 & 3) * 2;
    if constexpr (DUAL) {
      if constexpr (!k_smem(K0)) rs56<K0 != 0, 0, B>(d, w + 4 * k_idx(K0)); else ss56<1, 1, 0, D_W + k_idx(K0) * 128, B>(d, dw);
    } else if constexpr (N == 24) {
      if constexpr (!k_smem(K0)) rs24<K0 != 0, 0, B>(d, w + 4 * k_idx(K0)); else ss24<1, 1, 0, D_W + k_idx(K0) * 128, B>(d, dw);
    } else {
      if constexpr (!k_smem(K0)) rs32<K0 != 0, 0, B>(d, w + 4 * k_idx(K0)); else ss32<1, 1, 0, D_W + k_idx(K0) * 128, B>(d, dw);
    }
    seq_tok<N, K0 + 1, K1>(d, w, dw);
  }
}
template<bool DUAL, int T, int K0> DEVI void seq_wo(float* d, uint32_t dw) {
  if constexpr (K0 < 8) {
    if constexpr (DUAL) ss16<K0 != 0, 1, 1, D_WO + T * 1024 + K0 * 128, D_O + K0 * 32>(d, dw);
    else ss8<K0 != 0, 1, 1, D_WO + T * 1024 + K0 * 128, D_O + K0 * 32>(d, dw);
    seq_wo<DUAL, T, K0 + 1>(d, dw);
  }
}
template<long long Q, int K0> DEVI void seq_s(float* d) {
  if constexpr (K0 < 8) { ss40<K0 != 0, 1, 1, Q + K0 * 80, D_K + K0 * 80>(d, 0); seq_s<Q, K0 + 1>(d); }
}
template<bool DUAL, int J> DEVI void load_x(uint32_t sb, const Maps* M, int t, int rb) {
  if (DUAL) e_tma_3d_mc(sb + xslot(J & 7), &M->xd, J * 64, (t - LAG) * 32, 0, sb + B_XF + (J & 7) * 8, rb);
  else e_tma_3d_mc(sb + xslot(J & 7), &M->xs, 0, (t < NSEG ? t : t - LAG) * 32, J * 2, sb + B_XF + (J & 7) * 8, rb);
}
DEVI void load_x_lent(uint32_t sb, const Maps* M, int t, int j) {
  const bool dual = t >= LAG && t < NSEG;
  const uint32_t dst = sb + (j == 3 ? xslot(3) : xslot(5));
#pragma unroll
  for (int i = 0; i < 2; i++)
    e_tma_3d(dst + i * 8192, dual ? &M->xd : &M->xs, dual ? (j + i) * 64 : 0, (t < LAG ? t : t - LAG) * 32, dual ? 0 : (j + i) * 2, sb + B_XF + (j + i) * 8);
}
struct True { static constexpr bool value = true; };
struct False { static constexpr bool value = false; };
struct Ctx { uint32_t sb; const Maps* M; int last; bool issuer; int wi; bool lead; uint32_t par; };
#define XD 1
template<bool DUAL, int J> DEVI void tok_release(const Ctx& c, int t, int& budget) {
  constexpr int NC = DUAL ? 16 : 8, S = J & 7;
  if constexpr (J + 8 < NC) {
    p_arrive_at(c.sb + B_XE + S * 8, c.last, c.lead);
    p_expect_tx(c.sb + B_XF + S * 8, 8192, c.lead && c.wi == 0);
  } else if constexpr (S == 1 || S == 2 || S == 4 || S == 7) p_arrive(c.sb + B_ME + (S >> 1) * 8, c.lead);
  if constexpr (J == 0) {
    if (c.issuer && c.wi == 6) { mbar_wait(c.sb + B_FO, t & 1, budget); load_x<DUAL, 7>(c.sb, c.M, t, c.last); }
  }
  if constexpr (J >= XD && J - XD + 8 < NC) {
    constexpr int I = J - XD;
    if (c.issuer && c.wi == (I & 1) * 4 + 1) { mbar_wait(c.sb + B_XE + I * 8, (t - LAG) & 1, budget); load_x<DUAL, I + 8>(c.sb, c.M, t, c.last); }
  }
}
template<int N, int J, class F, class G> DEVI bool tok_pass(float* d, const uint32_t* w, uint32_t dw, Ctx& c, int t, int& budget, F after0, G setup) {
  constexpr bool DUAL = N > 32;
  constexpr int NC = DUAL ? 16 : 8, KC = 64 / NC;
  if constexpr (J < NC) {
    if constexpr (J > 1) mbar_wait(c.sb + B_XF + (J & 7) * 8, c.par ^ (J >> 3), budget);
    wg_fence();
    seq_tok<N, J * KC, (J + 1) * KC>(d, w, dw);
    wg_commit();
    if constexpr (J == 1) after0();
    if constexpr (J >= NC - 5 && J < NC - 2) setup(J - (NC - 5));
    if constexpr (J > 0) { wg_wait<1>(); tok_release<DUAL, J - 1>(c, t, budget); }
    return tok_pass<N, J + 1>(d, w, dw, c, t, budget, after0, setup);
  } else {
    const bool ok = mbar_test(c.sb + B_MF, t & 1);
    wg_wait<0>();
    tok_release<DUAL, NC - 1>(c, t, budget);
    if (!DUAL) c.par ^= 1;
    return ok;
  }
}
template<int NB> DEVI void pack_tok(uint32_t* e, const float* d) {
#pragma unroll
  for (int i = 0; i < 8; i++) if ((i & 3) < NB) e[i] = pack_bf16(d[4 * (i & 3) + 2 * (i >> 2)], d[4 * (i & 3) + 2 * (i >> 2) + 1]);
}
DEVI void push_tok(const uint32_t* e, uint32_t sb, uint32_t o, int r, int rank) {
  const uint32_t b = mapa(sb, r);
  st_async128(b + o, e[0], e[1], e[2], e[3], b + (rank == 2 ? B_AV : B_AT));
}
DEVI uint32_t h1_tag(int seg) { return ((seg >> 1) & 1) ^ 1; }
template<bool DUAL> DEVI uint4 pack_part(const float* c, int t) {
  if (!DUAL) { const uint32_t x = settag(pack_bf16(c[0], c[1]), h1_tag(t < NSEG ? t : t - LAG)), y = pack_bf16(c[2], c[3]); return make_uint4(x, y, x, y); }
  return make_uint4(settag(pack_bf16(c[0], c[1]), h1_tag(t)), pack_bf16(c[2], c[3]), settag(pack_bf16(c[4], c[5]), h1_tag(t - LAG)), pack_bf16(c[6], c[7]));
}
DEVI void put_part(char* p1, char* p2, uint4 z, int t) { p_stg_rlx64(p1, z.x, z.y, t < NSEG); p_stg_rlx64(p2, z.z, z.w, t >= LAG); }

DEVI void rec_math(const uint32_t sb, const int wi, const Maps& M) {
  const int h = cta_id() / 3, rb = cluster_rank() >= 3 ? 3 : 0, rank = cluster_rank() - rb;
  const int warp = wi & 3, wg = wi >> 2;
  const bool lead = (threadIdx.x & 127) == 0;
  int budget = SPIN_BUDGET;
  uint32_t w[4 * KR];
  const int last = cluster_last();
  Ctx cx{sb, &M, last, rb + rank == last, wi, lead, 0};
  {
    const int lane = lane_id();
    const uint32_t a = sb + wg * STG + ((lane & 7) + (lane >> 4) * 8) * 128 + (((warp * 2 + ((lane >> 3) & 1)) ^ (lane & 7)) << 4);
    for (int i = 0; i < (wg == 1 || rank == 2 ? 12 : 8); i++)
      stg_rlx64((char*)g_h1[i & 3] + ((wo_tile(rank, wg, i >> 2) * 4 + warp) * 4 + (lane >> 3)) * 2048 + h * 64 + (lane & 7) * 8, 0, 0);
    mbar_wait(sb + B_ST + wg * 8, 0, budget);
#pragma unroll
    for (int k = 0; k < KR; k++) ldsm4t(a + k * 2048, w[4*k], w[4*k+1], w[4*k+2], w[4*k+3]);
    nbar_arrive<NB_ST, 384>();
    nbar_sync_r(NB_W0 + wg, 128);
    for (int i = 0; i < 5; i++) p_arrive_at(sb + B_FA + i * 8, i == 4 ? last : 0, lead);
    mbar_wait(sb + B_WS, 0, budget);
  }
  uint4 z = make_uint4(0, 0, 0, 0);
  char *z1 = nullptr, *z2 = nullptr;
  uint32_t rt0 = 0, rt1 = 0;
  mbar_wait(sb + B_XF, 0, budget); mbar_wait(sb + B_XF + 8, 0, budget);
#pragma unroll 1
  for (int t = 0;; t++) {
    const uint32_t dw = wg * (WSZ >> 4);
    uint32_t e[16];
    bool ok;
    auto finish = [&]() { put_part(z1, z2, z, t - 1); p_arrive_at(sb + B_FO, last, lead); };
    const int seg = t - rank * LAG;
    const bool att = rank < 2 && (unsigned)seg < (unsigned)NSEG;
    char* p1;
    uint32_t pw, oo;
    uint64_t u0, u1;
    int lane;
    auto setup = [&](int part) {
      if (part == 0) {
        lane = lane_id();
      } else if (part == 1) {
        char* const p = (char*)g_h1 + ((wo_tile(rank, wg, 0) * 4 + warp) * 4 + (lane >> 3)) * 2048 + h * 64 + (lane & 7) * 8;
        p1 = p + (t & 1) * sizeof(g_h1[0]);
        pin2(p1, nullptr);
      } else if (part == 2) {
        oo = OB + (lane >> 4) * 2048 + warp * 512 + (t < NSEG ? rank * 256 : 0) + (lane & 15) * 16;
        pw = sb + PB + (wg ? lane * 4 : 768 + warp * 768 + lane * 16);
        pin2(pw, oo);
      } else {
        if (wg) {
          const uint32_t ra = mapa(sb, rb + ((warp & 1) ? 2 : (rank ^ 1) & 1)), rc = mapa(sb, rb + ((warp & 1) ? (rank ^ 1) & 1 : 2));
          u0 = pair(ra + oo, ra + B_OB); u1 = pair(rc + oo, rc + B_OB);
        } else {
          u0 = (uint64_t)((char*)(g_ot + rank * O_LAYER) + (size_t)(h * DH + warp * 16 + (lane >> 2)) * (SEQ * 2) + seg * 64 + (lane & 3) * 16);
          u1 = (uint32_t)((lane & 24) + ((lane >> 2) & 1) + 2 * warp - 8 * (lane & 3));
        }
        pin2(u0, u1);
      }
    };
    RPROF_STEP;
    auto mem_pass = [&](auto dual_c) {
      constexpr bool DUAL = decltype(dual_c)::value;
      float m[DUAL ? 12 : 8];
      RPROF(8 + wg * 12 - 32);
      if (!ok) mbar_wait(sb + B_MF, t & 1, budget);
      wg_fence(); seq_mem<DUAL, 0, 8>(m, w, dw); wg_commit();
      const uint32_t ao = ATT + rank * 10240 + wi * 1280, to = ao + 128 + (lane & 3) * 128 + (lane >> 2) * 16;
      const int la = DUAL ? rank == 0 || (rank == 2 && wg) : t >= NSEG;
      RPROF(1 + wg * 12);
      if (DUAL && la) {
#pragma unroll
        for (int i = 0; i < 8; i++) { const uint32_t x = e[i]; e[i] = e[8 + i]; e[8 + i] = x; }
      }
      auto piece = [&](int i) { push_tok(e + 4 * i, sb, to + (i & 1) * 640, rb + (la ^ (i >> 1)), rank); };
      piece(0);
      wg_fence(); seq_mem<DUAL, 8, 16>(m, w, dw); wg_commit();
      piece(1);
      mbar_wait(sb + B_MF + 8, t & 1, budget);
      wg_fence(); seq_mem<DUAL, 16, 24>(m, w, dw); wg_commit();
      if (DUAL) piece(2);
      wg_fence(); seq_mem<DUAL, 24, 32>(m, w, dw); wg_commit();
      if (DUAL) piece(3);
      mbar_wait(sb + B_MF + 16, t & 1, budget);
      wg_fence(); seq_mem<DUAL, 32, 48>(m, w, dw); wg_commit();
      wg_wait<1>(); p_arrive(sb + B_PD, lead);
      const uint32_t r0 = mapa(sb, rb + la), r1 = mapa(sb, rb + (la ^ 1)), m0 = r0 + ao + lane * 4, m1 = r1 + ao + lane * 4, ab = rank == 2 ? B_AV : B_AB;
      const uint64_t q0 = pair(m0, r0 + ab), q1 = pair(m0 + 640, r0 + ab), q2 = pair(m1, r1 + ab), q3 = pair(m1 + 640, r1 + ab);
      pin2(q0, q1);
      if (DUAL) pin2(q2, q3);
      mbar_wait(sb + B_MF + 24, t & 1, budget);
      wg_fence(); seq_mem<DUAL, 48, 64>(m, w, dw); wg_commit();
      wg_wait<1>(); p_arrive_at(sb + B_FA, 0, lead);
      wg_wait<0>();
      const uint32_t a0 = pack_bf16(m[0], m[1]), a1 = pack_bf16(m[2], m[3]), a2 = pack_bf16(m[4], m[5]), a3 = pack_bf16(m[6], m[7]);
      if constexpr (DUAL) {
        st_async32(q0, la ? a2 : a0); st_async32(q1, la ? a3 : a1); st_async32(q2, la ? a0 : a2); st_async32(q3, la ? a1 : a3);
        rt0 = pack_bf16(m[8], m[9]); rt1 = pack_bf16(m[10], m[11]);
      } else { st_async32(q0, a0); st_async32(q1, a1); rt0 = a2; rt1 = a3; }
      p_arrive(sb + B_WE, lead);
    };
    if (t >= LAG && t < NSEG) {
      float d[28];
      ok = tok_pass<56, 0>(d, w, dw, cx, t, budget, finish, setup);
      pack_tok<4>(e + 8, d); pack_tok<3>(e, d + 16); e[3] = rt0; e[7] = rt1;
      mem_pass(True());
    } else {
      float d[16];
      if (t > 0) finish();
      if (t > 0 && t < LAG) {
        ok = tok_pass<24, 0>(d, w, dw, cx, t, budget, []() {}, setup);
        pack_tok<3>(e, d); e[3] = rt0; e[7] = rt1;
      } else {
        ok = tok_pass<32, 0>(d, w, dw, cx, t, budget, []() {}, setup);
        pack_tok<4>(e, d);
      }
      mem_pass(False());
    }
    {
      RPROF(2 + wg * 12);
      auto wo_ready = [&]() { if (t == 0) mbar_wait(sb + B_WO, 0, budget); if (t < NSTEP - 1) mbar_wait(sb + B_WT, t & 1, budget); };
      constexpr float SC = 0.08838834764831845f * 1.4426950408889634f;
      if (!att) wo_ready();
      else {
        float s[32];
        setup(3);
        if (wg) {
          uint32_t one[4];
#pragma unroll
          for (int i = 0; i < 4; i++) one[i] = 0x3F803F80u + (pw >> 31);
          mbar_wait_cluster(sb + B_AT, seg & 1, budget);
          mbar_wait_cluster(sb + B_AB, seg & 1, budget);
          fence_proxy_async();
          RPROF(3 + 12);
          wg_fence(); seq_s<D_QM, 0>(s); wg_commit();
          nbar_arrive<NB_P, 256>();
          if (warp == 1) sts32(pw + 640, 0);
          mbar_wait_cluster(sb + B_AV, seg & 1, budget);
          wg_wait<0>();
          float mx = fmaxf(fmaxf(fmaxf(s[0], s[1]), fmaxf(s[4], s[5])), fmaxf(fmaxf(fmaxf(s[8], s[9]), fmaxf(s[12], s[13])), fmaxf(s[16], s[17])));
          const float x1 = __shfl_xor_sync(0xffffffffu, mx, 1), x2 = __shfl_xor_sync(0xffffffffu, mx, 2), x3 = __shfl_xor_sync(0xffffffffu, mx, 3);
          const float u = (warp & 2) ? ((warp & 1) ? s[16] : s[12]) : ((warp & 1) ? s[8] : s[4]);
          const float v = (warp & 2) ? ((warp & 1) ? s[17] : s[13]) : ((warp & 1) ? s[9] : s[5]);
          const float ms = -SC * fmaxf(fmaxf(mx, x1), fmaxf(x2, x3));
          sts32(pw + 128 + warp * 128, pack_bf16(ex2(fmaf(u, SC, ms)), ex2(fmaf(v, SC, ms))));
          if (warp == 0) sts32(pw, pack_bf16(ex2(fmaf(s[0], SC, ms)), ex2(fmaf(s[1], SC, ms))));
          fence_proxy_async();
          nbar_sync<NB_W1, 128>();
          RPROF(4 + 12);
          wg_fence();
          rs8<0, 0, D_P>(s + 8, one); rs8<1, 0, D_P + 16>(s + 8, one); rs8<1, 0, D_P + 32>(s + 8, one);
          wg_commit();
          ss8<0, 0, 0, D_V, D_P>(s, 0); ss8<0, 0, 0, D_V + 320, D_P>(s + 4, 0);
          ss8<1, 0, 0, D_V + 16, D_P + 16>(s, 0); ss8<1, 0, 0, D_V + 336, D_P + 16>(s + 4, 0);
          ss8<1, 0, 0, D_V + 32, D_P + 32>(s, 0); ss8<1, 0, 0, D_V + 352, D_P + 32>(s + 4, 0);
          wg_commit();
          wg_wait<1>();
          const float i0 = rcp(s[8]), i1 = rcp(s[9]);
          wg_wait<0>();
          stsm4(sb + oo, pack_bf16(s[0] * i0, s[1] * i1), pack_bf16(s[2] * i0, s[3] * i1), pack_bf16(s[4] * i0, s[5] * i1), pack_bf16(s[6] * i0, s[7] * i1));
          __syncwarp();
          const uint4 y = lds128v(sb + oo);
          if (t < NSTEP - 1) { st_async128(u0, y); st_async128(u1, y); e_complete_tx(sb + B_OB, 512); }
          wo_ready();
        } else {
          const int lim = (int)u1;
          char* const og = (char*)u0;
          nbar_sync<NB_P, 256>();
          RPROF(3);
          wg_fence();
          seq_s<D_QT, 0>(s);
          wg_commit();
          mbar_wait_cluster(sb + B_AV, seg & 1, budget);
          wg_wait<0>();
#pragma unroll
          for (int i = 0; i < 8; i++) { float& v = s[4 + 4 * (i >> 1) + (i & 1)]; v = i <= lim ? v : -INFINITY; }
          float mx = fmaxf(fmaxf(fmaxf(s[0], s[1]), fmaxf(s[4], s[5])), fmaxf(fmaxf(fmaxf(s[8], s[9]), fmaxf(s[12], s[13])), fmaxf(s[16], s[17])));
          const float x1 = __shfl_xor_sync(0xffffffffu, mx, 1), x2 = __shfl_xor_sync(0xffffffffu, mx, 2), x3 = __shfl_xor_sync(0xffffffffu, mx, 3);
          const float ms = -SC * fmaxf(fmaxf(mx, x1), fmaxf(x2, x3));
#pragma unroll
          for (int i = 0; i < 10; i++) { float& v = s[4 * (i >> 1) + (i & 1)]; v = ex2(fmaf(v, SC, ms)); }
          const float sum = (((s[0] + s[1]) + (s[4] + s[5])) + ((s[8] + s[9]) + (s[12] + s[13]))) + (s[16] + s[17]);
          const float y1 = __shfl_xor_sync(0xffffffffu, sum, 1), y2 = __shfl_xor_sync(0xffffffffu, sum, 2), y3 = __shfl_xor_sync(0xffffffffu, sum, 3);
          const float inv = rcp((sum + y1) + (y2 + y3));
          stsm4(pw, pack_bf16(s[0] * inv, s[1] * inv), pack_bf16(s[4] * inv, s[5] * inv), pack_bf16(s[8] * inv, s[9] * inv), pack_bf16(s[12] * inv, s[13] * inv));
          stsm2(pw + 512, pack_bf16(s[16] * inv, s[17] * inv), 0);
          fence_proxy_async();
          nbar_sync<NB_W0, 128>();
          RPROF(4);
          wg_fence();
          ss32<0, 0, 0, D_V, D_P + 48>(s, 0); ss32<0, 0, 0, D_V + 320, D_P + 48>(s + 16, 0);
          ss32<1, 0, 0, D_V + 16, D_P + 64>(s, 0); ss32<1, 0, 0, D_V + 336, D_P + 64>(s + 16, 0);
          ss32<1, 0, 0, D_V + 32, D_P + 80>(s, 0); ss32<1, 0, 0, D_V + 352, D_P + 80>(s + 16, 0);
          wg_commit();
          wo_ready();
          wg_wait<0>();
#pragma unroll
          for (int i = 0; i < 4; i++) {
            const float* d = s + (i >> 1) * 16 + (i & 1) * 2;
            stg128(og + ((i >> 1) * 64 + (i & 1) * 8) * (SEQ * 2), pack_bf16(d[0], d[1]), pack_bf16(d[4], d[5]), pack_bf16(d[8], d[9]), pack_bf16(d[12], d[13]));
          }
          if ((seg & 3) == 3) nbar_arrive<NB_O, 160>();
        }
      }
      RPROF(5 + wg * 12);
      const bool three = wg == 1 || rank == 2;
      char* const p2 = p1 + (2 + ((t - LAG) & 1) - (t & 1)) * (int)sizeof(g_h1[0]);
      if (t < NSTEP - 1) {
        auto wo_pass = [&](auto dual_c) {
          constexpr bool DUAL = decltype(dual_c)::value;
          float c[24];
          const uint32_t dt = wg ? 0 : 3072;
          mbar_wait_cluster(sb + B_OB, t & 1, budget);
          fence_proxy_async();
          RPROF(6 + wg * 12);
          wg_fence(); seq_wo<DUAL, 0, 0>(c, dt); wg_commit(); seq_wo<DUAL, 1, 0>(c + 8, dt); wg_commit();
          mbar_wait(sb + B_XF, cx.par, budget);
          wg_wait<1>();
          if (warp == 2) load_x_lent(sb, &M, t + 1, wg ? 3 : 5);
          put_part(p1, p2, pack_part<DUAL>(c, t), t);
          const int o3 = (wo_tile(rank, wg, three ? 2 : 1) - wo_tile(rank, wg, 0)) * 32768;
          z1 = p1 + o3; z2 = p2 + o3;
          if (three) {
            wg_fence(); seq_wo<DUAL, 2, 0>(c + 16, dt); wg_commit();
            wg_wait<1>(); put_part(p1 + 6 * 32768, p2 + 6 * 32768, pack_part<DUAL>(c + 8, t), t);
            mbar_wait(sb + B_XF + 8, cx.par, budget);
            wg_wait<0>(); z = pack_part<DUAL>(c + 16, t);
          } else { mbar_wait(sb + B_XF + 8, cx.par, budget); wg_wait<0>(); z = pack_part<DUAL>(c + 8, t); }
        };
        if (t >= LAG && t < NSEG) wo_pass(True()); else wo_pass(False());
      } else break;
      RPROF(7 + wg * 12);
    }
  }
}

DEVI void wait_xa(const int* p, int& budget) {
  while (__any_sync(0xffffffffu, ldg_acq32(p) < 64) && --budget > 0) {}
  fence_proxy_global();
}
template<bool DUAL> DEVI void first_loads(uint32_t sb, const Maps* M, int n, int h, int rb, int& budget) {
  if (n >= LAG && ((n - LAG) & 3) == 0) e_prefetch_3d(&M->xs, 0, (n - LAG) * 32, h & 14);
  mbar_wait(sb + B_FA, n & 1, budget);
  load_x<DUAL, 0>(sb, M, n, rb); load_x<DUAL, 1>(sb, M, n, rb); load_x<DUAL, 2>(sb, M, n, rb);
}
template<bool DUAL> DEVI void lent_loads(uint32_t sb, const Maps* M, int n, int rb, int& budget) {
  mbar_wait(sb + B_FB, n & 1, budget);
  load_x<DUAL, 3>(sb, M, n, rb); load_x<DUAL, 4>(sb, M, n, rb); load_x<DUAL, 5>(sb, M, n, rb); load_x<DUAL, 6>(sb, M, n, rb);
}
DEVI void rec_comm(const uint32_t sb, const int warp, const Maps& M, const bf16* __restrict__ mem0) {
  const int lane = threadIdx.x & 31, h = cta_id() / 3, rb = cluster_rank() >= 3 ? 3 : 0, rank = cluster_rank() - rb;
  int budget = SPIN_BUDGET;
  const bool two = warp == 3 || (rank == 2 && warp == 2);
  const int ntask = two ? 2 : 1, qi = two ? (warp == 3 ? rank : 3) : rank * 3 + warp;
  const int task0 = two ? h * 2 + (qi >> 1) : 64 + h * 4 + (qi >> 1);
  auto h2_word = [&](int i, int ln) {
    const int task = task0 + i * 192;
    return (char*)g_h2 + (task >> 6) * 8192 + ((qi ^ i) & 1) * 4096 + ((task >> 2) & 15) * 256 + (task & 3) * 32 + (ln & 8) * 16 + (ln & 7) * 4;
  };
  auto first_x = [&](int t) {
    const int n = t + 1;
    p_expect_tx(sb + B_XF + (lane_id() & 7) * 8, 8192, lane_id() < 8);
    if (rb + rank == 0) {
      if (n >= LAG && ((n - LAG) & 3) == 0) wait_xa(&g_xa[1][(n - LAG) >> 2], budget);
      if (n >= LAG && n < NSEG) first_loads<true>(sb, &M, n, h, cluster_last(), budget); else first_loads<false>(sb, &M, n, h, cluster_last(), budget);
    }
  };
  {
    const int task = task0 + (lane >> 4) * 192, L = (task & 3) * 8 + (lane & 7);
    if ((lane >> 4) < ntask) {
      const bf16* p = mem0 + (L & 3) * 2 * DM + (task >> 2) * 16 + (L >> 2) + (lane & 8);
      uint32_t m0 = (uint32_t)__bfloat16_as_ushort(p[0]) | (uint32_t)__bfloat16_as_ushort(p[DM]) << 16;
      m0 = m0 ? m0 : 0x8000u;
      stg_rlx32(h2_word(lane >> 4, lane), ((qi ^ (lane >> 4)) & 1) ? 0 : m0);
      for (int i = 1; i < 4; i++) stg_rlx32(h2_word(lane >> 4, lane) + i * sizeof(g_h2[0]), 0);
      sts32(sb + M0 + warp * 128 + lane * 4, m0);
    }
    __syncwarp();
    nbar_sync<NB_ST, 384>();
    if (warp == 2) {
      e_expect_tx(sb + B_WS, 2 * WSZ);
#pragma unroll 1
      for (int i = 0; i < 2 * (64 - KR); i++) e_tma_2d(sb + WS + (i & 1) * WSZ + (i >> 1) * 2048, &M.w[rank], h * DH + (i & 1) * 64, k_of_smem(i >> 1) * 16, sb + B_WS);
      const int nt = rank == 2 ? 6 : 5;
      e_expect_tx(sb + B_WO, (nt - 2) * 16384);
#pragma unroll 1
      for (int i = 1; i < nt; i++) if (i != 3) e_tma_2d(sb + WO + i * 16384, &M.wo, wo_tile(rank, 1 - i / 3, i % 3) * 64, h * DH, sb + B_WO);
    }
    wait_xa(&g_xa[0][0], budget);
    if (warp == 3) { first_x(-1); if (rb + rank == 0) lent_loads<false>(sb, &M, 0, cluster_last(), budget); }
  }
  uint32_t cpp = 0;
  const uint32_t cp = sb + B_CP + warp * 8;
  uint32_t f_dst, f_chk, f_bar, f_time = gtime() - 4000;
  const char *f_src, *f_xr;
  auto prepare = [&](int s) {
    const int ck = warp ^ (warp < 2 && (s < LAG || s >= NSEG) && (rank & 1) == (s >= NSEG)), ln = lane_id();
    f_dst = sb + RING + mslot(ck); f_chk = f_dst + ln * 32 + (ln >> 2) * 4; f_bar = sb + ck * 8;
    f_src = (const char*)g_h2[s & 3] + ck * 8192 + (s >= NSEG ? 4096 : 0);
    f_xr = (const char*)g_xr[(s + 1) & 63] + ck * 4096;
    pin2(f_chk, 0u);
    return s <= LAG ? TP(9) + ck * TP(11) : s <= NSEG ? TP(1) + ck * TP(4) : TP(13) + ck * TP(11);
  };
  prepare(0);
#pragma unroll 1
  for (int t = 0;; t++) {
    const int n = t + 1;
    const bool dual = t >= LAG && t < NSEG;
    RPROF_STEP;
    {
      const uint32_t bytes = dual ? 8192 : 4096;
      e_expect_tx(cp, bytes + (n < NSEG ? 4096 : 0));
      mbar_wait(f_bar + B_ME, t & 1, budget);
      if (n < NSEG) e_bulk_g2s(f_dst + 8192, f_xr, 4096, cp);
      wait_time(f_time);
      RPROF(24); CPROF(0, gtime());
      int tries = 0;
      while (true) {
        tries++;
        e_bulk_g2s(f_dst, f_src, bytes, cp);
        mbar_wait(cp, cpp, budget); cpp ^= 1;
        uint32_t mn = min(min(lds32v(f_chk), lds32v(f_chk + 1024)), min(lds32v(f_chk + 2048), lds32v(f_chk + 3072)));
        if (dual) mn = min(min(mn, min(lds32v(f_chk + 4096), lds32v(f_chk + 5120))), min(lds32v(f_chk + 6144), lds32v(f_chk + 7168)));
        if (!__any_sync(0xffffffffu, mn == 0) || --budget < 0) break;
        e_expect_tx(cp, bytes);
      }
      e_arrive(f_bar + B_MF);
      RPROF(25); CPROF(1, gtime()); CPROF(2, tries);
    }
    const int seg = t - rank * LAG;
    const bool att = rank < 2 && (unsigned)seg < (unsigned)NSEG;
    if (warp == 0) {
      if (att) { e_expect_tx(sb + B_AT, 16384); e_expect_tx(sb + B_AB, 4096); e_expect_tx(sb + B_AV, 10240); }
      if (n < NSTEP) e_expect_tx(sb + B_OB, dual ? 4096 : 2048);
    }
    if (n + 1 < NSEG && (n & 3) == 3) wait_xa(&g_xa[0][(n + 1) >> 2], budget);
    if (rank == 2 && warp == 1) {
      if (h < 16 ? n < NSEG : n > LAG && n < NSTEP && ((n - LAG) & 3)) e_prefetch_3d(&M.xs, 0, (h < 16 ? n : n - LAG) * 32, (h & 7) * 2);
      if (h >= 16 && n + 1 < NSEG) asm volatile(ELECT "cp.async.bulk.prefetch.L2.global [%0], 2048;}" :: "l"((const char*)g_xr[n + 1] + (h & 7) * 2048) : "memory");
    }
    {
      const int ln = lane_id(), i = ln >> 4;
      char* const w = h2_word(i, ln);
      if (i < ntask) {
        stg_rlx32(w + ((t + 3) & 3) * sizeof(g_h2[0]), 0);
        if (n == LAG && ((qi ^ i) & 1)) stg_rlx32(w + (n & 3) * sizeof(g_h2[0]), lds32v(sb + M0 + warp * 128 + ln * 4));
      }
      __syncwarp();
    }
    if (n < NSTEP) {
      const uint32_t tag = (n >> 1) & 31;
      mbar_wait(sb + B_PD, t & 1, budget);
      uint32_t t0 = clock32();
      if (warp == 2) {
        e_expect_tx(sb + B_WT, 32768);
        e_tma_2d(sb + WO + 49152, &M.wo, wo_tile(rank, 0, 0) * 64, h * DH, sb + B_WT);
        mbar_wait(sb + B_WE, t & 1, budget);
        e_tma_2d(sb + WO, &M.wo, wo_tile(rank, 1, 0) * 64, h * DH, sb + B_WT);
      }
      if (warp == 3) first_x(t);
      if (warp == 0 && rank == (t >= NSEG)) { mbar_wait(sb + B_AB, seg & 1, budget); e_stg_rlx32(&g_ts[t & 1][h], (gtime() & ~31u) | tag); }
      const int fd = prepare(n), ln = lane_id();
      const int sa = t - (qi & 1) * LAG, sc = t - (~qi & 1) * LAG;
      const int i0 = (unsigned)sa < (unsigned)(NSEG - 1) ? 0 : 1, i1 = two && (unsigned)sc < (unsigned)(NSEG - 1) ? 2 : 1;
      const char* src = (const char*)g_h1[(qi & 1) * 2 + (sa & 1)] + task0 * 2048 + ln * 8;
      char* dst = h2_word(0, ln) + (n & 3) * sizeof(g_h2[0]);
      const int ds = ((~qi & 1) * 2 + (sc & 1) - (qi & 1) * 2 - (sa & 1)) * (int)sizeof(g_h1[0]) + 192 * 2048, dd = 3 * 8192 + ((qi & 1) ? -4096 : 4096);
      if (i0) { src += ds; dst += dd; }
      pin2(src, dst);
      spin_until(t0, TSD);
      uint32_t v0;
      do { v0 = ldg_rlx32(&g_ts[t & 1][ln]); } while (__any_sync(0xffffffffu, (v0 & 31) != tag) && --budget > 0);
      const uint32_t now = __shfl_sync(0xffffffffu, v0, 0);
      t0 = now + __reduce_max_sync(0xffffffffu, (int)(v0 - now));
      f_time = t0 + fd;
      RPROF(26); CPROF(3, t0);
      t0 += t < LAG ? TP(8) : t < NSEG ? TP(0) : TP(12);
#pragma unroll 1
      for (int i = i0; i < i1; i++) {
        const uint32_t tg = h1_tag(i ? sc : sa);
        uint2 v[8];
        wait_time(t0 + (!two ? 0 : i ? TP(3) : -TP(10)));
        int tries = 0;
        float a[4];
        while (true) {
          tries++;
#pragma unroll
          for (int k = 0; k < 8; k++) v[k] = ldg_rlx64(src + k * 256);
          asm volatile("{.reg .pred p; setp.eq.s32 p, %0, 0x7fffffff; @p exit;}" :: "r"(budget) : "memory");
          uint32_t bad = 0;
#pragma unroll
          for (int k = 0; k < 8; k++) {
            bad = xor_or(v[k].x, tg, bad);
            a[0] = k ? a[0] + bf_lo(v[k].x) : bf_lo(v[k].x); a[1] = k ? a[1] + bf_hi(v[k].x) : bf_hi(v[k].x);
            a[2] = k ? a[2] + bf_lo(v[k].y) : bf_lo(v[k].y); a[3] = k ? a[3] + bf_hi(v[k].y) : bf_hi(v[k].y);
          }
#pragma unroll
          for (int k = 0; k < 2; k++) {
            const float keep = (ln & 8) ? a[2+k] : a[k], send = (ln & 8) ? a[k] : a[2+k];
            a[k] = keep + __shfl_xor_sync(0xffffffffu, send, 8);
          }
#pragma unroll
          for (int k = 0; k < 2; k++) a[k] += __shfl_xor_sync(0xffffffffu, a[k], 16);
          if (!__any_sync(0xffffffffu, bad & 1) || --budget < 0) break;
        }
        const uint32_t out = pack_bf16(a[0], a[1]);
        if (ln < 16) stg_rlx32(dst, out ? out : 0x8000u);
        __syncwarp();
        src += ds; dst += dd;
        if (i == 0) { RPROF(28); CPROF(6, gtime()); CPROF(4, gtime()); CPROF(5, tries); } else CPROF(7, gtime());
      }
    }
    if (n == NSTEP) cluster_arrive();
    if (warp == (dual ? 2 : 1) && att && (seg & 3) == 3) { nbar_sync<NB_O, 160>(); e_flag_add(&g_dep[E_O1 + rank * 16 + (seg >> 2)]); }
    if (n == NSTEP) break;
  }
  if (h == 0 && rank == 0 && warp < 2) g_xa[warp][lane_id()] = 0;
}
}

__global__ void __launch_bounds__(384, 1)
rec_kernel(const __grid_constant__ rec::Maps M, const bf16* __restrict__ mem0) {
  using namespace rec;
  extern __shared__ __align__(1024) uint8_t smem[];
  const uint32_t sb = __shfl_sync(0xffffffffu, smem_u32(smem), 0);
  const int tid = threadIdx.x, wi = __shfl_sync(0xffffffffu, tid >> 5, 0);
  if ((sb & 0x3FFFF) != SMEM_BASE) __trap();
  if (wi == 0) {
    const int h = cta_id() / 3, rank = cta_id() - h * 3;
    const int nwg = 2 * cluster_last() + 2;
    for (int i = tid; i < NBAR; i += 32) mbar_init(sb + BARS + i * 8, i < 13 ? nwg : i < 19 ? 2 : 1);
    ((uint32_t*)(smem + PAD))[tid] = 0;
    fence_mbar_init(); fence_proxy_async();
    __syncwarp();
    e_expect_tx(sb + B_ST, STG); e_expect_tx(sb + B_ST + 8, STG);
    for (int i = 0; i < 2 * KR; i++) e_tma_2d(sb + (i & 1) * STG + (i >> 1) * 2048, &M.w[rank], h * DH + (i & 1) * 64, k_of_reg(i >> 1) * 16, sb + B_ST + (i & 1) * 8);
  } else if (wi == 1) {
    if (blockIdx.x < NEV / 32) { g_dep[blockIdx.x * 32 + (tid & 31)] = 0; g_claim[blockIdx.x * 32 + (tid & 31)] = 0; __threadfence(); }
    __syncwarp();
    asm volatile("griddepcontrol.launch_dependents;" ::: "memory");
  } else if (wi == 2) {
    if ((tid & 31) < 3) asm volatile("prefetch.tensormap [%0];" :: "l"(&M.wo + (tid & 31)) : "memory");
    __syncwarp();
  }
  cluster_arrive(); cluster_wait();
  if (wi < 8) { reg_inc<232>(); rec_math(sb, wi, M); cluster_arrive(); cluster_wait(); }
  else { reg_dec<40>(); rec_comm(sb, wi & 3, M, mem0); cluster_wait(); }
}

namespace gm {
struct Maps { CUtensorMap ot, wo, xn, wg, wu, hl, hs, wd, out; };
constexpr int STAGES = 6, STAGE = 32768;
constexpr uint32_t SO = STAGES * STAGE, BARS = SO + 32768;
constexpr uint32_t B_FULL = BARS, B_EMPTY = BARS + 48, B_TF = BARS + 96, B_TE = BARS + 112, B_ORD = BARS + 128, B_PM = BARS + 144, B_GO = BARS + 160;
constexpr uint32_t MAIL = BARS + 176, PMAIL = BARS + 192;
constexpr uint32_t SMEM = BARS + 256;
constexpr int END = -1;
#define DQ 8
#define GT gtime

struct Tile {
  bool isO, isG, l2; int blk, col, k0, n;
  DEVI Tile(int task, int rank) {
    const int e = task >> 8, id = task & 255;
    const bool isD = e < E_G1 || e >= E_D2;
    isO = e >= E_O1 && e < E_G2; isG = !isD && !isO; l2 = e >= E_O2;
    blk = l2 && !isO ? (e & 7) * 2 + rank : isD ? e >> 1 : e & 15;
    col = l2 && !isO ? id : (isG ? id : id & 3) * 2 + rank;
    k0 = isO ? (id >> 2) * 2048 : isG ? 0 : ((l2 ? e >> 3 : e) & 1) * 1792;
    n = isO ? 32 : isG ? 16 : 28;
    if (e >= E_D2 + DQ) { n = 14; k0 += (id >> 3) * 896; col = id & 7; }
  }
};

DEVI float geglu(float g, float u) {
  const float z = g * (0.7978845608028654f + 0.035677408136300125f * g * g);
  float t; asm("tanh.approx.f32 %0, %1;" : "=f"(t) : "f"(z));
  const float hg = 0.5f * g;
  return fmaf(hg, t, hg) * u;
}
struct Sched {
  int need, size, e;
  bool filler;
  uint4 dep, cl;
  DEVI void init(int lane) {
    e = (lane < 4 ? lane + 12 : lane < 16 ? lane - 4 : lane) * 4;
    const bool d = e < E_G1 || e >= E_D2, o = e >= E_O1 && e < E_G2;
    need = e >= E_D2 ? 56 : d ? 28 : e < E_O1 ? 64 : o ? 32 : 128;
    size = e >= E_D2 ? (e < E_D2 + DQ ? 8 : e < E_D2 + 16 ? 16 : 0) : d ? 4 : o ? 8 : e < E_O1 ? 28 : e < E_G2 + 8 ? 56 : 0;
    filler = (int)blockIdx.x >= TP(5);
  }
  DEVI void scan(int lane) { cl = ldg_rlx128(g_claim + e); dep = ldg_rlx128(g_dep + e); }
  DEVI int next(int lane, int& budget) {
    while (--budget > 0) {
      int av[4], open = 0;
#pragma unroll
      for (int i = 0; i < 4; i++) { const int r = max(size - (int)(&cl.x)[i], 0); open |= r; av[i] = ((int)(&dep.x)[i] >= need ? r : 0) + (i ? av[i - 1] : 0); }
      const uint32_t mo = __ballot_sync(0xffffffffu, open);
      if (!mo) break;
      if (filler) {
        const int x = TP(6) & 3, dx = x == 0 ? dep.x : x == 1 ? dep.y : x == 2 ? dep.z : dep.w;
        filler = !__any_sync(0xffffffffu, e == ((E_O1 + TP(6)) & ~3) && dx >= need);
      }
      if (!filler && (mo & 0xffff) && lane >= E_O2 / 4) av[3] = 0;
      int inc = av[3], pos = 0;
      while (true) {
        const uint32_t m = __ballot_sync(0xffffffffu, inc > pos && av[3]);
        if (!m) break;
        const int l = __ffs(m) - 1, rel = pos - (inc - av[3]), i = (rel >= av[0]) + (rel >= av[1]) + (rel >= av[2]);
        int r = 0;
        if (lane == l) {
          const int tk = atomicAdd(g_claim + e + i, 1);
          r = tk < size ? (e + i) << 8 | tk : -1 - (inc - av[3] + (i == 0 ? av[0] : i == 1 ? av[1] : i == 2 ? av[2] : av[3]) + tk - size);
        }
        r = __shfl_sync(0xffffffffu, r, l);
        if (r >= 0) return r;
        if (pos == 0) {
#pragma unroll
          for (int o = 1; o < 32; o <<= 1) { const int v = __shfl_up_sync(0xffffffffu, inc, o); if (lane >= o) inc += v; }
        }
        pos = -1 - r;
      }
      if (pos == 0) __nanosleep(TP(7));
      scan(lane);
    }
    return END;
  }
};

DEVI void scheduler(const uint32_t sb) {
  const int lane = threadIdx.x & 31;
  int budget = SPIN_BUDGET;
  Sched sc; sc.init(lane);
#pragma unroll 1
  for (int i = 0;; i++) {
    if (i) mbar_wait(sb + B_GO, (i & 1) ^ 1, budget);
    sc.scan(lane);
    if (i == 0) cluster_wait();
    const int task = sc.next(lane, budget);
    const uint32_t r = mapa(sb, lane & 1);
    if (lane < 2) st_async32(r + PMAIL + (i & 1) * 4, task, r + B_PM + (i & 1) * 8);
    __syncwarp();
    if (task == END) break;
  }
}

DEVI void producer(const uint32_t sb, const Maps& M) {
  const int lane = threadIdx.x & 31, rank = cluster_rank();
  int budget = SPIN_BUDGET, s = 0, ph = 0;
#pragma unroll 1
  for (int i = 0;; i++) {
    e_expect_tx(sb + B_PM + (i & 1) * 8, 4);
    mbar_wait_cluster(sb + B_PM + (i & 1) * 8, (i >> 1) & 1, budget);
    const int task = budget < 0 ? END : __shfl_sync(0xffffffffu, (int)lds32v(sb + PMAIL + (i & 1) * 4), 0);
    fence_proxy_global();
    for (int z = 0; z < (task == END ? 2 : 1); z++) {
      const int g = (i + z) & 1;
      mbar_wait(sb + B_TE + g * 8, (((i + z) >> 1) & 1) ^ 1, budget);
      if (lane == 0) { sts64(sb + MAIL + g * 8, task, s | ph << 8); mbar_arrive(sb + B_TF + g * 8); }
      __syncwarp();
    }
    if (task == END) break;
    const Tile T(task, rank);
    const bool shareB = T.l2 && !T.isO;
    const CUtensorMap* mA = T.isO ? &M.ot : T.isG ? &M.xn : &M.hl;
    const CUtensorMap* mB0 = T.isO ? &M.wo : T.isG ? &M.wg : &M.wd;
    const CUtensorMap* mB1 = T.isG ? &M.wu : mB0;
    const int c0 = T.col * (T.isG ? 64 : 128), c1 = T.isG ? c0 : c0 + 64, row = T.blk * 128;
    const int ok = 0;
    int k = T.k0;
#pragma unroll 1
    for (int it = 0; it < T.n; it++, k += 64) {
      const uint32_t a = sb + s * STAGE, fb = sb + B_FULL + s * 8;
      mbar_wait(sb + B_EMPTY + s * 8, ph ^ 1, budget);
      e_expect_tx(fb, STAGE);
      if (shareB) {
        e_tma_2d_mc(a + 16384 + rank * 8192, rank ? mB1 : mB0, rank ? c1 : c0, k, fb);
        e_tma_2d(a, mA, k, row, fb); e_tma_2d(a + 8192, mA, k, row + 64, fb);
      } else {
        e_tma_2d_mc(a + rank * 8192, mA, T.isO ? row + rank * 64 : k, T.isO ? k + ok : row + rank * 64, fb);
        e_tma_2d(a + 16384, mB0, c0, k, fb); e_tma_2d(a + 24576, mB1, c1, k, fb);
      }
      if (it == T.n - TP(2)) e_arrive(sb + B_GO);
      if (++s == STAGES) { s = 0; ph ^= 1; }
    }
  }
}

template<int TA> DEVI void mainloop(float* d0, float* d1, uint32_t sb, int n, int s, int ph, bool lead, uint32_t ord, int& budget) {
  int prev = 0;
  const uint32_t rel = threadIdx.x & 127;
#pragma unroll 1
  for (int i = 0; i < n; i++) {
    mbar_wait(sb + B_FULL + s * 8, ph, budget);
    const uint32_t a = sb + s * STAGE;
    const uint64_t da = mkdesc(a, 16, 1024), db = mkdesc(a + 16384, 8192, 1024);
    wg_fence();
#pragma unroll
    for (int k = 0; k < 4; k++) {
      wgmma_n128<TA>(d0, da + k * (TA ? 128 : 2), db + k * 128, (i | k) != 0);
      wgmma_n128<TA>(d1, da + 512 + k * (TA ? 128 : 2), db + k * 128, (i | k) != 0);
    }
    wg_commit();
    if (i > 0) { wg_wait<1>(); p_arrive_at(sb + B_EMPTY + prev * 8, rel & 1, rel < 2); }
    prev = s;
    if (++s == STAGES) { s = 0; ph ^= 1; }
  }
  p_arrive(ord, lead);
  wg_wait<0>();
  p_arrive_at(sb + B_EMPTY + prev * 8, rel & 1, rel < 2);
}

DEVI void consumer(const uint32_t sb, const Maps& M, const int wg) {
  const int tid = threadIdx.x, lane = tid & 31, warp = (tid >> 5) & 3;
  const bool lead = (tid & 127) == 0;
  const uint32_t so = sb + SO + wg * 16384;
  int budget = SPIN_BUDGET;
  float d0[64], d1[64];
#pragma unroll 1
  for (int m = 0;; m++) {
    mbar_wait(sb + B_TF + wg * 8, m & 1, budget);
    const uint2 mail = lds64v(sb + MAIL + wg * 8);
    const int task = __shfl_sync(0xffffffffu, (int)mail.x, 0), pos = __shfl_sync(0xffffffffu, (int)mail.y, 0);
    e_arrive(sb + B_TE + wg * 8);
    if (task == END || budget < 0) break;
    const Tile T(task, cluster_rank());
    mbar_wait(sb + B_ORD + wg * 8, (m & 1) ^ wg ^ 1, budget);
    if (T.isO) mainloop<1>(d0, d1, sb, T.n, pos & 255, pos >> 8, lead, sb + B_ORD + (wg ^ 1) * 8, budget);
    else mainloop<0>(d0, d1, sb, T.n, pos & 255, pos >> 8, lead, sb + B_ORD + (wg ^ 1) * 8, budget);
    const uint32_t st = so + (warp * 16 + (lane & 15)) * 128;
    if (T.isG) {
      int* const fl = &g_dep[T.l2 ? E_D2 + (T.col >= 28) * 8 + (T.blk >> 1) : E_D1 + T.blk * 2 + (T.col >= 28)];
#pragma unroll
      for (int mm = 0; mm < 2; mm++) {
        const float* d = mm ? d1 : d0;
#pragma unroll
        for (int c = 0; c < 4; c++) {
          uint32_t r[4];
#pragma unroll
          for (int i = 0; i < 4; i++) r[i] = pack_bf16(geglu(d[8*c+2*i], d[32+8*c+2*i]), geglu(d[8*c+2*i+1], d[33+8*c+2*i]));
          stsm4(st + mm * 8192 + (((2 * c + (lane >> 4)) ^ (lane & 7)) << 4), r[0], r[1], r[2], r[3]);
        }
      }
      fence_proxy_async();
      nbar_sync_r(1 + wg, 128);
      if (lead) {
        tma_store_2d(&M.hs, so, T.col * 64, T.blk * 128);
        bulk_commit();
        bulk_wait<0>();
        flag_add(fl);
      }
    } else {
#pragma unroll
      for (int hf = 0; hf < 2; hf++) {
        if (hf) { if (lead) bulk_wait_read<0>(); nbar_sync_r(1 + wg, 128); }
#pragma unroll
        for (int mm = 0; mm < 2; mm++) {
          const float* d = (mm ? d1 : d0) + hf * 32;
#pragma unroll
          for (int c = 0; c < 4; c++)
            stsm4(st + mm * 8192 + (((2 * c + (lane >> 4)) ^ (lane & 7)) << 4), pack_bf16(d[8*c], d[8*c+1]), pack_bf16(d[8*c+2], d[8*c+3]),
                  pack_bf16(d[8*c+4], d[8*c+5]), pack_bf16(d[8*c+6], d[8*c+7]));
        }
        fence_proxy_async();
        nbar_sync_r(1 + wg, 128);
        if (lead) { tma_radd_2d(&M.out, so, T.col * 128 + hf * 64, T.blk * 128); bulk_commit(); }
      }
      if (lead) {
        bulk_wait<0>();
        if (T.isO || !T.l2) flag_add(&g_dep[(!T.isO ? E_LX2 : T.l2 ? E_LX1B : E_LX1A) + T.blk]);
      }
    }
    __syncwarp();
  }
}

DEVI void norm_helper(const bf16* __restrict__ x, bf16* out) {
  const int lane = threadIdx.x & 31;
  int budget = SPIN_BUDGET, tk = lane < 4 ? -1 : 1024;
#pragma unroll 1
  while (--budget > 0) {
    if (tk < 0) tk = atomicAdd(g_claim + E_LI + lane, 1);
    if (__all_sync(0xffffffffu, tk >= 1024)) break;
    const uint32_t m = __ballot_sync(0xffffffffu, tk < 1024 && (lane == 0 || ldg_acq32(g_dep + E_LI + lane * 16 + (tk >> 6)) >= 16));
    if (!m) { __nanosleep(TP(7)); continue; }
    const int ql = __ffs(m) - 1, task = __shfl_sync(0xffffffffu, tk, ql), q = E_LI + ql * 16, ev = task >> 6;
    if (lane == ql) tk = -1;
    const size_t off = (size_t)task * (DM * 4) + lane * 16;
    const char* src = (const char*)(q == E_LI ? x : out) + off;
    uint4 u[8];
#pragma unroll
    for (int i = 0; i < 8; i++) u[i] = ldg_rlx128(src + i * 512);
    if (q == E_LI) {
#pragma unroll
      for (int i = 0; i < 8; i++) stg128((char*)out + off + i * 512, u[i].x, u[i].y, u[i].z, u[i].w);
    }
    int* const fl = q == E_LI ? &g_xa[0][ev] : q == E_LX2 ? &g_xa[1][ev] : &g_dep[q == E_LX1A ? E_G1 + ev : E_G2 + (ev >> 1)];
    float mean[2], rs[2];
#pragma unroll
    for (int r = 0; r < 2; r++) {
      float s0 = 0, s1 = 0;
#pragma unroll
      for (int i = 0; i < 16; i++) { const uint32_t v = (&u[4*r + (i >> 2)].x)[i & 3]; s0 += bf_lo(v); s1 += bf_hi(v); }
      mean[r] = (s0 + s1) * (1.f / 32);
      s0 = s1 = 0;
#pragma unroll
      for (int i = 0; i < 16; i++) { const uint32_t v = (&u[4*r + (i >> 2)].x)[i & 3]; const float a = bf_lo(v) - mean[r], b = bf_hi(v) - mean[r]; s0 = fmaf(a, a, s0); s1 = fmaf(b, b, s1); }
      rs[r] = s0 + s1;
    }
    {
      const bool hi = lane & 16;
      float m1 = hi ? mean[1] : mean[0], q1 = hi ? rs[1] : rs[0], m2 = hi ? mean[0] : mean[1], q2 = hi ? rs[0] : rs[1], cnt = 16;
#pragma unroll
      for (int o = 16; o; o >>= 1) {
        m2 = __shfl_xor_sync(0xffffffffu, m2, o); q2 = __shfl_xor_sync(0xffffffffu, q2, o);
        const float dl = m1 - m2;
        q2 = q1 = fmaf(dl * dl, cnt, q1 + q2); m2 = m1 = 0.5f * (m1 + m2);
        cnt *= 2;
      }
      q1 = rsqrtf(q1 * (1.f / DM) + 1e-5f);
      m2 = __shfl_xor_sync(0xffffffffu, m1, 16); q2 = __shfl_xor_sync(0xffffffffu, q1, 16);
      mean[0] = hi ? m2 : m1; mean[1] = hi ? m1 : m2; rs[0] = hi ? q2 : q1; rs[1] = hi ? q1 : q2;
    }
#pragma unroll
    for (int i = 0; i < 8; i++) {
      uint32_t y[4];
#pragma unroll
      for (int c = 0; c < 4; c++) { const uint32_t v = (&u[i].x)[c]; y[c] = pack_bf16((bf_lo(v) - mean[i >> 2]) * rs[i >> 2], (bf_hi(v) - mean[i >> 2]) * rs[i >> 2]); }
      stg128((char*)g_xn + off + i * 512, y[0], y[1], y[2], y[3]);
      u[i] = make_uint4(y[0], y[1], y[2], y[3]);
    }
    if (q == E_LI && (task & 15) >= 12) {
      uint32_t* const xr = g_xr[task >> 4] + lane * 32 + (task & 3);
#pragma unroll
      for (int i = 0; i < 16; i++) {
        const uint32_t a = (&u[i >> 2].x)[i & 3], b = (&u[4 + (i >> 2)].x)[i & 3];
        xr[(i >> 2) * 1024 + (i & 3) * 8] = __byte_perm(a, b, 0x5410); xr[(i >> 2) * 1024 + (i & 3) * 8 + 4] = __byte_perm(a, b, 0x7632);
      }
    }
    fence_proxy_global();
    __syncwarp();
    if (lane == 0) flag_add(fl);
    __syncwarp();
  }
}
}

__global__ void __cluster_dims__(2, 1, 1) __launch_bounds__(384, 1)
gemm_kernel(const __grid_constant__ gm::Maps M, const bf16* __restrict__ x, bf16* out) {
  using namespace gm;
  extern __shared__ __align__(1024) uint8_t smem[];
  const uint32_t sb = __shfl_sync(0xffffffffu, smem_u32(smem), 0);
  const int tid = threadIdx.x, wi = __shfl_sync(0xffffffffu, tid >> 5, 0);
  if (tid < 21) mbar_init(sb + BARS + tid * 8, tid == 14 || tid == 15 ? 4 : tid >= 6 && tid < 12 ? 2 : 1);
  fence_mbar_init();
  if (tid >= 256 && tid < 265) asm volatile("prefetch.tensormap [%0];" :: "l"(&M.ot + (tid - 256)) : "memory");
  __syncwarp();
  cluster_arrive();
  const bool sched = wi == 11 && cluster_rank() == 0;
  if (!sched) cluster_wait();
  if (wi < 8) { reg_inc<208>(); consumer(sb, M, wi >> 2); cluster_arrive(); cluster_wait(); }
  else {
    reg_dec<88>();
    if (wi == 8) producer(sb, M);
    else if (sched) scheduler(sb);
    else {
      norm_helper(x, out);
      asm volatile("griddepcontrol.wait;" ::: "memory");
    }
    __syncwarp();
    cluster_arrive(); cluster_wait();
  }
}

typedef CUresult (*PFN_encodeTiled)(CUtensorMap*, CUtensorMapDataType, cuuint32_t, void*, const cuuint64_t*, const cuuint64_t*,
                                    const cuuint32_t*, const cuuint32_t*, CUtensorMapInterleave, CUtensorMapSwizzle,
                                    CUtensorMapL2promotion, CUtensorMapFloatOOBfill);
static PFN_encodeTiled g_encode = nullptr;
static CUtensorMap make_map(const void* ptr, uint64_t rows, uint64_t cols, uint32_t box_rows, CUtensorMapL2promotion pr = CU_TENSOR_MAP_L2_PROMOTION_L2_256B) {
  CUtensorMap m;
  cuuint64_t dims[2] = {cols, rows}, strides[1] = {cols * 2};
  cuuint32_t box[2] = {64, box_rows}, es[2] = {1, 1};
  g_encode(&m, CU_TENSOR_MAP_DATA_TYPE_BFLOAT16, 2, (void*)ptr, dims, strides, box, es, CU_TENSOR_MAP_INTERLEAVE_NONE,
           CU_TENSOR_MAP_SWIZZLE_128B, pr, CU_TENSOR_MAP_FLOAT_OOB_FILL_NONE);
  return m;
}

static CUtensorMap make_map3(const void* ptr, uint64_t d0, uint64_t d1, uint64_t d2, uint64_t stride2) {
  CUtensorMap m;
  cuuint64_t dims[3] = {d0, d1, d2}, strides[2] = {DM * 2, stride2};
  cuuint32_t box[3] = {64, 32, 2}, es[3] = {1, 1, 1};
  g_encode(&m, CU_TENSOR_MAP_DATA_TYPE_BFLOAT16, 3, (void*)ptr, dims, strides, box, es, CU_TENSOR_MAP_INTERLEAVE_NONE,
           CU_TENSOR_MAP_SWIZZLE_128B, CU_TENSOR_MAP_L2_PROMOTION_L2_256B, CU_TENSOR_MAP_FLOAT_OOB_FILL_NONE);
  return m;
}

extern "C" void kernel_launch(void* const* d_in, const int* in_sizes, int n_in, void* d_out, int out_size) {
  const bf16* x = (const bf16*)d_in[0];
  const bf16* mem0 = (const bf16*)d_in[1];
  if (!g_encode) {
    void* p = nullptr; cudaDriverEntryPointQueryResult q;
    cudaGetDriverEntryPoint("cuTensorMapEncodeTiled", &p, cudaEnableDefault, &q);
    g_encode = (PFN_encodeTiled)p;
    cudaFuncSetAttribute(gemm_kernel, cudaFuncAttributeMaxDynamicSharedMemorySize, gm::SMEM);
    cudaFuncSetAttribute(rec_kernel, cudaFuncAttributeMaxDynamicSharedMemorySize, rec::SMEM);
  }
  bf16 *xn, *ot, *hh;
  cudaGetSymbolAddress((void**)&xn, g_xn); cudaGetSymbolAddress((void**)&ot, g_ot); cudaGetSymbolAddress((void**)&hh, g_h);
  rec::Maps R;
  for (int i = 0; i < 3; i++) R.w[i] = make_map(d_in[2 + i], DM, NH * DH, 16, CU_TENSOR_MAP_L2_PROMOTION_NONE);
  R.wo = make_map(d_in[5], NH * DH, DM, 128);
  R.xd = make_map3(xn, DM, SEQ - LAG * 32, 2, (uint64_t)LAG * 32 * DM * 2); R.xs = make_map3(xn, 64, SEQ, DM / 64, 128);
  gm::Maps G;
  G.ot = make_map(ot, NH * DH + O_LAYER / SEQ, SEQ, 64); G.wo = make_map(d_in[5], NH * DH, DM, 64); G.xn = make_map(xn, SEQ, DM, 64);
  G.wg = make_map(d_in[8], DM, DF, 64); G.wu = make_map(d_in[9], DM, DF, 64); G.hl = make_map(hh, SEQ, DF, 64); G.hs = make_map(hh, SEQ, DF, 128);
  G.wd = make_map(d_in[10], DF, DM, 64); G.out = make_map(d_out, SEQ, DM, 128);
  cudaLaunchConfig_t cfg = {};
  cudaLaunchAttribute at[1];
  cfg.attrs = at; cfg.numAttrs = 1;
  cfg.gridDim = dim3(3 * NH); cfg.blockDim = dim3(384); cfg.dynamicSmemBytes = rec::SMEM; cfg.stream = cudaStreamPerThread;
  at[0].id = cudaLaunchAttributeClusterDimension; at[0].val.clusterDim.y = at[0].val.clusterDim.z = 1;
  static int csize = 0;
  if (!csize) {
    int n = 0;
    at[0].val.clusterDim.x = 6;
    csize = cudaOccupancyMaxActiveClusters(&n, rec_kernel, &cfg) == cudaSuccess && n >= NH / 2 ? 6 : 3;
  }
  at[0].val.clusterDim.x = csize;
  cudaLaunchKernelEx(&cfg, rec_kernel, R, mem0);
  cfg.gridDim = dim3(132); cfg.blockDim = dim3(384); cfg.dynamicSmemBytes = gm::SMEM; cfg.stream = cudaStreamPerThread;
  at[0].id = cudaLaunchAttributeProgrammaticStreamSerialization; at[0].val.programmaticStreamSerializationAllowed = 1;
  cudaLaunchKernelEx(&cfg, gemm_kernel, G, x, (bf16*)d_out);
}
```

```cpp
#include <cuda_runtime.h>
#include <cuda_bf16.h>
#include <cuda.h>
#include <stdint.h>

#define DEVI __device__ __forceinline__
typedef __nv_bfloat16 bf16;

constexpr int SEQ = 2048, DM = 1024, NH = 32, DH = 128, DF = 3584, NSEG = 64;
#define LAG 19
constexpr int NSTEP = NSEG + LAG;

#define TSD 1800
constexpr size_t O_LAYER = 0;
__device__ __align__(1024) bf16 g_xn[SEQ * DM];
__device__ __align__(1024) bf16 g_ot[SEQ * NH * DH + O_LAYER];
__device__ __align__(1024) bf16 g_h[SEQ * DF];
__device__ __align__(1024) uint32_t g_xr[NSEG][DM * 4];
__device__ __align__(1024) uint2 g_h1[4][256 * 256];
__device__ __align__(1024) uint4 g_h2[4][2048];
__device__ __align__(128) uint32_t g_ts[2][32];
enum { E_D1 = 0, E_G1 = 32, E_O1 = 48, E_O2 = 64, E_G2 = 80, E_D2 = 96,
       E_LI = 128, E_LX2 = 144, E_LX1A = 160, E_LX1B = 176, NEV = 256 };
__device__ __align__(128) int g_dep[NEV];
__device__ __align__(128) int g_claim[NEV];
__device__ __align__(128) int g_xa[2][32];

#define TUNE_DEFAULTS 1650, 2450, 6, 100, 100, 8, 13, 100, 1500, 2225, 100, 110, 1500, 2225, 200, 0
constexpr int c_D[16] = {TUNE_DEFAULTS};
template<int I> struct TPV { static constexpr int v = c_D[I]; };
#define TP(i) TPV<i>::v

DEVI uint32_t smem_u32(const void* p) { return (uint32_t)__cvta_generic_to_shared(p); }
DEVI void mbar_init(uint32_t bar, uint32_t cnt) { asm volatile("mbarrier.init.shared::cta.b64 [%0], %1;" :: "r"(bar), "r"(cnt) : "memory"); }
DEVI void mbar_arrive(uint32_t bar) { asm volatile("mbarrier.arrive.shared::cta.b64 _, [%0];" :: "r"(bar) : "memory"); }
DEVI bool mbar_try(uint32_t bar, uint32_t parity) {
  uint32_t p;
  asm volatile("{.reg .pred p; mbarrier.try_wait.parity.shared::cta.b64 p, [%1], %2; selp.u32 %0, 1, 0, p;}" : "=r"(p) : "r"(bar), "r"(parity) : "memory");
  return p;
}
DEVI bool mbar_test(uint32_t bar, uint32_t parity) {
  uint32_t p;
  asm volatile("{.reg .pred p; mbarrier.test_wait.parity.shared::cta.b64 p, [%1], %2; selp.u32 %0, 1, 0, p;}" : "=r"(p) : "r"(bar), "r"(parity) : "memory");
  return p;
}
constexpr int SPIN_BUDGET = 1 << 18;
DEVI void mbar_wait(uint32_t bar, uint32_t parity, int& budget) {
  while (!mbar_try(bar, parity)) { if (--budget < 0) break; }
}
DEVI bool mbar_try_cluster(uint32_t bar, uint32_t parity) {
  uint32_t p;
  asm volatile("{.reg .pred p; mbarrier.try_wait.parity.acquire.cluster.shared::cta.b64 p, [%1], %2; selp.u32 %0, 1, 0, p;}" : "=r"(p) : "r"(bar), "r"(parity) : "memory");
  return p;
}
DEVI void mbar_wait_cluster(uint32_t bar, uint32_t parity, int& budget) {
  while (!mbar_try_cluster(bar, parity)) { if (--budget < 0) break; }
}
DEVI uint32_t mapa(uint32_t addr, uint32_t rank) { uint32_t r; asm("mapa.shared::cluster.u32 %0, %1, %2;" : "=r"(r) : "r"(addr), "r"(rank)); return r; }
DEVI void cluster_arrive() { asm volatile("barrier.cluster.arrive.relaxed.aligned;" ::: "memory"); }
DEVI void cluster_wait() { asm volatile("barrier.cluster.wait.aligned;" ::: "memory"); }
DEVI void fence_mbar_init() { asm volatile("fence.mbarrier_init.release.cluster;" ::: "memory"); }
DEVI void fence_proxy_async() { asm volatile("fence.proxy.async.shared::cta;" ::: "memory"); }
DEVI void fence_proxy_global() { asm volatile("fence.proxy.async.global;" ::: "memory"); }
#define ELECT "{.reg .pred p; elect.sync _|p, 0xffffffff;\n @p "
DEVI void e_expect_tx(uint32_t bar, uint32_t bytes) { asm volatile(ELECT "mbarrier.arrive.expect_tx.shared::cta.b64 _, [%0], %1;}" :: "r"(bar), "r"(bytes) : "memory"); }
DEVI void e_complete_tx(uint32_t bar, uint32_t bytes) { asm volatile("fence.acq_rel.cta;\n" ELECT "mbarrier.complete_tx.relaxed.cta.shared::cta.b64 [%0], %1;}" :: "r"(bar), "r"(bytes) : "memory"); }
DEVI void e_arrive(uint32_t bar) { asm volatile(ELECT "mbarrier.arrive.shared::cta.b64 _, [%0];}" :: "r"(bar) : "memory"); }
DEVI void e_tma_2d(uint32_t dst, const CUtensorMap* m, int c0, int c1, uint32_t bar) {
  asm volatile(ELECT "cp.async.bulk.tensor.2d.shared::cluster.global.mbarrier::complete_tx::bytes [%0], [%1, {%3, %4}], [%2];}"
    :: "r"(dst), "l"(m), "r"(bar), "r"(c0), "r"(c1) : "memory");
}
DEVI void e_prefetch_3d(const CUtensorMap* m, int c0, int c1, int c2) {
  asm volatile(ELECT "cp.async.bulk.prefetch.tensor.3d.L2.global [%0, {%1, %2, %3}];}" :: "l"(m), "r"(c0), "r"(c1), "r"(c2) : "memory");
}
DEVI void e_bulk_g2s(uint32_t dst, const void* src, uint32_t bytes, uint32_t bar) {
  asm volatile(ELECT "cp.async.bulk.shared::cluster.global.mbarrier::complete_tx::bytes [%0], [%1], %2, [%3];}" :: "r"(dst), "l"(src), "r"(bytes), "r"(bar) : "memory");
}
DEVI void e_tma_3d(uint32_t dst, const CUtensorMap* m, int c0, int c1, int c2, uint32_t bar) {
  asm volatile(ELECT "cp.async.bulk.tensor.3d.shared::cluster.global.mbarrier::complete_tx::bytes [%0], [%1, {%3, %4, %5}], [%2];}"
    :: "r"(dst), "l"(m), "r"(bar), "r"(c0), "r"(c1), "r"(c2) : "memory");
}
DEVI void e_tma_3d_mc(uint32_t dst, const CUtensorMap* m, int c0, int c1, int c2, uint32_t bar, int last) {
  asm volatile(ELECT "cp.async.bulk.tensor.3d.shared::cluster.global.mbarrier::complete_tx::bytes.multicast::cluster [%0], [%1, {%3, %4, %5}], [%2], %6;}"
    :: "r"(dst), "l"(m), "r"(bar), "r"(c0), "r"(c1), "r"(c2), "h"((uint16_t)((2 << last) - 1)) : "memory");
}
DEVI void e_tma_2d_mc(uint32_t dst, const CUtensorMap* m, int c0, int c1, uint32_t bar) {
  asm volatile(ELECT "cp.async.bulk.tensor.2d.shared::cluster.global.mbarrier::complete_tx::bytes.multicast::cluster [%0], [%1, {%3, %4}], [%2], %5;}"
    :: "r"(dst), "l"(m), "r"(bar), "r"(c0), "r"(c1), "h"((uint16_t)3) : "memory");
}
DEVI void p_arrive_at(uint32_t bar, uint32_t rank, bool c) {
  asm volatile("{.reg .pred p; .reg .b32 a; setp.ne.u32 p, %2, 0; mapa.shared::cluster.u32 a, %0, %1; @p mbarrier.arrive.shared::cluster.b64 _, [a];}"
    :: "r"(bar), "r"(rank), "r"((uint32_t)c) : "memory");
}
DEVI void p_expect_tx(uint32_t bar, uint32_t bytes, bool c) {
  asm volatile("{.reg .pred p; setp.ne.u32 p, %2, 0; @p mbarrier.arrive.expect_tx.shared::cta.b64 _, [%0], %1;}" :: "r"(bar), "r"(bytes), "r"((uint32_t)c) : "memory");
}
DEVI void p_arrive(uint32_t bar, bool c) { asm volatile("{.reg .pred p; setp.ne.u32 p, %1, 0; @p mbarrier.arrive.shared::cta.b64 _, [%0];}" :: "r"(bar), "r"((uint32_t)c) : "memory"); }
DEVI void tma_store_2d(const CUtensorMap* m, uint32_t src, int c0, int c1) {
  asm volatile("cp.async.bulk.tensor.2d.global.shared::cta.bulk_group [%0, {%2, %3}], [%1];" :: "l"(m), "r"(src), "r"(c0), "r"(c1) : "memory");
}
DEVI void tma_radd_2d(const CUtensorMap* m, uint32_t src, int c0, int c1) {
  asm volatile("cp.reduce.async.bulk.tensor.2d.global.shared::cta.add.bulk_group [%0, {%2, %3}], [%1];" :: "l"(m), "r"(src), "r"(c0), "r"(c1) : "memory");
}
DEVI void bulk_commit() { asm volatile("cp.async.bulk.commit_group;" ::: "memory"); }
template<int N> DEVI void bulk_wait_read() { asm volatile("cp.async.bulk.wait_group.read %0;" :: "n"(N) : "memory"); }
template<int N> DEVI void bulk_wait() { asm volatile("cp.async.bulk.wait_group %0;" :: "n"(N) : "memory"); }
template<int ID, int N> DEVI void nbar_sync() { asm volatile("bar.sync %0, %1;" :: "n"(ID), "n"(N) : "memory"); }
template<int ID, int N> DEVI void nbar_arrive() { asm volatile("bar.arrive %0, %1;" :: "n"(ID), "n"(N) : "memory"); }
DEVI void nbar_sync_r(int id, int n) { asm volatile("bar.sync %0, %1;" :: "r"(id), "r"(n) : "memory"); }
template<int R> DEVI void reg_inc() { asm volatile("setmaxnreg.inc.sync.aligned.u32 %0;" :: "n"(R)); }
template<int R> DEVI void reg_dec() { asm volatile("setmaxnreg.dec.sync.aligned.u32 %0;" :: "n"(R)); }
DEVI void wg_fence() { asm volatile("wgmma.fence.sync.aligned;" ::: "memory"); }
DEVI void wg_commit() { asm volatile("wgmma.commit_group.sync.aligned;" ::: "memory"); }
template<int N> DEVI void wg_wait() { asm volatile("wgmma.wait_group.sync.aligned %0;" :: "n"(N) : "memory"); }
DEVI uint64_t mkdesc(uint32_t addr, uint32_t lbo, uint32_t sbo, uint32_t sw = 1) {
  return ((uint64_t)((addr & 0x3FFFF) >> 4)) | ((uint64_t)(lbo >> 4) << 16) | ((uint64_t)(sbo >> 4) << 32) | ((uint64_t)sw << 62);
}
constexpr uint32_t SMEM_BASE = 1024;
__host__ __device__ constexpr long long CD(uint32_t off, uint32_t lbo, uint32_t sbo, uint32_t sw) {
  return (long long)(((uint64_t)((SMEM_BASE + off) >> 4)) | ((uint64_t)(lbo >> 4) << 16) | ((uint64_t)(sbo >> 4) << 32) | ((uint64_t)sw << 62));
}
DEVI uint32_t pack_bf16(float lo, float hi) { uint32_t r; asm("cvt.rn.bf16x2.f32 %0, %1, %2;" : "=r"(r) : "f"(hi), "f"(lo)); return r; }
DEVI float bf_lo(uint32_t v) { return __uint_as_float(v << 16); }
DEVI float bf_hi(uint32_t v) { return __uint_as_float(v & 0xffff0000u); }
DEVI void ldsm4t(uint32_t addr, uint32_t& r0, uint32_t& r1, uint32_t& r2, uint32_t& r3) {
  asm volatile("ldmatrix.sync.aligned.m8n8.x4.trans.shared.b16 {%0,%1,%2,%3}, [%4];" : "=r"(r0), "=r"(r1), "=r"(r2), "=r"(r3) : "r"(addr) : "memory");
}
DEVI void stsm4(uint32_t addr, uint32_t r0, uint32_t r1, uint32_t r2, uint32_t r3) {
  asm volatile("stmatrix.sync.aligned.m8n8.x4.shared.b16 [%0], {%1,%2,%3,%4};" :: "r"(addr), "r"(r0), "r"(r1), "r"(r2), "r"(r3) : "memory");
}
DEVI uint2 lds64v(uint32_t a) { uint2 v; asm volatile("ld.volatile.shared.v2.u32 {%0,%1}, [%2];" : "=r"(v.x), "=r"(v.y) : "r"(a) : "memory"); return v; }
DEVI uint32_t lds32v(uint32_t a) { uint32_t v; asm volatile("ld.volatile.shared.u32 %0, [%1];" : "=r"(v) : "r"(a) : "memory"); return v; }
DEVI uint4 lds128v(uint32_t a) { uint4 v; asm volatile("ld.volatile.shared.v4.u32 {%0,%1,%2,%3}, [%4];" : "=r"(v.x), "=r"(v.y), "=r"(v.z), "=r"(v.w) : "r"(a) : "memory"); return v; }
DEVI void sts32(uint32_t a, uint32_t x) { asm volatile("st.shared.u32 [%0], %1;" :: "r"(a), "r"(x) : "memory"); }
DEVI int lane_id() { int r; asm volatile("mov.u32 %0, %%laneid;" : "=r"(r)); return r; }
DEVI void sts64(uint32_t a, uint32_t x, uint32_t y) { asm volatile("st.shared.v2.u32 [%0], {%1,%2};" :: "r"(a), "r"(x), "r"(y) : "memory"); }
DEVI void st_async128(uint32_t a, uint32_t x, uint32_t y, uint32_t z, uint32_t w, uint32_t bar) {
  asm volatile("st.async.weak.shared::cluster.mbarrier::complete_tx::bytes.v4.b32 [%0], {%1,%2,%3,%4}, [%5];" :: "r"(a), "r"(x), "r"(y), "r"(z), "r"(w), "r"(bar) : "memory");
}
DEVI void st_async32(uint32_t a, uint32_t x, uint32_t bar) {
  asm volatile("st.async.weak.shared::cluster.mbarrier::complete_tx::bytes.b32 [%0], %1, [%2];" :: "r"(a), "r"(x), "r"(bar) : "memory");
}
DEVI uint4 ldg_rlx128(const void* p) {
  uint4 v;
  asm volatile("ld.relaxed.gpu.global.v4.b32 {%0,%1,%2,%3}, [%4];" : "=r"(v.x), "=r"(v.y), "=r"(v.z), "=r"(v.w) : "l"(p) : "memory");
  return v;
}
DEVI int ldg_rlx32(const void* p) { int v; asm volatile("ld.relaxed.gpu.global.b32 %0, [%1];" : "=r"(v) : "l"(p) : "memory"); return v; }
DEVI int ldg_acq32(const void* p) { int v; asm volatile("ld.acquire.gpu.global.b32 %0, [%1];" : "=r"(v) : "l"(p) : "memory"); return v; }
DEVI void stg128(void* p, uint32_t x, uint32_t y, uint32_t z, uint32_t w) {
  asm volatile("st.global.v4.b32 [%0], {%1,%2,%3,%4};" :: "l"(p), "r"(x), "r"(y), "r"(z), "r"(w) : "memory");
}
DEVI uint2 ldg_rlx64(const void* p) { uint2 v; asm volatile("{.reg .b64 a; ld.relaxed.gpu.global.b64 a, [%2]; mov.b64 {%0,%1}, a;}" : "=r"(v.x), "=r"(v.y) : "l"(p) : "memory"); return v; }
DEVI void stg_rlx64(void* p, uint32_t x, uint32_t y) { asm volatile("{.reg .b64 a; mov.b64 a, {%1,%2}; st.relaxed.gpu.global.b64 [%0], a;}" :: "l"(p), "r"(x), "r"(y) : "memory"); }
DEVI void stg_rlx32(void* p, uint32_t x) { asm volatile("st.relaxed.gpu.global.b32 [%0], %1;" :: "l"(p), "r"(x) : "memory"); }
DEVI void flag_add(int* p) { asm volatile("fence.proxy.async.global; red.release.gpu.global.add.s32 [%0], 1;" :: "l"(p) : "memory"); }
DEVI void e_stg_rlx32(void* p, uint32_t x) { asm volatile(ELECT "st.relaxed.gpu.global.b32 [%0], %1;}" :: "l"(p), "r"(x) : "memory"); }
DEVI void e_flag_add(int* p) { asm volatile("fence.proxy.async.global;\n" ELECT "red.release.gpu.global.add.s32 [%0], 1;}" :: "l"(p) : "memory"); }
DEVI int cluster_rank() { int r; asm volatile("mov.u32 %0, %%cluster_ctarank;" : "=r"(r)); return __shfl_sync(0xffffffffu, r, 0); }
DEVI int cluster_last() { int r; asm volatile("mov.u32 %0, %%cluster_nctarank;" : "=r"(r)); return __shfl_sync(0xffffffffu, r, 0) - 1; }
DEVI int cta_id() { int r; asm volatile("mov.u32 %0, %%ctaid.x;" : "=r"(r)); return __shfl_sync(0xffffffffu, r, 0); }
DEVI uint32_t clock32() { uint32_t c; asm volatile("mov.u32 %0, %%clock;" : "=r"(c)); return c; }
DEVI uint32_t gtime() { uint32_t c; asm volatile("mov.u32 %0, %%globaltimer_lo;" : "=r"(c)); return c; }
DEVI void wait_time(uint32_t t) { while (__any_sync(0xffffffffu, t - gtime() - 1 < 4000u)) {} }
DEVI void spin_until(uint32_t t0, int d) {
  int r;
  while (__any_sync(0xffffffffu, (r = d - (int)(clock32() - t0)) > 0)) {
    if (r > 300) __nanosleep(r >> 2);
  }
}
DEVI void pin2(const void* a, const void* b) { asm volatile("{.reg .pred p; setp.eq.u64 p, %0, %1; @p st.volatile.global.u64 [%0], %1;}" :: "l"(a), "l"(b) : "memory"); }
DEVI void pin2(uint32_t a, uint32_t b) { asm volatile("{.reg .pred p; setp.eq.u32 p, %0, %1; @p st.volatile.shared.u32 [%0], %1;}" :: "r"(a), "r"(b) : "memory"); }
DEVI void p_stg_rlx64(void* p, uint32_t x, uint32_t y, bool c) {
  asm volatile("{.reg .pred p; .reg .b64 a; setp.ne.u32 p, %3, 0; mov.b64 a, {%1,%2}; @p st.relaxed.gpu.global.b64 [%0], a;}" :: "l"(p), "r"(x), "r"(y), "r"((uint32_t)c) : "memory");
}
DEVI void pin2(uint64_t a, uint64_t b) { pin2((const void*)a, (const void*)b); }
DEVI uint64_t pair(uint32_t a, uint32_t bar) { return a | (uint64_t)bar << 32; }
DEVI void st_async32(uint64_t q, uint32_t x) { st_async32((uint32_t)q, x, (uint32_t)(q >> 32)); }
DEVI void st_async128(uint64_t q, uint4 v) { st_async128((uint32_t)q, v.x, v.y, v.z, v.w, (uint32_t)(q >> 32)); }
DEVI float ex2(float x) { float r; asm("ex2.approx.ftz.f32 %0, %1;" : "=f"(r) : "f"(x)); return r; }
DEVI float rcp(float x) { float r; asm("rcp.approx.ftz.f32 %0, %1;" : "=f"(r) : "f"(x)); return r; }
DEVI uint32_t xor_or(uint32_t a, uint32_t t, uint32_t acc) { uint32_t r; asm("lop3.b32 %0, %1, %2, %3, 0xbe;" : "=r"(r) : "r"(a), "r"(t), "r"(acc)); return r; }
DEVI void stsm2(uint32_t addr, uint32_t r0, uint32_t r1) {
  asm volatile("stmatrix.sync.aligned.m8n8.x2.shared.b16 [%0], {%1,%2};" :: "r"(addr), "r"(r0), "r"(r1) : "memory");
}
DEVI uint32_t settag(uint32_t v, uint32_t tag) { return (v & ~1u) | tag; }

#define A4(c, o)  c(d[o+0]), c(d[o+1]), c(d[o+2]), c(d[o+3])
#define A8(c, o)  A4(c, o), A4(c, o+4)
#define A16(c, o) A8(c, o), A8(c, o+8)
#define A12(c, o) A8(c, o), A4(c, o+8)
#define A28(c, o) A16(c, o), A12(c, o+16)
#define RL12 "{%0,%1,%2,%3,%4,%5,%6,%7,%8,%9,%10,%11}"
#define RL28 "{%0,%1,%2,%3,%4,%5,%6,%7,%8,%9,%10,%11,%12,%13,%14,%15,%16,%17,%18,%19,%20,%21,%22,%23,%24,%25,%26,%27}"
#define A20(c, o) A16(c, o), A4(c, o+16)
#define A32(c, o) A16(c, o), A16(c, o+16)
#define RL8  "{%0,%1,%2,%3,%4,%5,%6,%7}"
#define RL16 "{%0,%1,%2,%3,%4,%5,%6,%7,%8,%9,%10,%11,%12,%13,%14,%15}"
#define RL20 "{%0,%1,%2,%3,%4,%5,%6,%7,%8,%9,%10,%11,%12,%13,%14,%15,%16,%17,%18,%19}"
#define RL32 "{%0,%1,%2,%3,%4,%5,%6,%7,%8,%9,%10,%11,%12,%13,%14,%15,%16,%17,%18,%19,%20,%21,%22,%23,%24,%25,%26,%27,%28,%29,%30,%31}"
#define RL64 "{%0,%1,%2,%3,%4,%5,%6,%7,%8,%9,%10,%11,%12,%13,%14,%15,%16,%17,%18,%19,%20,%21,%22,%23,%24,%25,%26,%27,%28,%29,%30,%31," \
  "%32,%33,%34,%35,%36,%37,%38,%39,%40,%41,%42,%43,%44,%45,%46,%47,%48,%49,%50,%51,%52,%53,%54,%55,%56,%57,%58,%59,%60,%61,%62,%63}"
#define WG_OP(shape) "wgmma.mma_async.sync.aligned." shape "k16.f32.bf16.bf16 "
#define DEF_WGMMA(N, RL, AL, i0, i1, i2, i3, i4, i5, i6)                                                                         \
  template<int SC, int TB, long long CB> DEVI void rs##N(float* d, const uint32_t* a) {                                          \
    if (SC) asm volatile("{.reg .b64 tb; mov.b64 tb, %" #i4 ";\n" WG_OP("m64n" #N) RL ", {%" #i0 ",%" #i1 ",%" #i2 ",%" #i3 "}, tb, 1, 1, 1, %" #i5 ";}" \
      : AL("+f", 0) : "r"(a[0]), "r"(a[1]), "r"(a[2]), "r"(a[3]), "n"(CB), "n"(TB));                                             \
    else asm volatile("{.reg .b64 tb; mov.b64 tb, %" #i4 ";\n" WG_OP("m64n" #N) RL ", {%" #i0 ",%" #i1 ",%" #i2 ",%" #i3 "}, tb, 0, 1, 1, %" #i5 ";}" \
      : AL("=f", 0) : "r"(a[0]), "r"(a[1]), "r"(a[2]), "r"(a[3]), "n"(CB), "n"(TB));                                             \
  }                                                                                                                              \
  template<int SC, int TA, int TB, long long CA, long long CB> DEVI void ss##N(float* d, uint32_t a) {                           \
    if (SC) asm volatile("{.reg .b64 ta, tb; .reg .b32 lo, hi; add.u32 lo, %" #i0 ", %" #i1 "; mov.b32 hi, %" #i2 "; mov.b64 ta, {lo, hi}; mov.b64 tb, %" #i3 ";\n" \
      WG_OP("m64n" #N) RL ", ta, tb, 1, 1, 1, %" #i4 ", %" #i5 ";}"                                                              \
      : AL("+f", 0) : "r"(a), "n"((int)CA), "n"((int)(CA >> 32)), "n"(CB), "n"(TA), "n"(TB));                                    \
    else asm volatile("{.reg .b64 ta, tb; .reg .b32 lo, hi; add.u32 lo, %" #i0 ", %" #i1 "; mov.b32 hi, %" #i2 "; mov.b64 ta, {lo, hi}; mov.b64 tb, %" #i3 ";\n" \
      WG_OP("m64n" #N) RL ", ta, tb, 0, 1, 1, %" #i4 ", %" #i5 ";}"                                                              \
      : AL("=f", 0) : "r"(a), "n"((int)CA), "n"((int)(CA >> 32)), "n"(CB), "n"(TA), "n"(TB));                                    \
  }
DEF_WGMMA(8, "{%0,%1,%2,%3}", A4, 4, 5, 6, 7, 8, 9, 10)
DEF_WGMMA(16, RL8, A8, 8, 9, 10, 11, 12, 13, 14)
DEF_WGMMA(32, RL16, A16, 16, 17, 18, 19, 20, 21, 22)
DEF_WGMMA(40, RL20, A20, 20, 21, 22, 23, 24, 25, 26)
DEF_WGMMA(24, RL12, A12, 12, 13, 14, 15, 16, 17, 18)
DEF_WGMMA(56, RL28, A28, 28, 29, 30, 31, 32, 33, 34)
template<int TA> DEVI void wgmma_n128(float* d, uint64_t a, uint64_t b, int scale_d) {
  asm volatile("{.reg .pred p; setp.ne.b32 p, %66, 0;\n" WG_OP("m64n128") RL64 ", %64, %65, p, 1, 1, %67, 1;}"
    : A32("+f", 0), A32("+f", 32) : "l"(a), "l"(b), "r"(scale_d), "n"(TA));
}

namespace rec {
constexpr int KR = 43;
constexpr uint32_t WSZ = (64 - KR) * 2048, STG = KR * 2048;
constexpr uint32_t WS = 0;
constexpr uint32_t RING = 2 * WSZ;
constexpr uint32_t OB = RING + 3 * 8192;
constexpr uint32_t PB = OB + 4096;
constexpr uint32_t WO = RING + 32768;
constexpr uint32_t ATT = WO + 5 * 16384;
constexpr uint32_t AK = ATT + 10240, AV = ATT + 20480;
constexpr uint32_t PAD = ATT + 30720;
constexpr uint32_t BARS = PAD + 128;
constexpr uint32_t B_XE = BARS  , B_FA = BARS + 64  , B_FB = BARS + 88, B_FO = BARS + 96;
constexpr uint32_t B_ME = BARS + 104  , B_WE = BARS + 136, B_PD = BARS + 144;
constexpr uint32_t B_XF = BARS + 152  , B_MF = BARS + 216  , B_CP = BARS + 248  , B_WT = BARS + 280  ;
constexpr uint32_t B_AB = BARS + 296, B_OB = BARS + 304, B_ST = BARS + 312  , B_WS = BARS + 328, B_WO = BARS + 336, B_AT = BARS + 352, B_AV = BARS + 360;
constexpr int NBAR = 46;
constexpr uint32_t M0 = BARS + 384;
constexpr uint32_t SMEM = 232448;
constexpr int NB_P = 1, NB_ST = 2, NB_O = 3, NB_W0 = 4, NB_W1 = 5;
__host__ __device__ constexpr int wo_tile(int rank, int g, int i) { return i < 2 ? i * 6 + (rank == 2 ? g : 4 - 2 * g + rank) : 13 + rank - g; }
constexpr long long D_W = CD(WS, 16, 1024, 1), D_X = CD(0, 16, 1024, 1), D_O = CD(OB, 128, 256, 0);
constexpr long long D_WO = CD(WO, 16, 1024, 1), D_QM = CD(ATT, 640, 0, 0), D_QT = CD(ATT + 128, 640, 64, 0), D_K = CD(AK, 640, 128, 0);
constexpr long long D_V = CD(AV, 128, 640, 0), D_P = CD(PB, 128, 768, 0);
struct Maps { CUtensorMap w[3], wo, xd, xs; };
__host__ __device__ constexpr uint32_t mslot(int c) { return (c ^ (c >> 1)) * 12288; }
__host__ __device__ constexpr uint32_t xslot(int s) { return s < 3 ? RING + s * 8192 : s < 5 ? WO + (s - 3) * 8192 : s < 7 ? WO + (s + 1) * 8192 : OB; }
__host__ __device__ constexpr bool k_smem(int k) { return k % 3 == 2; }
__host__ __device__ constexpr int k_idx(int k) { return k % 3 == 2 ? k / 3 : k - k / 3; }
__host__ __device__ constexpr int k_of_reg(int i) { return i + (i >> 1); }
__host__ __device__ constexpr int k_of_smem(int i) { return 3 * i + 2; }

#define RPROF(i)
#define RPROF_STEP
#define CPROF(i, v)

template<bool DUAL, int K0, int K1> DEVI void seq_mem(float* d, const uint32_t* w, uint32_t dw) {
  if constexpr (K0 < K1) {
    constexpr long long B = CD(RING, 128, DUAL ? 4096 : 8192, 0) + mslot(K0 >> 4) / 16 + (K0 & 15) * 16;
    if constexpr (DUAL) {
      if constexpr (!k_smem(K0)) rs24<K0 != 0, 1, B>(d, w + 4 * k_idx(K0)); else ss24<1, 1, 1, D_W + k_idx(K0) * 128, B>(d, dw);
    } else {
      if constexpr (!k_smem(K0)) rs16<K0 != 0, 1, B>(d, w + 4 * k_idx(K0)); else ss16<1, 1, 1, D_W + k_idx(K0) * 128, B>(d, dw);
    }
    seq_mem<DUAL, K0 + 1, K1>(d, w, dw);
  }
}
template<int N, int K0, int K1> DEVI void seq_tok(float* d, const uint32_t* w, uint32_t dw) {
  if constexpr (K0 < K1) {
    constexpr bool DUAL = N > 32;
    constexpr long long B = D_X + (DUAL ? xslot((K0 >> 2) & 7) / 16 : xslot(K0 >> 3) / 16 + ((K0 >> 2) & 1) * 256) + (K0 & 3) * 2;
    if constexpr (DUAL) {
      if constexpr (!k_smem(K0)) rs56<K0 != 0, 0, B>(d, w + 4 * k_idx(K0)); else ss56<1, 1, 0, D_W + k_idx(K0) * 128, B>(d, dw);
    } else if constexpr (N == 24) {
      if constexpr (!k_smem(K0)) rs24<K0 != 0, 0, B>(d, w + 4 * k_idx(K0)); else ss24<1, 1, 0, D_W + k_idx(K0) * 128, B>(d, dw);
    } else {
      if constexpr (!k_smem(K0)) rs32<K0 != 0, 0, B>(d, w + 4 * k_idx(K0)); else ss32<1, 1, 0, D_W + k_idx(K0) * 128, B>(d, dw);
    }
    seq_tok<N, K0 + 1, K1>(d, w, dw);
  }
}
template<bool DUAL, int T, int K0> DEVI void seq_wo(float* d, uint32_t dw) {
  if constexpr (K0 < 8) {
    if constexpr (DUAL) ss16<K0 != 0, 1, 1, D_WO + T * 1024 + K0 * 128, D_O + K0 * 32>(d, dw);
    else ss8<K0 != 0, 1, 1, D_WO + T * 1024 + K0 * 128, D_O + K0 * 32>(d, dw);
    seq_wo<DUAL, T, K0 + 1>(d, dw);
  }
}
template<long long Q, int K0> DEVI void seq_s(float* d) {
  if constexpr (K0 < 8) { ss40<K0 != 0, 1, 1, Q + K0 * 80, D_K + K0 * 80>(d, 0); seq_s<Q, K0 + 1>(d); }
}
template<bool DUAL, int J> DEVI void load_x(uint32_t sb, const Maps* M, int t, int rb) {
  if (DUAL) e_tma_3d_mc(sb + xslot(J & 7), &M->xd, J * 64, (t - LAG) * 32, 0, sb + B_XF + (J & 7) * 8, rb);
  else e_tma_3d_mc(sb + xslot(J & 7), &M->xs, 0, (t < NSEG ? t : t - LAG) * 32, J * 2, sb + B_XF + (J & 7) * 8, rb);
}
DEVI void load_x_lent(uint32_t sb, const Maps* M, int t, int j) {
  const bool dual = t >= LAG && t < NSEG;
  const uint32_t dst = sb + (j == 3 ? xslot(3) : xslot(5));
#pragma unroll
  for (int i = 0; i < 2; i++)
    e_tma_3d(dst + i * 8192, dual ? &M->xd : &M->xs, dual ? (j + i) * 64 : 0, (t < LAG ? t : t - LAG) * 32, dual ? 0 : (j + i) * 2, sb + B_XF + (j + i) * 8);
}
struct True { static constexpr bool value = true; };
struct False { static constexpr bool value = false; };
struct Ctx { uint32_t sb; const Maps* M; int last; bool issuer; int wi; bool lead; uint32_t par; };
#define XD 1
template<bool DUAL, int J> DEVI void tok_release(const Ctx& c, int t, int& budget) {
  constexpr int NC = DUAL ? 16 : 8, S = J & 7;
  if constexpr (J + 8 < NC) {
    p_arrive_at(c.sb + B_XE + S * 8, c.last, c.lead);
    p_expect_tx(c.sb + B_XF + S * 8, 8192, c.lead && c.wi == 0);
  } else if constexpr (S == 1 || S == 2 || S == 4 || S == 7) p_arrive(c.sb + B_ME + (S >> 1) * 8, c.lead);
  if constexpr (J == 0) {
    if (c.issuer && c.wi == 6) { mbar_wait(c.sb + B_FO, t & 1, budget); load_x<DUAL, 7>(c.sb, c.M, t, c.last); }
  }
  if constexpr (J >= XD && J - XD + 8 < NC) {
    constexpr int I = J - XD;
    if (c.issuer && c.wi == (I & 1) * 4 + 1) { mbar_wait(c.sb + B_XE + I * 8, (t - LAG) & 1, budget); load_x<DUAL, I + 8>(c.sb, c.M, t, c.last); }
  }
}
template<int N, int J, class F, class G> DEVI bool tok_pass(float* d, const uint32_t* w, uint32_t dw, Ctx& c, int t, int& budget, F after0, G setup) {
  constexpr bool DUAL = N > 32;
  constexpr int NC = DUAL ? 16 : 8, KC = 64 / NC;
  if constexpr (J < NC) {
    if constexpr (J > 1) mbar_wait(c.sb + B_XF + (J & 7) * 8, c.par ^ (J >> 3), budget);
    wg_fence();
    seq_tok<N, J * KC, (J + 1) * KC>(d, w, dw);
    wg_commit();
    if constexpr (J == 1) after0();
    if constexpr (J >= NC - 5 && J < NC - 2) setup(J - (NC - 5));
    if constexpr (J > 0) { wg_wait<1>(); tok_release<DUAL, J - 1>(c, t, budget); }
    return tok_pass<N, J + 1>(d, w, dw, c, t, budget, after0, setup);
  } else {
    const bool ok = mbar_test(c.sb + B_MF, t & 1);
    wg_wait<0>();
    tok_release<DUAL, NC - 1>(c, t, budget);
    if (!DUAL) c.par ^= 1;
    return ok;
  }
}
template<int NB> DEVI void pack_tok(uint32_t* e, const float* d) {
#pragma unroll
  for (int i = 0; i < 8; i++) if ((i & 3) < NB) e[i] = pack_bf16(d[4 * (i & 3) + 2 * (i >> 2)], d[4 * (i & 3) + 2 * (i >> 2) + 1]);
}
DEVI void push_tok(const uint32_t* e, uint32_t sb, uint32_t o, int r, int rank) {
  const uint32_t b = mapa(sb, r);
  st_async128(b + o, e[0], e[1], e[2], e[3], b + (rank == 2 ? B_AV : B_AT));
}
DEVI uint32_t h1_tag(int seg) { return ((seg >> 1) & 1) ^ 1; }
template<bool DUAL> DEVI uint4 pack_part(const float* c, int t) {
  if (!DUAL) { const uint32_t x = settag(pack_bf16(c[0], c[1]), h1_tag(t < NSEG ? t : t - LAG)), y = pack_bf16(c[2], c[3]); return make_uint4(x, y, x, y); }
  return make_uint4(settag(pack_bf16(c[0], c[1]), h1_tag(t)), pack_bf16(c[2], c[3]), settag(pack_bf16(c[4], c[5]), h1_tag(t - LAG)), pack_bf16(c[6], c[7]));
}
DEVI void put_part(char* p1, char* p2, uint4 z, int t) { p_stg_rlx64(p1, z.x, z.y, t < NSEG); p_stg_rlx64(p2, z.z, z.w, t >= LAG); }

DEVI void rec_math(const uint32_t sb, const int wi, const Maps& M) {
  const int h = cta_id() / 3, rb = cluster_rank() >= 3 ? 3 : 0, rank = cluster_rank() - rb;
  const int warp = wi & 3, wg = wi >> 2;
  const bool lead = (threadIdx.x & 127) == 0;
  int budget = SPIN_BUDGET;
  uint32_t w[4 * KR];
  const int last = cluster_last();
  Ctx cx{sb, &M, last, rb + rank == last, wi, lead, 0};
  {
    const int lane = lane_id();
    const uint32_t a = sb + wg * STG + ((lane & 7) + (lane >> 4) * 8) * 128 + (((warp * 2 + ((lane >> 3) & 1)) ^ (lane & 7)) << 4);
    for (int i = 0; i < (wg == 1 || rank == 2 ? 12 : 8); i++)
      stg_rlx64((char*)g_h1[i & 3] + ((wo_tile(rank, wg, i >> 2) * 4 + warp) * 4 + (lane >> 3)) * 2048 + h * 64 + (lane & 7) * 8, 0, 0);
    mbar_wait(sb + B_ST + wg * 8, 0, budget);
#pragma unroll
    for (int k = 0; k < KR; k++) ldsm4t(a + k * 2048, w[4*k], w[4*k+1], w[4*k+2], w[4*k+3]);
    nbar_arrive<NB_ST, 384>();
    nbar_sync_r(NB_W0 + wg, 128);
    for (int i = 0; i < 5; i++) p_arrive_at(sb + B_FA + i * 8, i == 4 ? last : 0, lead);
    mbar_wait(sb + B_WS, 0, budget);
  }
  uint4 z = make_uint4(0, 0, 0, 0);
  char *z1 = nullptr, *z2 = nullptr;
  uint32_t rt0 = 0, rt1 = 0;
  mbar_wait(sb + B_XF, 0, budget); mbar_wait(sb + B_XF + 8, 0, budget);
#pragma unroll 1
  for (int t = 0;; t++) {
    const uint32_t dw = wg * (WSZ >> 4);
    uint32_t e[16];
    bool ok;
    auto finish = [&]() { put_part(z1, z2, z, t - 1); p_arrive_at(sb + B_FO, last, lead); };
    const int seg = t - rank * LAG;
    const bool att = rank < 2 && (unsigned)seg < (unsigned)NSEG;
    char* p1;
    uint32_t pw, oo;
    uint64_t u0, u1;
    int lane;
    auto setup = [&](int part) {
      if (part == 0) {
        lane = lane_id();
      } else if (part == 1) {
        char* const p = (char*)g_h1 + ((wo_tile(rank, wg, 0) * 4 + warp) * 4 + (lane >> 3)) * 2048 + h * 64 + (lane & 7) * 8;
        p1 = p + (t & 1) * sizeof(g_h1[0]);
        pin2(p1, nullptr);
      } else if (part == 2) {
        oo = OB + (lane >> 4) * 2048 + warp * 512 + (t < NSEG ? rank * 256 : 0) + (lane & 15) * 16;
        pw = sb + PB + (wg ? lane * 4 : 768 + warp * 768 + lane * 16);
        pin2(pw, oo);
      } else {
        if (wg) {
          const uint32_t ra = mapa(sb, rb + ((warp & 1) ? 2 : (rank ^ 1) & 1)), rc = mapa(sb, rb + ((warp & 1) ? (rank ^ 1) & 1 : 2));
          u0 = pair(ra + oo, ra + B_OB); u1 = pair(rc + oo, rc + B_OB);
        } else {
          u0 = (uint64_t)((char*)(g_ot + rank * O_LAYER) + (size_t)(h * DH + warp * 16 + (lane >> 2)) * (SEQ * 2) + seg * 64 + (lane & 3) * 16);
          u1 = (uint32_t)((lane & 24) + ((lane >> 2) & 1) + 2 * warp - 8 * (lane & 3));
        }
        pin2(u0, u1);
      }
    };
    RPROF_STEP;
    auto mem_pass = [&](auto dual_c) {
      constexpr bool DUAL = decltype(dual_c)::value;
      float m[DUAL ? 12 : 8];
      RPROF(8 + wg * 12 - 32);
      if (!ok) mbar_wait(sb + B_MF, t & 1, budget);
      wg_fence(); seq_mem<DUAL, 0, 8>(m, w, dw); wg_commit();
      const uint32_t ao = ATT + rank * 10240 + wi * 1280, to = ao + 128 + (lane & 3) * 128 + (lane >> 2) * 16;
      const int la = DUAL ? rank == 0 || (rank == 2 && wg) : t >= NSEG;
      RPROF(1 + wg * 12);
      if (DUAL && la) {
#pragma unroll
        for (int i = 0; i < 8; i++) { const uint32_t x = e[i]; e[i] = e[8 + i]; e[8 + i] = x; }
      }
      auto piece = [&](int i) { push_tok(e + 4 * i, sb, to + (i & 1) * 640, rb + (la ^ (i >> 1)), rank); };
      piece(0);
      wg_fence(); seq_mem<DUAL, 8, 16>(m, w, dw); wg_commit();
      piece(1);
      mbar_wait(sb + B_MF + 8, t & 1, budget);
      wg_fence(); seq_mem<DUAL, 16, 24>(m, w, dw); wg_commit();
      if (DUAL) piece(2);
      wg_fence(); seq_mem<DUAL, 24, 32>(m, w, dw); wg_commit();
      if (DUAL) piece(3);
      mbar_wait(sb + B_MF + 16, t & 1, budget);
      wg_fence(); seq_mem<DUAL, 32, 48>(m, w, dw); wg_commit();
      wg_wait<1>(); p_arrive(sb + B_PD, lead);
      const uint32_t r0 = mapa(sb, rb + la), r1 = mapa(sb, rb + (la ^ 1)), m0 = r0 + ao + lane * 4, m1 = r1 + ao + lane * 4, ab = rank == 2 ? B_AV : B_AB;
      const uint64_t q0 = pair(m0, r0 + ab), q1 = pair(m0 + 640, r0 + ab), q2 = pair(m1, r1 + ab), q3 = pair(m1 + 640, r1 + ab);
      pin2(q0, q1);
      if (DUAL) pin2(q2, q3);
      mbar_wait(sb + B_MF + 24, t & 1, budget);
      wg_fence(); seq_mem<DUAL, 48, 64>(m, w, dw); wg_commit();
      wg_wait<1>(); p_arrive_at(sb + B_FA, 0, lead);
      wg_wait<0>();
      const uint32_t a0 = pack_bf16(m[0], m[1]), a1 = pack_bf16(m[2], m[3]), a2 = pack_bf16(m[4], m[5]), a3 = pack_bf16(m[6], m[7]);
      if constexpr (DUAL) {
        st_async32(q0, la ? a2 : a0); st_async32(q1, la ? a3 : a1); st_async32(q2, la ? a0 : a2); st_async32(q3, la ? a1 : a3);
        rt0 = pack_bf16(m[8], m[9]); rt1 = pack_bf16(m[10], m[11]);
      } else { st_async32(q0, a0); st_async32(q1, a1); rt0 = a2; rt1 = a3; }
      p_arrive(sb + B_WE, lead);
    };
    if (t >= LAG && t < NSEG) {
      float d[28];
      ok = tok_pass<56, 0>(d, w, dw, cx, t, budget, finish, setup);
      pack_tok<4>(e + 8, d); pack_tok<3>(e, d + 16); e[3] = rt0; e[7] = rt1;
      mem_pass(True());
    } else {
      float d[16];
      if (t > 0) finish();
      if (t > 0 && t < LAG) {
        ok = tok_pass<24, 0>(d, w, dw, cx, t, budget, []() {}, setup);
        pack_tok<3>(e, d); e[3] = rt0; e[7] = rt1;
      } else {
        ok = tok_pass<32, 0>(d, w, dw, cx, t, budget, []() {}, setup);
        pack_tok<4>(e, d);
      }
      mem_pass(False());
    }
    {
      RPROF(2 + wg * 12);
      auto wo_ready = [&]() { if (t == 0) mbar_wait(sb + B_WO, 0, budget); if (t < NSTEP - 1) mbar_wait(sb + B_WT, t & 1, budget); };
      constexpr float SC = 0.08838834764831845f * 1.4426950408889634f;
      if (!att) wo_ready();
      else {
        float s[32];
        setup(3);
        if (wg) {
          uint32_t one[4];
#pragma unroll
          for (int i = 0; i < 4; i++) one[i] = 0x3F803F80u + (pw >> 31);
          mbar_wait_cluster(sb + B_AT, seg & 1, budget);
          mbar_wait_cluster(sb + B_AB, seg & 1, budget);
          fence_proxy_async();
          RPROF(3 + 12);
          wg_fence(); seq_s<D_QM, 0>(s); wg_commit();
          nbar_arrive<NB_P, 256>();
          if (warp == 1) sts32(pw + 640, 0);
          mbar_wait_cluster(sb + B_AV, seg & 1, budget);
          wg_wait<0>();
          float mx = fmaxf(fmaxf(fmaxf(s[0], s[1]), fmaxf(s[4], s[5])), fmaxf(fmaxf(fmaxf(s[8], s[9]), fmaxf(s[12], s[13])), fmaxf(s[16], s[17])));
          const float x1 = __shfl_xor_sync(0xffffffffu, mx, 1), x2 = __shfl_xor_sync(0xffffffffu, mx, 2), x3 = __shfl_xor_sync(0xffffffffu, mx, 3);
          const float u = (warp & 2) ? ((warp & 1) ? s[16] : s[12]) : ((warp & 1) ? s[8] : s[4]);
          const float v = (warp & 2) ? ((warp & 1) ? s[17] : s[13]) : ((warp & 1) ? s[9] : s[5]);
          const float ms = -SC * fmaxf(fmaxf(mx, x1), fmaxf(x2, x3));
          sts32(pw + 128 + warp * 128, pack_bf16(ex2(fmaf(u, SC, ms)), ex2(fmaf(v, SC, ms))));
          if (warp == 0) sts32(pw, pack_bf16(ex2(fmaf(s[0], SC, ms)), ex2(fmaf(s[1], SC, ms))));
          fence_proxy_async();
          nbar_sync<NB_W1, 128>();
          RPROF(4 + 12);
          wg_fence();
          rs8<0, 0, D_P>(s + 8, one); rs8<1, 0, D_P + 16>(s + 8, one); rs8<1, 0, D_P + 32>(s + 8, one);
          wg_commit();
          ss8<0, 0, 0, D_V, D_P>(s, 0); ss8<0, 0, 0, D_V + 320, D_P>(s + 4, 0);
          ss8<1, 0, 0, D_V + 16, D_P + 16>(s, 0); ss8<1, 0, 0, D_V + 336, D_P + 16>(s + 4, 0);
          ss8<1, 0, 0, D_V + 32, D_P + 32>(s, 0); ss8<1, 0, 0, D_V + 352, D_P + 32>(s + 4, 0);
          wg_commit();
          wg_wait<1>();
          const float i0 = rcp(s[8]), i1 = rcp(s[9]);
          wg_wait<0>();
          stsm4(sb + oo, pack_bf16(s[0] * i0, s[1] * i1), pack_bf16(s[2] * i0, s[3] * i1), pack_bf16(s[4] * i0, s[5] * i1), pack_bf16(s[6] * i0, s[7] * i1));
          __syncwarp();
          const uint4 y = lds128v(sb + oo);
          if (t < NSTEP - 1) { st_async128(u0, y); st_async128(u1, y); e_complete_tx(sb + B_OB, 512); }
          wo_ready();
        } else {
          const int lim = (int)u1;
          char* const og = (char*)u0;
          nbar_sync<NB_P, 256>();
          RPROF(3);
          wg_fence();
          seq_s<D_QT, 0>(s);
          wg_commit();
          mbar_wait_cluster(sb + B_AV, seg & 1, budget);
          wg_wait<0>();
#pragma unroll
          for (int i = 0; i < 8; i++) { float& v = s[4 + 4 * (i >> 1) + (i & 1)]; v = i <= lim ? v : -INFINITY; }
          float mx = fmaxf(fmaxf(fmaxf(s[0], s[1]), fmaxf(s[4], s[5])), fmaxf(fmaxf(fmaxf(s[8], s[9]), fmaxf(s[12], s[13])), fmaxf(s[16], s[17])));
          const float x1 = __shfl_xor_sync(0xffffffffu, mx, 1), x2 = __shfl_xor_sync(0xffffffffu, mx, 2), x3 = __shfl_xor_sync(0xffffffffu, mx, 3);
          const float ms = -SC * fmaxf(fmaxf(mx, x1), fmaxf(x2, x3));
#pragma unroll
          for (int i = 0; i < 10; i++) { float& v = s[4 * (i >> 1) + (i & 1)]; v = ex2(fmaf(v, SC, ms)); }
          const float sum = (((s[0] + s[1]) + (s[4] + s[5])) + ((s[8] + s[9]) + (s[12] + s[13]))) + (s[16] + s[17]);
          const float y1 = __shfl_xor_sync(0xffffffffu, sum, 1), y2 = __shfl_xor_sync(0xffffffffu, sum, 2), y3 = __shfl_xor_sync(0xffffffffu, sum, 3);
          const float inv = rcp((sum + y1) + (y2 + y3));
          stsm4(pw, pack_bf16(s[0] * inv, s[1] * inv), pack_bf16(s[4] * inv, s[5] * inv), pack_bf16(s[8] * inv, s[9] * inv), pack_bf16(s[12] * inv, s[13] * inv));
          stsm2(pw + 512, pack_bf16(s[16] * inv, s[17] * inv), 0);
          fence_proxy_async();
          nbar_sync<NB_W0, 128>();
          RPROF(4);
          wg_fence();
          ss32<0, 0, 0, D_V, D_P + 48>(s, 0); ss32<0, 0, 0, D_V + 320, D_P + 48>(s + 16, 0);
          ss32<1, 0, 0, D_V + 16, D_P + 64>(s, 0); ss32<1, 0, 0, D_V + 336, D_P + 64>(s + 16, 0);
          ss32<1, 0, 0, D_V + 32, D_P + 80>(s, 0); ss32<1, 0, 0, D_V + 352, D_P + 80>(s + 16, 0);
          wg_commit();
          wo_ready();
          wg_wait<0>();
#pragma unroll
          for (int i = 0; i < 4; i++) {
            const float* d = s + (i >> 1) * 16 + (i & 1) * 2;
            stg128(og + ((i >> 1) * 64 + (i & 1) * 8) * (SEQ * 2), pack_bf16(d[0], d[1]), pack_bf16(d[4], d[5]), pack_bf16(d[8], d[9]), pack_bf16(d[12], d[13]));
          }
          if ((seg & 3) == 3) nbar_arrive<NB_O, 160>();
        }
      }
      RPROF(5 + wg * 12);
      const bool three = wg == 1 || rank == 2;
      char* const p2 = p1 + (2 + ((t - LAG) & 1) - (t & 1)) * (int)sizeof(g_h1[0]);
      if (t < NSTEP - 1) {
        auto wo_pass = [&](auto dual_c) {
          constexpr bool DUAL = decltype(dual_c)::value;
          float c[24];
          const uint32_t dt = wg ? 0 : 3072;
          mbar_wait_cluster(sb + B_OB, t & 1, budget);
          fence_proxy_async();
          RPROF(6 + wg * 12);
          wg_fence(); seq_wo<DUAL, 0, 0>(c, dt); wg_commit(); seq_wo<DUAL, 1, 0>(c + 8, dt); wg_commit();
          mbar_wait(sb + B_XF, cx.par, budget);
          wg_wait<1>();
          if (warp == 2) load_x_lent(sb, &M, t + 1, wg ? 3 : 5);
          put_part(p1, p2, pack_part<DUAL>(c, t), t);
          const int o3 = (wo_tile(rank, wg, three ? 2 : 1) - wo_tile(rank, wg, 0)) * 32768;
          z1 = p1 + o3; z2 = p2 + o3;
          if (three) {
            wg_fence(); seq_wo<DUAL, 2, 0>(c + 16, dt); wg_commit();
            wg_wait<1>(); put_part(p1 + 6 * 32768, p2 + 6 * 32768, pack_part<DUAL>(c + 8, t), t);
            mbar_wait(sb + B_XF + 8, cx.par, budget);
            wg_wait<0>(); z = pack_part<DUAL>(c + 16, t);
          } else { mbar_wait(sb + B_XF + 8, cx.par, budget); wg_wait<0>(); z = pack_part<DUAL>(c + 8, t); }
        };
        if (t >= LAG && t < NSEG) wo_pass(True()); else wo_pass(False());
      } else break;
      RPROF(7 + wg * 12);
    }
  }
}

DEVI void wait_xa(const int* p, int& budget) {
  while (__any_sync(0xffffffffu, ldg_acq32(p) < 64) && --budget > 0) {}
  fence_proxy_global();
}
template<bool DUAL> DEVI void first_loads(uint32_t sb, const Maps* M, int n, int h, int rb, int& budget) {
  if (n >= LAG && ((n - LAG) & 3) == 0) e_prefetch_3d(&M->xs, 0, (n - LAG) * 32, h & 14);
  mbar_wait(sb + B_FA, n & 1, budget);
  load_x<DUAL, 0>(sb, M, n, rb); load_x<DUAL, 1>(sb, M, n, rb); load_x<DUAL, 2>(sb, M, n, rb);
}
template<bool DUAL> DEVI void lent_loads(uint32_t sb, const Maps* M, int n, int rb, int& budget) {
  mbar_wait(sb + B_FB, n & 1, budget);
  load_x<DUAL, 3>(sb, M, n, rb); load_x<DUAL, 4>(sb, M, n, rb); load_x<DUAL, 5>(sb, M, n, rb); load_x<DUAL, 6>(sb, M, n, rb);
}
DEVI void rec_comm(const uint32_t sb, const int warp, const Maps& M, const bf16* __restrict__ mem0) {
  const int lane = threadIdx.x & 31, h = cta_id() / 3, rb = cluster_rank() >= 3 ? 3 : 0, rank = cluster_rank() - rb;
  int budget = SPIN_BUDGET;
  const bool two = warp == 3 || (rank == 2 && warp == 2);
  const int ntask = two ? 2 : 1, qi = two ? (warp == 3 ? rank : 3) : rank * 3 + warp;
  const int task0 = two ? h * 2 + (qi >> 1) : 64 + h * 4 + (qi >> 1);
  auto h2_word = [&](int i, int ln) {
    const int task = task0 + i * 192;
    return (char*)g_h2 + (task >> 6) * 8192 + ((qi ^ i) & 1) * 4096 + ((task >> 2) & 15) * 256 + (task & 3) * 32 + (ln & 8) * 16 + (ln & 7) * 4;
  };
  auto first_x = [&](int t) {
    const int n = t + 1;
    p_expect_tx(sb + B_XF + (lane_id() & 7) * 8, 8192, lane_id() < 8);
    if (rb + rank == 0) {
      if (n >= LAG && ((n - LAG) & 3) == 0) wait_xa(&g_xa[1][(n - LAG) >> 2], budget);
      if (n >= LAG && n < NSEG) first_loads<true>(sb, &M, n, h, cluster_last(), budget); else first_loads<false>(sb, &M, n, h, cluster_last(), budget);
    }
  };
  {
    const int task = task0 + (lane >> 4) * 192, L = (task & 3) * 8 + (lane & 7);
    if ((lane >> 4) < ntask) {
      const bf16* p = mem0 + (L & 3) * 2 * DM + (task >> 2) * 16 + (L >> 2) + (lane & 8);
      uint32_t m0 = (uint32_t)__bfloat16_as_ushort(p[0]) | (uint32_t)__bfloat16_as_ushort(p[DM]) << 16;
      m0 = m0 ? m0 : 0x8000u;
      stg_rlx32(h2_word(lane >> 4, lane), ((qi ^ (lane >> 4)) & 1) ? 0 : m0);
      for (int i = 1; i < 4; i++) stg_rlx32(h2_word(lane >> 4, lane) + i * sizeof(g_h2[0]), 0);
      sts32(sb + M0 + warp * 128 + lane * 4, m0);
    }
    __syncwarp();
    nbar_sync<NB_ST, 384>();
    if (warp == 2) {
      e_expect_tx(sb + B_WS, 2 * WSZ);
#pragma unroll 1
      for (int i = 0; i < 2 * (64 - KR); i++) e_tma_2d(sb + WS + (i & 1) * WSZ + (i >> 1) * 2048, &M.w[rank], h * DH + (i & 1) * 64, k_of_smem(i >> 1) * 16, sb + B_WS);
      const int nt = rank == 2 ? 6 : 5;
      e_expect_tx(sb + B_WO, (nt - 2) * 16384);
#pragma unroll 1
      for (int i = 1; i < nt; i++) if (i != 3) e_tma_2d(sb + WO + i * 16384, &M.wo, wo_tile(rank, 1 - i / 3, i % 3) * 64, h * DH, sb + B_WO);
    }
    wait_xa(&g_xa[0][0], budget);
    if (warp == 3) { first_x(-1); if (rb + rank == 0) lent_loads<false>(sb, &M, 0, cluster_last(), budget); }
  }
  uint32_t cpp = 0;
  const uint32_t cp = sb + B_CP + warp * 8;
  uint32_t f_dst, f_chk, f_bar, f_time = gtime() - 4000;
  const char *f_src, *f_xr;
  auto prepare = [&](int s) {
    const int ck = warp ^ (warp < 2 && (s < LAG || s >= NSEG) && (rank & 1) == (s >= NSEG)), ln = lane_id();
    f_dst = sb + RING + mslot(ck); f_chk = f_dst + ln * 32 + (ln >> 2) * 4; f_bar = sb + ck * 8;
    f_src = (const char*)g_h2[s & 3] + ck * 8192 + (s >= NSEG ? 4096 : 0);
    f_xr = (const char*)g_xr[(s + 1) & 63] + ck * 4096;
    pin2(f_chk, 0u);
    return s <= LAG ? TP(9) + ck * TP(11) : s <= NSEG ? TP(1) + ck * TP(4) : TP(13) + ck * TP(11);
  };
  prepare(0);
#pragma unroll 1
  for (int t = 0;; t++) {
    const int n = t + 1;
    const bool dual = t >= LAG && t < NSEG;
    RPROF_STEP;
    {
      const uint32_t bytes = dual ? 8192 : 4096;
      e_expect_tx(cp, bytes + (n < NSEG ? 4096 : 0));
      mbar_wait(f_bar + B_ME, t & 1, budget);
      if (n < NSEG) e_bulk_g2s(f_dst + 8192, f_xr, 4096, cp);
      wait_time(f_time);
      RPROF(24); CPROF(0, gtime());
      int tries = 0;
      while (true) {
        tries++;
        e_bulk_g2s(f_dst, f_src, bytes, cp);
        mbar_wait(cp, cpp, budget); cpp ^= 1;
        uint32_t mn = min(min(lds32v(f_chk), lds32v(f_chk + 1024)), min(lds32v(f_chk + 2048), lds32v(f_chk + 3072)));
        if (dual) mn = min(min(mn, min(lds32v(f_chk + 4096), lds32v(f_chk + 5120))), min(lds32v(f_chk + 6144), lds32v(f_chk + 7168)));
        if (!__any_sync(0xffffffffu, mn == 0) || --budget < 0) break;
        e_expect_tx(cp, bytes);
      }
      e_arrive(f_bar + B_MF);
      RPROF(25); CPROF(1, gtime()); CPROF(2, tries);
    }
    const int seg = t - rank * LAG;
    const bool att = rank < 2 && (unsigned)seg < (unsigned)NSEG;
    auto block_done = [&]() {
      if (warp == 1 && att && (seg & 3) == 3) { nbar_sync<NB_O, 160>(); e_flag_add(&g_dep[E_O1 + rank * 16 + (seg >> 2)]); }
    };
    if (warp == 0) {
      if (att) { e_expect_tx(sb + B_AT, 16384); e_expect_tx(sb + B_AB, 4096); e_expect_tx(sb + B_AV, 10240); }
      if (n < NSTEP) e_expect_tx(sb + B_OB, dual ? 4096 : 2048);
    }
    if (n + 1 < NSEG && (n & 3) == 3) wait_xa(&g_xa[0][(n + 1) >> 2], budget);
    if (rank == 2 && warp == 1) {
      if (h < 16 ? n < NSEG : n > LAG && n < NSTEP && ((n - LAG) & 3)) e_prefetch_3d(&M.xs, 0, (h < 16 ? n : n - LAG) * 32, (h & 7) * 2);
      if (h >= 16 && n + 1 < NSEG) asm volatile(ELECT "cp.async.bulk.prefetch.L2.global [%0], 2048;}" :: "l"((const char*)g_xr[n + 1] + (h & 7) * 2048) : "memory");
    }
    {
      const int ln = lane_id(), i = ln >> 4;
      char* const w = h2_word(i, ln);
      if (i < ntask) {
        stg_rlx32(w + ((t + 3) & 3) * sizeof(g_h2[0]), 0);
        if (n == LAG && ((qi ^ i) & 1)) stg_rlx32(w + (n & 3) * sizeof(g_h2[0]), lds32v(sb + M0 + warp * 128 + ln * 4));
      }
      __syncwarp();
    }
    if (n < NSTEP) {
      const uint32_t tag = (n >> 1) & 31;
      mbar_wait(sb + B_PD, t & 1, budget);
      uint32_t t0 = clock32();
      if (warp == 2) {
        e_expect_tx(sb + B_WT, 32768);
        e_tma_2d(sb + WO + 49152, &M.wo, wo_tile(rank, 0, 0) * 64, h * DH, sb + B_WT);
        mbar_wait(sb + B_WE, t & 1, budget);
        e_tma_2d(sb + WO, &M.wo, wo_tile(rank, 1, 0) * 64, h * DH, sb + B_WT);
      }
      if (warp == 3) first_x(t);
      if (warp == 0 && rank == (t >= NSEG)) { mbar_wait(sb + B_AB, seg & 1, budget); e_stg_rlx32(&g_ts[t & 1][h], (gtime() & ~31u) | tag); }
      const int fd = prepare(n), ln = lane_id();
      const int sa = t - (qi & 1) * LAG, sc = t - (~qi & 1) * LAG;
      const int i0 = (unsigned)sa < (unsigned)(NSEG - 1) ? 0 : 1, i1 = two && (unsigned)sc < (unsigned)(NSEG - 1) ? 2 : 1;
      const char* src = (const char*)g_h1[(qi & 1) * 2 + (sa & 1)] + task0 * 2048 + ln * 8;
      char* dst = h2_word(0, ln) + (n & 3) * sizeof(g_h2[0]);
      const int ds = ((~qi & 1) * 2 + (sc & 1) - (qi & 1) * 2 - (sa & 1)) * (int)sizeof(g_h1[0]) + 192 * 2048, dd = 3 * 8192 + ((qi & 1) ? -4096 : 4096);
      if (i0) { src += ds; dst += dd; }
      pin2(src, dst);
      spin_until(t0, TSD);
      uint32_t v0;
      do { v0 = ldg_rlx32(&g_ts[t & 1][ln]); } while (__any_sync(0xffffffffu, (v0 & 31) != tag) && --budget > 0);
      const uint32_t now = __shfl_sync(0xffffffffu, v0, 0);
      t0 = now + __reduce_max_sync(0xffffffffu, (int)(v0 - now));
      f_time = t0 + fd;
      RPROF(26); CPROF(3, t0);
      block_done();
      t0 += t < LAG ? TP(8) : t < NSEG ? TP(0) : TP(12);
#pragma unroll 1
      for (int i = i0; i < i1; i++) {
        const uint32_t tg = h1_tag(i ? sc : sa);
        uint2 v[8];
        wait_time(t0 + (!two ? 0 : i ? TP(3) : -TP(10)));
        int tries = 0;
        float a[4];
        while (true) {
          tries++;
#pragma unroll
          for (int k = 0; k < 8; k++) v[k] = ldg_rlx64(src + k * 256);
          asm volatile("{.reg .pred p; setp.eq.s32 p, %0, 0x7fffffff; @p exit;}" :: "r"(budget) : "memory");
          uint32_t bad = 0;
#pragma unroll
          for (int k = 0; k < 8; k++) {
            bad = xor_or(v[k].x, tg, bad);
            a[0] = k ? a[0] + bf_lo(v[k].x) : bf_lo(v[k].x); a[1] = k ? a[1] + bf_hi(v[k].x) : bf_hi(v[k].x);
            a[2] = k ? a[2] + bf_lo(v[k].y) : bf_lo(v[k].y); a[3] = k ? a[3] + bf_hi(v[k].y) : bf_hi(v[k].y);
          }
#pragma unroll
          for (int k = 0; k < 2; k++) {
            const float keep = (ln & 8) ? a[2+k] : a[k], send = (ln & 8) ? a[k] : a[2+k];
            a[k] = keep + __shfl_xor_sync(0xffffffffu, send, 8);
          }
#pragma unroll
          for (int k = 0; k < 2; k++) a[k] += __shfl_xor_sync(0xffffffffu, a[k], 16);
          if (!__any_sync(0xffffffffu, bad & 1) || --budget < 0) break;
        }
        const uint32_t out = pack_bf16(a[0], a[1]);
        if (ln < 16) stg_rlx32(dst, out ? out : 0x8000u);
        __syncwarp();
        src += ds; dst += dd;
        if (i == 0) { RPROF(28); CPROF(6, gtime()); CPROF(4, gtime()); CPROF(5, tries); } else CPROF(7, gtime());
      }
    }
    if (n == NSTEP) { cluster_arrive(); block_done(); }
    if (n == NSTEP) break;
  }
  if (h == 0 && rank == 0 && warp < 2) g_xa[warp][lane_id()] = 0;
}
}

__global__ void __launch_bounds__(384, 1)
rec_kernel(const __grid_constant__ rec::Maps M, const bf16* __restrict__ mem0) {
  using namespace rec;
  extern __shared__ __align__(1024) uint8_t smem[];
  const uint32_t sb = __shfl_sync(0xffffffffu, smem_u32(smem), 0);
  const int tid = threadIdx.x, wi = __shfl_sync(0xffffffffu, tid >> 5, 0);
  if ((sb & 0x3FFFF) != SMEM_BASE) __trap();
  if (wi == 0) {
    const int h = cta_id() / 3, rank = cta_id() - h * 3;
    const int nwg = 2 * cluster_last() + 2;
    for (int i = tid; i < NBAR; i += 32) mbar_init(sb + BARS + i * 8, i < 13 ? nwg : i < 19 ? 2 : 1);
    ((uint32_t*)(smem + PAD))[tid] = 0;
    fence_mbar_init(); fence_proxy_async();
    __syncwarp();
    e_expect_tx(sb + B_ST, STG); e_expect_tx(sb + B_ST + 8, STG);
    for (int i = 0; i < 2 * KR; i++) e_tma_2d(sb + (i & 1) * STG + (i >> 1) * 2048, &M.w[rank], h * DH + (i & 1) * 64, k_of_reg(i >> 1) * 16, sb + B_ST + (i & 1) * 8);
  } else if (wi == 1) {
    if (blockIdx.x < NEV / 32) { g_dep[blockIdx.x * 32 + (tid & 31)] = 0; g_claim[blockIdx.x * 32 + (tid & 31)] = 0; __threadfence(); }
    __syncwarp();
    asm volatile("griddepcontrol.launch_dependents;" ::: "memory");
  } else if (wi == 2) {
    if ((tid & 31) < 3) asm volatile("prefetch.tensormap [%0];" :: "l"(&M.wo + (tid & 31)) : "memory");
    __syncwarp();
  }
  cluster_arrive(); cluster_wait();
  if (wi < 8) { reg_inc<232>(); rec_math(sb, wi, M); cluster_arrive(); cluster_wait(); }
  else { reg_dec<40>(); rec_comm(sb, wi & 3, M, mem0); cluster_wait(); }
}

namespace gm {
struct Maps { CUtensorMap ot, wo, xn, wg, wu, hl, hs, wd, out; };
constexpr int STAGES = 6, STAGE = 32768;
constexpr uint32_t SO = STAGES * STAGE, BARS = SO + 32768;
constexpr uint32_t B_FULL = BARS, B_EMPTY = BARS + 48, B_TF = BARS + 96, B_TE = BARS + 112, B_ORD = BARS + 128, B_PM = BARS + 144, B_GO = BARS + 160;
constexpr uint32_t MAIL = BARS + 176, PMAIL = BARS + 192;
constexpr uint32_t SMEM = BARS + 256;
constexpr int END = -1;
#define DQ 8
#define GT gtime

struct Tile {
  bool isO, isG, l2; int blk, col, k0, n;
  DEVI Tile(int task, int rank) {
    const int e = task >> 8, id = task & 255;
    const bool isD = e < E_G1 || e >= E_D2;
    isO = e >= E_O1 && e < E_G2; isG = !isD && !isO; l2 = e >= E_O2;
    blk = l2 && !isO ? (e & 7) * 2 + rank : isD ? e >> 1 : e & 15;
    col = l2 && !isO ? id : (isG ? id : id & 3) * 2 + rank;
    k0 = isO ? (id >> 2) * 2048 : isG ? 0 : ((l2 ? e >> 3 : e) & 1) * 1792;
    n = isO ? 32 : isG ? 16 : 28;
    if (e >= E_D2 + DQ) { n = 14; k0 += (id >> 3) * 896; col = id & 7; }
  }
};

DEVI float geglu(float g, float u) {
  const float z = g * (0.7978845608028654f + 0.035677408136300125f * g * g);
  float t; asm("tanh.approx.f32 %0, %1;" : "=f"(t) : "f"(z));
  const float hg = 0.5f * g;
  return fmaf(hg, t, hg) * u;
}
struct Sched {
  int need, size, e;
  bool filler;
  uint4 dep, cl;
  DEVI void init(int lane) {
    e = (lane < 4 ? lane + 12 : lane < 16 ? lane - 4 : lane) * 4;
    const bool d = e < E_G1 || e >= E_D2, o = e >= E_O1 && e < E_G2;
    need = e >= E_D2 ? 56 : d ? 28 : e < E_O1 ? 64 : o ? 32 : 128;
    size = e >= E_D2 ? (e < E_D2 + DQ ? 8 : e < E_D2 + 16 ? 16 : 0) : d ? 4 : o ? 8 : e < E_O1 ? 28 : e < E_G2 + 8 ? 56 : 0;
    filler = (int)blockIdx.x >= TP(5);
  }
  DEVI void scan(int lane) { cl = ldg_rlx128(g_claim + e); dep = ldg_rlx128(g_dep + e); }
  DEVI int next(int lane, int& budget) {
    while (--budget > 0) {
      int av[4], open = 0;
#pragma unroll
      for (int i = 0; i < 4; i++) { const int r = max(size - (int)(&cl.x)[i], 0); open |= r; av[i] = ((int)(&dep.x)[i] >= need ? r : 0) + (i ? av[i - 1] : 0); }
      const uint32_t mo = __ballot_sync(0xffffffffu, open);
      if (!mo) break;
      if (filler) {
        const int x = TP(6) & 3, dx = x == 0 ? dep.x : x == 1 ? dep.y : x == 2 ? dep.z : dep.w;
        filler = !__any_sync(0xffffffffu, e == ((E_O1 + TP(6)) & ~3) && dx >= need);
      }
      if (!filler && (mo & 0xffff) && lane >= E_O2 / 4) av[3] = 0;
      int inc = av[3], pos = 0;
      while (true) {
        const uint32_t m = __ballot_sync(0xffffffffu, inc > pos && av[3]);
        if (!m) break;
        const int l = __ffs(m) - 1, rel = pos - (inc - av[3]), i = (rel >= av[0]) + (rel >= av[1]) + (rel >= av[2]);
        int r = 0;
        if (lane == l) {
          const int tk = atomicAdd(g_claim + e + i, 1);
          r = tk < size ? (e + i) << 8 | tk : -1 - (inc - av[3] + (i == 0 ? av[0] : i == 1 ? av[1] : i == 2 ? av[2] : av[3]) + tk - size);
        }
        r = __shfl_sync(0xffffffffu, r, l);
        if (r >= 0) return r;
        if (pos == 0) {
#pragma unroll
          for (int o = 1; o < 32; o <<= 1) { const int v = __shfl_up_sync(0xffffffffu, inc, o); if (lane >= o) inc += v; }
        }
        pos = -1 - r;
      }
      if (pos == 0) __nanosleep(TP(7));
      scan(lane);
    }
    return END;
  }
};

DEVI void scheduler(const uint32_t sb) {
  const int lane = threadIdx.x & 31;
  int budget = SPIN_BUDGET;
  Sched sc; sc.init(lane);
#pragma unroll 1
  for (int i = 0;; i++) {
    if (i) mbar_wait(sb + B_GO, (i & 1) ^ 1, budget);
    sc.scan(lane);
    if (i == 0) cluster_wait();
    const int task = sc.next(lane, budget);
    const uint32_t r = mapa(sb, lane & 1);
    if (lane < 2) st_async32(r + PMAIL + (i & 1) * 4, task, r + B_PM + (i & 1) * 8);
    __syncwarp();
    if (task == END) break;
  }
}

DEVI void producer(const uint32_t sb, const Maps& M) {
  const int lane = threadIdx.x & 31, rank = cluster_rank();
  int budget = SPIN_BUDGET, s = 0, ph = 0;
#pragma unroll 1
  for (int i = 0;; i++) {
    e_expect_tx(sb + B_PM + (i & 1) * 8, 4);
    mbar_wait_cluster(sb + B_PM + (i & 1) * 8, (i >> 1) & 1, budget);
    const int task = budget < 0 ? END : __shfl_sync(0xffffffffu, (int)lds32v(sb + PMAIL + (i & 1) * 4), 0);
    fence_proxy_global();
    for (int z = 0; z < (task == END ? 2 : 1); z++) {
      const int g = (i + z) & 1;
      mbar_wait(sb + B_TE + g * 8, (((i + z) >> 1) & 1) ^ 1, budget);
      if (lane == 0) { sts64(sb + MAIL + g * 8, task, s | ph << 8); mbar_arrive(sb + B_TF + g * 8); }
      __syncwarp();
    }
    if (task == END) break;
    const Tile T(task, rank);
    const bool shareB = T.l2 && !T.isO;
    const CUtensorMap* mA = T.isO ? &M.ot : T.isG ? &M.xn : &M.hl;
    const CUtensorMap* mB0 = T.isO ? &M.wo : T.isG ? &M.wg : &M.wd;
    const CUtensorMap* mB1 = T.isG ? &M.wu : mB0;
    const int c0 = T.col * (T.isG ? 64 : 128), c1 = T.isG ? c0 : c0 + 64, row = T.blk * 128;
    const int ok = 0;
    int k = T.k0;
#pragma unroll 1
    for (int it = 0; it < T.n; it++, k += 64) {
      const uint32_t a = sb + s * STAGE, fb = sb + B_FULL + s * 8;
      mbar_wait(sb + B_EMPTY + s * 8, ph ^ 1, budget);
      e_expect_tx(fb, STAGE);
      if (shareB) {
        e_tma_2d_mc(a + 16384 + rank * 8192, rank ? mB1 : mB0, rank ? c1 : c0, k, fb);
        e_tma_2d(a, mA, k, row, fb); e_tma_2d(a + 8192, mA, k, row + 64, fb);
      } else {
        e_tma_2d_mc(a + rank * 8192, mA, T.isO ? row + rank * 64 : k, T.isO ? k + ok : row + rank * 64, fb);
        e_tma_2d(a + 16384, mB0, c0, k, fb); e_tma_2d(a + 24576, mB1, c1, k, fb);
      }
      if (it == T.n - TP(2)) e_arrive(sb + B_GO);
      if (++s == STAGES) { s = 0; ph ^= 1; }
    }
  }
}

template<int TA> DEVI void mainloop(float* d0, float* d1, uint32_t sb, int n, int s, int ph, bool lead, uint32_t ord, int& budget) {
  int prev = 0;
  const uint32_t rel = threadIdx.x & 127;
#pragma unroll 1
  for (int i = 0; i < n; i++) {
    mbar_wait(sb + B_FULL + s * 8, ph, budget);
    const uint32_t a = sb + s * STAGE;
    const uint64_t da = mkdesc(a, 16, 1024), db = mkdesc(a + 16384, 8192, 1024);
    wg_fence();
#pragma unroll
    for (int k = 0; k < 4; k++) {
      wgmma_n128<TA>(d0, da + k * (TA ? 128 : 2), db + k * 128, (i | k) != 0);
      wgmma_n128<TA>(d1, da + 512 + k * (TA ? 128 : 2), db + k * 128, (i | k) != 0);
    }
    wg_commit();
    if (i > 0) { wg_wait<1>(); p_arrive_at(sb + B_EMPTY + prev * 8, rel & 1, rel < 2); }
    prev = s;
    if (++s == STAGES) { s = 0; ph ^= 1; }
  }
  p_arrive(ord, lead);
  wg_wait<0>();
  p_arrive_at(sb + B_EMPTY + prev * 8, rel & 1, rel < 2);
}

DEVI void consumer(const uint32_t sb, const Maps& M, const int wg) {
  const int tid = threadIdx.x, lane = tid & 31, warp = (tid >> 5) & 3;
  const bool lead = (tid & 127) == 0;
  const uint32_t so = sb + SO + wg * 16384;
  int budget = SPIN_BUDGET;
  float d0[64], d1[64];
#pragma unroll 1
  for (int m = 0;; m++) {
    mbar_wait(sb + B_TF + wg * 8, m & 1, budget);
    const uint2 mail = lds64v(sb + MAIL + wg * 8);
    const int task = __shfl_sync(0xffffffffu, (int)mail.x, 0), pos = __shfl_sync(0xffffffffu, (int)mail.y, 0);
    e_arrive(sb + B_TE + wg * 8);
    if (task == END || budget < 0) break;
    const Tile T(task, cluster_rank());
    mbar_wait(sb + B_ORD + wg * 8, (m & 1) ^ wg ^ 1, budget);
    if (T.isO) mainloop<1>(d0, d1, sb, T.n, pos & 255, pos >> 8, lead, sb + B_ORD + (wg ^ 1) * 8, budget);
    else mainloop<0>(d0, d1, sb, T.n, pos & 255, pos >> 8, lead, sb + B_ORD + (wg ^ 1) * 8, budget);
    const uint32_t st = so + (warp * 16 + (lane & 15)) * 128;
    if (T.isG) {
      int* const fl = &g_dep[T.l2 ? E_D2 + (T.col >= 28) * 8 + (T.blk >> 1) : E_D1 + T.blk * 2 + (T.col >= 28)];
#pragma unroll
      for (int mm = 0; mm < 2; mm++) {
        const float* d = mm ? d1 : d0;
#pragma unroll
        for (int c = 0; c < 4; c++) {
          uint32_t r[4];
#pragma unroll
          for (int i = 0; i < 4; i++) r[i] = pack_bf16(geglu(d[8*c+2*i], d[32+8*c+2*i]), geglu(d[8*c+2*i+1], d[33+8*c+2*i]));
          stsm4(st + mm * 8192 + (((2 * c + (lane >> 4)) ^ (lane & 7)) << 4), r[0], r[1], r[2], r[3]);
        }
      }
      fence_proxy_async();
      nbar_sync_r(1 + wg, 128);
      if (lead) {
        tma_store_2d(&M.hs, so, T.col * 64, T.blk * 128);
        bulk_commit();
        bulk_wait<0>();
        flag_add(fl);
      }
    } else {
#pragma unroll
      for (int hf = 0; hf < 2; hf++) {
        if (hf) { if (lead) bulk_wait_read<0>(); nbar_sync_r(1 + wg, 128); }
#pragma unroll
        for (int mm = 0; mm < 2; mm++) {
          const float* d = (mm ? d1 : d0) + hf * 32;
#pragma unroll
          for (int c = 0; c < 4; c++)
            stsm4(st + mm * 8192 + (((2 * c + (lane >> 4)) ^ (lane & 7)) << 4), pack_bf16(d[8*c], d[8*c+1]), pack_bf16(d[8*c+2], d[8*c+3]),
                  pack_bf16(d[8*c+4], d[8*c+5]), pack_bf16(d[8*c+6], d[8*c+7]));
        }
        fence_proxy_async();
        nbar_sync_r(1 + wg, 128);
        if (lead) { tma_radd_2d(&M.out, so, T.col * 128 + hf * 64, T.blk * 128); bulk_commit(); }
      }
      if (lead) {
        bulk_wait<0>();
        if (T.isO || !T.l2) flag_add(&g_dep[(!T.isO ? E_LX2 : T.l2 ? E_LX1B : E_LX1A) + T.blk]);
      }
    }
    __syncwarp();
  }
}

DEVI void norm_helper(const bf16* __restrict__ x, bf16* out) {
  const int lane = threadIdx.x & 31;
  int budget = SPIN_BUDGET, tk = lane < 4 ? -1 : 1024;
#pragma unroll 1
  while (--budget > 0) {
    if (tk < 0) tk = atomicAdd(g_claim + E_LI + lane, 1);
    if (__all_sync(0xffffffffu, tk >= 1024)) break;
    const uint32_t m = __ballot_sync(0xffffffffu, tk < 1024 && (lane == 0 || ldg_acq32(g_dep + E_LI + lane * 16 + (tk >> 6)) >= 16));
    if (!m) { __nanosleep(TP(7)); continue; }
    const int ql = __ffs(m) - 1, task = __shfl_sync(0xffffffffu, tk, ql), q = E_LI + ql * 16, ev = task >> 6;
    if (lane == ql) tk = -1;
    const size_t off = (size_t)task * (DM * 4) + lane * 16;
    const char* src = (const char*)(q == E_LI ? x : out) + off;
    uint4 u[8];
#pragma unroll
    for (int i = 0; i < 8; i++) u[i] = ldg_rlx128(src + i * 512);
    if (q == E_LI) {
#pragma unroll
      for (int i = 0; i < 8; i++) stg128((char*)out + off + i * 512, u[i].x, u[i].y, u[i].z, u[i].w);
    }
    int* const fl = q == E_LI ? &g_xa[0][ev] : q == E_LX2 ? &g_xa[1][ev] : &g_dep[q == E_LX1A ? E_G1 + ev : E_G2 + (ev >> 1)];
    float mean[2], rs[2];
#pragma unroll
    for (int r = 0; r < 2; r++) {
      float s0 = 0, s1 = 0;
#pragma unroll
      for (int i = 0; i < 16; i++) { const uint32_t v = (&u[4*r + (i >> 2)].x)[i & 3]; s0 += bf_lo(v); s1 += bf_hi(v); }
      mean[r] = (s0 + s1) * (1.f / 32);
      s0 = s1 = 0;
#pragma unroll
      for (int i = 0; i < 16; i++) { const uint32_t v = (&u[4*r + (i >> 2)].x)[i & 3]; const float a = bf_lo(v) - mean[r], b = bf_hi(v) - mean[r]; s0 = fmaf(a, a, s0); s1 = fmaf(b, b, s1); }
      rs[r] = s0 + s1;
    }
    {
      const bool hi = lane & 16;
      float m1 = hi ? mean[1] : mean[0], q1 = hi ? rs[1] : rs[0], m2 = hi ? mean[0] : mean[1], q2 = hi ? rs[0] : rs[1], cnt = 16;
#pragma unroll
      for (int o = 16; o; o >>= 1) {
        m2 = __shfl_xor_sync(0xffffffffu, m2, o); q2 = __shfl_xor_sync(0xffffffffu, q2, o);
        const float dl = m1 - m2;
        q2 = q1 = fmaf(dl * dl, cnt, q1 + q2); m2 = m1 = 0.5f * (m1 + m2);
        cnt *= 2;
      }
      q1 = rsqrtf(q1 * (1.f / DM) + 1e-5f);
      m2 = __shfl_xor_sync(0xffffffffu, m1, 16); q2 = __shfl_xor_sync(0xffffffffu, q1, 16);
      mean[0] = hi ? m2 : m1; mean[1] = hi ? m1 : m2; rs[0] = hi ? q2 : q1; rs[1] = hi ? q1 : q2;
    }
#pragma unroll
    for (int i = 0; i < 8; i++) {
      uint32_t y[4];
#pragma unroll
      for (int c = 0; c < 4; c++) { const uint32_t v = (&u[i].x)[c]; y[c] = pack_bf16((bf_lo(v) - mean[i >> 2]) * rs[i >> 2], (bf_hi(v) - mean[i >> 2]) * rs[i >> 2]); }
      stg128((char*)g_xn + off + i * 512, y[0], y[1], y[2], y[3]);
      u[i] = make_uint4(y[0], y[1], y[2], y[3]);
    }
    if (q == E_LI && (task & 15) >= 12) {
      uint32_t* const xr = g_xr[task >> 4] + lane * 32 + (task & 3);
#pragma unroll
      for (int i = 0; i < 16; i++) {
        const uint32_t a = (&u[i >> 2].x)[i & 3], b = (&u[4 + (i >> 2)].x)[i & 3];
        xr[(i >> 2) * 1024 + (i & 3) * 8] = __byte_perm(a, b, 0x5410); xr[(i >> 2) * 1024 + (i & 3) * 8 + 4] = __byte_perm(a, b, 0x7632);
      }
    }
    fence_proxy_global();
    __syncwarp();
    if (lane == 0) flag_add(fl);
    __syncwarp();
  }
}
}

__global__ void __cluster_dims__(2, 1, 1) __launch_bounds__(384, 1)
gemm_kernel(const __grid_constant__ gm::Maps M, const bf16* __restrict__ x, bf16* out) {
  using namespace gm;
  extern __shared__ __align__(1024) uint8_t smem[];
  const uint32_t sb = __shfl_sync(0xffffffffu, smem_u32(smem), 0);
  const int tid = threadIdx.x, wi = __shfl_sync(0xffffffffu, tid >> 5, 0);
  if (tid < 21) mbar_init(sb + BARS + tid * 8, tid == 14 || tid == 15 ? 4 : tid >= 6 && tid < 12 ? 2 : 1);
  fence_mbar_init();
  if (tid >= 256 && tid < 265) asm volatile("prefetch.tensormap [%0];" :: "l"(&M.ot + (tid - 256)) : "memory");
  __syncwarp();
  cluster_arrive();
  const bool sched = wi == 11 && cluster_rank() == 0;
  if (!sched) cluster_wait();
  if (wi < 8) { reg_inc<208>(); consumer(sb, M, wi >> 2); cluster_arrive(); cluster_wait(); }
  else {
    reg_dec<88>();
    if (wi == 8) producer(sb, M);
    else if (sched) scheduler(sb);
    else {
      norm_helper(x, out);
      asm volatile("griddepcontrol.wait;" ::: "memory");
    }
    __syncwarp();
    cluster_arrive(); cluster_wait();
  }
}

typedef CUresult (*PFN_encodeTiled)(CUtensorMap*, CUtensorMapDataType, cuuint32_t, void*, const cuuint64_t*, const cuuint64_t*,
                                    const cuuint32_t*, const cuuint32_t*, CUtensorMapInterleave, CUtensorMapSwizzle,
                                    CUtensorMapL2promotion, CUtensorMapFloatOOBfill);
static PFN_encodeTiled g_encode = nullptr;
static CUtensorMap make_map(const void* ptr, uint64_t rows, uint64_t cols, uint32_t box_rows, CUtensorMapL2promotion pr = CU_TENSOR_MAP_L2_PROMOTION_L2_256B) {
  CUtensorMap m;
  cuuint64_t dims[2] = {cols, rows}, strides[1] = {cols * 2};
  cuuint32_t box[2] = {64, box_rows}, es[2] = {1, 1};
  g_encode(&m, CU_TENSOR_MAP_DATA_TYPE_BFLOAT16, 2, (void*)ptr, dims, strides, box, es, CU_TENSOR_MAP_INTERLEAVE_NONE,
           CU_TENSOR_MAP_SWIZZLE_128B, pr, CU_TENSOR_MAP_FLOAT_OOB_FILL_NONE);
  return m;
}

static CUtensorMap make_map3(const void* ptr, uint64_t d0, uint64_t d1, uint64_t d2, uint64_t stride2) {
  CUtensorMap m;
  cuuint64_t dims[3] = {d0, d1, d2}, strides[2] = {DM * 2, stride2};
  cuuint32_t box[3] = {64, 32, 2}, es[3] = {1, 1, 1};
  g_encode(&m, CU_TENSOR_MAP_DATA_TYPE_BFLOAT16, 3, (void*)ptr, dims, strides, box, es, CU_TENSOR_MAP_INTERLEAVE_NONE,
           CU_TENSOR_MAP_SWIZZLE_128B, CU_TENSOR_MAP_L2_PROMOTION_L2_256B, CU_TENSOR_MAP_FLOAT_OOB_FILL_NONE);
  return m;
}

extern "C" void kernel_launch(void* const* d_in, const int* in_sizes, int n_in, void* d_out, int out_size) {
  const bf16* x = (const bf16*)d_in[0];
  const bf16* mem0 = (const bf16*)d_in[1];
  if (!g_encode) {
    void* p = nullptr; cudaDriverEntryPointQueryResult q;
    cudaGetDriverEntryPoint("cuTensorMapEncodeTiled", &p, cudaEnableDefault, &q);
    g_encode = (PFN_encodeTiled)p;
    cudaFuncSetAttribute(gemm_kernel, cudaFuncAttributeMaxDynamicSharedMemorySize, gm::SMEM);
    cudaFuncSetAttribute(rec_kernel, cudaFuncAttributeMaxDynamicSharedMemorySize, rec::SMEM);
  }
  bf16 *xn, *ot, *hh;
  cudaGetSymbolAddress((void**)&xn, g_xn); cudaGetSymbolAddress((void**)&ot, g_ot); cudaGetSymbolAddress((void**)&hh, g_h);
  rec::Maps R;
  for (int i = 0; i < 3; i++) R.w[i] = make_map(d_in[2 + i], DM, NH * DH, 16, CU_TENSOR_MAP_L2_PROMOTION_NONE);
  R.wo = make_map(d_in[5], NH * DH, DM, 128);
  R.xd = make_map3(xn, DM, SEQ - LAG * 32, 2, (uint64_t)LAG * 32 * DM * 2); R.xs = make_map3(xn, 64, SEQ, DM / 64, 128);
  gm::Maps G;
  G.ot = make_map(ot, NH * DH + O_LAYER / SEQ, SEQ, 64); G.wo = make_map(d_in[5], NH * DH, DM, 64); G.xn = make_map(xn, SEQ, DM, 64);
  G.wg = make_map(d_in[8], DM, DF, 64); G.wu = make_map(d_in[9], DM, DF, 64); G.hl = make_map(hh, SEQ, DF, 64); G.hs = make_map(hh, SEQ, DF, 128);
  G.wd = make_map(d_in[10], DF, DM, 64); G.out = make_map(d_out, SEQ, DM, 128);
  cudaLaunchConfig_t cfg = {};
  cudaLaunchAttribute at[1];
  cfg.attrs = at; cfg.numAttrs = 1;
  cfg.gridDim = dim3(3 * NH); cfg.blockDim = dim3(384); cfg.dynamicSmemBytes = rec::SMEM; cfg.stream = cudaStreamPerThread;
  at[0].id = cudaLaunchAttributeClusterDimension; at[0].val.clusterDim.y = at[0].val.clusterDim.z = 1;
  static int csize = 0;
  if (!csize) {
    int n = 0;
    at[0].val.clusterDim.x = 6;
    csize = cudaOccupancyMaxActiveClusters(&n, rec_kernel, &cfg) == cudaSuccess && n >= NH / 2 ? 6 : 3;
  }
  at[0].val.clusterDim.x = csize;
  cudaLaunchKernelEx(&cfg, rec_kernel, R, mem0);
  cfg.gridDim = dim3(132); cfg.blockDim = dim3(384); cfg.dynamicSmemBytes = gm::SMEM; cfg.stream = cudaStreamPerThread;
  at[0].id = cudaLaunchAttributeProgrammaticStreamSerialization; at[0].val.programmaticStreamSerializationAllowed = 1;
  cudaLaunchKernelEx(&cfg, gemm_kernel, G, x, (bf16*)d_out);
}
```

```cpp
#include <cuda_runtime.h>
#include <cuda_bf16.h>
#include <cuda.h>
#include <stdint.h>

#define DEVI __device__ __forceinline__
typedef __nv_bfloat16 bf16;

constexpr int SEQ = 2048, DM = 1024, NH = 32, DH = 128, DF = 3584, NSEG = 64;
#define LAG 19
constexpr int NSTEP = NSEG + LAG;

#define TSD 1800
constexpr size_t O_LAYER = 0;
__device__ __align__(1024) bf16 g_xn[SEQ * DM];
__device__ __align__(1024) bf16 g_ot[SEQ * NH * DH + O_LAYER];
__device__ __align__(1024) bf16 g_h[SEQ * DF];
__device__ __align__(1024) uint32_t g_xr[NSEG][DM * 4];
__device__ __align__(1024) uint2 g_h1[4][256 * 256];
__device__ __align__(1024) uint4 g_h2[4][2048];
__device__ __align__(128) uint32_t g_ts[2][32];
enum { E_D1 = 0, E_G1 = 32, E_O1 = 48, E_O2 = 64, E_G2 = 80, E_D2 = 96,
       E_LI = 128, E_LX2 = 144, E_LX1A = 160, E_LX1B = 176, NEV = 256 };
__device__ __align__(128) int g_dep[NEV];
__device__ __align__(128) int g_claim[NEV];
__device__ __align__(128) int g_xa[2][32];

#define TUNE_DEFAULTS 1650, 2450, 6, 100, 100, 8, 13, 100, 1500, 2225, 100, 110, 1500, 2225, 200, 0
constexpr int c_D[16] = {TUNE_DEFAULTS};
template<int I> struct TPV { static constexpr int v = c_D[I]; };
#define TP(i) TPV<i>::v

DEVI uint32_t smem_u32(const void* p) { return (uint32_t)__cvta_generic_to_shared(p); }
DEVI void mbar_init(uint32_t bar, uint32_t cnt) { asm volatile("mbarrier.init.shared::cta.b64 [%0], %1;" :: "r"(bar), "r"(cnt) : "memory"); }
DEVI void mbar_arrive(uint32_t bar) { asm volatile("mbarrier.arrive.shared::cta.b64 _, [%0];" :: "r"(bar) : "memory"); }
DEVI bool mbar_try(uint32_t bar, uint32_t parity) {
  uint32_t p;
  asm volatile("{.reg .pred p; mbarrier.try_wait.parity.shared::cta.b64 p, [%1], %2; selp.u32 %0, 1, 0, p;}" : "=r"(p) : "r"(bar), "r"(parity) : "memory");
  return p;
}
DEVI bool mbar_test(uint32_t bar, uint32_t parity) {
  uint32_t p;
  asm volatile("{.reg .pred p; mbarrier.test_wait.parity.shared::cta.b64 p, [%1], %2; selp.u32 %0, 1, 0, p;}" : "=r"(p) : "r"(bar), "r"(parity) : "memory");
  return p;
}
constexpr int SPIN_BUDGET = 1 << 18;
DEVI void mbar_wait(uint32_t bar, uint32_t parity, int& budget) {
  while (!mbar_try(bar, parity)) { if (--budget < 0) break; }
}
DEVI bool mbar_try_cluster(uint32_t bar, uint32_t parity) {
  uint32_t p;
  asm volatile("{.reg .pred p; mbarrier.try_wait.parity.acquire.cluster.shared::cta.b64 p, [%1], %2; selp.u32 %0, 1, 0, p;}" : "=r"(p) : "r"(bar), "r"(parity) : "memory");
  return p;
}
DEVI void mbar_wait_cluster(uint32_t bar, uint32_t parity, int& budget) {
  while (!mbar_try_cluster(bar, parity)) { if (--budget < 0) break; }
}
DEVI uint32_t mapa(uint32_t addr, uint32_t rank) { uint32_t r; asm("mapa.shared::cluster.u32 %0, %1, %2;" : "=r"(r) : "r"(addr), "r"(rank)); return r; }
DEVI void cluster_arrive() { asm volatile("barrier.cluster.arrive.relaxed.aligned;" ::: "memory"); }
DEVI void cluster_wait() { asm volatile("barrier.cluster.wait.aligned;" ::: "memory"); }
DEVI void fence_mbar_init() { asm volatile("fence.mbarrier_init.release.cluster;" ::: "memory"); }
DEVI void fence_proxy_async() { asm volatile("fence.proxy.async.shared::cta;" ::: "memory"); }
DEVI void fence_proxy_global() { asm volatile("fence.proxy.async.global;" ::: "memory"); }
#define ELECT "{.reg .pred p; elect.sync _|p, 0xffffffff;\n @p "
DEVI void e_expect_tx(uint32_t bar, uint32_t bytes) { asm volatile(ELECT "mbarrier.arrive.expect_tx.shared::cta.b64 _, [%0], %1;}" :: "r"(bar), "r"(bytes) : "memory"); }
DEVI void e_complete_tx(uint32_t bar, uint32_t bytes) { asm volatile("fence.acq_rel.cta;\n" ELECT "mbarrier.complete_tx.relaxed.cta.shared::cta.b64 [%0], %1;}" :: "r"(bar), "r"(bytes) : "memory"); }
DEVI void e_arrive(uint32_t bar) { asm volatile(ELECT "mbarrier.arrive.shared::cta.b64 _, [%0];}" :: "r"(bar) : "memory"); }
DEVI void e_tma_2d(uint32_t dst, const CUtensorMap* m, int c0, int c1, uint32_t bar) {
  asm volatile(ELECT "cp.async.bulk.tensor.2d.shared::cluster.global.mbarrier::complete_tx::bytes [%0], [%1, {%3, %4}], [%2];}"
    :: "r"(dst), "l"(m), "r"(bar), "r"(c0), "r"(c1) : "memory");
}
DEVI void e_prefetch_3d(const CUtensorMap* m, int c0, int c1, int c2) {
  asm volatile(ELECT "cp.async.bulk.prefetch.tensor.3d.L2.global [%0, {%1, %2, %3}];}" :: "l"(m), "r"(c0), "r"(c1), "r"(c2) : "memory");
}
DEVI void e_bulk_g2s(uint32_t dst, const void* src, uint32_t bytes, uint32_t bar) {
  asm volatile(ELECT "cp.async.bulk.shared::cluster.global.mbarrier::complete_tx::bytes [%0], [%1], %2, [%3];}" :: "r"(dst), "l"(src), "r"(bytes), "r"(bar) : "memory");
}
DEVI void e_tma_3d(uint32_t dst, const CUtensorMap* m, int c0, int c1, int c2, uint32_t bar) {
  asm volatile(ELECT "cp.async.bulk.tensor.3d.shared::cluster.global.mbarrier::complete_tx::bytes [%0], [%1, {%3, %4, %5}], [%2];}"
    :: "r"(dst), "l"(m), "r"(bar), "r"(c0), "r"(c1), "r"(c2) : "memory");
}
DEVI void e_tma_3d_mc(uint32_t dst, const CUtensorMap* m, int c0, int c1, int c2, uint32_t bar, int last) {
  asm volatile(ELECT "cp.async.bulk.tensor.3d.shared::cluster.global.mbarrier::complete_tx::bytes.multicast::cluster [%0], [%1, {%3, %4, %5}], [%2], %6;}"
    :: "r"(dst), "l"(m), "r"(bar), "r"(c0), "r"(c1), "r"(c2), "h"((uint16_t)((2 << last) - 1)) : "memory");
}
DEVI void e_tma_2d_mc(uint32_t dst, const CUtensorMap* m, int c0, int c1, uint32_t bar) {
  asm volatile(ELECT "cp.async.bulk.tensor.2d.shared::cluster.global.mbarrier::complete_tx::bytes.multicast::cluster [%0], [%1, {%3, %4}], [%2], %5;}"
    :: "r"(dst), "l"(m), "r"(bar), "r"(c0), "r"(c1), "h"((uint16_t)3) : "memory");
}
DEVI void p_arrive_at(uint32_t bar, uint32_t rank, bool c) {
  asm volatile("{.reg .pred p; .reg .b32 a; setp.ne.u32 p, %2, 0; mapa.shared::cluster.u32 a, %0, %1; @p mbarrier.arrive.shared::cluster.b64 _, [a];}"
    :: "r"(bar), "r"(rank), "r"((uint32_t)c) : "memory");
}
DEVI void p_expect_tx(uint32_t bar, uint32_t bytes, bool c) {
  asm volatile("{.reg .pred p; setp.ne.u32 p, %2, 0; @p mbarrier.arrive.expect_tx.shared::cta.b64 _, [%0], %1;}" :: "r"(bar), "r"(bytes), "r"((uint32_t)c) : "memory");
}
DEVI void p_arrive(uint32_t bar, bool c) { asm volatile("{.reg .pred p; setp.ne.u32 p, %1, 0; @p mbarrier.arrive.shared::cta.b64 _, [%0];}" :: "r"(bar), "r"((uint32_t)c) : "memory"); }
DEVI void tma_store_2d(const CUtensorMap* m, uint32_t src, int c0, int c1) {
  asm volatile("cp.async.bulk.tensor.2d.global.shared::cta.bulk_group [%0, {%2, %3}], [%1];" :: "l"(m), "r"(src), "r"(c0), "r"(c1) : "memory");
}
DEVI void tma_radd_2d(const CUtensorMap* m, uint32_t src, int c0, int c1) {
  asm volatile("cp.reduce.async.bulk.tensor.2d.global.shared::cta.add.bulk_group [%0, {%2, %3}], [%1];" :: "l"(m), "r"(src), "r"(c0), "r"(c1) : "memory");
}
DEVI void bulk_commit() { asm volatile("cp.async.bulk.commit_group;" ::: "memory"); }
template<int N> DEVI void bulk_wait_read() { asm volatile("cp.async.bulk.wait_group.read %0;" :: "n"(N) : "memory"); }
template<int N> DEVI void bulk_wait() { asm volatile("cp.async.bulk.wait_group %0;" :: "n"(N) : "memory"); }
template<int ID, int N> DEVI void nbar_sync() { asm volatile("bar.sync %0, %1;" :: "n"(ID), "n"(N) : "memory"); }
template<int ID, int N> DEVI void nbar_arrive() { asm volatile("bar.arrive %0, %1;" :: "n"(ID), "n"(N) : "memory"); }
DEVI void nbar_sync_r(int id, int n) { asm volatile("bar.sync %0, %1;" :: "r"(id), "r"(n) : "memory"); }
template<int R> DEVI void reg_inc() { asm volatile("setmaxnreg.inc.sync.aligned.u32 %0;" :: "n"(R)); }
template<int R> DEVI void reg_dec() { asm volatile("setmaxnreg.dec.sync.aligned.u32 %0;" :: "n"(R)); }
DEVI void wg_fence() { asm volatile("wgmma.fence.sync.aligned;" ::: "memory"); }
DEVI void wg_commit() { asm volatile("wgmma.commit_group.sync.aligned;" ::: "memory"); }
template<int N> DEVI void wg_wait() { asm volatile("wgmma.wait_group.sync.aligned %0;" :: "n"(N) : "memory"); }
DEVI uint64_t mkdesc(uint32_t addr, uint32_t lbo, uint32_t sbo, uint32_t sw = 1) {
  return ((uint64_t)((addr & 0x3FFFF) >> 4)) | ((uint64_t)(lbo >> 4) << 16) | ((uint64_t)(sbo >> 4) << 32) | ((uint64_t)sw << 62);
}
constexpr uint32_t SMEM_BASE = 1024;
__host__ __device__ constexpr long long CD(uint32_t off, uint32_t lbo, uint32_t sbo, uint32_t sw) {
  return (long long)(((uint64_t)((SMEM_BASE + off) >> 4)) | ((uint64_t)(lbo >> 4) << 16) | ((uint64_t)(sbo >> 4) << 32) | ((uint64_t)sw << 62));
}
DEVI uint32_t pack_bf16(float lo, float hi) { uint32_t r; asm("cvt.rn.bf16x2.f32 %0, %1, %2;" : "=r"(r) : "f"(hi), "f"(lo)); return r; }
DEVI float bf_lo(uint32_t v) { return __uint_as_float(v << 16); }
DEVI float bf_hi(uint32_t v) { return __uint_as_float(v & 0xffff0000u); }
DEVI void ldsm4t(uint32_t addr, uint32_t& r0, uint32_t& r1, uint32_t& r2, uint32_t& r3) {
  asm volatile("ldmatrix.sync.aligned.m8n8.x4.trans.shared.b16 {%0,%1,%2,%3}, [%4];" : "=r"(r0), "=r"(r1), "=r"(r2), "=r"(r3) : "r"(addr) : "memory");
}
DEVI void stsm4(uint32_t addr, uint32_t r0, uint32_t r1, uint32_t r2, uint32_t r3) {
  asm volatile("stmatrix.sync.aligned.m8n8.x4.shared.b16 [%0], {%1,%2,%3,%4};" :: "r"(addr), "r"(r0), "r"(r1), "r"(r2), "r"(r3) : "memory");
}
DEVI uint2 lds64v(uint32_t a) { uint2 v; asm volatile("ld.volatile.shared.v2.u32 {%0,%1}, [%2];" : "=r"(v.x), "=r"(v.y) : "r"(a) : "memory"); return v; }
DEVI uint32_t lds32v(uint32_t a) { uint32_t v; asm volatile("ld.volatile.shared.u32 %0, [%1];" : "=r"(v) : "r"(a) : "memory"); return v; }
DEVI uint4 lds128v(uint32_t a) { uint4 v; asm volatile("ld.volatile.shared.v4.u32 {%0,%1,%2,%3}, [%4];" : "=r"(v.x), "=r"(v.y), "=r"(v.z), "=r"(v.w) : "r"(a) : "memory"); return v; }
DEVI void sts32(uint32_t a, uint32_t x) { asm volatile("st.shared.u32 [%0], %1;" :: "r"(a), "r"(x) : "memory"); }
DEVI int lane_id() { int r; asm volatile("mov.u32 %0, %%laneid;" : "=r"(r)); return r; }
DEVI void sts64(uint32_t a, uint32_t x, uint32_t y) { asm volatile("st.shared.v2.u32 [%0], {%1,%2};" :: "r"(a), "r"(x), "r"(y) : "memory"); }
DEVI void st_async128(uint32_t a, uint32_t x, uint32_t y, uint32_t z, uint32_t w, uint32_t bar) {
  asm volatile("st.async.weak.shared::cluster.mbarrier::complete_tx::bytes.v4.b32 [%0], {%1,%2,%3,%4}, [%5];" :: "r"(a), "r"(x), "r"(y), "r"(z), "r"(w), "r"(bar) : "memory");
}
DEVI void st_async32(uint32_t a, uint32_t x, uint32_t bar) {
  asm volatile("st.async.weak.shared::cluster.mbarrier::complete_tx::bytes.b32 [%0], %1, [%2];" :: "r"(a), "r"(x), "r"(bar) : "memory");
}
DEVI uint4 ldg_rlx128(const void* p) {
  uint4 v;
  asm volatile("ld.relaxed.gpu.global.v4.b32 {%0,%1,%2,%3}, [%4];" : "=r"(v.x), "=r"(v.y), "=r"(v.z), "=r"(v.w) : "l"(p) : "memory");
  return v;
}
DEVI int ldg_rlx32(const void* p) { int v; asm volatile("ld.relaxed.gpu.global.b32 %0, [%1];" : "=r"(v) : "l"(p) : "memory"); return v; }
DEVI int ldg_acq32(const void* p) { int v; asm volatile("ld.acquire.gpu.global.b32 %0, [%1];" : "=r"(v) : "l"(p) : "memory"); return v; }
DEVI void stg128(void* p, uint32_t x, uint32_t y, uint32_t z, uint32_t w) {
  asm volatile("st.global.v4.b32 [%0], {%1,%2,%3,%4};" :: "l"(p), "r"(x), "r"(y), "r"(z), "r"(w) : "memory");
}
DEVI uint2 ldg_rlx64(const void* p) { uint2 v; asm volatile("{.reg .b64 a; ld.relaxed.gpu.global.b64 a, [%2]; mov.b64 {%0,%1}, a;}" : "=r"(v.x), "=r"(v.y) : "l"(p) : "memory"); return v; }
DEVI void stg_rlx64(void* p, uint32_t x, uint32_t y) { asm volatile("{.reg .b64 a; mov.b64 a, {%1,%2}; st.relaxed.gpu.global.b64 [%0], a;}" :: "l"(p), "r"(x), "r"(y) : "memory"); }
DEVI void stg_rlx32(void* p, uint32_t x) { asm volatile("st.relaxed.gpu.global.b32 [%0], %1;" :: "l"(p), "r"(x) : "memory"); }
DEVI void flag_add(int* p) { asm volatile("fence.proxy.async.global; red.release.gpu.global.add.s32 [%0], 1;" :: "l"(p) : "memory"); }
DEVI void e_stg_rlx32(void* p, uint32_t x) { asm volatile(ELECT "st.relaxed.gpu.global.b32 [%0], %1;}" :: "l"(p), "r"(x) : "memory"); }
DEVI void e_flag_add(int* p) { asm volatile("fence.proxy.async.global;\n" ELECT "red.release.gpu.global.add.s32 [%0], 1;}" :: "l"(p) : "memory"); }
DEVI int cluster_rank() { int r; asm volatile("mov.u32 %0, %%cluster_ctarank;" : "=r"(r)); return __shfl_sync(0xffffffffu, r, 0); }
DEVI int cluster_last() { int r; asm volatile("mov.u32 %0, %%cluster_nctarank;" : "=r"(r)); return __shfl_sync(0xffffffffu, r, 0) - 1; }
DEVI int cta_id() { int r; asm volatile("mov.u32 %0, %%ctaid.x;" : "=r"(r)); return __shfl_sync(0xffffffffu, r, 0); }
DEVI uint32_t clock32() { uint32_t c; asm volatile("mov.u32 %0, %%clock;" : "=r"(c)); return c; }
DEVI uint32_t gtime() { uint32_t c; asm volatile("mov.u32 %0, %%globaltimer_lo;" : "=r"(c)); return c; }
DEVI void wait_time(uint32_t t) { while (__any_sync(0xffffffffu, t - gtime() - 1 < 4000u)) {} }
DEVI void spin_until(uint32_t t0, int d) {
  int r;
  while (__any_sync(0xffffffffu, (r = d - (int)(clock32() - t0)) > 0)) {
    if (r > 300) __nanosleep(r >> 2);
  }
}
DEVI void pin2(const void* a, const void* b) { asm volatile("{.reg .pred p; setp.eq.u64 p, %0, %1; @p st.volatile.global.u64 [%0], %1;}" :: "l"(a), "l"(b) : "memory"); }
DEVI void pin2(uint32_t a, uint32_t b) { asm volatile("{.reg .pred p; setp.eq.u32 p, %0, %1; @p st.volatile.shared.u32 [%0], %1;}" :: "r"(a), "r"(b) : "memory"); }
DEVI void p_stg_rlx64(void* p, uint32_t x, uint32_t y, bool c) {
  asm volatile("{.reg .pred p; .reg .b64 a; setp.ne.u32 p, %3, 0; mov.b64 a, {%1,%2}; @p st.relaxed.gpu.global.b64 [%0], a;}" :: "l"(p), "r"(x), "r"(y), "r"((uint32_t)c) : "memory");
}
DEVI void pin2(uint64_t a, uint64_t b) { pin2((const void*)a, (const void*)b); }
DEVI uint64_t pair(uint32_t a, uint32_t bar) { return a | (uint64_t)bar << 32; }
DEVI void st_async32(uint64_t q, uint32_t x) { st_async32((uint32_t)q, x, (uint32_t)(q >> 32)); }
DEVI void st_async128(uint64_t q, uint4 v) { st_async128((uint32_t)q, v.x, v.y, v.z, v.w, (uint32_t)(q >> 32)); }
DEVI float ex2(float x) { float r; asm("ex2.approx.ftz.f32 %0, %1;" : "=f"(r) : "f"(x)); return r; }
DEVI float rcp(float x) { float r; asm("rcp.approx.ftz.f32 %0, %1;" : "=f"(r) : "f"(x)); return r; }
DEVI uint32_t xor_or(uint32_t a, uint32_t t, uint32_t acc) { uint32_t r; asm("lop3.b32 %0, %1, %2, %3, 0xbe;" : "=r"(r) : "r"(a), "r"(t), "r"(acc)); return r; }
DEVI void stsm2(uint32_t addr, uint32_t r0, uint32_t r1) {
  asm volatile("stmatrix.sync.aligned.m8n8.x2.shared.b16 [%0], {%1,%2};" :: "r"(addr), "r"(r0), "r"(r1) : "memory");
}
DEVI uint32_t settag(uint32_t v, uint32_t tag) { return (v & ~1u) | tag; }

#define A4(c, o)  c(d[o+0]), c(d[o+1]), c(d[o+2]), c(d[o+3])
#define A8(c, o)  A4(c, o), A4(c, o+4)
#define A16(c, o) A8(c, o), A8(c, o+8)
#define A12(c, o) A8(c, o), A4(c, o+8)
#define A28(c, o) A16(c, o), A12(c, o+16)
#define RL12 "{%0,%1,%2,%3,%4,%5,%6,%7,%8,%9,%10,%11}"
#define RL28 "{%0,%1,%2,%3,%4,%5,%6,%7,%8,%9,%10,%11,%12,%13,%14,%15,%16,%17,%18,%19,%20,%21,%22,%23,%24,%25,%26,%27}"
#define A20(c, o) A16(c, o), A4(c, o+16)
#define A32(c, o) A16(c, o), A16(c, o+16)
#define RL8  "{%0,%1,%2,%3,%4,%5,%6,%7}"
#define RL16 "{%0,%1,%2,%3,%4,%5,%6,%7,%8,%9,%10,%11,%12,%13,%14,%15}"
#define RL20 "{%0,%1,%2,%3,%4,%5,%6,%7,%8,%9,%10,%11,%12,%13,%14,%15,%16,%17,%18,%19}"
#define RL32 "{%0,%1,%2,%3,%4,%5,%6,%7,%8,%9,%10,%11,%12,%13,%14,%15,%16,%17,%18,%19,%20,%21,%22,%23,%24,%25,%26,%27,%28,%29,%30,%31}"
#define RL64 "{%0,%1,%2,%3,%4,%5,%6,%7,%8,%9,%10,%11,%12,%13,%14,%15,%16,%17,%18,%19,%20,%21,%22,%23,%24,%25,%26,%27,%28,%29,%30,%31," \
  "%32,%33,%34,%35,%36,%37,%38,%39,%40,%41,%42,%43,%44,%45,%46,%47,%48,%49,%50,%51,%52,%53,%54,%55,%56,%57,%58,%59,%60,%61,%62,%63}"
#define WG_OP(shape) "wgmma.mma_async.sync.aligned." shape "k16.f32.bf16.bf16 "
#define DEF_WGMMA(N, RL, AL, i0, i1, i2, i3, i4, i5, i6)                                                                         \
  template<int SC, int TB, long long CB> DEVI void rs##N(float* d, const uint32_t* a) {                                          \
    if (SC) asm volatile("{.reg .b64 tb; mov.b64 tb, %" #i4 ";\n" WG_OP("m64n" #N) RL ", {%" #i0 ",%" #i1 ",%" #i2 ",%" #i3 "}, tb, 1, 1, 1, %" #i5 ";}" \
      : AL("+f", 0) : "r"(a[0]), "r"(a[1]), "r"(a[2]), "r"(a[3]), "n"(CB), "n"(TB));                                             \
    else asm volatile("{.reg .b64 tb; mov.b64 tb, %" #i4 ";\n" WG_OP("m64n" #N) RL ", {%" #i0 ",%" #i1 ",%" #i2 ",%" #i3 "}, tb, 0, 1, 1, %" #i5 ";}" \
      : AL("=f", 0) : "r"(a[0]), "r"(a[1]), "r"(a[2]), "r"(a[3]), "n"(CB), "n"(TB));                                             \
  }                                                                                                                              \
  template<int SC, int TA, int TB, long long CA, long long CB> DEVI void ss##N(float* d, uint32_t a) {                           \
    if (SC) asm volatile("{.reg .b64 ta, tb; .reg .b32 lo, hi; add.u32 lo, %" #i0 ", %" #i1 "; mov.b32 hi, %" #i2 "; mov.b64 ta, {lo, hi}; mov.b64 tb, %" #i3 ";\n" \
      WG_OP("m64n" #N) RL ", ta, tb, 1, 1, 1, %" #i4 ", %" #i5 ";}"                                                              \
      : AL("+f", 0) : "r"(a), "n"((int)CA), "n"((int)(CA >> 32)), "n"(CB), "n"(TA), "n"(TB));                                    \
    else asm volatile("{.reg .b64 ta, tb; .reg .b32 lo, hi; add.u32 lo, %" #i0 ", %" #i1 "; mov.b32 hi, %" #i2 "; mov.b64 ta, {lo, hi}; mov.b64 tb, %" #i3 ";\n" \
      WG_OP("m64n" #N) RL ", ta, tb, 0, 1, 1, %" #i4 ", %" #i5 ";}"                                                              \
      : AL("=f", 0) : "r"(a), "n"((int)CA), "n"((int)(CA >> 32)), "n"(CB), "n"(TA), "n"(TB));                                    \
  }
DEF_WGMMA(8, "{%0,%1,%2,%3}", A4, 4, 5, 6, 7, 8, 9, 10)
DEF_WGMMA(16, RL8, A8, 8, 9, 10, 11, 12, 13, 14)
DEF_WGMMA(32, RL16, A16, 16, 17, 18, 19, 20, 21, 22)
DEF_WGMMA(40, RL20, A20, 20, 21, 22, 23, 24, 25, 26)
DEF_WGMMA(24, RL12, A12, 12, 13, 14, 15, 16, 17, 18)
DEF_WGMMA(56, RL28, A28, 28, 29, 30, 31, 32, 33, 34)
template<int TA> DEVI void wgmma_n128(float* d, uint64_t a, uint64_t b, int scale_d) {
  asm volatile("{.reg .pred p; setp.ne.b32 p, %66, 0;\n" WG_OP("m64n128") RL64 ", %64, %65, p, 1, 1, %67, 1;}"
    : A32("+f", 0), A32("+f", 32) : "l"(a), "l"(b), "r"(scale_d), "n"(TA));
}

namespace rec {
constexpr int KR = 43;
constexpr uint32_t WSZ = (64 - KR) * 2048, STG = KR * 2048;
constexpr uint32_t WS = 0;
constexpr uint32_t RING = 2 * WSZ;
constexpr uint32_t OB = RING + 3 * 8192;
constexpr uint32_t PB = OB + 4096;
constexpr uint32_t WO = RING + 32768;
constexpr uint32_t ATT = WO + 5 * 16384;
constexpr uint32_t AK = ATT + 10240, AV = ATT + 20480;
constexpr uint32_t PAD = ATT + 30720;
constexpr uint32_t BARS = PAD + 128;
constexpr uint32_t B_XE = BARS  , B_FA = BARS + 64  , B_FB = BARS + 88, B_FO = BARS + 96;
constexpr uint32_t B_ME = BARS + 104  , B_WE = BARS + 136, B_PD = BARS + 144;
constexpr uint32_t B_XF = BARS + 152  , B_MF = BARS + 216  , B_CP = BARS + 248  , B_WT = BARS + 280  ;
constexpr uint32_t B_AB = BARS + 296, B_OB = BARS + 304, B_ST = BARS + 312  , B_WS = BARS + 328, B_WO = BARS + 336, B_AT = BARS + 352, B_AV = BARS + 360;
constexpr int NBAR = 46;
constexpr uint32_t M0 = BARS + 384;
constexpr uint32_t SMEM = 232448;
constexpr int NB_P = 1, NB_ST = 2, NB_O = 3, NB_W0 = 4, NB_W1 = 5;
__host__ __device__ constexpr int wo_tile(int rank, int g, int i) { return i < 2 ? i * 6 + (rank == 2 ? g : 4 - 2 * g + rank) : 13 + rank - g; }
constexpr long long D_W = CD(WS, 16, 1024, 1), D_X = CD(0, 16, 1024, 1), D_O = CD(OB, 128, 256, 0);
constexpr long long D_WO = CD(WO, 16, 1024, 1), D_QM = CD(ATT, 640, 0, 0), D_QT = CD(ATT + 128, 640, 64, 0), D_K = CD(AK, 640, 128, 0);
constexpr long long D_V = CD(AV, 128, 640, 0), D_P = CD(PB, 128, 768, 0);
struct Maps { CUtensorMap w[3], wo, xd, xs; };
__host__ __device__ constexpr uint32_t mslot(int c) { return (c ^ (c >> 1)) * 12288; }
__host__ __device__ constexpr uint32_t xslot(int s) { return s < 3 ? RING + s * 8192 : s < 5 ? WO + (s - 3) * 8192 : s < 7 ? WO + (s + 1) * 8192 : OB; }
__host__ __device__ constexpr bool k_smem(int k) { return k % 3 == 2; }
__host__ __device__ constexpr int k_idx(int k) { return k % 3 == 2 ? k / 3 : k - k / 3; }
__host__ __device__ constexpr int k_of_reg(int i) { return i + (i >> 1); }
__host__ __device__ constexpr int k_of_smem(int i) { return 3 * i + 2; }

#define RPROF(i)
#define RPROF_STEP
#define CPROF(i, v)

template<bool DUAL, int K0, int K1> DEVI void seq_mem(float* d, const uint32_t* w, uint32_t dw) {
  if constexpr (K0 < K1) {
    constexpr long long B = CD(RING, 128, DUAL ? 4096 : 8192, 0) + mslot(K0 >> 4) / 16 + (K0 & 15) * 16;
    if constexpr (DUAL) {
      if constexpr (!k_smem(K0)) rs24<K0 != 0, 1, B>(d, w + 4 * k_idx(K0)); else ss24<1, 1, 1, D_W + k_idx(K0) * 128, B>(d, dw);
    } else {
      if constexpr (!k_smem(K0)) rs16<K0 != 0, 1, B>(d, w + 4 * k_idx(K0)); else ss16<1, 1, 1, D_W + k_idx(K0) * 128, B>(d, dw);
    }
    seq_mem<DUAL, K0 + 1, K1>(d, w, dw);
  }
}
template<int N, int K0, int K1> DEVI void seq_tok(float* d, const uint32_t* w, uint32_t dw) {
  if constexpr (K0 < K1) {
    constexpr bool DUAL = N > 32;
    constexpr long long B = D_X + (DUAL ? xslot((K0 >> 2) & 7) / 16 : xslot(K0 >> 3) / 16 + ((K0 >> 2) & 1) * 256) + (K0 & 3) * 2;
    if constexpr (DUAL) {
      if constexpr (!k_smem(K0)) rs56<K0 != 0, 0, B>(d, w + 4 * k_idx(K0)); else ss56<1, 1, 0, D_W + k_idx(K0) * 128, B>(d, dw);
    } else if constexpr (N == 24) {
      if constexpr (!k_smem(K0)) rs24<K0 != 0, 0, B>(d, w + 4 * k_idx(K0)); else ss24<1, 1, 0, D_W + k_idx(K0) * 128, B>(d, dw);
    } else {
      if constexpr (!k_smem(K0)) rs32<K0 != 0, 0, B>(d, w + 4 * k_idx(K0)); else ss32<1, 1, 0, D_W + k_idx(K0) * 128, B>(d, dw);
    }
    seq_tok<N, K0 + 1, K1>(d, w, dw);
  }
}
template<bool DUAL, int T, int K0> DEVI void seq_wo(float* d, uint32_t dw) {
  if constexpr (K0 < 8) {
    if constexpr (DUAL) ss16<K0 != 0, 1, 1, D_WO + T * 1024 + K0 * 128, D_O + K0 * 32>(d, dw);
    else ss8<K0 != 0, 1, 1, D_WO + T * 1024 + K0 * 128, D_O + K0 * 32>(d, dw);
    seq_wo<DUAL, T, K0 + 1>(d, dw);
  }
}
template<long long Q, int K0> DEVI void seq_s(float* d) {
  if constexpr (K0 < 8) { ss40<K0 != 0, 1, 1, Q + K0 * 80, D_K + K0 * 80>(d, 0); seq_s<Q, K0 + 1>(d); }
}
template<bool DUAL, int J> DEVI void load_x(uint32_t sb, const Maps* M, int t, int rb) {
  if (DUAL) e_tma_3d_mc(sb + xslot(J & 7), &M->xd, J * 64, (t - LAG) * 32, 0, sb + B_XF + (J & 7) * 8, rb);
  else e_tma_3d_mc(sb + xslot(J & 7), &M->xs, 0, (t < NSEG ? t : t - LAG) * 32, J * 2, sb + B_XF + (J & 7) * 8, rb);
}
DEVI void load_x_lent(uint32_t sb, const Maps* M, int t, int j) {
  const bool dual = t >= LAG && t < NSEG;
  const uint32_t dst = sb + (j == 3 ? xslot(3) : xslot(5));
#pragma unroll
  for (int i = 0; i < 2; i++)
    e_tma_3d(dst + i * 8192, dual ? &M->xd : &M->xs, dual ? (j + i) * 64 : 0, (t < LAG ? t : t - LAG) * 32, dual ? 0 : (j + i) * 2, sb + B_XF + (j + i) * 8);
}
struct True { static constexpr bool value = true; };
struct False { static constexpr bool value = false; };
struct Ctx { uint32_t sb; const Maps* M; int last; bool issuer; int wi; bool lead; uint32_t par; };
#define XD 1
template<bool DUAL, int J> DEVI void tok_release(const Ctx& c, int t, int& budget) {
  constexpr int NC = DUAL ? 16 : 8, S = J & 7;
  if constexpr (J + 8 < NC) {
    p_arrive_at(c.sb + B_XE + S * 8, c.last, c.lead);
    p_expect_tx(c.sb + B_XF + S * 8, 8192, c.lead && c.wi == 0);
  } else if constexpr (S == 1 || S == 2 || S == 4 || S == 7) p_arrive(c.sb + B_ME + (S >> 1) * 8, c.lead);
  if constexpr (J == 0) {
    if (c.issuer && c.wi == 6) { mbar_wait(c.sb + B_FO, t & 1, budget); load_x<DUAL, 7>(c.sb, c.M, t, c.last); }
  }
  if constexpr (J >= XD && J - XD + 8 < NC) {
    constexpr int I = J - XD;
    if (c.issuer && c.wi == (I & 1) * 4 + 1) { mbar_wait(c.sb + B_XE + I * 8, (t - LAG) & 1, budget); load_x<DUAL, I + 8>(c.sb, c.M, t, c.last); }
  }
}
template<int N, int J, class F, class G> DEVI bool tok_pass(float* d, const uint32_t* w, uint32_t dw, Ctx& c, int t, int& budget, F after0, G setup) {
  constexpr bool DUAL = N > 32;
  constexpr int NC = DUAL ? 16 : 8, KC = 64 / NC;
  if constexpr (J < NC) {
    if constexpr (J > 1) mbar_wait(c.sb + B_XF + (J & 7) * 8, c.par ^ (J >> 3), budget);
    wg_fence();
    seq_tok<N, J * KC, (J + 1) * KC>(d, w, dw);
    wg_commit();
    if constexpr (J == 1) after0();
    if constexpr (J >= NC - 5 && J < NC - 2) setup(J - (NC - 5));
    if constexpr (J > 0) { wg_wait<1>(); tok_release<DUAL, J - 1>(c, t, budget); }
    return tok_pass<N, J + 1>(d, w, dw, c, t, budget, after0, setup);
  } else {
    const bool ok = mbar_test(c.sb + B_MF, t & 1);
    wg_wait<0>();
    tok_release<DUAL, NC - 1>(c, t, budget);
    if (!DUAL) c.par ^= 1;
    return ok;
  }
}
template<int NB> DEVI void pack_tok(uint32_t* e, const float* d) {
#pragma unroll
  for (int i = 0; i < 8; i++) if ((i & 3) < NB) e[i] = pack_bf16(d[4 * (i & 3) + 2 * (i >> 2)], d[4 * (i & 3) + 2 * (i >> 2) + 1]);
}
DEVI void push_tok(const uint32_t* e, uint32_t sb, uint32_t o, int r, int rank) {
  const uint32_t b = mapa(sb, r);
  st_async128(b + o, e[0], e[1], e[2], e[3], b + (rank == 2 ? B_AV : B_AT));
}
DEVI uint32_t h1_tag(int seg) { return ((seg >> 1) & 1) ^ 1; }
template<bool DUAL> DEVI uint4 pack_part(const float* c, int t) {
  if (!DUAL) { const uint32_t x = settag(pack_bf16(c[0], c[1]), h1_tag(t < NSEG ? t : t - LAG)), y = pack_bf16(c[2], c[3]); return make_uint4(x, y, x, y); }
  return make_uint4(settag(pack_bf16(c[0], c[1]), h1_tag(t)), pack_bf16(c[2], c[3]), settag(pack_bf16(c[4], c[5]), h1_tag(t - LAG)), pack_bf16(c[6], c[7]));
}
DEVI void put_part(char* p1, char* p2, uint4 z, int t) { p_stg_rlx64(p1, z.x, z.y, t < NSEG); p_stg_rlx64(p2, z.z, z.w, t >= LAG); }

DEVI void rec_math(const uint32_t sb, const int wi, const Maps& M) {
  const int h = cta_id() / 3, rb = cluster_rank() >= 3 ? 3 : 0, rank = cluster_rank() - rb;
  const int warp = wi & 3, wg = wi >> 2;
  const bool lead = (threadIdx.x & 127) == 0;
  int budget = SPIN_BUDGET;
  uint32_t w[4 * KR];
  const int last = cluster_last();
  Ctx cx{sb, &M, last, rb + rank == last, wi, lead, 0};
  {
    const int lane = lane_id();
    const uint32_t a = sb + wg * STG + ((lane & 7) + (lane >> 4) * 8) * 128 + (((warp * 2 + ((lane >> 3) & 1)) ^ (lane & 7)) << 4);
    for (int i = 0; i < (wg == 1 || rank == 2 ? 12 : 8); i++)
      stg_rlx64((char*)g_h1[i & 3] + ((wo_tile(rank, wg, i >> 2) * 4 + warp) * 4 + (lane >> 3)) * 2048 + h * 64 + (lane & 7) * 8, 0, 0);
    mbar_wait(sb + B_ST + wg * 8, 0, budget);
#pragma unroll
    for (int k = 0; k < KR; k++) ldsm4t(a + k * 2048, w[4*k], w[4*k+1], w[4*k+2], w[4*k+3]);
    nbar_arrive<NB_ST, 384>();
    nbar_sync_r(NB_W0 + wg, 128);
    for (int i = 0; i < 5; i++) p_arrive_at(sb + B_FA + i * 8, i == 4 ? last : 0, lead);
    mbar_wait(sb + B_WS, 0, budget);
  }
  uint4 z = make_uint4(0, 0, 0, 0);
  char *z1 = nullptr, *z2 = nullptr;
  uint32_t rt0 = 0, rt1 = 0;
  mbar_wait(sb + B_XF, 0, budget); mbar_wait(sb + B_XF + 8, 0, budget);
#pragma unroll 1
  for (int t = 0;; t++) {
    const uint32_t dw = wg * (WSZ >> 4);
    uint32_t e[16];
    bool ok;
    auto finish = [&]() { put_part(z1, z2, z, t - 1); p_arrive_at(sb + B_FO, last, lead); };
    const int seg = t - rank * LAG;
    const bool att = rank < 2 && (unsigned)seg < (unsigned)NSEG;
    char* p1;
    uint32_t pw, oo;
    uint64_t u0, u1;
    int lane;
    auto setup = [&](int part) {
      if (part == 0) {
        lane = lane_id();
      } else if (part == 1) {
        char* const p = (char*)g_h1 + ((wo_tile(rank, wg, 0) * 4 + warp) * 4 + (lane >> 3)) * 2048 + h * 64 + (lane & 7) * 8;
        p1 = p + (t & 1) * sizeof(g_h1[0]);
        pin2(p1, nullptr);
      } else if (part == 2) {
        oo = OB + (lane >> 4) * 2048 + warp * 512 + (t < NSEG ? rank * 256 : 0) + (lane & 15) * 16;
        pw = sb + PB + (wg ? lane * 4 : 768 + warp * 768 + lane * 16);
        pin2(pw, oo);
      } else {
        if (wg) {
          const uint32_t ra = mapa(sb, rb + ((warp & 1) ? 2 : (rank ^ 1) & 1)), rc = mapa(sb, rb + ((warp & 1) ? (rank ^ 1) & 1 : 2));
          u0 = pair(ra + oo, ra + B_OB); u1 = pair(rc + oo, rc + B_OB);
        } else {
          u0 = (uint64_t)((char*)(g_ot + rank * O_LAYER) + (size_t)(h * DH + warp * 16 + (lane >> 2)) * (SEQ * 2) + seg * 64 + (lane & 3) * 16);
          u1 = (uint32_t)((lane & 24) + ((lane >> 2) & 1) + 2 * warp - 8 * (lane & 3));
        }
        pin2(u0, u1);
      }
    };
    RPROF_STEP;
    auto mem_pass = [&](auto dual_c) {
      constexpr bool DUAL = decltype(dual_c)::value;
      float m[DUAL ? 12 : 8];
      RPROF(8 + wg * 12 - 32);
      if (!ok) mbar_wait(sb + B_MF, t & 1, budget);
      wg_fence(); seq_mem<DUAL, 0, 8>(m, w, dw); wg_commit();
      const uint32_t ao = ATT + rank * 10240 + wi * 1280, to = ao + 128 + (lane & 3) * 128 + (lane >> 2) * 16;
      const int la = DUAL ? rank == 0 || (rank == 2 && wg) : t >= NSEG;
      RPROF(1 + wg * 12);
      if (DUAL && la) {
#pragma unroll
        for (int i = 0; i < 8; i++) { const uint32_t x = e[i]; e[i] = e[8 + i]; e[8 + i] = x; }
      }
      auto piece = [&](int i) { push_tok(e + 4 * i, sb, to + (i & 1) * 640, rb + (la ^ (i >> 1)), rank); };
      piece(0);
      wg_fence(); seq_mem<DUAL, 8, 16>(m, w, dw); wg_commit();
      piece(1);
      mbar_wait(sb + B_MF + 8, t & 1, budget);
      wg_fence(); seq_mem<DUAL, 16, 24>(m, w, dw); wg_commit();
      if (DUAL) piece(2);
      wg_fence(); seq_mem<DUAL, 24, 32>(m, w, dw); wg_commit();
      if (DUAL) piece(3);
      mbar_wait(sb + B_MF + 16, t & 1, budget);
      wg_fence(); seq_mem<DUAL, 32, 48>(m, w, dw); wg_commit();
      wg_wait<1>(); p_arrive(sb + B_PD, lead);
      const uint32_t r0 = mapa(sb, rb + la), r1 = mapa(sb, rb + (la ^ 1)), m0 = r0 + ao + lane * 4, m1 = r1 + ao + lane * 4, ab = rank == 2 ? B_AV : B_AB;
      const uint64_t q0 = pair(m0, r0 + ab), q1 = pair(m0 + 640, r0 + ab), q2 = pair(m1, r1 + ab), q3 = pair(m1 + 640, r1 + ab);
      pin2(q0, q1);
      if (DUAL) pin2(q2, q3);
      mbar_wait(sb + B_MF + 24, t & 1, budget);
      wg_fence(); seq_mem<DUAL, 48, 64>(m, w, dw); wg_commit();
      wg_wait<1>(); p_arrive_at(sb + B_FA, 0, lead);
      wg_wait<0>();
      const uint32_t a0 = pack_bf16(m[0], m[1]), a1 = pack_bf16(m[2], m[3]), a2 = pack_bf16(m[4], m[5]), a3 = pack_bf16(m[6], m[7]);
      if constexpr (DUAL) {
        st_async32(q0, la ? a2 : a0); st_async32(q1, la ? a3 : a1); st_async32(q2, la ? a0 : a2); st_async32(q3, la ? a1 : a3);
        rt0 = pack_bf16(m[8], m[9]); rt1 = pack_bf16(m[10], m[11]);
      } else { st_async32(q0, a0); st_async32(q1, a1); rt0 = a2; rt1 = a3; }
      p_arrive(sb + B_WE, lead);
    };
    if (t >= LAG && t < NSEG) {
      float d[28];
      ok = tok_pass<56, 0>(d, w, dw, cx, t, budget, finish, setup);
      pack_tok<4>(e + 8, d); pack_tok<3>(e, d + 16); e[3] = rt0; e[7] = rt1;
      mem_pass(True());
    } else {
      float d[16];
      if (t > 0) finish();
      if (t > 0 && t < LAG) {
        ok = tok_pass<24, 0>(d, w, dw, cx, t, budget, []() {}, setup);
        pack_tok<3>(e, d); e[3] = rt0; e[7] = rt1;
      } else {
        ok = tok_pass<32, 0>(d, w, dw, cx, t, budget, []() {}, setup);
        pack_tok<4>(e, d);
      }
      mem_pass(False());
    }
    {
      RPROF(2 + wg * 12);
      auto wo_ready = [&]() { if (t == 0) mbar_wait(sb + B_WO, 0, budget); if (t < NSTEP - 1) mbar_wait(sb + B_WT, t & 1, budget); };
      constexpr float SC = 0.08838834764831845f * 1.4426950408889634f;
      if (!att) wo_ready();
      else {
        float s[32];
        setup(3);
        if (wg) {
          uint32_t one[4];
#pragma unroll
          for (int i = 0; i < 4; i++) one[i] = 0x3F803F80u + (pw >> 31);
          mbar_wait_cluster(sb + B_AT, seg & 1, budget);
          mbar_wait_cluster(sb + B_AB, seg & 1, budget);
          fence_proxy_async();
          RPROF(3 + 12);
          wg_fence(); seq_s<D_QM, 0>(s); wg_commit();
          nbar_arrive<NB_P, 256>();
          if (warp == 1) sts32(pw + 640, 0);
          mbar_wait_cluster(sb + B_AV, seg & 1, budget);
          wg_wait<0>();
          float mx = fmaxf(fmaxf(fmaxf(s[0], s[1]), fmaxf(s[4], s[5])), fmaxf(fmaxf(fmaxf(s[8], s[9]), fmaxf(s[12], s[13])), fmaxf(s[16], s[17])));
          const float x1 = __shfl_xor_sync(0xffffffffu, mx, 1), x2 = __shfl_xor_sync(0xffffffffu, mx, 2), x3 = __shfl_xor_sync(0xffffffffu, mx, 3);
          const float u = (warp & 2) ? ((warp & 1) ? s[16] : s[12]) : ((warp & 1) ? s[8] : s[4]);
          const float v = (warp & 2) ? ((warp & 1) ? s[17] : s[13]) : ((warp & 1) ? s[9] : s[5]);
          const float ms = -SC * fmaxf(fmaxf(mx, x1), fmaxf(x2, x3));
          sts32(pw + 128 + warp * 128, pack_bf16(ex2(fmaf(u, SC, ms)), ex2(fmaf(v, SC, ms))));
          if (warp == 0) sts32(pw, pack_bf16(ex2(fmaf(s[0], SC, ms)), ex2(fmaf(s[1], SC, ms))));
          fence_proxy_async();
          nbar_sync<NB_W1, 128>();
          RPROF(4 + 12);
          wg_fence();
          rs8<0, 0, D_P>(s + 8, one); rs8<1, 0, D_P + 16>(s + 8, one); rs8<1, 0, D_P + 32>(s + 8, one);
          wg_commit();
          ss8<0, 0, 0, D_V, D_P>(s, 0); ss8<0, 0, 0, D_V + 320, D_P>(s + 4, 0);
          ss8<1, 0, 0, D_V + 16, D_P + 16>(s, 0); ss8<1, 0, 0, D_V + 336, D_P + 16>(s + 4, 0);
          ss8<1, 0, 0, D_V + 32, D_P + 32>(s, 0); ss8<1, 0, 0, D_V + 352, D_P + 32>(s + 4, 0);
          wg_commit();
          wg_wait<1>();
          const float i0 = rcp(s[8]), i1 = rcp(s[9]);
          wg_wait<0>();
          stsm4(sb + oo, pack_bf16(s[0] * i0, s[1] * i1), pack_bf16(s[2] * i0, s[3] * i1), pack_bf16(s[4] * i0, s[5] * i1), pack_bf16(s[6] * i0, s[7] * i1));
          __syncwarp();
          const uint4 y = lds128v(sb + oo);
          if (t < NSTEP - 1) { st_async128(u0, y); st_async128(u1, y); e_complete_tx(sb + B_OB, 512); }
          wo_ready();
        } else {
          const int lim = (int)u1;
          char* const og = (char*)u0;
          nbar_sync<NB_P, 256>();
          RPROF(3);
          wg_fence();
          seq_s<D_QT, 0>(s);
          wg_commit();
          mbar_wait_cluster(sb + B_AV, seg & 1, budget);
          wg_wait<0>();
#pragma unroll
          for (int i = 0; i < 8; i++) { float& v = s[4 + 4 * (i >> 1) + (i & 1)]; v = i <= lim ? v : -INFINITY; }
          float mx = fmaxf(fmaxf(fmaxf(s[0], s[1]), fmaxf(s[4], s[5])), fmaxf(fmaxf(fmaxf(s[8], s[9]), fmaxf(s[12], s[13])), fmaxf(s[16], s[17])));
          const float x1 = __shfl_xor_sync(0xffffffffu, mx, 1), x2 = __shfl_xor_sync(0xffffffffu, mx, 2), x3 = __shfl_xor_sync(0xffffffffu, mx, 3);
          const float ms = -SC * fmaxf(fmaxf(mx, x1), fmaxf(x2, x3));
#pragma unroll
          for (int i = 0; i < 10; i++) { float& v = s[4 * (i >> 1) + (i & 1)]; v = ex2(fmaf(v, SC, ms)); }
          const float sum = (((s[0] + s[1]) + (s[4] + s[5])) + ((s[8] + s[9]) + (s[12] + s[13]))) + (s[16] + s[17]);
          const float y1 = __shfl_xor_sync(0xffffffffu, sum, 1), y2 = __shfl_xor_sync(0xffffffffu, sum, 2), y3 = __shfl_xor_sync(0xffffffffu, sum, 3);
          const float inv = rcp((sum + y1) + (y2 + y3));
          stsm4(pw, pack_bf16(s[0] * inv, s[1] * inv), pack_bf16(s[4] * inv, s[5] * inv), pack_bf16(s[8] * inv, s[9] * inv), pack_bf16(s[12] * inv, s[13] * inv));
          stsm2(pw + 512, pack_bf16(s[16] * inv, s[17] * inv), 0);
          fence_proxy_async();
          nbar_sync<NB_W0, 128>();
          RPROF(4);
          wg_fence();
          ss32<0, 0, 0, D_V, D_P + 48>(s, 0); ss32<0, 0, 0, D_V + 320, D_P + 48>(s + 16, 0);
          ss32<1, 0, 0, D_V + 16, D_P + 64>(s, 0); ss32<1, 0, 0, D_V + 336, D_P + 64>(s + 16, 0);
          ss32<1, 0, 0, D_V + 32, D_P + 80>(s, 0); ss32<1, 0, 0, D_V + 352, D_P + 80>(s + 16, 0);
          wg_commit();
          wo_ready();
          wg_wait<0>();
#pragma unroll
          for (int i = 0; i < 4; i++) {
            const float* d = s + (i >> 1) * 16 + (i & 1) * 2;
            stg128(og + ((i >> 1) * 64 + (i & 1) * 8) * (SEQ * 2), pack_bf16(d[0], d[1]), pack_bf16(d[4], d[5]), pack_bf16(d[8], d[9]), pack_bf16(d[12], d[13]));
          }
          if ((seg & 3) == 3) nbar_arrive<NB_O, 160>();
        }
      }
      RPROF(5 + wg * 12);
      const bool three = wg == 1 || rank == 2;
      char* const p2 = p1 + (2 + ((t - LAG) & 1) - (t & 1)) * (int)sizeof(g_h1[0]);
      if (t < NSTEP - 1) {
        auto wo_pass = [&](auto dual_c) {
          constexpr bool DUAL = decltype(dual_c)::value;
          float c[24];
          const uint32_t dt = wg ? 0 : 3072;
          mbar_wait_cluster(sb + B_OB, t & 1, budget);
          fence_proxy_async();
          RPROF(6 + wg * 12);
          wg_fence(); seq_wo<DUAL, 0, 0>(c, dt); wg_commit(); seq_wo<DUAL, 1, 0>(c + 8, dt); wg_commit();
          mbar_wait(sb + B_XF, cx.par, budget);
          wg_wait<1>();
          if (warp == 2) load_x_lent(sb, &M, t + 1, wg ? 3 : 5);
          put_part(p1, p2, pack_part<DUAL>(c, t), t);
          const int o3 = (wo_tile(rank, wg, three ? 2 : 1) - wo_tile(rank, wg, 0)) * 32768;
          z1 = p1 + o3; z2 = p2 + o3;
          if (three) {
            wg_fence(); seq_wo<DUAL, 2, 0>(c + 16, dt); wg_commit();
            wg_wait<1>(); put_part(p1 + 6 * 32768, p2 + 6 * 32768, pack_part<DUAL>(c + 8, t), t);
            mbar_wait(sb + B_XF + 8, cx.par, budget);
            wg_wait<0>(); z = pack_part<DUAL>(c + 16, t);
          } else { mbar_wait(sb + B_XF + 8, cx.par, budget); wg_wait<0>(); z = pack_part<DUAL>(c + 8, t); }
        };
        if (t >= LAG && t < NSEG) wo_pass(True()); else wo_pass(False());
      } else break;
      RPROF(7 + wg * 12);
    }
  }
}

DEVI void wait_xa(const int* p, int& budget) {
  while (__any_sync(0xffffffffu, ldg_acq32(p) < 64) && --budget > 0) {}
  fence_proxy_global();
}
template<bool DUAL> DEVI void first_loads(uint32_t sb, const Maps* M, int n, int h, int rb, int& budget) {
  if (n >= LAG && ((n - LAG) & 3) == 0) e_prefetch_3d(&M->xs, 0, (n - LAG) * 32, h & 14);
  mbar_wait(sb + B_FA, n & 1, budget);
  load_x<DUAL, 0>(sb, M, n, rb); load_x<DUAL, 1>(sb, M, n, rb); load_x<DUAL, 2>(sb, M, n, rb);
}
template<bool DUAL> DEVI void lent_loads(uint32_t sb, const Maps* M, int n, int rb, int& budget) {
  mbar_wait(sb + B_FB, n & 1, budget);
  load_x<DUAL, 3>(sb, M, n, rb); load_x<DUAL, 4>(sb, M, n, rb); load_x<DUAL, 5>(sb, M, n, rb); load_x<DUAL, 6>(sb, M, n, rb);
}
DEVI void rec_comm(const uint32_t sb, const int warp, const Maps& M, const bf16* __restrict__ mem0) {
  const int lane = threadIdx.x & 31, h = cta_id() / 3, rb = cluster_rank() >= 3 ? 3 : 0, rank = cluster_rank() - rb;
  int budget = SPIN_BUDGET;
  const bool two = warp == 3 || (rank == 2 && warp == 2);
  const int ntask = two ? 2 : 1, qi = two ? (warp == 3 ? rank : 3) : rank * 3 + warp;
  const int task0 = two ? h * 2 + (qi >> 1) : 64 + h * 4 + (qi >> 1);
  auto h2_word = [&](int i, int ln) {
    const int task = task0 + i * 192;
    return (char*)g_h2 + (task >> 6) * 8192 + ((qi ^ i) & 1) * 4096 + ((task >> 2) & 15) * 256 + (task & 3) * 32 + (ln & 8) * 16 + (ln & 7) * 4;
  };
  auto first_x = [&](int t) {
    const int n = t + 1;
    p_expect_tx(sb + B_XF + (lane_id() & 7) * 8, 8192, lane_id() < 8);
    if (rb + rank == 0) {
      if (n >= LAG && ((n - LAG) & 3) == 0) wait_xa(&g_xa[1][(n - LAG) >> 2], budget);
      if (n >= LAG && n < NSEG) first_loads<true>(sb, &M, n, h, cluster_last(), budget); else first_loads<false>(sb, &M, n, h, cluster_last(), budget);
    }
  };
  {
    const int task = task0 + (lane >> 4) * 192, L = (task & 3) * 8 + (lane & 7);
    if ((lane >> 4) < ntask) {
      const bf16* p = mem0 + (L & 3) * 2 * DM + (task >> 2) * 16 + (L >> 2) + (lane & 8);
      uint32_t m0 = (uint32_t)__bfloat16_as_ushort(p[0]) | (uint32_t)__bfloat16_as_ushort(p[DM]) << 16;
      m0 = m0 ? m0 : 0x8000u;
      stg_rlx32(h2_word(lane >> 4, lane), ((qi ^ (lane >> 4)) & 1) ? 0 : m0);
      for (int i = 1; i < 4; i++) stg_rlx32(h2_word(lane >> 4, lane) + i * sizeof(g_h2[0]), 0);
      sts32(sb + M0 + warp * 128 + lane * 4, m0);
    }
    __syncwarp();
    nbar_sync<NB_ST, 384>();
    if (warp == 2) {
      e_expect_tx(sb + B_WS, 2 * WSZ);
#pragma unroll 1
      for (int i = 0; i < 2 * (64 - KR); i++) e_tma_2d(sb + WS + (i & 1) * WSZ + (i >> 1) * 2048, &M.w[rank], h * DH + (i & 1) * 64, k_of_smem(i >> 1) * 16, sb + B_WS);
      const int nt = rank == 2 ? 6 : 5;
      e_expect_tx(sb + B_WO, (nt - 2) * 16384);
#pragma unroll 1
      for (int i = 1; i < nt; i++) if (i != 3) e_tma_2d(sb + WO + i * 16384, &M.wo, wo_tile(rank, 1 - i / 3, i % 3) * 64, h * DH, sb + B_WO);
    }
    wait_xa(&g_xa[0][0], budget);
    if (warp == 3) { first_x(-1); if (rb + rank == 0) lent_loads<false>(sb, &M, 0, cluster_last(), budget); }
  }
  uint32_t cpp = 0;
  const uint32_t cp = sb + B_CP + warp * 8;
  uint32_t f_dst, f_chk, f_bar, f_time = gtime() - 4000;
  const char *f_src, *f_xr;
  auto prepare = [&](int s) {
    const int ck = warp ^ (warp < 2 && (s < LAG || s >= NSEG) && (rank & 1) == (s >= NSEG)), ln = lane_id();
    f_dst = sb + RING + mslot(ck); f_chk = f_dst + ln * 32 + (ln >> 2) * 4; f_bar = sb + ck * 8;
    f_src = (const char*)g_h2[s & 3] + ck * 8192 + (s >= NSEG ? 4096 : 0);
    f_xr = (const char*)g_xr[(s + 1) & 63] + ck * 4096;
    pin2(f_chk, 0u);
    return s <= LAG ? TP(9) + ck * TP(11) : s <= NSEG ? TP(1) + ck * TP(4) : TP(13) + ck * TP(11);
  };
  prepare(0);
#pragma unroll 1
  for (int t = 0;; t++) {
    const int n = t + 1;
    const bool dual = t >= LAG && t < NSEG;
    RPROF_STEP;
    {
      const uint32_t bytes = dual ? 8192 : 4096;
      e_expect_tx(cp, bytes + (n < NSEG ? 4096 : 0));
      mbar_wait(f_bar + B_ME, t & 1, budget);
      if (n < NSEG) e_bulk_g2s(f_dst + 8192, f_xr, 4096, cp);
      wait_time(f_time);
      RPROF(24); CPROF(0, gtime());
      int tries = 0;
      while (true) {
        tries++;
        e_bulk_g2s(f_dst, f_src, bytes, cp);
        mbar_wait(cp, cpp, budget); cpp ^= 1;
        uint32_t mn = min(min(lds32v(f_chk), lds32v(f_chk + 1024)), min(lds32v(f_chk + 2048), lds32v(f_chk + 3072)));
        if (dual) mn = min(min(mn, min(lds32v(f_chk + 4096), lds32v(f_chk + 5120))), min(lds32v(f_chk + 6144), lds32v(f_chk + 7168)));
        if (!__any_sync(0xffffffffu, mn == 0) || --budget < 0) break;
        e_expect_tx(cp, bytes);
      }
      e_arrive(f_bar + B_MF);
      RPROF(25); CPROF(1, gtime()); CPROF(2, tries);
    }
    const int seg = t - rank * LAG;
    const bool att = rank < 2 && (unsigned)seg < (unsigned)NSEG;
    auto block_done = [&]() {
      if (warp == 1 && att && (seg & 3) == 3) { nbar_sync<NB_O, 160>(); e_flag_add(&g_dep[E_O1 + rank * 16 + (seg >> 2)]); }
    };
    if (warp == 0) {
      if (att) { e_expect_tx(sb + B_AT, 16384); e_expect_tx(sb + B_AB, 4096); e_expect_tx(sb + B_AV, 10240); }
      if (n < NSTEP) e_expect_tx(sb + B_OB, dual ? 4096 : 2048);
    }
    if (n + 1 < NSEG && (n & 3) == 3) wait_xa(&g_xa[0][(n + 1) >> 2], budget);
    if (rank == 2 && warp == 1) {
      if (h < 16 ? n < NSEG : n > LAG && n < NSTEP && ((n - LAG) & 3)) e_prefetch_3d(&M.xs, 0, (h < 16 ? n : n - LAG) * 32, (h & 7) * 2);
      if (h >= 16 && n + 1 < NSEG) asm volatile(ELECT "cp.async.bulk.prefetch.L2.global [%0], 2048;}" :: "l"((const char*)g_xr[n + 1] + (h & 7) * 2048) : "memory");
    }
    {
      const int ln = lane_id(), i = ln >> 4;
      char* const w = h2_word(i, ln);
      if (i < ntask) {
        stg_rlx32(w + ((t + 3) & 3) * sizeof(g_h2[0]), 0);
        if (n == LAG && ((qi ^ i) & 1)) stg_rlx32(w + (n & 3) * sizeof(g_h2[0]), lds32v(sb + M0 + warp * 128 + ln * 4));
      }
      __syncwarp();
    }
    if (n < NSTEP) {
      const uint32_t tag = (n >> 1) & 31;
      mbar_wait(sb + B_PD, t & 1, budget);
      uint32_t t0 = clock32();
      if (warp == 2) {
        e_expect_tx(sb + B_WT, 32768);
        e_tma_2d(sb + WO + 49152, &M.wo, wo_tile(rank, 0, 0) * 64, h * DH, sb + B_WT);
        mbar_wait(sb + B_WE, t & 1, budget);
        e_tma_2d(sb + WO, &M.wo, wo_tile(rank, 1, 0) * 64, h * DH, sb + B_WT);
      }
      if (warp == 3) first_x(t);
      if (warp == 0 && rank == (t >= NSEG)) { mbar_wait(sb + B_AB, seg & 1, budget); e_stg_rlx32(&g_ts[t & 1][h], (gtime() & ~31u) | tag); }
      const int fd = prepare(n), ln = lane_id();
      const int sa = t - (qi & 1) * LAG, sc = t - (~qi & 1) * LAG;
      const int i0 = (unsigned)sa < (unsigned)(NSEG - 1) ? 0 : 1, i1 = two && (unsigned)sc < (unsigned)(NSEG - 1) ? 2 : 1;
      const char* src = (const char*)g_h1[(qi & 1) * 2 + (sa & 1)] + task0 * 2048 + ln * 8;
      char* dst = h2_word(0, ln) + (n & 3) * sizeof(g_h2[0]);
      const int ds = ((~qi & 1) * 2 + (sc & 1) - (qi & 1) * 2 - (sa & 1)) * (int)sizeof(g_h1[0]) + 192 * 2048, dd = 3 * 8192 + ((qi & 1) ? -4096 : 4096);
      if (i0) { src += ds; dst += dd; }
      pin2(src, dst);
      spin_until(t0, TSD);
      uint32_t v0;
      do { v0 = ldg_rlx32(&g_ts[t & 1][ln]); } while (__any_sync(0xffffffffu, (v0 & 31) != tag) && --budget > 0);
      const uint32_t now = __shfl_sync(0xffffffffu, v0, 0);
      t0 = now + __reduce_max_sync(0xffffffffu, (int)(v0 - now));
      f_time = t0 + fd;
      RPROF(26); CPROF(3, t0);
      block_done();
      t0 += t < LAG ? TP(8) : t < NSEG ? TP(0) : TP(12);
#pragma unroll 1
      for (int i = i0; i < i1; i++) {
        const uint32_t tg = h1_tag(i ? sc : sa);
        uint2 v[8];
        wait_time(t0 + (!two ? 0 : i ? TP(3) : -TP(10)));
        int tries = 0;
        float a[4];
        while (true) {
          tries++;
#pragma unroll
          for (int k = 0; k < 8; k++) v[k] = ldg_rlx64(src + k * 256);
          asm volatile("{.reg .pred p; setp.eq.s32 p, %0, 0x7fffffff; @p exit;}" :: "r"(budget) : "memory");
          uint32_t bad = 0;
#pragma unroll
          for (int k = 0; k < 8; k++) {
            bad = xor_or(v[k].x, tg, bad);
            a[0] = k ? a[0] + bf_lo(v[k].x) : bf_lo(v[k].x); a[1] = k ? a[1] + bf_hi(v[k].x) : bf_hi(v[k].x);
            a[2] = k ? a[2] + bf_lo(v[k].y) : bf_lo(v[k].y); a[3] = k ? a[3] + bf_hi(v[k].y) : bf_hi(v[k].y);
          }
#pragma unroll
          for (int k = 0; k < 2; k++) {
            const float keep = (ln & 8) ? a[2+k] : a[k], send = (ln & 8) ? a[k] : a[2+k];
            a[k] = keep + __shfl_xor_sync(0xffffffffu, send, 8);
          }
#pragma unroll
          for (int k = 0; k < 2; k++) a[k] += __shfl_xor_sync(0xffffffffu, a[k], 16);
          if (!__any_sync(0xffffffffu, bad & 1) || --budget < 0) break;
        }
        const uint32_t out = pack_bf16(a[0], a[1]);
        if (ln < 16) stg_rlx32(dst, out ? out : 0x8000u);
        __syncwarp();
        src += ds; dst += dd;
        if (i == 0) { RPROF(28); CPROF(6, gtime()); CPROF(4, gtime()); CPROF(5, tries); } else CPROF(7, gtime());
      }
    }
    if (n == NSTEP) { cluster_arrive(); block_done(); }
    if (n == NSTEP) break;
  }
  if (h == 0 && rank == 0 && warp < 2) g_xa[warp][lane_id()] = 0;
}
}

__global__ void __launch_bounds__(384, 1)
rec_kernel(const __grid_constant__ rec::Maps M, const bf16* __restrict__ mem0) {
  using namespace rec;
  extern __shared__ __align__(1024) uint8_t smem[];
  const uint32_t sb = __shfl_sync(0xffffffffu, smem_u32(smem), 0);
  const int tid = threadIdx.x, wi = __shfl_sync(0xffffffffu, tid >> 5, 0);
  if ((sb & 0x3FFFF) != SMEM_BASE) __trap();
  if (wi == 0) {
    const int h = cta_id() / 3, rank = cta_id() - h * 3;
    const int nwg = 2 * cluster_last() + 2;
    for (int i = tid; i < NBAR; i += 32) mbar_init(sb + BARS + i * 8, i < 13 ? nwg : i < 19 ? 2 : 1);
    ((uint32_t*)(smem + PAD))[tid] = 0;
    fence_mbar_init(); fence_proxy_async();
    __syncwarp();
    e_expect_tx(sb + B_ST, STG); e_expect_tx(sb + B_ST + 8, STG);
    for (int i = 0; i < 2 * KR; i++) e_tma_2d(sb + (i & 1) * STG + (i >> 1) * 2048, &M.w[rank], h * DH + (i & 1) * 64, k_of_reg(i >> 1) * 16, sb + B_ST + (i & 1) * 8);
  } else if (wi == 1) {
    if (blockIdx.x < NEV / 32) { g_dep[blockIdx.x * 32 + (tid & 31)] = 0; g_claim[blockIdx.x * 32 + (tid & 31)] = 0; __threadfence(); }
    __syncwarp();
    asm volatile("griddepcontrol.launch_dependents;" ::: "memory");
  } else if (wi == 2) {
    if ((tid & 31) < 3) asm volatile("prefetch.tensormap [%0];" :: "l"(&M.wo + (tid & 31)) : "memory");
    __syncwarp();
  }
  cluster_arrive(); cluster_wait();
  if (wi < 8) { reg_inc<232>(); rec_math(sb, wi, M); cluster_arrive(); cluster_wait(); }
  else { reg_dec<40>(); rec_comm(sb, wi & 3, M, mem0); cluster_wait(); }
}

namespace gm {
struct Maps { CUtensorMap ot, wo, xn, wg, wu, hl, hs, wd, out; };
constexpr int STAGES = 6, STAGE = 32768;
constexpr uint32_t SO = STAGES * STAGE, BARS = SO + 32768;
constexpr uint32_t B_FULL = BARS, B_EMPTY = BARS + 48, B_TF = BARS + 96, B_TE = BARS + 112, B_ORD = BARS + 128, B_PM = BARS + 144, B_GO = BARS + 160, B_SF = BARS + 168;
constexpr uint32_t MAIL = BARS + 176, PMAIL = BARS + 192;
constexpr uint32_t SMEM = BARS + 256;
constexpr int END = -1;
#define DQ 8
#define GT gtime

struct Tile {
  bool isO, isG, l2; int blk, col, k0, n;
  DEVI Tile(int task, int rank) {
    const int e = task >> 8, id = task & 255;
    const bool isD = e < E_G1 || e >= E_D2;
    isO = e >= E_O1 && e < E_G2; isG = !isD && !isO; l2 = e >= E_O2;
    blk = l2 && !isO ? (e & 7) * 2 + rank : isD ? e >> 1 : e & 15;
    col = l2 && !isO ? id : (isG ? id : id & 3) * 2 + rank;
    k0 = isO ? (id >> 2) * 2048 : isG ? 0 : ((l2 ? e >> 3 : e) & 1) * 1792;
    n = isO ? 32 : isG ? 16 : 28;
    if (e >= E_D2 + DQ) { n = 14; k0 += (id >> 3) * 896; col = id & 7; }
  }
};

DEVI float geglu(float g, float u) {
  const float z = g * (0.7978845608028654f + 0.035677408136300125f * g * g);
  float t; asm("tanh.approx.f32 %0, %1;" : "=f"(t) : "f"(z));
  const float hg = 0.5f * g;
  return fmaf(hg, t, hg) * u;
}
struct Sched {
  int need, size, e;
  bool filler;
  uint4 dep, cl;
  DEVI void init(int lane) {
    e = (lane < 4 ? lane + 12 : lane < 16 ? lane - 4 : lane) * 4;
    const bool d = e < E_G1 || e >= E_D2, o = e >= E_O1 && e < E_G2;
    need = e >= E_D2 ? 56 : d ? 28 : e < E_O1 ? 64 : o ? 32 : 128;
    size = e >= E_D2 ? (e < E_D2 + DQ ? 8 : e < E_D2 + 16 ? 16 : 0) : d ? 4 : o ? 8 : e < E_O1 ? 28 : e < E_G2 + 8 ? 56 : 0;
    filler = (int)blockIdx.x >= TP(5);
  }
  DEVI void scan(int lane) { cl = ldg_rlx128(g_claim + e); dep = ldg_rlx128(g_dep + e); }
  DEVI int next(int lane, int& budget) {
    while (--budget > 0) {
      int av[4], open = 0;
#pragma unroll
      for (int i = 0; i < 4; i++) { const int r = max(size - (int)(&cl.x)[i], 0); open |= r; av[i] = ((int)(&dep.x)[i] >= need ? r : 0) + (i ? av[i - 1] : 0); }
      const uint32_t mo = __ballot_sync(0xffffffffu, open);
      if (!mo) break;
      if (filler) {
        const int x = TP(6) & 3, dx = x == 0 ? dep.x : x == 1 ? dep.y : x == 2 ? dep.z : dep.w;
        filler = !__any_sync(0xffffffffu, e == ((E_O1 + TP(6)) & ~3) && dx >= need);
      }
      if (!filler && (mo & 0xffff) && lane >= E_O2 / 4) av[3] = 0;
      int inc = av[3], pos = 0;
      while (true) {
        const uint32_t m = __ballot_sync(0xffffffffu, inc > pos && av[3]);
        if (!m) break;
        const int l = __ffs(m) - 1, rel = pos - (inc - av[3]), i = (rel >= av[0]) + (rel >= av[1]) + (rel >= av[2]);
        int r = 0;
        if (lane == l) {
          const int tk = atomicAdd(g_claim + e + i, 1);
          r = tk < size ? (e + i) << 8 | tk : -1 - (inc - av[3] + (i == 0 ? av[0] : i == 1 ? av[1] : i == 2 ? av[2] : av[3]) + tk - size);
        }
        r = __shfl_sync(0xffffffffu, r, l);
        if (r >= 0) return r;
        if (pos == 0) {
#pragma unroll
          for (int o = 1; o < 32; o <<= 1) { const int v = __shfl_up_sync(0xffffffffu, inc, o); if (lane >= o) inc += v; }
        }
        pos = -1 - r;
      }
      if (pos == 0) __nanosleep(TP(7));
      scan(lane);
    }
    return END;
  }
};

DEVI void scheduler(const uint32_t sb) {
  const int lane = threadIdx.x & 31;
  int budget = SPIN_BUDGET;
  Sched sc; sc.init(lane);
#pragma unroll 1
  for (int i = 0;; i++) {
    if (i) mbar_wait(sb + B_GO, (i & 1) ^ 1, budget);
    sc.scan(lane);
    if (i == 0) cluster_wait();
    const int task = sc.next(lane, budget);
    const uint32_t r = mapa(sb, lane & 1);
    if (lane < 2) st_async32(r + PMAIL + (i & 1) * 4, task, r + B_PM + (i & 1) * 8);
    __syncwarp();
    if (task == END) break;
  }
}

DEVI void producer(const uint32_t sb, const Maps& M) {
  const int lane = threadIdx.x & 31, rank = cluster_rank();
  int budget = SPIN_BUDGET, s = 0, ph = 0;
#pragma unroll 1
  for (int i = 0;; i++) {
    e_expect_tx(sb + B_PM + (i & 1) * 8, 4);
    mbar_wait_cluster(sb + B_PM + (i & 1) * 8, (i >> 1) & 1, budget);
    const int task = budget < 0 ? END : __shfl_sync(0xffffffffu, (int)lds32v(sb + PMAIL + (i & 1) * 4), 0);
    fence_proxy_global();
    for (int z = 0; z < (task == END ? 2 : 1); z++) {
      const int g = (i + z) & 1;
      mbar_wait(sb + B_TE + g * 8, (((i + z) >> 1) & 1) ^ 1, budget);
      if (lane == 0) { sts64(sb + MAIL + g * 8, task, s | ph << 8); mbar_arrive(sb + B_TF + g * 8); }
      __syncwarp();
    }
    if (task == END) break;
    const Tile T(task, rank);
    const bool shareB = T.l2 && !T.isO;
    const CUtensorMap* mA = T.isO ? &M.ot : T.isG ? &M.xn : &M.hl;
    const CUtensorMap* mB0 = T.isO ? &M.wo : T.isG ? &M.wg : &M.wd;
    const CUtensorMap* mB1 = T.isG ? &M.wu : mB0;
    const int c0 = T.col * (T.isG ? 64 : 128), c1 = T.isG ? c0 : c0 + 64, row = T.blk * 128;
    const int ok = 0;
    int k = T.k0;
#pragma unroll 1
    for (int it = 0; it < T.n; it++, k += 64) {
      const uint32_t a = sb + s * STAGE, fb = sb + B_FULL + s * 8;
      mbar_wait(sb + B_EMPTY + s * 8, ph ^ 1, budget);
      e_expect_tx(fb, STAGE);
      if (shareB) {
        e_tma_2d_mc(a + 16384 + rank * 8192, rank ? mB1 : mB0, rank ? c1 : c0, k, fb);
        e_tma_2d(a, mA, k, row, fb); e_tma_2d(a + 8192, mA, k, row + 64, fb);
      } else {
        e_tma_2d_mc(a + rank * 8192, mA, T.isO ? row + rank * 64 : k, T.isO ? k + ok : row + rank * 64, fb);
        e_tma_2d(a + 16384, mB0, c0, k, fb); e_tma_2d(a + 24576, mB1, c1, k, fb);
      }
      if (it == T.n - TP(2)) e_arrive(sb + B_GO);
      if (++s == STAGES) { s = 0; ph ^= 1; }
    }
  }
}

template<int TA> DEVI void mainloop(float* d0, float* d1, uint32_t sb, int n, int s, int ph, bool lead, uint32_t ord, int& budget) {
  int prev = 0;
  const uint32_t rel = threadIdx.x & 127;
#pragma unroll 1
  for (int i = 0; i < n; i++) {
    mbar_wait(sb + B_FULL + s * 8, ph, budget);
    const uint32_t a = sb + s * STAGE;
    const uint64_t da = mkdesc(a, 16, 1024), db = mkdesc(a + 16384, 8192, 1024);
    wg_fence();
#pragma unroll
    for (int k = 0; k < 4; k++) {
      wgmma_n128<TA>(d0, da + k * (TA ? 128 : 2), db + k * 128, (i | k) != 0);
      wgmma_n128<TA>(d1, da + 512 + k * (TA ? 128 : 2), db + k * 128, (i | k) != 0);
    }
    wg_commit();
    if (i > 0) { wg_wait<1>(); p_arrive_at(sb + B_EMPTY + prev * 8, rel & 1, rel < 2); }
    prev = s;
    if (++s == STAGES) { s = 0; ph ^= 1; }
  }
  p_arrive(ord, lead);
  wg_wait<0>();
  p_arrive_at(sb + B_EMPTY + prev * 8, rel & 1, rel < 2);
}

DEVI void consumer(const uint32_t sb, const Maps& M, const int wg) {
  const int tid = threadIdx.x, lane = tid & 31, warp = (tid >> 5) & 3;
  const bool lead = (tid & 127) == 0;
  const uint32_t so = sb + SO;
  int budget = SPIN_BUDGET;
  float d0[64], d1[64];
#pragma unroll 1
  for (int m = 0;; m++) {
    mbar_wait(sb + B_TF + wg * 8, m & 1, budget);
    const uint2 mail = lds64v(sb + MAIL + wg * 8);
    const int task = __shfl_sync(0xffffffffu, (int)mail.x, 0), pos = __shfl_sync(0xffffffffu, (int)mail.y, 0);
    e_arrive(sb + B_TE + wg * 8);
    if (task == END || budget < 0) break;
    const Tile T(task, cluster_rank());
    mbar_wait(sb + B_ORD + wg * 8, (m & 1) ^ wg ^ 1, budget);
    if (T.isO) mainloop<1>(d0, d1, sb, T.n, pos & 255, pos >> 8, lead, sb + B_ORD + (wg ^ 1) * 8, budget);
    else mainloop<0>(d0, d1, sb, T.n, pos & 255, pos >> 8, lead, sb + B_ORD + (wg ^ 1) * 8, budget);
    mbar_wait(sb + B_SF, wg ^ 1, budget);
    const uint32_t st = so + (warp * 16 + (lane & 15)) * 128;
    if (T.isG) {
      int* const fl = &g_dep[T.l2 ? E_D2 + (T.col >= 28) * 8 + (T.blk >> 1) : E_D1 + T.blk * 2 + (T.col >= 28)];
#pragma unroll
      for (int mm = 0; mm < 2; mm++) {
        const float* d = mm ? d1 : d0;
#pragma unroll
        for (int c = 0; c < 4; c++) {
          uint32_t r[4];
#pragma unroll
          for (int i = 0; i < 4; i++) r[i] = pack_bf16(geglu(d[8*c+2*i], d[32+8*c+2*i]), geglu(d[8*c+2*i+1], d[33+8*c+2*i]));
          stsm4(st + mm * 8192 + (((2 * c + (lane >> 4)) ^ (lane & 7)) << 4), r[0], r[1], r[2], r[3]);
        }
      }
      fence_proxy_async();
      nbar_sync_r(1 + wg, 128);
      if (lead) {
        tma_store_2d(&M.hs, so, T.col * 64, T.blk * 128);
        bulk_commit();
        bulk_wait<0>();
        mbar_arrive(sb + B_SF);
        flag_add(fl);
      }
    } else {
#pragma unroll
      for (int hf = 0; hf < 2; hf++) {
#pragma unroll
        for (int mm = 0; mm < 2; mm++) {
          const float* d = (mm ? d1 : d0) + hf * 32;
#pragma unroll
          for (int c = 0; c < 4; c++)
            stsm4(st + hf * 16384 + mm * 8192 + (((2 * c + (lane >> 4)) ^ (lane & 7)) << 4), pack_bf16(d[8*c], d[8*c+1]), pack_bf16(d[8*c+2], d[8*c+3]),
                  pack_bf16(d[8*c+4], d[8*c+5]), pack_bf16(d[8*c+6], d[8*c+7]));
        }
        fence_proxy_async();
        nbar_sync_r(1 + wg, 128);
        if (lead) { tma_radd_2d(&M.out, so + hf * 16384, T.col * 128 + hf * 64, T.blk * 128); bulk_commit(); }
      }
      if (lead) {
        bulk_wait<0>();
        mbar_arrive(sb + B_SF);
        if (T.isO || !T.l2) flag_add(&g_dep[(!T.isO ? E_LX2 : T.l2 ? E_LX1B : E_LX1A) + T.blk]);
      }
    }
    __syncwarp();
  }
}

DEVI void norm_helper(const bf16* __restrict__ x, bf16* out) {
  const int lane = threadIdx.x & 31;
  int budget = SPIN_BUDGET, tk = lane < 4 ? -1 : 1024;
#pragma unroll 1
  while (--budget > 0) {
    if (tk < 0) tk = atomicAdd(g_claim + E_LI + lane, 1);
    if (__all_sync(0xffffffffu, tk >= 1024)) break;
    const uint32_t m = __ballot_sync(0xffffffffu, tk < 1024 && (lane == 0 || ldg_acq32(g_dep + E_LI + lane * 16 + (tk >> 6)) >= 16));
    if (!m) { __nanosleep(TP(7)); continue; }
    const int ql = __ffs(m) - 1, task = __shfl_sync(0xffffffffu, tk, ql), q = E_LI + ql * 16, ev = task >> 6;
    if (lane == ql) tk = -1;
    const size_t off = (size_t)task * (DM * 4) + lane * 16;
    const char* src = (const char*)(q == E_LI ? x : out) + off;
    uint4 u[8];
#pragma unroll
    for (int i = 0; i < 8; i++) u[i] = ldg_rlx128(src + i * 512);
    if (q == E_LI) {
#pragma unroll
      for (int i = 0; i < 8; i++) stg128((char*)out + off + i * 512, u[i].x, u[i].y, u[i].z, u[i].w);
    }
    int* const fl = q == E_LI ? &g_xa[0][ev] : q == E_LX2 ? &g_xa[1][ev] : &g_dep[q == E_LX1A ? E_G1 + ev : E_G2 + (ev >> 1)];
    float mean[2], rs[2];
#pragma unroll
    for (int r = 0; r < 2; r++) {
      float s0 = 0, s1 = 0;
#pragma unroll
      for (int i = 0; i < 16; i++) { const uint32_t v = (&u[4*r + (i >> 2)].x)[i & 3]; s0 += bf_lo(v); s1 += bf_hi(v); }
      mean[r] = (s0 + s1) * (1.f / 32);
      s0 = s1 = 0;
#pragma unroll
      for (int i = 0; i < 16; i++) { const uint32_t v = (&u[4*r + (i >> 2)].x)[i & 3]; const float a = bf_lo(v) - mean[r], b = bf_hi(v) - mean[r]; s0 = fmaf(a, a, s0); s1 = fmaf(b, b, s1); }
      rs[r] = s0 + s1;
    }
    {
      const bool hi = lane & 16;
      float m1 = hi ? mean[1] : mean[0], q1 = hi ? rs[1] : rs[0], m2 = hi ? mean[0] : mean[1], q2 = hi ? rs[0] : rs[1], cnt = 16;
#pragma unroll
      for (int o = 16; o; o >>= 1) {
        m2 = __shfl_xor_sync(0xffffffffu, m2, o); q2 = __shfl_xor_sync(0xffffffffu, q2, o);
        const float dl = m1 - m2;
        q2 = q1 = fmaf(dl * dl, cnt, q1 + q2); m2 = m1 = 0.5f * (m1 + m2);
        cnt *= 2;
      }
      q1 = rsqrtf(q1 * (1.f / DM) + 1e-5f);
      m2 = __shfl_xor_sync(0xffffffffu, m1, 16); q2 = __shfl_xor_sync(0xffffffffu, q1, 16);
      mean[0] = hi ? m2 : m1; mean[1] = hi ? m1 : m2; rs[0] = hi ? q2 : q1; rs[1] = hi ? q1 : q2;
    }
#pragma unroll
    for (int i = 0; i < 8; i++) {
      uint32_t y[4];
#pragma unroll
      for (int c = 0; c < 4; c++) { const uint32_t v = (&u[i].x)[c]; y[c] = pack_bf16((bf_lo(v) - mean[i >> 2]) * rs[i >> 2], (bf_hi(v) - mean[i >> 2]) * rs[i >> 2]); }
      stg128((char*)g_xn + off + i * 512, y[0], y[1], y[2], y[3]);
      u[i] = make_uint4(y[0], y[1], y[2], y[3]);
    }
    if (q == E_LI && (task & 15) >= 12) {
      uint32_t* const xr = g_xr[task >> 4] + lane * 32 + (task & 3);
#pragma unroll
      for (int i = 0; i < 16; i++) {
        const uint32_t a = (&u[i >> 2].x)[i & 3], b = (&u[4 + (i >> 2)].x)[i & 3];
        xr[(i >> 2) * 1024 + (i & 3) * 8] = __byte_perm(a, b, 0x5410); xr[(i >> 2) * 1024 + (i & 3) * 8 + 4] = __byte_perm(a, b, 0x7632);
      }
    }
    fence_proxy_global();
    __syncwarp();
    if (lane == 0) flag_add(fl);
    __syncwarp();
  }
}
}

__global__ void __cluster_dims__(2, 1, 1) __launch_bounds__(384, 1)
gemm_kernel(const __grid_constant__ gm::Maps M, const bf16* __restrict__ x, bf16* out) {
  using namespace gm;
  extern __shared__ __align__(1024) uint8_t smem[];
  const uint32_t sb = __shfl_sync(0xffffffffu, smem_u32(smem), 0);
  const int tid = threadIdx.x, wi = __shfl_sync(0xffffffffu, tid >> 5, 0);
  if (tid < 22) mbar_init(sb + BARS + tid * 8, tid == 14 || tid == 15 ? 4 : tid >= 6 && tid < 12 ? 2 : 1);
  fence_mbar_init();
  if (tid >= 256 && tid < 265) asm volatile("prefetch.tensormap [%0];" :: "l"(&M.ot + (tid - 256)) : "memory");
  __syncwarp();
  cluster_arrive();
  const bool sched = wi == 11 && cluster_rank() == 0;
  if (!sched) cluster_wait();
  if (wi < 8) { reg_inc<208>(); consumer(sb, M, wi >> 2); cluster_arrive(); cluster_wait(); }
  else {
    reg_dec<88>();
    if (wi == 8) producer(sb, M);
    else if (sched) scheduler(sb);
    else {
      norm_helper(x, out);
      asm volatile("griddepcontrol.wait;" ::: "memory");
    }
    __syncwarp();
    cluster_arrive(); cluster_wait();
  }
}

typedef CUresult (*PFN_encodeTiled)(CUtensorMap*, CUtensorMapDataType, cuuint32_t, void*, const cuuint64_t*, const cuuint64_t*,
                                    const cuuint32_t*, const cuuint32_t*, CUtensorMapInterleave, CUtensorMapSwizzle,
                                    CUtensorMapL2promotion, CUtensorMapFloatOOBfill);
static PFN_encodeTiled g_encode = nullptr;
static CUtensorMap make_map(const void* ptr, uint64_t rows, uint64_t cols, uint32_t box_rows, CUtensorMapL2promotion pr = CU_TENSOR_MAP_L2_PROMOTION_L2_256B) {
  CUtensorMap m;
  cuuint64_t dims[2] = {cols, rows}, strides[1] = {cols * 2};
  cuuint32_t box[2] = {64, box_rows}, es[2] = {1, 1};
  g_encode(&m, CU_TENSOR_MAP_DATA_TYPE_BFLOAT16, 2, (void*)ptr, dims, strides, box, es, CU_TENSOR_MAP_INTERLEAVE_NONE,
           CU_TENSOR_MAP_SWIZZLE_128B, pr, CU_TENSOR_MAP_FLOAT_OOB_FILL_NONE);
  return m;
}

static CUtensorMap make_map3(const void* ptr, uint64_t d0, uint64_t d1, uint64_t d2, uint64_t stride2) {
  CUtensorMap m;
  cuuint64_t dims[3] = {d0, d1, d2}, strides[2] = {DM * 2, stride2};
  cuuint32_t box[3] = {64, 32, 2}, es[3] = {1, 1, 1};
  g_encode(&m, CU_TENSOR_MAP_DATA_TYPE_BFLOAT16, 3, (void*)ptr, dims, strides, box, es, CU_TENSOR_MAP_INTERLEAVE_NONE,
           CU_TENSOR_MAP_SWIZZLE_128B, CU_TENSOR_MAP_L2_PROMOTION_L2_256B, CU_TENSOR_MAP_FLOAT_OOB_FILL_NONE);
  return m;
}

extern "C" void kernel_launch(void* const* d_in, const int* in_sizes, int n_in, void* d_out, int out_size) {
  const bf16* x = (const bf16*)d_in[0];
  const bf16* mem0 = (const bf16*)d_in[1];
  if (!g_encode) {
    void* p = nullptr; cudaDriverEntryPointQueryResult q;
    cudaGetDriverEntryPoint("cuTensorMapEncodeTiled", &p, cudaEnableDefault, &q);
    g_encode = (PFN_encodeTiled)p;
    cudaFuncSetAttribute(gemm_kernel, cudaFuncAttributeMaxDynamicSharedMemorySize, gm::SMEM);
    cudaFuncSetAttribute(rec_kernel, cudaFuncAttributeMaxDynamicSharedMemorySize, rec::SMEM);
  }
  bf16 *xn, *ot, *hh;
  cudaGetSymbolAddress((void**)&xn, g_xn); cudaGetSymbolAddress((void**)&ot, g_ot); cudaGetSymbolAddress((void**)&hh, g_h);
  rec::Maps R;
  for (int i = 0; i < 3; i++) R.w[i] = make_map(d_in[2 + i], DM, NH * DH, 16, CU_TENSOR_MAP_L2_PROMOTION_NONE);
  R.wo = make_map(d_in[5], NH * DH, DM, 128);
  R.xd = make_map3(xn, DM, SEQ - LAG * 32, 2, (uint64_t)LAG * 32 * DM * 2); R.xs = make_map3(xn, 64, SEQ, DM / 64, 128);
  gm::Maps G;
  G.ot = make_map(ot, NH * DH + O_LAYER / SEQ, SEQ, 64); G.wo = make_map(d_in[5], NH * DH, DM, 64); G.xn = make_map(xn, SEQ, DM, 64);
  G.wg = make_map(d_in[8], DM, DF, 64); G.wu = make_map(d_in[9], DM, DF, 64); G.hl = make_map(hh, SEQ, DF, 64); G.hs = make_map(hh, SEQ, DF, 128);
  G.wd = make_map(d_in[10], DF, DM, 64); G.out = make_map(d_out, SEQ, DM, 128);
  cudaLaunchConfig_t cfg = {};
  cudaLaunchAttribute at[1];
  cfg.attrs = at; cfg.numAttrs = 1;
  cfg.gridDim = dim3(3 * NH); cfg.blockDim = dim3(384); cfg.dynamicSmemBytes = rec::SMEM; cfg.stream = cudaStreamPerThread;
  at[0].id = cudaLaunchAttributeClusterDimension; at[0].val.clusterDim.y = at[0].val.clusterDim.z = 1;
  static int csize = 0;
  if (!csize) {
    int n = 0;
    at[0].val.clusterDim.x = 6;
    csize = cudaOccupancyMaxActiveClusters(&n, rec_kernel, &cfg) == cudaSuccess && n >= NH / 2 ? 6 : 3;
  }
  at[0].val.clusterDim.x = csize;
  cudaLaunchKernelEx(&cfg, rec_kernel, R, mem0);
  cfg.gridDim = dim3(132); cfg.blockDim = dim3(384); cfg.dynamicSmemBytes = gm::SMEM; cfg.stream = cudaStreamPerThread;
  at[0].id = cudaLaunchAttributeProgrammaticStreamSerialization; at[0].val.programmaticStreamSerializationAllowed = 1;
  cudaLaunchKernelEx(&cfg, gemm_kernel, G, x, (bf16*)d_out);
}
```

```cpp
#include <cuda_runtime.h>
#include <cuda_bf16.h>
#include <cuda.h>
#include <stdint.h>

#define DEVI __device__ __forceinline__
typedef __nv_bfloat16 bf16;

constexpr int SEQ = 2048, DM = 1024, NH = 32, DH = 128, DF = 3584, NSEG = 64;
#define LAG 19
constexpr int NSTEP = NSEG + LAG;

#define TSD 1800
constexpr size_t O_LAYER = 0;
__device__ __align__(1024) bf16 g_xn[SEQ * DM];
__device__ __align__(1024) bf16 g_ot[SEQ * NH * DH + O_LAYER];
__device__ __align__(1024) bf16 g_h[SEQ * DF];
__device__ __align__(1024) uint32_t g_xr[NSEG][DM * 4];
__device__ __align__(1024) uint2 g_h1[4][256 * 256];
__device__ __align__(1024) uint4 g_h2[4][2048];
__device__ __align__(128) uint32_t g_ts[2][32];
enum { E_D1 = 0, E_G1 = 32, E_O1 = 48, E_O2 = 64, E_G2 = 80, E_D2 = 96,
       E_LI = 128, E_LX2 = 144, E_LX1A = 160, E_LX1B = 176, NEV = 256 };
__device__ __align__(128) int g_dep[NEV];
__device__ __align__(128) int g_claim[NEV];
__device__ __align__(128) int g_xa[2][32];

#define TUNE_DEFAULTS 1650, 2450, 6, 100, 100, 8, 13, 100, 1500, 2225, 100, 110, 1500, 2225, 200, 0
constexpr int c_D[16] = {TUNE_DEFAULTS};
template<int I> struct TPV { static constexpr int v = c_D[I]; };
#define TP(i) TPV<i>::v

DEVI uint32_t smem_u32(const void* p) { return (uint32_t)__cvta_generic_to_shared(p); }
DEVI void mbar_init(uint32_t bar, uint32_t cnt) { asm volatile("mbarrier.init.shared::cta.b64 [%0], %1;" :: "r"(bar), "r"(cnt) : "memory"); }
DEVI void mbar_arrive(uint32_t bar) { asm volatile("mbarrier.arrive.shared::cta.b64 _, [%0];" :: "r"(bar) : "memory"); }
DEVI bool mbar_try(uint32_t bar, uint32_t parity) {
  uint32_t p;
  asm volatile("{.reg .pred p; mbarrier.try_wait.parity.shared::cta.b64 p, [%1], %2; selp.u32 %0, 1, 0, p;}" : "=r"(p) : "r"(bar), "r"(parity) : "memory");
  return p;
}
DEVI bool mbar_test(uint32_t bar, uint32_t parity) {
  uint32_t p;
  asm volatile("{.reg .pred p; mbarrier.test_wait.parity.shared::cta.b64 p, [%1], %2; selp.u32 %0, 1, 0, p;}" : "=r"(p) : "r"(bar), "r"(parity) : "memory");
  return p;
}
constexpr int SPIN_BUDGET = 1 << 18;
DEVI void mbar_wait(uint32_t bar, uint32_t parity, int& budget) {
  while (!mbar_try(bar, parity)) { if (--budget < 0) break; }
}
DEVI bool mbar_try_cluster(uint32_t bar, uint32_t parity) {
  uint32_t p;
  asm volatile("{.reg .pred p; mbarrier.try_wait.parity.acquire.cluster.shared::cta.b64 p, [%1], %2; selp.u32 %0, 1, 0, p;}" : "=r"(p) : "r"(bar), "r"(parity) : "memory");
  return p;
}
DEVI void mbar_wait_cluster(uint32_t bar, uint32_t parity, int& budget) {
  while (!mbar_try_cluster(bar, parity)) { if (--budget < 0) break; }
}
DEVI void mbar_spin(uint32_t bar, uint32_t parity) {
  asm volatile("{.reg .pred p;\nW: mbarrier.try_wait.parity.shared::cta.b64 p, [%0], %1;\n@!p bra.uni W;}" :: "r"(bar), "r"(parity) : "memory");
}
DEVI void mbar_spin_cluster(uint32_t bar, uint32_t parity) {
  asm volatile("{.reg .pred p;\nW: mbarrier.try_wait.parity.acquire.cluster.shared::cta.b64 p, [%0], %1;\n@!p bra.uni W;}" :: "r"(bar), "r"(parity) : "memory");
}
DEVI uint32_t mapa(uint32_t addr, uint32_t rank) { uint32_t r; asm("mapa.shared::cluster.u32 %0, %1, %2;" : "=r"(r) : "r"(addr), "r"(rank)); return r; }
DEVI void cluster_arrive() { asm volatile("barrier.cluster.arrive.relaxed.aligned;" ::: "memory"); }
DEVI void cluster_wait() { asm volatile("barrier.cluster.wait.aligned;" ::: "memory"); }
DEVI void fence_mbar_init() { asm volatile("fence.mbarrier_init.release.cluster;" ::: "memory"); }
DEVI void fence_proxy_async() { asm volatile("fence.proxy.async.shared::cta;" ::: "memory"); }
DEVI void fence_proxy_global() { asm volatile("fence.proxy.async.global;" ::: "memory"); }
#define ELECT "{.reg .pred p; elect.sync _|p, 0xffffffff;\n @p "
DEVI void e_expect_tx(uint32_t bar, uint32_t bytes) { asm volatile(ELECT "mbarrier.arrive.expect_tx.shared::cta.b64 _, [%0], %1;}" :: "r"(bar), "r"(bytes) : "memory"); }
DEVI void e_complete_tx(uint32_t bar, uint32_t bytes) { asm volatile("fence.acq_rel.cta;\n" ELECT "mbarrier.complete_tx.relaxed.cta.shared::cta.b64 [%0], %1;}" :: "r"(bar), "r"(bytes) : "memory"); }
DEVI void e_arrive(uint32_t bar) { asm volatile(ELECT "mbarrier.arrive.shared::cta.b64 _, [%0];}" :: "r"(bar) : "memory"); }
DEVI void e_tma_2d(uint32_t dst, const CUtensorMap* m, int c0, int c1, uint32_t bar) {
  asm volatile(ELECT "cp.async.bulk.tensor.2d.shared::cluster.global.mbarrier::complete_tx::bytes [%0], [%1, {%3, %4}], [%2];}"
    :: "r"(dst), "l"(m), "r"(bar), "r"(c0), "r"(c1) : "memory");
}
DEVI void e_prefetch_3d(const CUtensorMap* m, int c0, int c1, int c2) {
  asm volatile(ELECT "cp.async.bulk.prefetch.tensor.3d.L2.global [%0, {%1, %2, %3}];}" :: "l"(m), "r"(c0), "r"(c1), "r"(c2) : "memory");
}
DEVI void e_bulk_g2s(uint32_t dst, const void* src, uint32_t bytes, uint32_t bar) {
  asm volatile(ELECT "cp.async.bulk.shared::cluster.global.mbarrier::complete_tx::bytes [%0], [%1], %2, [%3];}" :: "r"(dst), "l"(src), "r"(bytes), "r"(bar) : "memory");
}
DEVI void e_tma_3d(uint32_t dst, const CUtensorMap* m, int c0, int c1, int c2, uint32_t bar) {
  asm volatile(ELECT "cp.async.bulk.tensor.3d.shared::cluster.global.mbarrier::complete_tx::bytes [%0], [%1, {%3, %4, %5}], [%2];}"
    :: "r"(dst), "l"(m), "r"(bar), "r"(c0), "r"(c1), "r"(c2) : "memory");
}
DEVI void e_tma_3d_mc(uint32_t dst, const CUtensorMap* m, int c0, int c1, int c2, uint32_t bar, int last) {
  asm volatile(ELECT "cp.async.bulk.tensor.3d.shared::cluster.global.mbarrier::complete_tx::bytes.multicast::cluster [%0], [%1, {%3, %4, %5}], [%2], %6;}"
    :: "r"(dst), "l"(m), "r"(bar), "r"(c0), "r"(c1), "r"(c2), "h"((uint16_t)((2 << last) - 1)) : "memory");
}
DEVI void e_tma_2d_mc(uint32_t dst, const CUtensorMap* m, int c0, int c1, uint32_t bar) {
  asm volatile(ELECT "cp.async.bulk.tensor.2d.shared::cluster.global.mbarrier::complete_tx::bytes.multicast::cluster [%0], [%1, {%3, %4}], [%2], %5;}"
    :: "r"(dst), "l"(m), "r"(bar), "r"(c0), "r"(c1), "h"((uint16_t)3) : "memory");
}
DEVI void p_arrive_at(uint32_t bar, uint32_t rank, bool c) {
  asm volatile("{.reg .pred p; .reg .b32 a; setp.ne.u32 p, %2, 0; mapa.shared::cluster.u32 a, %0, %1; @p mbarrier.arrive.shared::cluster.b64 _, [a];}"
    :: "r"(bar), "r"(rank), "r"((uint32_t)c) : "memory");
}
DEVI void p_expect_tx(uint32_t bar, uint32_t bytes, bool c) {
  asm volatile("{.reg .pred p; setp.ne.u32 p, %2, 0; @p mbarrier.arrive.expect_tx.shared::cta.b64 _, [%0], %1;}" :: "r"(bar), "r"(bytes), "r"((uint32_t)c) : "memory");
}
DEVI void p_arrive(uint32_t bar, bool c) { asm volatile("{.reg .pred p; setp.ne.u32 p, %1, 0; @p mbarrier.arrive.shared::cta.b64 _, [%0];}" :: "r"(bar), "r"((uint32_t)c) : "memory"); }
DEVI void tma_store_2d(const CUtensorMap* m, uint32_t src, int c0, int c1) {
  asm volatile("cp.async.bulk.tensor.2d.global.shared::cta.bulk_group [%0, {%2, %3}], [%1];" :: "l"(m), "r"(src), "r"(c0), "r"(c1) : "memory");
}
DEVI void tma_radd_2d(const CUtensorMap* m, uint32_t src, int c0, int c1) {
  asm volatile("cp.reduce.async.bulk.tensor.2d.global.shared::cta.add.bulk_group [%0, {%2, %3}], [%1];" :: "l"(m), "r"(src), "r"(c0), "r"(c1) : "memory");
}
DEVI void bulk_commit() { asm volatile("cp.async.bulk.commit_group;" ::: "memory"); }
template<int N> DEVI void bulk_wait_read() { asm volatile("cp.async.bulk.wait_group.read %0;" :: "n"(N) : "memory"); }
template<int N> DEVI void bulk_wait() { asm volatile("cp.async.bulk.wait_group %0;" :: "n"(N) : "memory"); }
template<int ID, int N> DEVI void nbar_sync() { asm volatile("bar.sync %0, %1;" :: "n"(ID), "n"(N) : "memory"); }
template<int ID, int N> DEVI void nbar_arrive() { asm volatile("bar.arrive %0, %1;" :: "n"(ID), "n"(N) : "memory"); }
DEVI void nbar_sync_r(int id, int n) { asm volatile("bar.sync %0, %1;" :: "r"(id), "r"(n) : "memory"); }
template<int R> DEVI void reg_inc() { asm volatile("setmaxnreg.inc.sync.aligned.u32 %0;" :: "n"(R)); }
template<int R> DEVI void reg_dec() { asm volatile("setmaxnreg.dec.sync.aligned.u32 %0;" :: "n"(R)); }
DEVI void wg_fence() { asm volatile("wgmma.fence.sync.aligned;" ::: "memory"); }
DEVI void wg_commit() { asm volatile("wgmma.commit_group.sync.aligned;" ::: "memory"); }
template<int N> DEVI void wg_wait() { asm volatile("wgmma.wait_group.sync.aligned %0;" :: "n"(N) : "memory"); }
DEVI uint64_t mkdesc(uint32_t addr, uint32_t lbo, uint32_t sbo, uint32_t sw = 1) {
  return ((uint64_t)((addr & 0x3FFFF) >> 4)) | ((uint64_t)(lbo >> 4) << 16) | ((uint64_t)(sbo >> 4) << 32) | ((uint64_t)sw << 62);
}
constexpr uint32_t SMEM_BASE = 1024;
__host__ __device__ constexpr long long CD(uint32_t off, uint32_t lbo, uint32_t sbo, uint32_t sw) {
  return (long long)(((uint64_t)((SMEM_BASE + off) >> 4)) | ((uint64_t)(lbo >> 4) << 16) | ((uint64_t)(sbo >> 4) << 32) | ((uint64_t)sw << 62));
}
DEVI uint32_t pack_bf16(float lo, float hi) { uint32_t r; asm("cvt.rn.bf16x2.f32 %0, %1, %2;" : "=r"(r) : "f"(hi), "f"(lo)); return r; }
DEVI float bf_lo(uint32_t v) { return __uint_as_float(v << 16); }
DEVI float bf_hi(uint32_t v) { return __uint_as_float(v & 0xffff0000u); }
DEVI void ldsm4t(uint32_t addr, uint32_t& r0, uint32_t& r1, uint32_t& r2, uint32_t& r3) {
  asm volatile("ldmatrix.sync.aligned.m8n8.x4.trans.shared.b16 {%0,%1,%2,%3}, [%4];" : "=r"(r0), "=r"(r1), "=r"(r2), "=r"(r3) : "r"(addr) : "memory");
}
DEVI void stsm4(uint32_t addr, uint32_t r0, uint32_t r1, uint32_t r2, uint32_t r3) {
  asm volatile("stmatrix.sync.aligned.m8n8.x4.shared.b16 [%0], {%1,%2,%3,%4};" :: "r"(addr), "r"(r0), "r"(r1), "r"(r2), "r"(r3) : "memory");
}
DEVI uint2 lds64v(uint32_t a) { uint2 v; asm volatile("ld.volatile.shared.v2.u32 {%0,%1}, [%2];" : "=r"(v.x), "=r"(v.y) : "r"(a) : "memory"); return v; }
DEVI uint32_t lds32v(uint32_t a) { uint32_t v; asm volatile("ld.volatile.shared.u32 %0, [%1];" : "=r"(v) : "r"(a) : "memory"); return v; }
DEVI uint4 lds128v(uint32_t a) { uint4 v; asm volatile("ld.volatile.shared.v4.u32 {%0,%1,%2,%3}, [%4];" : "=r"(v.x), "=r"(v.y), "=r"(v.z), "=r"(v.w) : "r"(a) : "memory"); return v; }
DEVI void sts32(uint32_t a, uint32_t x) { asm volatile("st.shared.u32 [%0], %1;" :: "r"(a), "r"(x) : "memory"); }
DEVI int lane_id() { int r; asm volatile("mov.u32 %0, %%laneid;" : "=r"(r)); return r; }
DEVI void sts64(uint32_t a, uint32_t x, uint32_t y) { asm volatile("st.shared.v2.u32 [%0], {%1,%2};" :: "r"(a), "r"(x), "r"(y) : "memory"); }
DEVI void st_async128(uint32_t a, uint32_t x, uint32_t y, uint32_t z, uint32_t w, uint32_t bar) {
  asm volatile("st.async.weak.shared::cluster.mbarrier::complete_tx::bytes.v4.b32 [%0], {%1,%2,%3,%4}, [%5];" :: "r"(a), "r"(x), "r"(y), "r"(z), "r"(w), "r"(bar) : "memory");
}
DEVI void st_async32(uint32_t a, uint32_t x, uint32_t bar) {
  asm volatile("st.async.weak.shared::cluster.mbarrier::complete_tx::bytes.b32 [%0], %1, [%2];" :: "r"(a), "r"(x), "r"(bar) : "memory");
}
DEVI uint4 ldg_rlx128(const void* p) {
  uint4 v;
  asm volatile("ld.relaxed.gpu.global.v4.b32 {%0,%1,%2,%3}, [%4];" : "=r"(v.x), "=r"(v.y), "=r"(v.z), "=r"(v.w) : "l"(p) : "memory");
  return v;
}
DEVI int ldg_rlx32(const void* p) { int v; asm volatile("ld.relaxed.gpu.global.b32 %0, [%1];" : "=r"(v) : "l"(p) : "memory"); return v; }
DEVI int ldg_acq32(const void* p) { int v; asm volatile("ld.acquire.gpu.global.b32 %0, [%1];" : "=r"(v) : "l"(p) : "memory"); return v; }
DEVI void stg128(void* p, uint32_t x, uint32_t y, uint32_t z, uint32_t w) {
  asm volatile("st.global.v4.b32 [%0], {%1,%2,%3,%4};" :: "l"(p), "r"(x), "r"(y), "r"(z), "r"(w) : "memory");
}
DEVI uint2 ldg_rlx64(const void* p) { uint2 v; asm volatile("{.reg .b64 a; ld.relaxed.gpu.global.b64 a, [%2]; mov.b64 {%0,%1}, a;}" : "=r"(v.x), "=r"(v.y) : "l"(p) : "memory"); return v; }
DEVI void stg_rlx64(void* p, uint32_t x, uint32_t y) { asm volatile("{.reg .b64 a; mov.b64 a, {%1,%2}; st.relaxed.gpu.global.b64 [%0], a;}" :: "l"(p), "r"(x), "r"(y) : "memory"); }
DEVI void stg_rlx32(void* p, uint32_t x) { asm volatile("st.relaxed.gpu.global.b32 [%0], %1;" :: "l"(p), "r"(x) : "memory"); }
DEVI void flag_add(int* p) { asm volatile("fence.proxy.async.global; red.release.gpu.global.add.s32 [%0], 1;" :: "l"(p) : "memory"); }
DEVI void e_stg_rlx32(void* p, uint32_t x) { asm volatile(ELECT "st.relaxed.gpu.global.b32 [%0], %1;}" :: "l"(p), "r"(x) : "memory"); }
DEVI void e_flag_add(int* p) { asm volatile("fence.proxy.async.global;\n" ELECT "red.release.gpu.global.add.s32 [%0], 1;}" :: "l"(p) : "memory"); }
DEVI int cluster_rank() { int r; asm volatile("mov.u32 %0, %%cluster_ctarank;" : "=r"(r)); return __shfl_sync(0xffffffffu, r, 0); }
DEVI int cluster_last() { int r; asm volatile("mov.u32 %0, %%cluster_nctarank;" : "=r"(r)); return __shfl_sync(0xffffffffu, r, 0) - 1; }
DEVI int cta_id() { int r; asm volatile("mov.u32 %0, %%ctaid.x;" : "=r"(r)); return __shfl_sync(0xffffffffu, r, 0); }
DEVI uint32_t clock32() { uint32_t c; asm volatile("mov.u32 %0, %%clock;" : "=r"(c)); return c; }
DEVI uint32_t gtime() { uint32_t c; asm volatile("mov.u32 %0, %%globaltimer_lo;" : "=r"(c)); return c; }
DEVI void wait_time(uint32_t t) { while (__any_sync(0xffffffffu, t - gtime() - 1 < 4000u)) {} }
DEVI void spin_until(uint32_t t0, int d) {
  int r;
  while (__any_sync(0xffffffffu, (r = d - (int)(clock32() - t0)) > 0)) {
    if (r > 300) __nanosleep(r >> 2);
  }
}
DEVI void pin2(const void* a, const void* b) { asm volatile("{.reg .pred p; setp.eq.u64 p, %0, %1; @p st.volatile.global.u64 [%0], %1;}" :: "l"(a), "l"(b) : "memory"); }
DEVI void pin2(uint32_t a, uint32_t b) { asm volatile("{.reg .pred p; setp.eq.u32 p, %0, %1; @p st.volatile.shared.u32 [%0], %1;}" :: "r"(a), "r"(b) : "memory"); }
DEVI void p_stg_rlx64(void* p, uint32_t x, uint32_t y, bool c) {
  asm volatile("{.reg .pred p; .reg .b64 a; setp.ne.u32 p, %3, 0; mov.b64 a, {%1,%2}; @p st.relaxed.gpu.global.b64 [%0], a;}" :: "l"(p), "r"(x), "r"(y), "r"((uint32_t)c) : "memory");
}
DEVI void pin2(uint64_t a, uint64_t b) { pin2((const void*)a, (const void*)b); }
DEVI uint64_t pair(uint32_t a, uint32_t bar) { return a | (uint64_t)bar << 32; }
DEVI void st_async32(uint64_t q, uint32_t x) { st_async32((uint32_t)q, x, (uint32_t)(q >> 32)); }
DEVI void st_async128(uint64_t q, uint4 v) { st_async128((uint32_t)q, v.x, v.y, v.z, v.w, (uint32_t)(q >> 32)); }
DEVI float ex2(float x) { float r; asm("ex2.approx.ftz.f32 %0, %1;" : "=f"(r) : "f"(x)); return r; }
DEVI float rcp(float x) { float r; asm("rcp.approx.ftz.f32 %0, %1;" : "=f"(r) : "f"(x)); return r; }
DEVI uint32_t xor_or(uint32_t a, uint32_t t, uint32_t acc) { uint32_t r; asm("lop3.b32 %0, %1, %2, %3, 0xbe;" : "=r"(r) : "r"(a), "r"(t), "r"(acc)); return r; }
DEVI void stsm2(uint32_t addr, uint32_t r0, uint32_t r1) {
  asm volatile("stmatrix.sync.aligned.m8n8.x2.shared.b16 [%0], {%1,%2};" :: "r"(addr), "r"(r0), "r"(r1) : "memory");
}
DEVI uint32_t settag(uint32_t v, uint32_t tag) { return (v & ~1u) | tag; }

#define A4(c, o)  c(d[o+0]), c(d[o+1]), c(d[o+2]), c(d[o+3])
#define A8(c, o)  A4(c, o), A4(c, o+4)
#define A16(c, o) A8(c, o), A8(c, o+8)
#define A12(c, o) A8(c, o), A4(c, o+8)
#define A28(c, o) A16(c, o), A12(c, o+16)
#define RL12 "{%0,%1,%2,%3,%4,%5,%6,%7,%8,%9,%10,%11}"
#define RL28 "{%0,%1,%2,%3,%4,%5,%6,%7,%8,%9,%10,%11,%12,%13,%14,%15,%16,%17,%18,%19,%20,%21,%22,%23,%24,%25,%26,%27}"
#define A20(c, o) A16(c, o), A4(c, o+16)
#define A32(c, o) A16(c, o), A16(c, o+16)
#define RL8  "{%0,%1,%2,%3,%4,%5,%6,%7}"
#define RL16 "{%0,%1,%2,%3,%4,%5,%6,%7,%8,%9,%10,%11,%12,%13,%14,%15}"
#define RL20 "{%0,%1,%2,%3,%4,%5,%6,%7,%8,%9,%10,%11,%12,%13,%14,%15,%16,%17,%18,%19}"
#define RL32 "{%0,%1,%2,%3,%4,%5,%6,%7,%8,%9,%10,%11,%12,%13,%14,%15,%16,%17,%18,%19,%20,%21,%22,%23,%24,%25,%26,%27,%28,%29,%30,%31}"
#define RL64 "{%0,%1,%2,%3,%4,%5,%6,%7,%8,%9,%10,%11,%12,%13,%14,%15,%16,%17,%18,%19,%20,%21,%22,%23,%24,%25,%26,%27,%28,%29,%30,%31," \
  "%32,%33,%34,%35,%36,%37,%38,%39,%40,%41,%42,%43,%44,%45,%46,%47,%48,%49,%50,%51,%52,%53,%54,%55,%56,%57,%58,%59,%60,%61,%62,%63}"
#define WG_OP(shape) "wgmma.mma_async.sync.aligned." shape "k16.f32.bf16.bf16 "
#define DEF_WGMMA(N, RL, AL, i0, i1, i2, i3, i4, i5, i6)                                                                         \
  template<int SC, int TB, int CB> DEVI void rs##N(float* d, const uint32_t* a, uint64_t b) {                                    \
    if (SC) asm volatile("{.reg .b64 tb; add.s64 tb, %" #i4 ", %" #i5 ";\n" WG_OP("m64n" #N) RL ", {%" #i0 ",%" #i1 ",%" #i2 ",%" #i3 "}, tb, 1, 1, 1, %" #i6 ";}" \
      : AL("+f", 0) : "r"(a[0]), "r"(a[1]), "r"(a[2]), "r"(a[3]), "l"(b), "n"(CB), "n"(TB));                                     \
    else asm volatile("{.reg .b64 tb; add.s64 tb, %" #i4 ", %" #i5 ";\n" WG_OP("m64n" #N) RL ", {%" #i0 ",%" #i1 ",%" #i2 ",%" #i3 "}, tb, 0, 1, 1, %" #i6 ";}" \
      : AL("=f", 0) : "r"(a[0]), "r"(a[1]), "r"(a[2]), "r"(a[3]), "l"(b), "n"(CB), "n"(TB));                                     \
  }                                                                                                                              \
  template<int SC, int TA, int TB, int CA, int CB> DEVI void ss##N(float* d, uint64_t a, uint64_t b) {                           \
    if (SC) asm volatile("{.reg .b64 ta, tb; add.s64 ta, %" #i0 ", %" #i2 "; add.s64 tb, %" #i1 ", %" #i3 ";\n" WG_OP("m64n" #N) RL ", ta, tb, 1, 1, 1, %" #i4 ", %" #i5 ";}" \
      : AL("+f", 0) : "l"(a), "l"(b), "n"(CA), "n"(CB), "n"(TA), "n"(TB));                                                       \
    else asm volatile("{.reg .b64 ta, tb; add.s64 ta, %" #i0 ", %" #i2 "; add.s64 tb, %" #i1 ", %" #i3 ";\n" WG_OP("m64n" #N) RL ", ta, tb, 0, 1, 1, %" #i4 ", %" #i5 ";}" \
      : AL("=f", 0) : "l"(a), "l"(b), "n"(CA), "n"(CB), "n"(TA), "n"(TB));                                                       \
  }
DEF_WGMMA(8, "{%0,%1,%2,%3}", A4, 4, 5, 6, 7, 8, 9, 10)
DEF_WGMMA(16, RL8, A8, 8, 9, 10, 11, 12, 13, 14)
DEF_WGMMA(32, RL16, A16, 16, 17, 18, 19, 20, 21, 22)
DEF_WGMMA(40, RL20, A20, 20, 21, 22, 23, 24, 25, 26)
DEF_WGMMA(24, RL12, A12, 12, 13, 14, 15, 16, 17, 18)
DEF_WGMMA(56, RL28, A28, 28, 29, 30, 31, 32, 33, 34)
template<int TA> DEVI void wgmma_n128(float* d, uint64_t a, uint64_t b, int scale_d) {
  asm volatile("{.reg .pred p; setp.ne.b32 p, %66, 0;\n" WG_OP("m64n128") RL64 ", %64, %65, p, 1, 1, %67, 1;}"
    : A32("+f", 0), A32("+f", 32) : "l"(a), "l"(b), "r"(scale_d), "n"(TA));
}

namespace rec {
constexpr int KR = 43;
constexpr uint32_t WSZ = (64 - KR) * 2048, STG = KR * 2048;
constexpr uint32_t WS = 0;
constexpr uint32_t RING = 2 * WSZ;
constexpr uint32_t OB = RING + 3 * 8192;
constexpr uint32_t PB = OB + 4096;
constexpr uint32_t WO = RING + 32768;
constexpr uint32_t ATT = WO + 5 * 16384;
constexpr uint32_t AK = ATT + 10240, AV = ATT + 20480;
constexpr uint32_t PAD = ATT + 30720;
constexpr uint32_t BARS = PAD + 128;
constexpr uint32_t B_XE = BARS  , B_FA = BARS + 64  , B_FB = BARS + 88, B_FO = BARS + 96;
constexpr uint32_t B_ME = BARS + 104  , B_WE = BARS + 136, B_PD = BARS + 144;
constexpr uint32_t B_XF = BARS + 152  , B_MF = BARS + 216  , B_CP = BARS + 248  , B_WT = BARS + 280  ;
constexpr uint32_t B_AB = BARS + 296, B_OB = BARS + 304, B_ST = BARS + 312  , B_WS = BARS + 328, B_WO = BARS + 336, B_AT = BARS + 352, B_AV = BARS + 360;
constexpr int NBAR = 46;
constexpr uint32_t M0 = BARS + 384;
constexpr uint32_t SMEM = 232448;
constexpr int NB_P = 1, NB_ST = 2, NB_O = 3, NB_W0 = 4, NB_W1 = 5;
__host__ __device__ constexpr int wo_tile(int rank, int g, int i) { return i < 2 ? i * 6 + (rank == 2 ? g : 4 - 2 * g + rank) : 13 + rank - g; }
enum { D_W  , D_X = 2, D_M  , D_O = 5, D_WO  , D_Q = 8  , D_K = 10, D_V, D_P, ND };
struct Maps { CUtensorMap w[3], wo, xd, xs; uint64_t d[6][ND]; };
static void fill_desc(uint64_t* d) {
  d[D_W] = CD(WS, 16, 1024, 1); d[D_W + 1] = CD(WS + WSZ, 16, 1024, 1); d[D_X] = CD(0, 16, 1024, 1);
  d[D_M] = CD(RING, 128, 8192, 0); d[D_M + 1] = CD(RING, 128, 4096, 0); d[D_O] = CD(OB, 128, 256, 0);
  d[D_WO] = CD(WO + 49152, 16, 1024, 1); d[D_WO + 1] = CD(WO, 16, 1024, 1);
  d[D_Q] = CD(ATT + 128, 640, 64, 0); d[D_Q + 1] = CD(ATT, 640, 0, 0); d[D_K] = CD(AK, 640, 128, 0);
  d[D_V] = CD(AV, 128, 640, 0); d[D_P] = CD(PB, 128, 768, 0);
}
__host__ __device__ constexpr uint32_t mslot(int c) { return (c ^ (c >> 1)) * 12288; }
__host__ __device__ constexpr uint32_t xslot(int s) { return s < 3 ? RING + s * 8192 : s < 5 ? WO + (s - 3) * 8192 : s < 7 ? WO + (s + 1) * 8192 : OB; }
__host__ __device__ constexpr bool k_smem(int k) { return k % 3 == 2; }
__host__ __device__ constexpr int k_idx(int k) { return k % 3 == 2 ? k / 3 : k - k / 3; }
__host__ __device__ constexpr int k_of_reg(int i) { return i + (i >> 1); }
__host__ __device__ constexpr int k_of_smem(int i) { return 3 * i + 2; }

#define RPROF(i)
#define RPROF_STEP
#define CPROF(i, v)

template<bool DUAL, int K0, int K1> DEVI void seq_mem(float* d, const uint32_t* w, uint64_t dw, uint64_t db) {
  if constexpr (K0 < K1) {
    constexpr int B = mslot(K0 >> 4) / 16 + (K0 & 15) * 16;
    if constexpr (DUAL) {
      if constexpr (!k_smem(K0)) rs24<K0 != 0, 1, B>(d, w + 4 * k_idx(K0), db); else ss24<1, 1, 1, k_idx(K0) * 128, B>(d, dw, db);
    } else {
      if constexpr (!k_smem(K0)) rs16<K0 != 0, 1, B>(d, w + 4 * k_idx(K0), db); else ss16<1, 1, 1, k_idx(K0) * 128, B>(d, dw, db);
    }
    seq_mem<DUAL, K0 + 1, K1>(d, w, dw, db);
  }
}
template<int N, int K0, int K1> DEVI void seq_tok(float* d, const uint32_t* w, uint64_t dw, uint64_t db) {
  if constexpr (K0 < K1) {
    constexpr bool DUAL = N > 32;
    constexpr int B = (DUAL ? xslot((K0 >> 2) & 7) / 16 : xslot(K0 >> 3) / 16 + ((K0 >> 2) & 1) * 256) + (K0 & 3) * 2;
    if constexpr (DUAL) {
      if constexpr (!k_smem(K0)) rs56<K0 != 0, 0, B>(d, w + 4 * k_idx(K0), db); else ss56<1, 1, 0, k_idx(K0) * 128, B>(d, dw, db);
    } else if constexpr (N == 24) {
      if constexpr (!k_smem(K0)) rs24<K0 != 0, 0, B>(d, w + 4 * k_idx(K0), db); else ss24<1, 1, 0, k_idx(K0) * 128, B>(d, dw, db);
    } else {
      if constexpr (!k_smem(K0)) rs32<K0 != 0, 0, B>(d, w + 4 * k_idx(K0), db); else ss32<1, 1, 0, k_idx(K0) * 128, B>(d, dw, db);
    }
    seq_tok<N, K0 + 1, K1>(d, w, dw, db);
  }
}
template<bool DUAL, int T, int K0> DEVI void seq_wo(float* d, uint64_t dw, uint64_t db) {
  if constexpr (K0 < 8) {
    if constexpr (DUAL) ss16<K0 != 0, 1, 1, T * 1024 + K0 * 128, K0 * 32>(d, dw, db);
    else ss8<K0 != 0, 1, 1, T * 1024 + K0 * 128, K0 * 32>(d, dw, db);
    seq_wo<DUAL, T, K0 + 1>(d, dw, db);
  }
}
template<int K0> DEVI void seq_s(float* d, uint64_t dq, uint64_t dk) {
  if constexpr (K0 < 8) { ss40<K0 != 0, 1, 1, K0 * 80, K0 * 80>(d, dq, dk); seq_s<K0 + 1>(d, dq, dk); }
}
template<bool DUAL, int J> DEVI void load_x(uint32_t sb, const Maps* M, int t, int rb) {
  if (DUAL) e_tma_3d_mc(sb + xslot(J & 7), &M->xd, J * 64, (t - LAG) * 32, 0, sb + B_XF + (J & 7) * 8, rb);
  else e_tma_3d_mc(sb + xslot(J & 7), &M->xs, 0, (t < NSEG ? t : t - LAG) * 32, J * 2, sb + B_XF + (J & 7) * 8, rb);
}
DEVI void load_x_lent(uint32_t sb, const Maps* M, int t, int j) {
  const bool dual = t >= LAG && t < NSEG;
  const uint32_t dst = sb + (j == 3 ? xslot(3) : xslot(5));
#pragma unroll
  for (int i = 0; i < 2; i++)
    e_tma_3d(dst + i * 8192, dual ? &M->xd : &M->xs, dual ? (j + i) * 64 : 0, (t < LAG ? t : t - LAG) * 32, dual ? 0 : (j + i) * 2, sb + B_XF + (j + i) * 8);
}
struct True { static constexpr bool value = true; };
struct False { static constexpr bool value = false; };
struct Ctx { uint32_t sb; const Maps* M; int last; bool issuer; int wi; bool lead; uint32_t par; };
#define XD 1
template<bool DUAL, int J> DEVI void tok_release(const Ctx& c, int t) {
  constexpr int NC = DUAL ? 16 : 8, S = J & 7;
  if constexpr (J + 8 < NC) {
    p_arrive_at(c.sb + B_XE + S * 8, c.last, c.lead);
    p_expect_tx(c.sb + B_XF + S * 8, 8192, c.lead && c.wi == 0);
  } else if constexpr (S == 1 || S == 2 || S == 4 || S == 7) p_arrive(c.sb + B_ME + (S >> 1) * 8, c.lead);
  if constexpr (J == 0) {
    if (c.issuer && c.wi == 6) { mbar_spin(c.sb + B_FO, t & 1); load_x<DUAL, 7>(c.sb, c.M, t, c.last); }
  }
  if constexpr (J >= XD && J - XD + 8 < NC) {
    constexpr int I = J - XD;
    if (c.issuer && c.wi == (I & 1) * 4 + 1) { mbar_spin(c.sb + B_XE + I * 8, (t - LAG) & 1); load_x<DUAL, I + 8>(c.sb, c.M, t, c.last); }
  }
}
template<int N, int J, class F, class G> DEVI bool tok_pass(float* d, const uint32_t* w, uint64_t dw, Ctx& c, int t, F after0, G setup) {
  constexpr bool DUAL = N > 32;
  constexpr int NC = DUAL ? 16 : 8, KC = 64 / NC;
  if constexpr (J < NC) {
    if constexpr (J > 1) mbar_spin(c.sb + B_XF + (J & 7) * 8, c.par ^ (J >> 3));
    wg_fence();
    seq_tok<N, J * KC, (J + 1) * KC>(d, w, dw, c.M->d[DUAL ? J >> 3 : N == 24 ? 2 : 3][D_X]);
    wg_commit();
    if constexpr (J == 1) after0();
    if constexpr (J >= NC - 5 && J < NC - 2) setup(J - (NC - 5));
    if constexpr (J > 0) { wg_wait<1>(); tok_release<DUAL, J - 1>(c, t); }
    return tok_pass<N, J + 1>(d, w, dw, c, t, after0, setup);
  } else {
    const bool ok = mbar_test(c.sb + B_MF, t & 1);
    wg_wait<0>();
    tok_release<DUAL, NC - 1>(c, t);
    if (!DUAL) c.par ^= 1;
    return ok;
  }
}
template<int NB> DEVI void pack_tok(uint32_t* e, const float* d) {
#pragma unroll
  for (int i = 0; i < 8; i++) if ((i & 3) < NB) e[i] = pack_bf16(d[4 * (i & 3) + 2 * (i >> 2)], d[4 * (i & 3) + 2 * (i >> 2) + 1]);
}
DEVI void push_tok(const uint32_t* e, uint32_t sb, uint32_t o, int r, int rank) {
  const uint32_t b = mapa(sb, r);
  st_async128(b + o, e[0], e[1], e[2], e[3], b + (rank == 2 ? B_AV : B_AT));
}
DEVI uint32_t h1_tag(int seg) { return ((seg >> 1) & 1) ^ 1; }
template<bool DUAL> DEVI uint4 pack_part(const float* c, int t) {
  if (!DUAL) { const uint32_t x = settag(pack_bf16(c[0], c[1]), h1_tag(t < NSEG ? t : t - LAG)), y = pack_bf16(c[2], c[3]); return make_uint4(x, y, x, y); }
  return make_uint4(settag(pack_bf16(c[0], c[1]), h1_tag(t)), pack_bf16(c[2], c[3]), settag(pack_bf16(c[4], c[5]), h1_tag(t - LAG)), pack_bf16(c[6], c[7]));
}
DEVI void put_part(char* p1, char* p2, uint4 z, int t) { p_stg_rlx64(p1, z.x, z.y, t < NSEG); p_stg_rlx64(p2, z.z, z.w, t >= LAG); }

DEVI void rec_math(const uint32_t sb, const int wi, const Maps& M) {
  const int h = cta_id() / 3, rb = cluster_rank() >= 3 ? 3 : 0, rank = cluster_rank() - rb;
  const int warp = wi & 3, wg = wi >> 2;
  const bool lead = (threadIdx.x & 127) == 0;
  uint32_t w[4 * KR];
  const int last = cluster_last();
  Ctx cx{sb, &M, last, rb + rank == last, wi, lead, 0};
  {
    const int lane = lane_id();
    const uint32_t a = sb + wg * STG + ((lane & 7) + (lane >> 4) * 8) * 128 + (((warp * 2 + ((lane >> 3) & 1)) ^ (lane & 7)) << 4);
    for (int i = 0; i < (wg == 1 || rank == 2 ? 12 : 8); i++)
      stg_rlx64((char*)g_h1[i & 3] + ((wo_tile(rank, wg, i >> 2) * 4 + warp) * 4 + (lane >> 3)) * 2048 + h * 64 + (lane & 7) * 8, 0, 0);
    mbar_spin(sb + B_ST + wg * 8, 0);
#pragma unroll
    for (int k = 0; k < KR; k++) ldsm4t(a + k * 2048, w[4*k], w[4*k+1], w[4*k+2], w[4*k+3]);
    nbar_arrive<NB_ST, 384>();
    nbar_sync_r(NB_W0 + wg, 128);
    for (int i = 0; i < 5; i++) p_arrive_at(sb + B_FA + i * 8, i == 4 ? last : 0, lead);
    mbar_spin(sb + B_WS, 0);
  }
  uint4 z = make_uint4(0, 0, 0, 0);
  char *z1 = nullptr, *z2 = nullptr;
  uint32_t rt0 = 0, rt1 = 0;
  mbar_spin(sb + B_XF, 0); mbar_spin(sb + B_XF + 8, 0);
#pragma unroll 1
  for (int t = 0;; t++) {
    uint32_t e[16];
    bool ok;
    auto finish = [&]() { put_part(z1, z2, z, t - 1); p_arrive_at(sb + B_FO, last, lead); };
    const int seg = t - rank * LAG;
    const bool att = rank < 2 && (unsigned)seg < (unsigned)NSEG;
    char* p1;
    uint32_t pw, oo;
    uint64_t u0, u1;
    int lane;
    auto setup = [&](int part) {
      if (part == 0) {
        lane = lane_id();
      } else if (part == 1) {
        char* const p = (char*)g_h1 + ((wo_tile(rank, wg, 0) * 4 + warp) * 4 + (lane >> 3)) * 2048 + h * 64 + (lane & 7) * 8;
        p1 = p + (t & 1) * sizeof(g_h1[0]);
        pin2(p1, nullptr);
      } else if (part == 2) {
        oo = OB + (lane >> 4) * 2048 + warp * 512 + (t < NSEG ? rank * 256 : 0) + (lane & 15) * 16;
        pw = sb + PB + (wg ? lane * 4 : 768 + warp * 768 + lane * 16);
        pin2(pw, oo);
      } else {
        if (wg) {
          const uint32_t ra = mapa(sb, rb + ((warp & 1) ? 2 : (rank ^ 1) & 1)), rc = mapa(sb, rb + ((warp & 1) ? (rank ^ 1) & 1 : 2));
          u0 = pair(ra + oo, ra + B_OB); u1 = pair(rc + oo, rc + B_OB);
        } else {
          u0 = (uint64_t)((char*)(g_ot + rank * O_LAYER) + (size_t)(h * DH + warp * 16 + (lane >> 2)) * (SEQ * 2) + seg * 64 + (lane & 3) * 16);
          u1 = (uint32_t)((lane & 24) + ((lane >> 2) & 1) + 2 * warp - 8 * (lane & 3));
        }
        pin2(u0, u1);
      }
    };
    RPROF_STEP;
    auto mem_pass = [&](auto dual_c) {
      constexpr bool DUAL = decltype(dual_c)::value;
      float m[DUAL ? 12 : 8];
      const uint64_t dw = M.d[4 + DUAL][D_W + wg], dm = M.d[0][D_M + DUAL];
      RPROF(8 + wg * 12 - 32);
      if (!ok) { int budget = SPIN_BUDGET; mbar_wait(sb + B_MF, t & 1, budget); }
      wg_fence(); seq_mem<DUAL, 0, 8>(m, w, dw, dm); wg_commit();
      const uint32_t ao = ATT + rank * 10240 + wi * 1280, to = ao + 128 + (lane & 3) * 128 + (lane >> 2) * 16;
      const int la = DUAL ? rank == 0 || (rank == 2 && wg) : t >= NSEG;
      RPROF(1 + wg * 12);
      if (DUAL && la) {
#pragma unroll
        for (int i = 0; i < 8; i++) { const uint32_t x = e[i]; e[i] = e[8 + i]; e[8 + i] = x; }
      }
      auto piece = [&](int i) { push_tok(e + 4 * i, sb, to + (i & 1) * 640, rb + (la ^ (i >> 1)), rank); };
      piece(0);
      wg_fence(); seq_mem<DUAL, 8, 16>(m, w, dw, dm); wg_commit();
      piece(1);
      mbar_spin(sb + B_MF + 8, t & 1);
      wg_fence(); seq_mem<DUAL, 16, 24>(m, w, dw, dm); wg_commit();
      if (DUAL) piece(2);
      wg_fence(); seq_mem<DUAL, 24, 32>(m, w, dw, dm); wg_commit();
      if (DUAL) piece(3);
      mbar_spin(sb + B_MF + 16, t & 1);
      wg_fence(); seq_mem<DUAL, 32, 48>(m, w, dw, dm); wg_commit();
      wg_wait<1>(); p_arrive(sb + B_PD, lead);
      const uint32_t r0 = mapa(sb, rb + la), r1 = mapa(sb, rb + (la ^ 1)), m0 = r0 + ao + lane * 4, m1 = r1 + ao + lane * 4, ab = rank == 2 ? B_AV : B_AB;
      const uint64_t q0 = pair(m0, r0 + ab), q1 = pair(m0 + 640, r0 + ab), q2 = pair(m1, r1 + ab), q3 = pair(m1 + 640, r1 + ab);
      pin2(q0, q1);
      if (DUAL) pin2(q2, q3);
      mbar_spin(sb + B_MF + 24, t & 1);
      wg_fence(); seq_mem<DUAL, 48, 64>(m, w, dw, dm); wg_commit();
      wg_wait<1>(); p_arrive_at(sb + B_FA, 0, lead);
      wg_wait<0>();
      const uint32_t a0 = pack_bf16(m[0], m[1]), a1 = pack_bf16(m[2], m[3]), a2 = pack_bf16(m[4], m[5]), a3 = pack_bf16(m[6], m[7]);
      if constexpr (DUAL) {
        st_async32(q0, la ? a2 : a0); st_async32(q1, la ? a3 : a1); st_async32(q2, la ? a0 : a2); st_async32(q3, la ? a1 : a3);
        rt0 = pack_bf16(m[8], m[9]); rt1 = pack_bf16(m[10], m[11]);
      } else { st_async32(q0, a0); st_async32(q1, a1); rt0 = a2; rt1 = a3; }
      p_arrive(sb + B_WE, lead);
    };
    if (t >= LAG && t < NSEG) {
      float d[28];
      ok = tok_pass<56, 0>(d, w, M.d[0][D_W + wg], cx, t, finish, setup);
      pack_tok<4>(e + 8, d); pack_tok<3>(e, d + 16); e[3] = rt0; e[7] = rt1;
      mem_pass(True());
    } else {
      float d[16];
      if (t > 0) finish();
      if (t > 0 && t < LAG) {
        ok = tok_pass<24, 0>(d, w, M.d[2][D_W + wg], cx, t, []() {}, setup);
        pack_tok<3>(e, d); e[3] = rt0; e[7] = rt1;
      } else {
        ok = tok_pass<32, 0>(d, w, M.d[3][D_W + wg], cx, t, []() {}, setup);
        pack_tok<4>(e, d);
      }
      mem_pass(False());
    }
    {
      RPROF(2 + wg * 12);
      auto wo_ready = [&]() { if (t == 0) mbar_spin(sb + B_WO, 0); if (t < NSTEP - 1) mbar_spin(sb + B_WT, t & 1); };
      constexpr float SC = 0.08838834764831845f * 1.4426950408889634f;
      if (!att) wo_ready();
      else {
        float s[32];
        setup(3);
        if (wg) {
          uint32_t one[4];
#pragma unroll
          for (int i = 0; i < 4; i++) one[i] = 0x3F803F80u + (pw >> 31);
          mbar_spin_cluster(sb + B_AT, seg & 1);
          mbar_spin_cluster(sb + B_AB, seg & 1);
          fence_proxy_async();
          RPROF(3 + 12);
          wg_fence(); seq_s<0>(s, M.d[0][D_Q + 1], M.d[0][D_K]); wg_commit();
          nbar_arrive<NB_P, 256>();
          if (warp == 1) sts32(pw + 640, 0);
          mbar_spin_cluster(sb + B_AV, seg & 1);
          wg_wait<0>();
          float mx = fmaxf(fmaxf(fmaxf(s[0], s[1]), fmaxf(s[4], s[5])), fmaxf(fmaxf(fmaxf(s[8], s[9]), fmaxf(s[12], s[13])), fmaxf(s[16], s[17])));
          const float x1 = __shfl_xor_sync(0xffffffffu, mx, 1), x2 = __shfl_xor_sync(0xffffffffu, mx, 2), x3 = __shfl_xor_sync(0xffffffffu, mx, 3);
          const float u = (warp & 2) ? ((warp & 1) ? s[16] : s[12]) : ((warp & 1) ? s[8] : s[4]);
          const float v = (warp & 2) ? ((warp & 1) ? s[17] : s[13]) : ((warp & 1) ? s[9] : s[5]);
          const float ms = -SC * fmaxf(fmaxf(mx, x1), fmaxf(x2, x3));
          sts32(pw + 128 + warp * 128, pack_bf16(ex2(fmaf(u, SC, ms)), ex2(fmaf(v, SC, ms))));
          if (warp == 0) sts32(pw, pack_bf16(ex2(fmaf(s[0], SC, ms)), ex2(fmaf(s[1], SC, ms))));
          fence_proxy_async();
          nbar_sync<NB_W1, 128>();
          RPROF(4 + 12);
          wg_fence();
          rs8<0, 0, 0>(s + 8, one, M.d[2][D_P]); rs8<1, 0, 16>(s + 8, one, M.d[2][D_P]); rs8<1, 0, 32>(s + 8, one, M.d[2][D_P]);
          wg_commit();
          ss8<0, 0, 0, 0, 0>(s, M.d[0][D_V], M.d[0][D_P]); ss8<0, 0, 0, 320, 0>(s + 4, M.d[0][D_V], M.d[1][D_P]);
          ss8<1, 0, 0, 16, 16>(s, M.d[0][D_V], M.d[0][D_P]); ss8<1, 0, 0, 336, 16>(s + 4, M.d[0][D_V], M.d[1][D_P]);
          ss8<1, 0, 0, 32, 32>(s, M.d[0][D_V], M.d[0][D_P]); ss8<1, 0, 0, 352, 32>(s + 4, M.d[0][D_V], M.d[1][D_P]);
          wg_commit();
          wg_wait<1>();
          const float i0 = rcp(s[8]), i1 = rcp(s[9]);
          wg_wait<0>();
          stsm4(sb + oo, pack_bf16(s[0] * i0, s[1] * i1), pack_bf16(s[2] * i0, s[3] * i1), pack_bf16(s[4] * i0, s[5] * i1), pack_bf16(s[6] * i0, s[7] * i1));
          __syncwarp();
          const uint4 y = lds128v(sb + oo);
          if (t < NSTEP - 1) { st_async128(u0, y); st_async128(u1, y); e_complete_tx(sb + B_OB, 512); }
          wo_ready();
        } else {
          const int lim = (int)u1;
          char* const og = (char*)u0;
          nbar_sync<NB_P, 256>();
          RPROF(3);
          wg_fence();
          seq_s<0>(s, M.d[0][D_Q], M.d[1][D_K]);
          wg_commit();
          mbar_spin_cluster(sb + B_AV, seg & 1);
          wg_wait<0>();
#pragma unroll
          for (int i = 0; i < 8; i++) { float& v = s[4 + 4 * (i >> 1) + (i & 1)]; v = i <= lim ? v : -INFINITY; }
          float mx = fmaxf(fmaxf(fmaxf(s[0], s[1]), fmaxf(s[4], s[5])), fmaxf(fmaxf(fmaxf(s[8], s[9]), fmaxf(s[12], s[13])), fmaxf(s[16], s[17])));
          const float x1 = __shfl_xor_sync(0xffffffffu, mx, 1), x2 = __shfl_xor_sync(0xffffffffu, mx, 2), x3 = __shfl_xor_sync(0xffffffffu, mx, 3);
          const float ms = -SC * fmaxf(fmaxf(mx, x1), fmaxf(x2, x3));
#pragma unroll
          for (int i = 0; i < 10; i++) { float& v = s[4 * (i >> 1) + (i & 1)]; v = ex2(fmaf(v, SC, ms)); }
          const float sum = (((s[0] + s[1]) + (s[4] + s[5])) + ((s[8] + s[9]) + (s[12] + s[13]))) + (s[16] + s[17]);
          const float y1 = __shfl_xor_sync(0xffffffffu, sum, 1), y2 = __shfl_xor_sync(0xffffffffu, sum, 2), y3 = __shfl_xor_sync(0xffffffffu, sum, 3);
          const float inv = rcp((sum + y1) + (y2 + y3));
          stsm4(pw, pack_bf16(s[0] * inv, s[1] * inv), pack_bf16(s[4] * inv, s[5] * inv), pack_bf16(s[8] * inv, s[9] * inv), pack_bf16(s[12] * inv, s[13] * inv));
          stsm2(pw + 512, pack_bf16(s[16] * inv, s[17] * inv), 0);
          fence_proxy_async();
          nbar_sync<NB_W0, 128>();
          RPROF(4);
          wg_fence();
          ss32<0, 0, 0, 0, 48>(s, M.d[1][D_V], M.d[3][D_P]); ss32<0, 0, 0, 320, 48>(s + 16, M.d[1][D_V], M.d[4][D_P]);
          ss32<1, 0, 0, 16, 64>(s, M.d[1][D_V], M.d[3][D_P]); ss32<1, 0, 0, 336, 64>(s + 16, M.d[1][D_V], M.d[4][D_P]);
          ss32<1, 0, 0, 32, 80>(s, M.d[1][D_V], M.d[3][D_P]); ss32<1, 0, 0, 352, 80>(s + 16, M.d[1][D_V], M.d[4][D_P]);
          wg_commit();
          wo_ready();
          wg_wait<0>();
#pragma unroll
          for (int i = 0; i < 4; i++) {
            const float* d = s + (i >> 1) * 16 + (i & 1) * 2;
            stg128(og + ((i >> 1) * 64 + (i & 1) * 8) * (SEQ * 2), pack_bf16(d[0], d[1]), pack_bf16(d[4], d[5]), pack_bf16(d[8], d[9]), pack_bf16(d[12], d[13]));
          }
          if ((seg & 3) == 3) nbar_arrive<NB_O, 160>();
        }
      }
      RPROF(5 + wg * 12);
      const bool three = wg == 1 || rank == 2;
      char* const p2 = p1 + (2 + ((t - LAG) & 1) - (t & 1)) * (int)sizeof(g_h1[0]);
      if (t < NSTEP - 1) {
        auto wo_pass = [&](auto dual_c) {
          constexpr bool DUAL = decltype(dual_c)::value;
          float c[24];
          const uint64_t dt = M.d[DUAL][D_WO + wg];
          mbar_spin_cluster(sb + B_OB, t & 1);
          fence_proxy_async();
          RPROF(6 + wg * 12);
          wg_fence(); seq_wo<DUAL, 0, 0>(c, dt, M.d[DUAL * 3 + 0][D_O]); wg_commit(); seq_wo<DUAL, 1, 0>(c + 8, dt, M.d[DUAL * 3 + 1][D_O]); wg_commit();
          mbar_spin(sb + B_XF, cx.par);
          wg_wait<1>();
          if (warp == 2) load_x_lent(sb, &M, t + 1, wg ? 3 : 5);
          put_part(p1, p2, pack_part<DUAL>(c, t), t);
          const int o3 = (wo_tile(rank, wg, three ? 2 : 1) - wo_tile(rank, wg, 0)) * 32768;
          z1 = p1 + o3; z2 = p2 + o3;
          if (three) {
            wg_fence(); seq_wo<DUAL, 2, 0>(c + 16, dt, M.d[DUAL * 3 + 2][D_O]); wg_commit();
            wg_wait<1>(); put_part(p1 + 6 * 32768, p2 + 6 * 32768, pack_part<DUAL>(c + 8, t), t);
            mbar_spin(sb + B_XF + 8, cx.par);
            wg_wait<0>(); z = pack_part<DUAL>(c + 16, t);
          } else { mbar_spin(sb + B_XF + 8, cx.par); wg_wait<0>(); z = pack_part<DUAL>(c + 8, t); }
        };
        if (t >= LAG && t < NSEG) wo_pass(True()); else wo_pass(False());
      } else { p_arrive(sb + B_PD, lead); break; }
      RPROF(7 + wg * 12);
    }
  }
}

DEVI void wait_xa(const int* p, int& budget) {
#pragma unroll 1
  while (__any_sync(0xffffffffu, ldg_acq32(p) < 64) && --budget > 0) {}
  fence_proxy_global();
}
template<bool DUAL> DEVI void first_loads(uint32_t sb, const Maps* M, int n, int h, int rb, int& budget) {
  if (n >= LAG && ((n - LAG) & 3) == 0) e_prefetch_3d(&M->xs, 0, (n - LAG) * 32, h & 14);
  mbar_wait(sb + B_FA, n & 1, budget);
  load_x<DUAL, 0>(sb, M, n, rb); load_x<DUAL, 1>(sb, M, n, rb); load_x<DUAL, 2>(sb, M, n, rb);
}
template<bool DUAL> DEVI void lent_loads(uint32_t sb, const Maps* M, int n, int rb, int& budget) {
  mbar_wait(sb + B_FB, n & 1, budget);
  load_x<DUAL, 3>(sb, M, n, rb); load_x<DUAL, 4>(sb, M, n, rb); load_x<DUAL, 5>(sb, M, n, rb); load_x<DUAL, 6>(sb, M, n, rb);
}
DEVI void rec_comm(const uint32_t sb, const int warp, const Maps& M, const bf16* __restrict__ mem0) {
  const int lane = threadIdx.x & 31, h = cta_id() / 3, rb = cluster_rank() >= 3 ? 3 : 0, rank = cluster_rank() - rb;
  int budget = SPIN_BUDGET;
  const bool two = warp == 3 || (rank == 2 && warp == 2);
  const int ntask = two ? 2 : 1, qi = two ? (warp == 3 ? rank : 3) : rank * 3 + warp;
  const int task0 = two ? h * 2 + (qi >> 1) : 64 + h * 4 + (qi >> 1);
  auto h2_word = [&](int i, int ln) {
    const int task = task0 + i * 192;
    return (char*)g_h2 + (task >> 6) * 8192 + ((qi ^ i) & 1) * 4096 + ((task >> 2) & 15) * 256 + (task & 3) * 32 + (ln & 8) * 16 + (ln & 7) * 4;
  };
  auto first_x = [&](int t) {
    const int n = t + 1;
    p_expect_tx(sb + B_XF + (lane_id() & 7) * 8, 8192, lane_id() < 8);
    if (rb + rank == 0) {
      if (n >= LAG && ((n - LAG) & 3) == 0) wait_xa(&g_xa[1][(n - LAG) >> 2], budget);
      if (n >= LAG && n < NSEG) first_loads<true>(sb, &M, n, h, cluster_last(), budget); else first_loads<false>(sb, &M, n, h, cluster_last(), budget);
    }
  };
  {
    const int task = task0 + (lane >> 4) * 192, L = (task & 3) * 8 + (lane & 7);
    if ((lane >> 4) < ntask) {
      const bf16* p = mem0 + (L & 3) * 2 * DM + (task >> 2) * 16 + (L >> 2) + (lane & 8);
      uint32_t m0 = (uint32_t)__bfloat16_as_ushort(p[0]) | (uint32_t)__bfloat16_as_ushort(p[DM]) << 16;
      m0 = m0 ? m0 : 0x8000u;
      stg_rlx32(h2_word(lane >> 4, lane), ((qi ^ (lane >> 4)) & 1) ? 0 : m0);
      for (int i = 1; i < 4; i++) stg_rlx32(h2_word(lane >> 4, lane) + i * sizeof(g_h2[0]), 0);
      sts32(sb + M0 + warp * 128 + lane * 4, m0);
    }
    __syncwarp();
    mbar_wait(sb + B_ST, 0, budget); mbar_wait(sb + B_ST + 8, 0, budget);
    if (budget <= 0) __trap();
    nbar_sync<NB_ST, 384>();
    if (warp == 2) {
      e_expect_tx(sb + B_WS, 2 * WSZ);
#pragma unroll 1
      for (int i = 0; i < 2 * (64 - KR); i++) e_tma_2d(sb + WS + (i & 1) * WSZ + (i >> 1) * 2048, &M.w[rank], h * DH + (i & 1) * 64, k_of_smem(i >> 1) * 16, sb + B_WS);
      const int nt = rank == 2 ? 6 : 5;
      e_expect_tx(sb + B_WO, (nt - 2) * 16384);
#pragma unroll 1
      for (int i = 1; i < nt; i++) if (i != 3) e_tma_2d(sb + WO + i * 16384, &M.wo, wo_tile(rank, 1 - i / 3, i % 3) * 64, h * DH, sb + B_WO);
    }
    wait_xa(&g_xa[0][0], budget);
    if (warp == 3) { first_x(-1); if (rb + rank == 0) lent_loads<false>(sb, &M, 0, cluster_last(), budget); }
  }
  uint32_t cpp = 0;
  const uint32_t cp = sb + B_CP + warp * 8;
  uint32_t f_dst, f_chk, f_bar, f_time = gtime() - 4000;
  const char *f_src, *f_xr;
  auto prepare = [&](int s) {
    const int ck = warp ^ (warp < 2 && (s < LAG || s >= NSEG) && (rank & 1) == (s >= NSEG)), ln = lane_id();
    f_dst = sb + RING + mslot(ck); f_chk = f_dst + ln * 32 + (ln >> 2) * 4; f_bar = sb + ck * 8;
    f_src = (const char*)g_h2[s & 3] + ck * 8192 + (s >= NSEG ? 4096 : 0);
    f_xr = (const char*)g_xr[(s + 1) & 63] + ck * 4096;
    pin2(f_chk, 0u);
    return s <= LAG ? TP(9) + ck * TP(11) : s <= NSEG ? TP(1) + ck * TP(4) : TP(13) + ck * TP(11);
  };
  prepare(0);
#pragma unroll 1
  for (int t = 0;; t++) {
    const int n = t + 1;
    const bool dual = t >= LAG && t < NSEG;
    RPROF_STEP;
    {
      const uint32_t bytes = dual ? 8192 : 4096;
      e_expect_tx(cp, bytes + (n < NSEG ? 4096 : 0));
      mbar_wait(f_bar + B_ME, t & 1, budget);
      if (n < NSEG) e_bulk_g2s(f_dst + 8192, f_xr, 4096, cp);
      wait_time(f_time);
      RPROF(24); CPROF(0, gtime());
      int tries = 0;
      while (true) {
        tries++;
        e_bulk_g2s(f_dst, f_src, bytes, cp);
        mbar_wait(cp, cpp, budget); cpp ^= 1;
        uint32_t mn = min(min(lds32v(f_chk), lds32v(f_chk + 1024)), min(lds32v(f_chk + 2048), lds32v(f_chk + 3072)));
        if (dual) mn = min(min(mn, min(lds32v(f_chk + 4096), lds32v(f_chk + 5120))), min(lds32v(f_chk + 6144), lds32v(f_chk + 7168)));
        if (!__any_sync(0xffffffffu, mn == 0) || --budget < 0) break;
        e_expect_tx(cp, bytes);
      }
      e_arrive(f_bar + B_MF);
      RPROF(25); CPROF(1, gtime()); CPROF(2, tries);
    }
    const int seg = t - rank * LAG;
    const bool att = rank < 2 && (unsigned)seg < (unsigned)NSEG;
    auto block_done = [&]() {
      if (warp == 1 && att && (seg & 3) == 3) { nbar_sync<NB_O, 160>(); e_flag_add(&g_dep[E_O1 + rank * 16 + (seg >> 2)]); }
    };
    if (warp == 0) {
      if (att) { e_expect_tx(sb + B_AT, 16384); e_expect_tx(sb + B_AB, 4096); e_expect_tx(sb + B_AV, 10240); }
      if (n < NSTEP) e_expect_tx(sb + B_OB, dual ? 4096 : 2048);
    }
    if (n + 1 < NSEG && (n & 3) == 3) wait_xa(&g_xa[0][(n + 1) >> 2], budget);
    if (rank == 2 && warp == 1) {
      if (h < 16 ? n < NSEG : n > LAG && n < NSTEP && ((n - LAG) & 3)) e_prefetch_3d(&M.xs, 0, (h < 16 ? n : n - LAG) * 32, (h & 7) * 2);
      if (h >= 16 && n + 1 < NSEG) asm volatile(ELECT "cp.async.bulk.prefetch.L2.global [%0], 2048;}" :: "l"((const char*)g_xr[n + 1] + (h & 7) * 2048) : "memory");
    }
    {
      const int ln = lane_id(), i = ln >> 4;
      char* const w = h2_word(i, ln);
      if (i < ntask) {
        stg_rlx32(w + ((t + 3) & 3) * sizeof(g_h2[0]), 0);
        if (n == LAG && ((qi ^ i) & 1)) stg_rlx32(w + (n & 3) * sizeof(g_h2[0]), lds32v(sb + M0 + warp * 128 + ln * 4));
      }
      __syncwarp();
    }
    if (n < NSTEP) {
      const uint32_t tag = (n >> 1) & 31;
      mbar_wait(sb + B_PD, t & 1, budget);
      uint32_t t0 = clock32();
      if (warp == 2) {
        e_expect_tx(sb + B_WT, 32768);
        e_tma_2d(sb + WO + 49152, &M.wo, wo_tile(rank, 0, 0) * 64, h * DH, sb + B_WT);
        mbar_wait(sb + B_WE, t & 1, budget);
        e_tma_2d(sb + WO, &M.wo, wo_tile(rank, 1, 0) * 64, h * DH, sb + B_WT);
      }
      if (warp == 3) first_x(t);
      if (warp == 0 && rank == (t >= NSEG)) { mbar_wait(sb + B_AB, seg & 1, budget); e_stg_rlx32(&g_ts[t & 1][h], (gtime() & ~31u) | tag); }
      const int fd = prepare(n), ln = lane_id();
      const int sa = t - (qi & 1) * LAG, sc = t - (~qi & 1) * LAG;
      const int i0 = (unsigned)sa < (unsigned)(NSEG - 1) ? 0 : 1, i1 = two && (unsigned)sc < (unsigned)(NSEG - 1) ? 2 : 1;
      const char* src = (const char*)g_h1[(qi & 1) * 2 + (sa & 1)] + task0 * 2048 + ln * 8;
      char* dst = h2_word(0, ln) + (n & 3) * sizeof(g_h2[0]);
      const int ds = ((~qi & 1) * 2 + (sc & 1) - (qi & 1) * 2 - (sa & 1)) * (int)sizeof(g_h1[0]) + 192 * 2048, dd = 3 * 8192 + ((qi & 1) ? -4096 : 4096);
      if (i0) { src += ds; dst += dd; }
      pin2(src, dst);
      spin_until(t0, TSD);
      uint32_t v0;
      do { v0 = ldg_rlx32(&g_ts[t & 1][ln]); } while (__any_sync(0xffffffffu, (v0 & 31) != tag) && --budget > 0);
      const uint32_t now = __shfl_sync(0xffffffffu, v0, 0);
      t0 = now + __reduce_max_sync(0xffffffffu, (int)(v0 - now));
      f_time = t0 + fd;
      RPROF(26); CPROF(3, t0);
      block_done();
      t0 += t < LAG ? TP(8) : t < NSEG ? TP(0) : TP(12);
#pragma unroll 1
      for (int i = i0; i < i1; i++) {
        const uint32_t tg = h1_tag(i ? sc : sa);
        uint2 v[8];
        wait_time(t0 + (!two ? 0 : i ? TP(3) : -TP(10)));
        int tries = 0;
        float a[4];
        while (true) {
          tries++;
#pragma unroll
          for (int k = 0; k < 8; k++) v[k] = ldg_rlx64(src + k * 256);
          asm volatile("{.reg .pred p; setp.eq.s32 p, %0, 0x7fffffff; @p exit;}" :: "r"(budget) : "memory");
          uint32_t bad = 0;
#pragma unroll
          for (int k = 0; k < 8; k++) {
            bad = xor_or(v[k].x, tg, bad);
            a[0] = k ? a[0] + bf_lo(v[k].x) : bf_lo(v[k].x); a[1] = k ? a[1] + bf_hi(v[k].x) : bf_hi(v[k].x);
            a[2] = k ? a[2] + bf_lo(v[k].y) : bf_lo(v[k].y); a[3] = k ? a[3] + bf_hi(v[k].y) : bf_hi(v[k].y);
          }
#pragma unroll
          for (int k = 0; k < 2; k++) {
            const float keep = (ln & 8) ? a[2+k] : a[k], send = (ln & 8) ? a[k] : a[2+k];
            a[k] = keep + __shfl_xor_sync(0xffffffffu, send, 8);
          }
#pragma unroll
          for (int k = 0; k < 2; k++) a[k] += __shfl_xor_sync(0xffffffffu, a[k], 16);
          if (!__any_sync(0xffffffffu, bad & 1) || --budget < 0) break;
        }
        const uint32_t out = pack_bf16(a[0], a[1]);
        if (ln < 16) stg_rlx32(dst, out ? out : 0x8000u);
        __syncwarp();
        src += ds; dst += dd;
        if (i == 0) { RPROF(28); CPROF(6, gtime()); CPROF(4, gtime()); CPROF(5, tries); } else CPROF(7, gtime());
      }
    }
    if (n == NSTEP) {
      cluster_arrive();
      if (warp == 0) { mbar_wait(sb + B_PD, t & 1, budget); mbar_wait(sb + B_PD, n & 1, budget); }
      block_done();
    }
    if (budget <= 0) __trap();
    if (n == NSTEP) break;
  }
  if (h == 0 && rank == 0 && warp < 2) g_xa[warp][lane_id()] = 0;
}
}

__global__ void __launch_bounds__(384, 1)
rec_kernel(const __grid_constant__ rec::Maps M, const bf16* __restrict__ mem0) {
  using namespace rec;
  extern __shared__ __align__(1024) uint8_t smem[];
  const uint32_t sb = __shfl_sync(0xffffffffu, smem_u32(smem), 0);
  const int tid = threadIdx.x, wi = __shfl_sync(0xffffffffu, tid >> 5, 0);
  if ((sb & 0x3FFFF) != SMEM_BASE) __trap();
  if (wi == 0) {
    const int h = cta_id() / 3, rank = cta_id() - h * 3;
    const int nwg = 2 * cluster_last() + 2;
    for (int i = tid; i < NBAR; i += 32) mbar_init(sb + BARS + i * 8, i < 13 ? nwg : i < 19 ? 2 : 1);
    ((uint32_t*)(smem + PAD))[tid] = 0;
    fence_mbar_init(); fence_proxy_async();
    __syncwarp();
    e_expect_tx(sb + B_ST, STG); e_expect_tx(sb + B_ST + 8, STG);
    for (int i = 0; i < 2 * KR; i++) e_tma_2d(sb + (i & 1) * STG + (i >> 1) * 2048, &M.w[rank], h * DH + (i & 1) * 64, k_of_reg(i >> 1) * 16, sb + B_ST + (i & 1) * 8);
  } else if (wi == 1) {
    if (blockIdx.x < NEV / 32) { g_dep[blockIdx.x * 32 + (tid & 31)] = 0; g_claim[blockIdx.x * 32 + (tid & 31)] = 0; __threadfence(); }
    __syncwarp();
    asm volatile("griddepcontrol.launch_dependents;" ::: "memory");
  } else if (wi == 2) {
    if ((tid & 31) < 3) asm volatile("prefetch.tensormap [%0];" :: "l"(&M.wo + (tid & 31)) : "memory");
    __syncwarp();
  }
  cluster_arrive(); cluster_wait();
  if (wi < 8) { reg_inc<232>(); rec_math(sb, wi, M); cluster_arrive(); cluster_wait(); }
  else { reg_dec<40>(); rec_comm(sb, wi & 3, M, mem0); cluster_wait(); }
}

namespace gm {
struct Maps { CUtensorMap ot, wo, xn, wg, wu, hl, hs, wd, out; };
constexpr int STAGES = 6, STAGE = 32768;
constexpr uint32_t SO = STAGES * STAGE, BARS = SO + 32768;
constexpr uint32_t B_FULL = BARS, B_EMPTY = BARS + 48, B_TF = BARS + 96, B_TE = BARS + 112, B_ORD = BARS + 128, B_PM = BARS + 144, B_GO = BARS + 160, B_SF = BARS + 168;
constexpr uint32_t MAIL = BARS + 176, PMAIL = BARS + 192;
constexpr uint32_t SMEM = BARS + 256;
constexpr int END = -1;
#define DQ 8
#define GT gtime

struct Tile {
  bool isO, isG, l2; int blk, col, k0, n;
  DEVI Tile(int task, int rank) {
    const int e = task >> 8, id = task & 255;
    const bool isD = e < E_G1 || e >= E_D2;
    isO = e >= E_O1 && e < E_G2; isG = !isD && !isO; l2 = e >= E_O2;
    blk = l2 && !isO ? (e & 7) * 2 + rank : isD ? e >> 1 : e & 15;
    col = l2 && !isO ? id : (isG ? id : id & 3) * 2 + rank;
    k0 = isO ? (id >> 2) * 2048 : isG ? 0 : ((l2 ? e >> 3 : e) & 1) * 1792;
    n = isO ? 32 : isG ? 16 : 28;
    if (e >= E_D2 + DQ) { n = 14; k0 += (id >> 3) * 896; col = id & 7; }
  }
};

DEVI float geglu(float g, float u) {
  const float z = g * (0.7978845608028654f + 0.035677408136300125f * g * g);
  float t; asm("tanh.approx.f32 %0, %1;" : "=f"(t) : "f"(z));
  const float hg = 0.5f * g;
  return fmaf(hg, t, hg) * u;
}
struct Sched {
  int need, size, e;
  bool filler;
  uint4 dep, cl;
  DEVI void init(int lane) {
    e = (lane < 4 ? lane + 12 : lane < 16 ? lane - 4 : lane) * 4;
    const bool d = e < E_G1 || e >= E_D2, o = e >= E_O1 && e < E_G2;
    need = e >= E_D2 ? 56 : d ? 28 : e < E_O1 ? 64 : o ? 32 : 128;
    size = e >= E_D2 ? (e < E_D2 + DQ ? 8 : e < E_D2 + 16 ? 16 : 0) : d ? 4 : o ? 8 : e < E_O1 ? 28 : e < E_G2 + 8 ? 56 : 0;
    filler = (int)blockIdx.x >= TP(5);
  }
  DEVI void scan(int lane) { cl = ldg_rlx128(g_claim + e); dep = ldg_rlx128(g_dep + e); }
  DEVI int next(int lane, int& budget) {
    while (--budget > 0) {
      int av[4], open = 0;
#pragma unroll
      for (int i = 0; i < 4; i++) { const int r = max(size - (int)(&cl.x)[i], 0); open |= r; av[i] = ((int)(&dep.x)[i] >= need ? r : 0) + (i ? av[i - 1] : 0); }
      const uint32_t mo = __ballot_sync(0xffffffffu, open);
      if (!mo) break;
      if (filler) {
        const int x = TP(6) & 3, dx = x == 0 ? dep.x : x == 1 ? dep.y : x == 2 ? dep.z : dep.w;
        filler = !__any_sync(0xffffffffu, e == ((E_O1 + TP(6)) & ~3) && dx >= need);
      }
      if (!filler && (mo & 0xffff) && lane >= E_O2 / 4) av[3] = 0;
      int inc = av[3], pos = 0;
      while (true) {
        const uint32_t m = __ballot_sync(0xffffffffu, inc > pos && av[3]);
        if (!m) break;
        const int l = __ffs(m) - 1, rel = pos - (inc - av[3]), i = (rel >= av[0]) + (rel >= av[1]) + (rel >= av[2]);
        int r = 0;
        if (lane == l) {
          const int tk = atomicAdd(g_claim + e + i, 1);
          r = tk < size ? (e + i) << 8 | tk : -1 - (inc - av[3] + (i == 0 ? av[0] : i == 1 ? av[1] : i == 2 ? av[2] : av[3]) + tk - size);
        }
        r = __shfl_sync(0xffffffffu, r, l);
        if (r >= 0) return r;
        if (pos == 0) {
#pragma unroll
          for (int o = 1; o < 32; o <<= 1) { const int v = __shfl_up_sync(0xffffffffu, inc, o); if (lane >= o) inc += v; }
        }
        pos = -1 - r;
      }
      if (pos == 0) __nanosleep(TP(7));
      scan(lane);
    }
    return END;
  }
};

DEVI void scheduler(const uint32_t sb) {
  const int lane = threadIdx.x & 31;
  int budget = SPIN_BUDGET;
  Sched sc; sc.init(lane);
#pragma unroll 1
  for (int i = 0;; i++) {
    if (i) mbar_wait(sb + B_GO, (i & 1) ^ 1, budget);
    sc.scan(lane);
    if (i == 0) cluster_wait();
    const int task = sc.next(lane, budget);
    const uint32_t r = mapa(sb, lane & 1);
    if (lane < 2) st_async32(r + PMAIL + (i & 1) * 4, task, r + B_PM + (i & 1) * 8);
    __syncwarp();
    if (task == END) break;
  }
}

DEVI void producer(const uint32_t sb, const Maps& M) {
  const int lane = threadIdx.x & 31, rank = cluster_rank();
  int budget = SPIN_BUDGET, s = 0, ph = 0;
#pragma unroll 1
  for (int i = 0;; i++) {
    e_expect_tx(sb + B_PM + (i & 1) * 8, 4);
    mbar_wait_cluster(sb + B_PM + (i & 1) * 8, (i >> 1) & 1, budget);
    const int task = budget < 0 ? END : __shfl_sync(0xffffffffu, (int)lds32v(sb + PMAIL + (i & 1) * 4), 0);
    fence_proxy_global();
    for (int z = 0; z < (task == END ? 2 : 1); z++) {
      const int g = (i + z) & 1;
      mbar_wait(sb + B_TE + g * 8, (((i + z) >> 1) & 1) ^ 1, budget);
      if (lane == 0) { sts64(sb + MAIL + g * 8, task, s | ph << 8); mbar_arrive(sb + B_TF + g * 8); }
      __syncwarp();
    }
    if (task == END) break;
    const Tile T(task, rank);
    const bool shareB = T.l2 && !T.isO;
    const CUtensorMap* mA = T.isO ? &M.ot : T.isG ? &M.xn : &M.hl;
    const CUtensorMap* mB0 = T.isO ? &M.wo : T.isG ? &M.wg : &M.wd;
    const CUtensorMap* mB1 = T.isG ? &M.wu : mB0;
    const int c0 = T.col * (T.isG ? 64 : 128), c1 = T.isG ? c0 : c0 + 64, row = T.blk * 128;
    const int ok = 0;
    int k = T.k0;
#pragma unroll 1
    for (int it = 0; it < T.n; it++, k += 64) {
      const uint32_t a = sb + s * STAGE, fb = sb + B_FULL + s * 8;
      mbar_wait(sb + B_EMPTY + s * 8, ph ^ 1, budget);
      e_expect_tx(fb, STAGE);
      if (shareB) {
        e_tma_2d_mc(a + 16384 + rank * 8192, rank ? mB1 : mB0, rank ? c1 : c0, k, fb);
        e_tma_2d(a, mA, k, row, fb); e_tma_2d(a + 8192, mA, k, row + 64, fb);
      } else {
        e_tma_2d_mc(a + rank * 8192, mA, T.isO ? row + rank * 64 : k, T.isO ? k + ok : row + rank * 64, fb);
        e_tma_2d(a + 16384, mB0, c0, k, fb); e_tma_2d(a + 24576, mB1, c1, k, fb);
      }
      if (it == T.n - TP(2)) e_arrive(sb + B_GO);
      if (++s == STAGES) { s = 0; ph ^= 1; }
    }
  }
}

template<int TA> DEVI void mainloop(float* d0, float* d1, uint32_t sb, int n, int s, int ph, bool lead, uint32_t ord, int& budget) {
  int prev = 0;
  const uint32_t rel = threadIdx.x & 127;
#pragma unroll 1
  for (int i = 0; i < n; i++) {
    mbar_wait(sb + B_FULL + s * 8, ph, budget);
    const uint32_t a = sb + s * STAGE;
    const uint64_t da = mkdesc(a, 16, 1024), db = mkdesc(a + 16384, 8192, 1024);
    wg_fence();
#pragma unroll
    for (int k = 0; k < 4; k++) {
      wgmma_n128<TA>(d0, da + k * (TA ? 128 : 2), db + k * 128, (i | k) != 0);
      wgmma_n128<TA>(d1, da + 512 + k * (TA ? 128 : 2), db + k * 128, (i | k) != 0);
    }
    wg_commit();
    if (i > 0) { wg_wait<1>(); p_arrive_at(sb + B_EMPTY + prev * 8, rel & 1, rel < 2); }
    prev = s;
    if (++s == STAGES) { s = 0; ph ^= 1; }
  }
  p_arrive(ord, lead);
  wg_wait<0>();
  p_arrive_at(sb + B_EMPTY + prev * 8, rel & 1, rel < 2);
}

DEVI void consumer(const uint32_t sb, const Maps& M, const int wg) {
  const int tid = threadIdx.x, lane = tid & 31, warp = (tid >> 5) & 3;
  const bool lead = (tid & 127) == 0;
  const uint32_t so = sb + SO;
  int budget = SPIN_BUDGET;
  float d0[64], d1[64];
#pragma unroll 1
  for (int m = 0;; m++) {
    mbar_wait(sb + B_TF + wg * 8, m & 1, budget);
    const uint2 mail = lds64v(sb + MAIL + wg * 8);
    const int task = __shfl_sync(0xffffffffu, (int)mail.x, 0), pos = __shfl_sync(0xffffffffu, (int)mail.y, 0);
    e_arrive(sb + B_TE + wg * 8);
    if (task == END || budget < 0) break;
    const Tile T(task, cluster_rank());
    mbar_wait(sb + B_ORD + wg * 8, (m & 1) ^ wg ^ 1, budget);
    if (T.isO) mainloop<1>(d0, d1, sb, T.n, pos & 255, pos >> 8, lead, sb + B_ORD + (wg ^ 1) * 8, budget);
    else mainloop<0>(d0, d1, sb, T.n, pos & 255, pos >> 8, lead, sb + B_ORD + (wg ^ 1) * 8, budget);
    mbar_wait(sb + B_SF, wg ^ 1, budget);
    const uint32_t st = so + (warp * 16 + (lane & 15)) * 128;
    if (T.isG) {
      int* const fl = &g_dep[T.l2 ? E_D2 + (T.col >= 28) * 8 + (T.blk >> 1) : E_D1 + T.blk * 2 + (T.col >= 28)];
#pragma unroll
      for (int mm = 0; mm < 2; mm++) {
        const float* d = mm ? d1 : d0;
#pragma unroll
        for (int c = 0; c < 4; c++) {
          uint32_t r[4];
#pragma unroll
          for (int i = 0; i < 4; i++) r[i] = pack_bf16(geglu(d[8*c+2*i], d[32+8*c+2*i]), geglu(d[8*c+2*i+1], d[33+8*c+2*i]));
          stsm4(st + mm * 8192 + (((2 * c + (lane >> 4)) ^ (lane & 7)) << 4), r[0], r[1], r[2], r[3]);
        }
      }
      fence_proxy_async();
      nbar_sync_r(1 + wg, 128);
      if (lead) {
        tma_store_2d(&M.hs, so, T.col * 64, T.blk * 128);
        bulk_commit();
        bulk_wait<0>();
        mbar_arrive(sb + B_SF);
        flag_add(fl);
      }
    } else {
#pragma unroll
      for (int hf = 0; hf < 2; hf++) {
#pragma unroll
        for (int mm = 0; mm < 2; mm++) {
          const float* d = (mm ? d1 : d0) + hf * 32;
#pragma unroll
          for (int c = 0; c < 4; c++)
            stsm4(st + hf * 16384 + mm * 8192 + (((2 * c + (lane >> 4)) ^ (lane & 7)) << 4), pack_bf16(d[8*c], d[8*c+1]), pack_bf16(d[8*c+2], d[8*c+3]),
                  pack_bf16(d[8*c+4], d[8*c+5]), pack_bf16(d[8*c+6], d[8*c+7]));
        }
        fence_proxy_async();
        nbar_sync_r(1 + wg, 128);
        if (lead) { tma_radd_2d(&M.out, so + hf * 16384, T.col * 128 + hf * 64, T.blk * 128); bulk_commit(); }
      }
      if (lead) {
        bulk_wait<0>();
        mbar_arrive(sb + B_SF);
        if (T.isO || !T.l2) flag_add(&g_dep[(!T.isO ? E_LX2 : T.l2 ? E_LX1B : E_LX1A) + T.blk]);
      }
    }
    __syncwarp();
  }
}

DEVI void norm_helper(const bf16* __restrict__ x, bf16* out) {
  const int lane = threadIdx.x & 31;
  int budget = SPIN_BUDGET, tk = lane < 4 ? -1 : 1024;
#pragma unroll 1
  while (--budget > 0) {
    if (tk < 0) tk = atomicAdd(g_claim + E_LI + lane, 1);
    if (__all_sync(0xffffffffu, tk >= 1024)) break;
    const uint32_t m = __ballot_sync(0xffffffffu, tk < 1024 && (lane == 0 || ldg_acq32(g_dep + E_LI + lane * 16 + (tk >> 6)) >= 16));
    if (!m) { __nanosleep(TP(7)); continue; }
    const int ql = __ffs(m) - 1, task = __shfl_sync(0xffffffffu, tk, ql), q = E_LI + ql * 16, ev = task >> 6;
    if (lane == ql) tk = -1;
    const size_t off = (size_t)task * (DM * 4) + lane * 16;
    const char* src = (const char*)(q == E_LI ? x : out) + off;
    uint4 u[8];
#pragma unroll
    for (int i = 0; i < 8; i++) u[i] = ldg_rlx128(src + i * 512);
    if (q == E_LI) {
#pragma unroll
      for (int i = 0; i < 8; i++) stg128((char*)out + off + i * 512, u[i].x, u[i].y, u[i].z, u[i].w);
    }
    int* const fl = q == E_LI ? &g_xa[0][ev] : q == E_LX2 ? &g_xa[1][ev] : &g_dep[q == E_LX1A ? E_G1 + ev : E_G2 + (ev >> 1)];
    float mean[2], rs[2];
#pragma unroll
    for (int r = 0; r < 2; r++) {
      float s0 = 0, s1 = 0;
#pragma unroll
      for (int i = 0; i < 16; i++) { const uint32_t v = (&u[4*r + (i >> 2)].x)[i & 3]; s0 += bf_lo(v); s1 += bf_hi(v); }
      mean[r] = (s0 + s1) * (1.f / 32);
      s0 = s1 = 0;
#pragma unroll
      for (int i = 0; i < 16; i++) { const uint32_t v = (&u[4*r + (i >> 2)].x)[i & 3]; const float a = bf_lo(v) - mean[r], b = bf_hi(v) - mean[r]; s0 = fmaf(a, a, s0); s1 = fmaf(b, b, s1); }
      rs[r] = s0 + s1;
    }
    {
      const bool hi = lane & 16;
      float m1 = hi ? mean[1] : mean[0], q1 = hi ? rs[1] : rs[0], m2 = hi ? mean[0] : mean[1], q2 = hi ? rs[0] : rs[1], cnt = 16;
#pragma unroll
      for (int o = 16; o; o >>= 1) {
        m2 = __shfl_xor_sync(0xffffffffu, m2, o); q2 = __shfl_xor_sync(0xffffffffu, q2, o);
        const float dl = m1 - m2;
        q2 = q1 = fmaf(dl * dl, cnt, q1 + q2); m2 = m1 = 0.5f * (m1 + m2);
        cnt *= 2;
      }
      q1 = rsqrtf(q1 * (1.f / DM) + 1e-5f);
      m2 = __shfl_xor_sync(0xffffffffu, m1, 16); q2 = __shfl_xor_sync(0xffffffffu, q1, 16);
      mean[0] = hi ? m2 : m1; mean[1] = hi ? m1 : m2; rs[0] = hi ? q2 : q1; rs[1] = hi ? q1 : q2;
    }
#pragma unroll
    for (int i = 0; i < 8; i++) {
      uint32_t y[4];
#pragma unroll
      for (int c = 0; c < 4; c++) { const uint32_t v = (&u[i].x)[c]; y[c] = pack_bf16((bf_lo(v) - mean[i >> 2]) * rs[i >> 2], (bf_hi(v) - mean[i >> 2]) * rs[i >> 2]); }
      stg128((char*)g_xn + off + i * 512, y[0], y[1], y[2], y[3]);
      u[i] = make_uint4(y[0], y[1], y[2], y[3]);
    }
    if (q == E_LI && (task & 15) >= 12) {
      uint32_t* const xr = g_xr[task >> 4] + lane * 32 + (task & 3);
#pragma unroll
      for (int i = 0; i < 16; i++) {
        const uint32_t a = (&u[i >> 2].x)[i & 3], b = (&u[4 + (i >> 2)].x)[i & 3];
        xr[(i >> 2) * 1024 + (i & 3) * 8] = __byte_perm(a, b, 0x5410); xr[(i >> 2) * 1024 + (i & 3) * 8 + 4] = __byte_perm(a, b, 0x7632);
      }
    }
    fence_proxy_global();
    __syncwarp();
    if (lane == 0) flag_add(fl);
    __syncwarp();
  }
}
}

__global__ void __cluster_dims__(2, 1, 1) __launch_bounds__(384, 1)
gemm_kernel(const __grid_constant__ gm::Maps M, const bf16* __restrict__ x, bf16* out) {
  using namespace gm;
  extern __shared__ __align__(1024) uint8_t smem[];
  const uint32_t sb = __shfl_sync(0xffffffffu, smem_u32(smem), 0);
  const int tid = threadIdx.x, wi = __shfl_sync(0xffffffffu, tid >> 5, 0);
  if (tid < 22) mbar_init(sb + BARS + tid * 8, tid == 14 || tid == 15 ? 4 : tid >= 6 && tid < 12 ? 2 : 1);
  fence_mbar_init();
  if (tid >= 256 && tid < 265) asm volatile("prefetch.tensormap [%0];" :: "l"(&M.ot + (tid - 256)) : "memory");
  __syncwarp();
  cluster_arrive();
  const bool sched = wi == 11 && cluster_rank() == 0;
  if (!sched) cluster_wait();
  if (wi < 8) { reg_inc<208>(); consumer(sb, M, wi >> 2); cluster_arrive(); cluster_wait(); }
  else {
    reg_dec<88>();
    if (wi == 8) producer(sb, M);
    else if (sched) scheduler(sb);
    else {
      norm_helper(x, out);
      asm volatile("griddepcontrol.wait;" ::: "memory");
    }
    __syncwarp();
    cluster_arrive(); cluster_wait();
  }
}

typedef CUresult (*PFN_encodeTiled)(CUtensorMap*, CUtensorMapDataType, cuuint32_t, void*, const cuuint64_t*, const cuuint64_t*,
                                    const cuuint32_t*, const cuuint32_t*, CUtensorMapInterleave, CUtensorMapSwizzle,
                                    CUtensorMapL2promotion, CUtensorMapFloatOOBfill);
static PFN_encodeTiled g_encode = nullptr;
static CUtensorMap make_map(const void* ptr, uint64_t rows, uint64_t cols, uint32_t box_rows, CUtensorMapL2promotion pr = CU_TENSOR_MAP_L2_PROMOTION_L2_256B) {
  CUtensorMap m;
  cuuint64_t dims[2] = {cols, rows}, strides[1] = {cols * 2};
  cuuint32_t box[2] = {64, box_rows}, es[2] = {1, 1};
  g_encode(&m, CU_TENSOR_MAP_DATA_TYPE_BFLOAT16, 2, (void*)ptr, dims, strides, box, es, CU_TENSOR_MAP_INTERLEAVE_NONE,
           CU_TENSOR_MAP_SWIZZLE_128B, pr, CU_TENSOR_MAP_FLOAT_OOB_FILL_NONE);
  return m;
}

static CUtensorMap make_map3(const void* ptr, uint64_t d0, uint64_t d1, uint64_t d2, uint64_t stride2) {
  CUtensorMap m;
  cuuint64_t dims[3] = {d0, d1, d2}, strides[2] = {DM * 2, stride2};
  cuuint32_t box[3] = {64, 32, 2}, es[3] = {1, 1, 1};
  g_encode(&m, CU_TENSOR_MAP_DATA_TYPE_BFLOAT16, 3, (void*)ptr, dims, strides, box, es, CU_TENSOR_MAP_INTERLEAVE_NONE,
           CU_TENSOR_MAP_SWIZZLE_128B, CU_TENSOR_MAP_L2_PROMOTION_L2_256B, CU_TENSOR_MAP_FLOAT_OOB_FILL_NONE);
  return m;
}

extern "C" void kernel_launch(void* const* d_in, const int* in_sizes, int n_in, void* d_out, int out_size) {
  const bf16* x = (const bf16*)d_in[0];
  const bf16* mem0 = (const bf16*)d_in[1];
  if (!g_encode) {
    void* p = nullptr; cudaDriverEntryPointQueryResult q;
    cudaGetDriverEntryPoint("cuTensorMapEncodeTiled", &p, cudaEnableDefault, &q);
    g_encode = (PFN_encodeTiled)p;
    cudaFuncSetAttribute(gemm_kernel, cudaFuncAttributeMaxDynamicSharedMemorySize, gm::SMEM);
    cudaFuncSetAttribute(rec_kernel, cudaFuncAttributeMaxDynamicSharedMemorySize, rec::SMEM);
  }
  bf16 *xn, *ot, *hh;
  cudaGetSymbolAddress((void**)&xn, g_xn); cudaGetSymbolAddress((void**)&ot, g_ot); cudaGetSymbolAddress((void**)&hh, g_h);
  rec::Maps R;
  for (int i = 0; i < 3; i++) R.w[i] = make_map(d_in[2 + i], DM, NH * DH, 16, CU_TENSOR_MAP_L2_PROMOTION_NONE);
  for (int i = 0; i < 6; i++) rec::fill_desc(R.d[i]);
  R.wo = make_map(d_in[5], NH * DH, DM, 128);
  R.xd = make_map3(xn, DM, SEQ - LAG * 32, 2, (uint64_t)LAG * 32 * DM * 2); R.xs = make_map3(xn, 64, SEQ, DM / 64, 128);
  gm::Maps G;
  G.ot = make_map(ot, NH * DH + O_LAYER / SEQ, SEQ, 64); G.wo = make_map(d_in[5], NH * DH, DM, 64); G.xn = make_map(xn, SEQ, DM, 64);
  G.wg = make_map(d_in[8], DM, DF, 64); G.wu = make_map(d_in[9], DM, DF, 64); G.hl = make_map(hh, SEQ, DF, 64); G.hs = make_map(hh, SEQ, DF, 128);
  G.wd = make_map(d_in[10], DF, DM, 64); G.out = make_map(d_out, SEQ, DM, 128);
  cudaLaunchConfig_t cfg = {};
  cudaLaunchAttribute at[1];
  cfg.attrs = at; cfg.numAttrs = 1;
  cfg.gridDim = dim3(3 * NH); cfg.blockDim = dim3(384); cfg.dynamicSmemBytes = rec::SMEM; cfg.stream = cudaStreamPerThread;
  at[0].id = cudaLaunchAttributeClusterDimension; at[0].val.clusterDim.y = at[0].val.clusterDim.z = 1;
  static int csize = 0;
  if (!csize) {
    int n = 0;
    at[0].val.clusterDim.x = 6;
    csize = cudaOccupancyMaxActiveClusters(&n, rec_kernel, &cfg) == cudaSuccess && n >= NH / 2 ? 6 : 3;
  }
  at[0].val.clusterDim.x = csize;
  cudaLaunchKernelEx(&cfg, rec_kernel, R, mem0);
  cfg.gridDim = dim3(132); cfg.blockDim = dim3(384); cfg.dynamicSmemBytes = gm::SMEM; cfg.stream = cudaStreamPerThread;
  at[0].id = cudaLaunchAttributeProgrammaticStreamSerialization; at[0].val.programmaticStreamSerializationAllowed = 1;
  cudaLaunchKernelEx(&cfg, gemm_kernel, G, x, (bf16*)d_out);
}
```

```cpp
#include <cuda_runtime.h>
#include <cuda_bf16.h>
#include <cuda.h>
#include <stdint.h>

#define DEVI __device__ __forceinline__
typedef __nv_bfloat16 bf16;

constexpr int SEQ = 2048, DM = 1024, NH = 32, DH = 128, DF = 3584, NSEG = 64;
#define LAG 19
constexpr int NSTEP = NSEG + LAG;

#define TSD 1800
constexpr size_t O_LAYER = 0;
__device__ __align__(1024) bf16 g_xn[SEQ * DM];
__device__ __align__(1024) bf16 g_ot[SEQ * NH * DH + O_LAYER];
__device__ __align__(1024) bf16 g_h[SEQ * DF];
__device__ __align__(1024) uint32_t g_xr[NSEG][DM * 4];
__device__ __align__(1024) uint2 g_h1[4][256 * 256];
__device__ __align__(1024) uint4 g_h2[4][2048];
__device__ __align__(128) uint32_t g_ts[2][32];
enum { E_D1 = 0, E_G1 = 32, E_O1 = 48, E_O2 = 64, E_G2 = 80, E_D2 = 96,
       E_LI = 128, E_LX2 = 144, E_LX1A = 160, E_LX1B = 176, NEV = 256 };
__device__ __align__(128) int g_dep[NEV];
__device__ __align__(128) int g_claim[NEV];
__device__ __align__(128) int g_xa[2][32];

#define TUNE_DEFAULTS 1650, 2450, 6, 100, 100, 8, 13, 100, 1500, 2225, 100, 110, 1500, 2225, 200, 0
constexpr int c_D[16] = {TUNE_DEFAULTS};
template<int I> struct TPV { static constexpr int v = c_D[I]; };
#define TP(i) TPV<i>::v

DEVI uint32_t smem_u32(const void* p) { return (uint32_t)__cvta_generic_to_shared(p); }
DEVI void mbar_init(uint32_t bar, uint32_t cnt) { asm volatile("mbarrier.init.shared::cta.b64 [%0], %1;" :: "r"(bar), "r"(cnt) : "memory"); }
DEVI void mbar_arrive(uint32_t bar) { asm volatile("mbarrier.arrive.shared::cta.b64 _, [%0];" :: "r"(bar) : "memory"); }
DEVI bool mbar_try(uint32_t bar, uint32_t parity) {
  uint32_t p;
  asm volatile("{.reg .pred p; mbarrier.try_wait.parity.shared::cta.b64 p, [%1], %2; selp.u32 %0, 1, 0, p;}" : "=r"(p) : "r"(bar), "r"(parity) : "memory");
  return p;
}
DEVI bool mbar_test(uint32_t bar, uint32_t parity) {
  uint32_t p;
  asm volatile("{.reg .pred p; mbarrier.test_wait.parity.shared::cta.b64 p, [%1], %2; selp.u32 %0, 1, 0, p;}" : "=r"(p) : "r"(bar), "r"(parity) : "memory");
  return p;
}
constexpr int SPIN_BUDGET = 1 << 18;
DEVI void mbar_wait(uint32_t bar, uint32_t parity, int& budget) {
  while (!mbar_try(bar, parity)) { if (--budget < 0) break; }
}
DEVI bool mbar_try_cluster(uint32_t bar, uint32_t parity) {
  uint32_t p;
  asm volatile("{.reg .pred p; mbarrier.try_wait.parity.acquire.cluster.shared::cta.b64 p, [%1], %2; selp.u32 %0, 1, 0, p;}" : "=r"(p) : "r"(bar), "r"(parity) : "memory");
  return p;
}
DEVI void mbar_wait_cluster(uint32_t bar, uint32_t parity, int& budget) {
  while (!mbar_try_cluster(bar, parity)) { if (--budget < 0) break; }
}
DEVI void mbar_spin(uint32_t bar, uint32_t parity) {
  asm volatile("{.reg .pred p;\nW: mbarrier.try_wait.parity.shared::cta.b64 p, [%0], %1;\n@!p bra.uni W;}" :: "r"(bar), "r"(parity) : "memory");
}
DEVI void mbar_spin_cluster(uint32_t bar, uint32_t parity) {
  asm volatile("{.reg .pred p;\nW: mbarrier.try_wait.parity.acquire.cluster.shared::cta.b64 p, [%0], %1;\n@!p bra.uni W;}" :: "r"(bar), "r"(parity) : "memory");
}
DEVI uint32_t mapa(uint32_t addr, uint32_t rank) { uint32_t r; asm("mapa.shared::cluster.u32 %0, %1, %2;" : "=r"(r) : "r"(addr), "r"(rank)); return r; }
DEVI void cluster_arrive() { asm volatile("barrier.cluster.arrive.relaxed.aligned;" ::: "memory"); }
DEVI void cluster_wait() { asm volatile("barrier.cluster.wait.aligned;" ::: "memory"); }
DEVI void fence_mbar_init() { asm volatile("fence.mbarrier_init.release.cluster;" ::: "memory"); }
DEVI void fence_proxy_async() { asm volatile("fence.proxy.async.shared::cta;" ::: "memory"); }
DEVI void fence_proxy_global() { asm volatile("fence.proxy.async.global;" ::: "memory"); }
#define ELECT "{.reg .pred p; elect.sync _|p, 0xffffffff;\n @p "
DEVI void e_expect_tx(uint32_t bar, uint32_t bytes) { asm volatile(ELECT "mbarrier.arrive.expect_tx.shared::cta.b64 _, [%0], %1;}" :: "r"(bar), "r"(bytes) : "memory"); }
DEVI void e_complete_tx(uint32_t bar, uint32_t bytes) { asm volatile("fence.acq_rel.cta;\n" ELECT "mbarrier.complete_tx.relaxed.cta.shared::cta.b64 [%0], %1;}" :: "r"(bar), "r"(bytes) : "memory"); }
DEVI void e_arrive(uint32_t bar) { asm volatile(ELECT "mbarrier.arrive.shared::cta.b64 _, [%0];}" :: "r"(bar) : "memory"); }
DEVI void e_tma_2d(uint32_t dst, const CUtensorMap* m, int c0, int c1, uint32_t bar) {
  asm volatile(ELECT "cp.async.bulk.tensor.2d.shared::cluster.global.mbarrier::complete_tx::bytes [%0], [%1, {%3, %4}], [%2];}"
    :: "r"(dst), "l"(m), "r"(bar), "r"(c0), "r"(c1) : "memory");
}
DEVI void e_prefetch_3d(const CUtensorMap* m, int c0, int c1, int c2) {
  asm volatile(ELECT "cp.async.bulk.prefetch.tensor.3d.L2.global [%0, {%1, %2, %3}];}" :: "l"(m), "r"(c0), "r"(c1), "r"(c2) : "memory");
}
DEVI void e_bulk_g2s(uint32_t dst, const void* src, uint32_t bytes, uint32_t bar) {
  asm volatile(ELECT "cp.async.bulk.shared::cluster.global.mbarrier::complete_tx::bytes [%0], [%1], %2, [%3];}" :: "r"(dst), "l"(src), "r"(bytes), "r"(bar) : "memory");
}
DEVI void e_tma_3d(uint32_t dst, const CUtensorMap* m, int c0, int c1, int c2, uint32_t bar) {
  asm volatile(ELECT "cp.async.bulk.tensor.3d.shared::cluster.global.mbarrier::complete_tx::bytes [%0], [%1, {%3, %4, %5}], [%2];}"
    :: "r"(dst), "l"(m), "r"(bar), "r"(c0), "r"(c1), "r"(c2) : "memory");
}
DEVI void e_tma_3d_mc(uint32_t dst, const CUtensorMap* m, int c0, int c1, int c2, uint32_t bar, int last) {
  asm volatile(ELECT "cp.async.bulk.tensor.3d.shared::cluster.global.mbarrier::complete_tx::bytes.multicast::cluster [%0], [%1, {%3, %4, %5}], [%2], %6;}"
    :: "r"(dst), "l"(m), "r"(bar), "r"(c0), "r"(c1), "r"(c2), "h"((uint16_t)((2 << last) - 1)) : "memory");
}
DEVI void e_tma_2d_mc(uint32_t dst, const CUtensorMap* m, int c0, int c1, uint32_t bar) {
  asm volatile(ELECT "cp.async.bulk.tensor.2d.shared::cluster.global.mbarrier::complete_tx::bytes.multicast::cluster [%0], [%1, {%3, %4}], [%2], %5;}"
    :: "r"(dst), "l"(m), "r"(bar), "r"(c0), "r"(c1), "h"((uint16_t)3) : "memory");
}
DEVI void p_arrive_at(uint32_t bar, uint32_t rank, bool c) {
  asm volatile("{.reg .pred p; .reg .b32 a; setp.ne.u32 p, %2, 0; mapa.shared::cluster.u32 a, %0, %1; @p mbarrier.arrive.shared::cluster.b64 _, [a];}"
    :: "r"(bar), "r"(rank), "r"((uint32_t)c) : "memory");
}
DEVI void p_expect_tx(uint32_t bar, uint32_t bytes, bool c) {
  asm volatile("{.reg .pred p; setp.ne.u32 p, %2, 0; @p mbarrier.arrive.expect_tx.shared::cta.b64 _, [%0], %1;}" :: "r"(bar), "r"(bytes), "r"((uint32_t)c) : "memory");
}
DEVI void p_arrive(uint32_t bar, bool c) { asm volatile("{.reg .pred p; setp.ne.u32 p, %1, 0; @p mbarrier.arrive.shared::cta.b64 _, [%0];}" :: "r"(bar), "r"((uint32_t)c) : "memory"); }
DEVI void tma_store_2d(const CUtensorMap* m, uint32_t src, int c0, int c1) {
  asm volatile("cp.async.bulk.tensor.2d.global.shared::cta.bulk_group [%0, {%2, %3}], [%1];" :: "l"(m), "r"(src), "r"(c0), "r"(c1) : "memory");
}
DEVI void tma_radd_2d(const CUtensorMap* m, uint32_t src, int c0, int c1) {
  asm volatile("cp.reduce.async.bulk.tensor.2d.global.shared::cta.add.bulk_group [%0, {%2, %3}], [%1];" :: "l"(m), "r"(src), "r"(c0), "r"(c1) : "memory");
}
DEVI void bulk_commit() { asm volatile("cp.async.bulk.commit_group;" ::: "memory"); }
template<int N> DEVI void bulk_wait_read() { asm volatile("cp.async.bulk.wait_group.read %0;" :: "n"(N) : "memory"); }
template<int N> DEVI void bulk_wait() { asm volatile("cp.async.bulk.wait_group %0;" :: "n"(N) : "memory"); }
template<int ID, int N> DEVI void nbar_sync() { asm volatile("bar.sync %0, %1;" :: "n"(ID), "n"(N) : "memory"); }
template<int ID, int N> DEVI void nbar_arrive() { asm volatile("bar.arrive %0, %1;" :: "n"(ID), "n"(N) : "memory"); }
DEVI void nbar_sync_r(int id, int n) { asm volatile("bar.sync %0, %1;" :: "r"(id), "r"(n) : "memory"); }
template<int R> DEVI void reg_inc() { asm volatile("setmaxnreg.inc.sync.aligned.u32 %0;" :: "n"(R)); }
template<int R> DEVI void reg_dec() { asm volatile("setmaxnreg.dec.sync.aligned.u32 %0;" :: "n"(R)); }
DEVI void wg_fence() { asm volatile("wgmma.fence.sync.aligned;" ::: "memory"); }
DEVI void wg_commit() { asm volatile("wgmma.commit_group.sync.aligned;" ::: "memory"); }
template<int N> DEVI void wg_wait() { asm volatile("wgmma.wait_group.sync.aligned %0;" :: "n"(N) : "memory"); }
DEVI uint64_t mkdesc(uint32_t addr, uint32_t lbo, uint32_t sbo, uint32_t sw = 1) {
  return ((uint64_t)((addr & 0x3FFFF) >> 4)) | ((uint64_t)(lbo >> 4) << 16) | ((uint64_t)(sbo >> 4) << 32) | ((uint64_t)sw << 62);
}
constexpr uint32_t SMEM_BASE = 1024;
__host__ __device__ constexpr long long CD(uint32_t off, uint32_t lbo, uint32_t sbo, uint32_t sw) {
  return (long long)(((uint64_t)((SMEM_BASE + off) >> 4)) | ((uint64_t)(lbo >> 4) << 16) | ((uint64_t)(sbo >> 4) << 32) | ((uint64_t)sw << 62));
}
DEVI uint32_t pack_bf16(float lo, float hi) { uint32_t r; asm("cvt.rn.bf16x2.f32 %0, %1, %2;" : "=r"(r) : "f"(hi), "f"(lo)); return r; }
DEVI float bf_lo(uint32_t v) { return __uint_as_float(v << 16); }
DEVI float bf_hi(uint32_t v) { return __uint_as_float(v & 0xffff0000u); }
DEVI void ldsm4t(uint32_t addr, uint32_t& r0, uint32_t& r1, uint32_t& r2, uint32_t& r3) {
  asm volatile("ldmatrix.sync.aligned.m8n8.x4.trans.shared.b16 {%0,%1,%2,%3}, [%4];" : "=r"(r0), "=r"(r1), "=r"(r2), "=r"(r3) : "r"(addr) : "memory");
}
DEVI void stsm4(uint32_t addr, uint32_t r0, uint32_t r1, uint32_t r2, uint32_t r3) {
  asm volatile("stmatrix.sync.aligned.m8n8.x4.shared.b16 [%0], {%1,%2,%3,%4};" :: "r"(addr), "r"(r0), "r"(r1), "r"(r2), "r"(r3) : "memory");
}
DEVI uint2 lds64v(uint32_t a) { uint2 v; asm volatile("ld.volatile.shared.v2.u32 {%0,%1}, [%2];" : "=r"(v.x), "=r"(v.y) : "r"(a) : "memory"); return v; }
DEVI uint32_t lds32v(uint32_t a) { uint32_t v; asm volatile("ld.volatile.shared.u32 %0, [%1];" : "=r"(v) : "r"(a) : "memory"); return v; }
DEVI uint4 lds128v(uint32_t a) { uint4 v; asm volatile("ld.volatile.shared.v4.u32 {%0,%1,%2,%3}, [%4];" : "=r"(v.x), "=r"(v.y), "=r"(v.z), "=r"(v.w) : "r"(a) : "memory"); return v; }
DEVI void sts32(uint32_t a, uint32_t x) { asm volatile("st.shared.u32 [%0], %1;" :: "r"(a), "r"(x) : "memory"); }
DEVI int lane_id() { int r; asm volatile("mov.u32 %0, %%laneid;" : "=r"(r)); return r; }
DEVI void sts64(uint32_t a, uint32_t x, uint32_t y) { asm volatile("st.shared.v2.u32 [%0], {%1,%2};" :: "r"(a), "r"(x), "r"(y) : "memory"); }
DEVI void st_async128(uint32_t a, uint32_t x, uint32_t y, uint32_t z, uint32_t w, uint32_t bar) {
  asm volatile("st.async.weak.shared::cluster.mbarrier::complete_tx::bytes.v4.b32 [%0], {%1,%2,%3,%4}, [%5];" :: "r"(a), "r"(x), "r"(y), "r"(z), "r"(w), "r"(bar) : "memory");
}
DEVI void st_async32(uint32_t a, uint32_t x, uint32_t bar) {
  asm volatile("st.async.weak.shared::cluster.mbarrier::complete_tx::bytes.b32 [%0], %1, [%2];" :: "r"(a), "r"(x), "r"(bar) : "memory");
}
DEVI uint4 ldg_rlx128(const void* p) {
  uint4 v;
  asm volatile("ld.relaxed.gpu.global.v4.b32 {%0,%1,%2,%3}, [%4];" : "=r"(v.x), "=r"(v.y), "=r"(v.z), "=r"(v.w) : "l"(p) : "memory");
  return v;
}
DEVI int ldg_rlx32(const void* p) { int v; asm volatile("ld.relaxed.gpu.global.b32 %0, [%1];" : "=r"(v) : "l"(p) : "memory"); return v; }
DEVI int ldg_acq32(const void* p) { int v; asm volatile("ld.acquire.gpu.global.b32 %0, [%1];" : "=r"(v) : "l"(p) : "memory"); return v; }
DEVI void stg128(void* p, uint32_t x, uint32_t y, uint32_t z, uint32_t w) {
  asm volatile("st.global.v4.b32 [%0], {%1,%2,%3,%4};" :: "l"(p), "r"(x), "r"(y), "r"(z), "r"(w) : "memory");
}
DEVI uint2 ldg_rlx64(const void* p) { uint2 v; asm volatile("{.reg .b64 a; ld.relaxed.gpu.global.b64 a, [%2]; mov.b64 {%0,%1}, a;}" : "=r"(v.x), "=r"(v.y) : "l"(p) : "memory"); return v; }
DEVI void stg_rlx64(void* p, uint32_t x, uint32_t y) { asm volatile("{.reg .b64 a; mov.b64 a, {%1,%2}; st.relaxed.gpu.global.b64 [%0], a;}" :: "l"(p), "r"(x), "r"(y) : "memory"); }
DEVI void stg_rlx32(void* p, uint32_t x) { asm volatile("st.relaxed.gpu.global.b32 [%0], %1;" :: "l"(p), "r"(x) : "memory"); }
DEVI void flag_add(int* p) { asm volatile("fence.proxy.async.global; red.release.gpu.global.add.s32 [%0], 1;" :: "l"(p) : "memory"); }
DEVI void e_stg_rlx32(void* p, uint32_t x) { asm volatile(ELECT "st.relaxed.gpu.global.b32 [%0], %1;}" :: "l"(p), "r"(x) : "memory"); }
DEVI void e_flag_add(int* p) { asm volatile("fence.proxy.async.global;\n" ELECT "red.release.gpu.global.add.s32 [%0], 1;}" :: "l"(p) : "memory"); }
DEVI int cluster_rank() { int r; asm volatile("mov.u32 %0, %%cluster_ctarank;" : "=r"(r)); return __shfl_sync(0xffffffffu, r, 0); }
DEVI int cluster_last() { int r; asm volatile("mov.u32 %0, %%cluster_nctarank;" : "=r"(r)); return __shfl_sync(0xffffffffu, r, 0) - 1; }
DEVI int cta_id() { int r; asm volatile("mov.u32 %0, %%ctaid.x;" : "=r"(r)); return __shfl_sync(0xffffffffu, r, 0); }
DEVI uint32_t clock32() { uint32_t c; asm volatile("mov.u32 %0, %%clock;" : "=r"(c)); return c; }
DEVI uint32_t gtime() { uint32_t c; asm volatile("mov.u32 %0, %%globaltimer_lo;" : "=r"(c)); return c; }
DEVI void wait_time(uint32_t t) { while (__any_sync(0xffffffffu, t - gtime() - 1 < 4000u)) {} }
DEVI void spin_until(uint32_t t0, int d) {
  int r;
  while (__any_sync(0xffffffffu, (r = d - (int)(clock32() - t0)) > 0)) {
    if (r > 300) __nanosleep(r >> 2);
  }
}
DEVI void pin2(const void* a, const void* b) { asm volatile("{.reg .pred p; setp.eq.u64 p, %0, %1; @p st.volatile.global.u64 [%0], %1;}" :: "l"(a), "l"(b) : "memory"); }
DEVI void pin2(uint32_t a, uint32_t b) { asm volatile("{.reg .pred p; setp.eq.u32 p, %0, %1; @p st.volatile.shared.u32 [%0], %1;}" :: "r"(a), "r"(b) : "memory"); }
DEVI void p_stg_rlx64(void* p, uint32_t x, uint32_t y, bool c) {
  asm volatile("{.reg .pred p; .reg .b64 a; setp.ne.u32 p, %3, 0; mov.b64 a, {%1,%2}; @p st.relaxed.gpu.global.b64 [%0], a;}" :: "l"(p), "r"(x), "r"(y), "r"((uint32_t)c) : "memory");
}
DEVI void pin2(uint64_t a, uint64_t b) { pin2((const void*)a, (const void*)b); }
DEVI uint64_t pair(uint32_t a, uint32_t bar) { return a | (uint64_t)bar << 32; }
DEVI void st_async32(uint64_t q, uint32_t x) { st_async32((uint32_t)q, x, (uint32_t)(q >> 32)); }
DEVI void st_async128(uint64_t q, uint4 v) { st_async128((uint32_t)q, v.x, v.y, v.z, v.w, (uint32_t)(q >> 32)); }
DEVI float ex2(float x) { float r; asm("ex2.approx.ftz.f32 %0, %1;" : "=f"(r) : "f"(x)); return r; }
DEVI float rcp(float x) { float r; asm("rcp.approx.ftz.f32 %0, %1;" : "=f"(r) : "f"(x)); return r; }
DEVI uint32_t xor_or(uint32_t a, uint32_t t, uint32_t acc) { uint32_t r; asm("lop3.b32 %0, %1, %2, %3, 0xbe;" : "=r"(r) : "r"(a), "r"(t), "r"(acc)); return r; }
DEVI void stsm2(uint32_t addr, uint32_t r0, uint32_t r1) {
  asm volatile("stmatrix.sync.aligned.m8n8.x2.shared.b16 [%0], {%1,%2};" :: "r"(addr), "r"(r0), "r"(r1) : "memory");
}
DEVI uint32_t settag(uint32_t v, uint32_t tag) { return (v & ~1u) | tag; }

#define A4(c, o)  c(d[o+0]), c(d[o+1]), c(d[o+2]), c(d[o+3])
#define A8(c, o)  A4(c, o), A4(c, o+4)
#define A16(c, o) A8(c, o), A8(c, o+8)
#define A12(c, o) A8(c, o), A4(c, o+8)
#define A28(c, o) A16(c, o), A12(c, o+16)
#define RL12 "{%0,%1,%2,%3,%4,%5,%6,%7,%8,%9,%10,%11}"
#define RL28 "{%0,%1,%2,%3,%4,%5,%6,%7,%8,%9,%10,%11,%12,%13,%14,%15,%16,%17,%18,%19,%20,%21,%22,%23,%24,%25,%26,%27}"
#define A20(c, o) A16(c, o), A4(c, o+16)
#define A32(c, o) A16(c, o), A16(c, o+16)
#define RL8  "{%0,%1,%2,%3,%4,%5,%6,%7}"
#define RL16 "{%0,%1,%2,%3,%4,%5,%6,%7,%8,%9,%10,%11,%12,%13,%14,%15}"
#define RL20 "{%0,%1,%2,%3,%4,%5,%6,%7,%8,%9,%10,%11,%12,%13,%14,%15,%16,%17,%18,%19}"
#define RL32 "{%0,%1,%2,%3,%4,%5,%6,%7,%8,%9,%10,%11,%12,%13,%14,%15,%16,%17,%18,%19,%20,%21,%22,%23,%24,%25,%26,%27,%28,%29,%30,%31}"
#define RL64 "{%0,%1,%2,%3,%4,%5,%6,%7,%8,%9,%10,%11,%12,%13,%14,%15,%16,%17,%18,%19,%20,%21,%22,%23,%24,%25,%26,%27,%28,%29,%30,%31," \
  "%32,%33,%34,%35,%36,%37,%38,%39,%40,%41,%42,%43,%44,%45,%46,%47,%48,%49,%50,%51,%52,%53,%54,%55,%56,%57,%58,%59,%60,%61,%62,%63}"
#define WG_OP(shape) "wgmma.mma_async.sync.aligned." shape "k16.f32.bf16.bf16 "
#define DEF_WGMMA(N, RL, AL, i0, i1, i2, i3, i4, i5, i6)                                                                         \
  template<int SC, int TB, int CB> DEVI void rs##N(float* d, const uint32_t* a, uint64_t b) {                                    \
    if (SC) asm volatile("{.reg .b64 tb; add.s64 tb, %" #i4 ", %" #i5 ";\n" WG_OP("m64n" #N) RL ", {%" #i0 ",%" #i1 ",%" #i2 ",%" #i3 "}, tb, 1, 1, 1, %" #i6 ";}" \
      : AL("+f", 0) : "r"(a[0]), "r"(a[1]), "r"(a[2]), "r"(a[3]), "l"(b), "n"(CB), "n"(TB));                                     \
    else asm volatile("{.reg .b64 tb; add.s64 tb, %" #i4 ", %" #i5 ";\n" WG_OP("m64n" #N) RL ", {%" #i0 ",%" #i1 ",%" #i2 ",%" #i3 "}, tb, 0, 1, 1, %" #i6 ";}" \
      : AL("=f", 0) : "r"(a[0]), "r"(a[1]), "r"(a[2]), "r"(a[3]), "l"(b), "n"(CB), "n"(TB));                                     \
  }                                                                                                                              \
  template<int SC, int TA, int TB, int CA, int CB> DEVI void ss##N(float* d, uint64_t a, uint64_t b) {                           \
    if (SC) asm volatile("{.reg .b64 ta, tb; add.s64 ta, %" #i0 ", %" #i2 "; add.s64 tb, %" #i1 ", %" #i3 ";\n" WG_OP("m64n" #N) RL ", ta, tb, 1, 1, 1, %" #i4 ", %" #i5 ";}" \
      : AL("+f", 0) : "l"(a), "l"(b), "n"(CA), "n"(CB), "n"(TA), "n"(TB));                                                       \
    else asm volatile("{.reg .b64 ta, tb; add.s64 ta, %" #i0 ", %" #i2 "; add.s64 tb, %" #i1 ", %" #i3 ";\n" WG_OP("m64n" #N) RL ", ta, tb, 0, 1, 1, %" #i4 ", %" #i5 ";}" \
      : AL("=f", 0) : "l"(a), "l"(b), "n"(CA), "n"(CB), "n"(TA), "n"(TB));                                                       \
  }
DEF_WGMMA(8, "{%0,%1,%2,%3}", A4, 4, 5, 6, 7, 8, 9, 10)
DEF_WGMMA(16, RL8, A8, 8, 9, 10, 11, 12, 13, 14)
DEF_WGMMA(32, RL16, A16, 16, 17, 18, 19, 20, 21, 22)
DEF_WGMMA(40, RL20, A20, 20, 21, 22, 23, 24, 25, 26)
DEF_WGMMA(24, RL12, A12, 12, 13, 14, 15, 16, 17, 18)
DEF_WGMMA(56, RL28, A28, 28, 29, 30, 31, 32, 33, 34)
template<int TA> DEVI void wgmma_n128(float* d, uint64_t a, uint64_t b, int scale_d) {
  asm volatile("{.reg .pred p; setp.ne.b32 p, %66, 0;\n" WG_OP("m64n128") RL64 ", %64, %65, p, 1, 1, %67, 1;}"
    : A32("+f", 0), A32("+f", 32) : "l"(a), "l"(b), "r"(scale_d), "n"(TA));
}

namespace rec {
constexpr int KR = 43;
constexpr uint32_t WSZ = (64 - KR) * 2048, STG = KR * 2048;
constexpr uint32_t WS = 0;
constexpr uint32_t RING = 2 * WSZ;
constexpr uint32_t OB = RING + 3 * 8192;
constexpr uint32_t PB = OB + 4096;
constexpr uint32_t WO = RING + 32768;
constexpr uint32_t ATT = WO + 5 * 16384;
constexpr uint32_t AK = ATT + 10240, AV = ATT + 20480;
constexpr uint32_t PAD = ATT + 30720;
constexpr uint32_t BARS = PAD + 128;
constexpr uint32_t B_XE = BARS  , B_FA = BARS + 64, B_FO = BARS + 96;
constexpr uint32_t B_ME = BARS + 104  , B_WE = BARS + 136, B_PD = BARS + 144;
constexpr uint32_t B_XF = BARS + 152  , B_MF = BARS + 216  , B_CP = BARS + 248  , B_WT = BARS + 280  ;
constexpr uint32_t B_AB = BARS + 296, B_OB = BARS + 304, B_ST = BARS + 312  , B_WS = BARS + 328, B_WO = BARS + 336, B_AT = BARS + 352, B_AV = BARS + 360;
constexpr int NBAR = 46;
constexpr uint32_t M0 = BARS + 384;
constexpr uint32_t SMEM = 232448;
constexpr int NB_P = 1, NB_ST = 2, NB_O = 3, NB_W0 = 4, NB_W1 = 5;
__host__ __device__ constexpr int wo_tile(int rank, int g, int i) { return i < 2 ? i * 6 + (rank == 2 ? g : 4 - 2 * g + rank) : 13 + rank - g; }
enum { D_W  , D_X = 2, D_M  , D_O = 5, D_WO  , D_Q = 8  , D_K = 10, D_V, D_P, ND };
struct Maps { CUtensorMap w[3], wo, xd, xs; uint64_t d[6][ND]; };
static void fill_desc(uint64_t* d) {
  d[D_W] = CD(WS, 16, 1024, 1); d[D_W + 1] = CD(WS + WSZ, 16, 1024, 1); d[D_X] = CD(0, 16, 1024, 1);
  d[D_M] = CD(RING, 128, 8192, 0); d[D_M + 1] = CD(RING, 128, 4096, 0); d[D_O] = CD(OB, 128, 256, 0);
  d[D_WO] = CD(WO + 49152, 16, 1024, 1); d[D_WO + 1] = CD(WO, 16, 1024, 1);
  d[D_Q] = CD(ATT + 128, 640, 64, 0); d[D_Q + 1] = CD(ATT, 640, 0, 0); d[D_K] = CD(AK, 640, 128, 0);
  d[D_V] = CD(AV, 128, 640, 0); d[D_P] = CD(PB, 128, 768, 0);
}
__host__ __device__ constexpr uint32_t mslot(int c) { return (c ^ (c >> 1)) * 12288; }
__host__ __device__ constexpr uint32_t xslot(int s) { return s < 3 ? RING + s * 8192 : s < 5 ? WO + (s - 3) * 8192 : s < 7 ? WO + (s + 1) * 8192 : OB; }
__host__ __device__ constexpr bool k_smem(int k) { return k % 3 == 2; }
__host__ __device__ constexpr int k_idx(int k) { return k % 3 == 2 ? k / 3 : k - k / 3; }
__host__ __device__ constexpr int k_of_reg(int i) { return i + (i >> 1); }
__host__ __device__ constexpr int k_of_smem(int i) { return 3 * i + 2; }

#define RPROF(i)
#define RPROF_STEP
#define CPROF(i, v)

template<bool DUAL, int K0, int K1> DEVI void seq_mem(float* d, const uint32_t* w, uint64_t dw, uint64_t db) {
  if constexpr (K0 < K1) {
    constexpr int B = mslot(K0 >> 4) / 16 + (K0 & 15) * 16;
    if constexpr (DUAL) {
      if constexpr (!k_smem(K0)) rs24<K0 != 0, 1, B>(d, w + 4 * k_idx(K0), db); else ss24<1, 1, 1, k_idx(K0) * 128, B>(d, dw, db);
    } else {
      if constexpr (!k_smem(K0)) rs16<K0 != 0, 1, B>(d, w + 4 * k_idx(K0), db); else ss16<1, 1, 1, k_idx(K0) * 128, B>(d, dw, db);
    }
    seq_mem<DUAL, K0 + 1, K1>(d, w, dw, db);
  }
}
template<int N, int K0, int K1> DEVI void seq_tok(float* d, const uint32_t* w, uint64_t dw, uint64_t db) {
  if constexpr (K0 < K1) {
    constexpr bool DUAL = N > 32;
    constexpr int B = (DUAL ? xslot((K0 >> 2) & 7) / 16 : xslot(K0 >> 3) / 16 + ((K0 >> 2) & 1) * 256) + (K0 & 3) * 2;
    if constexpr (DUAL) {
      if constexpr (!k_smem(K0)) rs56<K0 != 0, 0, B>(d, w + 4 * k_idx(K0), db); else ss56<1, 1, 0, k_idx(K0) * 128, B>(d, dw, db);
    } else if constexpr (N == 24) {
      if constexpr (!k_smem(K0)) rs24<K0 != 0, 0, B>(d, w + 4 * k_idx(K0), db); else ss24<1, 1, 0, k_idx(K0) * 128, B>(d, dw, db);
    } else {
      if constexpr (!k_smem(K0)) rs32<K0 != 0, 0, B>(d, w + 4 * k_idx(K0), db); else ss32<1, 1, 0, k_idx(K0) * 128, B>(d, dw, db);
    }
    seq_tok<N, K0 + 1, K1>(d, w, dw, db);
  }
}
template<bool DUAL, int T, int K0> DEVI void seq_wo(float* d, uint64_t dw, uint64_t db) {
  if constexpr (K0 < 8) {
    if constexpr (DUAL) ss16<K0 != 0, 1, 1, T * 1024 + K0 * 128, K0 * 32>(d, dw, db);
    else ss8<K0 != 0, 1, 1, T * 1024 + K0 * 128, K0 * 32>(d, dw, db);
    seq_wo<DUAL, T, K0 + 1>(d, dw, db);
  }
}
template<int K0> DEVI void seq_s(float* d, uint64_t dq, uint64_t dk) {
  if constexpr (K0 < 8) { ss40<K0 != 0, 1, 1, K0 * 80, K0 * 80>(d, dq, dk); seq_s<K0 + 1>(d, dq, dk); }
}
template<bool DUAL, int J> DEVI void load_x(uint32_t sb, const Maps* M, int t, int rb) {
  if (DUAL) e_tma_3d_mc(sb + xslot(J & 7), &M->xd, J * 64, (t - LAG) * 32, 0, sb + B_XF + (J & 7) * 8, rb);
  else e_tma_3d_mc(sb + xslot(J & 7), &M->xs, 0, (t < NSEG ? t : t - LAG) * 32, J * 2, sb + B_XF + (J & 7) * 8, rb);
}
DEVI void load_x_lent(uint32_t sb, const Maps* M, int t, int j) {
  const bool dual = t >= LAG && t < NSEG;
  const uint32_t dst = sb + (j == 3 ? xslot(3) : xslot(5));
#pragma unroll
  for (int i = 0; i < 2; i++)
    e_tma_3d(dst + i * 8192, dual ? &M->xd : &M->xs, dual ? (j + i) * 64 : 0, (t < LAG ? t : t - LAG) * 32, dual ? 0 : (j + i) * 2, sb + B_XF + (j + i) * 8);
}
DEVI int role_of(int cr) { return cr < 3 ? cr : cr == 3 ? 2 : cr - 4; }
DEVI int first_loader(int last) { return last == 5 ? 3 : 2; }
struct True { static constexpr bool value = true; };
struct False { static constexpr bool value = false; };
struct Ctx { uint32_t sb; const Maps* M; int last; bool issuer; int wi; bool lead; uint32_t par; };
#define XD 1
template<bool DUAL, int J> DEVI void tok_release(const Ctx& c, int t) {
  constexpr int NC = DUAL ? 16 : 8, S = J & 7;
  if constexpr (J + 8 < NC) {
    p_arrive_at(c.sb + B_XE + S * 8, 2, c.lead);
    p_expect_tx(c.sb + B_XF + S * 8, 8192, c.lead && c.wi == 0);
  } else if constexpr (S == 1 || S == 2 || S == 4 || S == 7) p_arrive(c.sb + B_ME + (S >> 1) * 8, c.lead);
  if constexpr (J == 0) {
    if (c.issuer && c.wi == 6) { mbar_spin(c.sb + B_FO, t & 1); load_x<DUAL, 7>(c.sb, c.M, t, c.last); }
  }
  if constexpr (J >= XD && J - XD + 8 < NC) {
    constexpr int I = J - XD;
    if (c.issuer && c.wi == (I & 1) * 4 + 1) { mbar_spin(c.sb + B_XE + I * 8, (t - LAG) & 1); load_x<DUAL, I + 8>(c.sb, c.M, t, c.last); }
  }
}
template<int N, int J, class F, class G> DEVI bool tok_pass(float* d, const uint32_t* w, uint64_t dw, Ctx& c, int t, F after0, G setup) {
  constexpr bool DUAL = N > 32;
  constexpr int NC = DUAL ? 16 : 8, KC = 64 / NC;
  if constexpr (J < NC) {
    if constexpr (J > 1) mbar_spin(c.sb + B_XF + (J & 7) * 8, c.par ^ (J >> 3));
    wg_fence();
    seq_tok<N, J * KC, (J + 1) * KC>(d, w, dw, c.M->d[DUAL ? J >> 3 : N == 24 ? 2 : 3][D_X]);
    wg_commit();
    if constexpr (J == 1) after0();
    if constexpr (J >= NC - 5 && J < NC - 2) setup(J - (NC - 5));
    if constexpr (J > 0) { wg_wait<1>(); tok_release<DUAL, J - 1>(c, t); }
    return tok_pass<N, J + 1>(d, w, dw, c, t, after0, setup);
  } else {
    const bool ok = mbar_test(c.sb + B_MF, t & 1);
    wg_wait<0>();
    tok_release<DUAL, NC - 1>(c, t);
    if (!DUAL) c.par ^= 1;
    return ok;
  }
}
template<int NB> DEVI void pack_tok(uint32_t* e, const float* d) {
#pragma unroll
  for (int i = 0; i < 8; i++) if ((i & 3) < NB) e[i] = pack_bf16(d[4 * (i & 3) + 2 * (i >> 2)], d[4 * (i & 3) + 2 * (i >> 2) + 1]);
}
DEVI void push_tok(const uint32_t* e, uint32_t sb, uint32_t o, int r, int rank) {
  const uint32_t b = mapa(sb, r);
  st_async128(b + o, e[0], e[1], e[2], e[3], b + (rank == 2 ? B_AV : B_AT));
}
DEVI uint32_t h1_tag(int seg) { return ((seg >> 1) & 1) ^ 1; }
template<bool DUAL> DEVI uint4 pack_part(const float* c, int t) {
  if (!DUAL) { const uint32_t x = settag(pack_bf16(c[0], c[1]), h1_tag(t < NSEG ? t : t - LAG)), y = pack_bf16(c[2], c[3]); return make_uint4(x, y, x, y); }
  return make_uint4(settag(pack_bf16(c[0], c[1]), h1_tag(t)), pack_bf16(c[2], c[3]), settag(pack_bf16(c[4], c[5]), h1_tag(t - LAG)), pack_bf16(c[6], c[7]));
}
DEVI void put_part(char* p1, char* p2, uint4 z, int t) { p_stg_rlx64(p1, z.x, z.y, t < NSEG); p_stg_rlx64(p2, z.z, z.w, t >= LAG); }

DEVI void rec_math(const uint32_t sb, const int wi, const Maps& M) {
  const int h = cta_id() / 3, rb = cluster_rank() >= 3 ? 4 : 0, rank = role_of(cluster_rank());
  const int warp = wi & 3, wg = wi >> 2;
  const bool lead = (threadIdx.x & 127) == 0;
  uint32_t w[4 * KR];
  const int last = cluster_last();
  Ctx cx{sb, &M, last, rb + rank == 2, wi, lead, 0};
  {
    const int lane = lane_id();
    const uint32_t a = sb + wg * STG + ((lane & 7) + (lane >> 4) * 8) * 128 + (((warp * 2 + ((lane >> 3) & 1)) ^ (lane & 7)) << 4);
    for (int i = 0; i < (wg == 1 || rank == 2 ? 12 : 8); i++)
      stg_rlx64((char*)g_h1[i & 3] + ((wo_tile(rank, wg, i >> 2) * 4 + warp) * 4 + (lane >> 3)) * 2048 + h * 64 + (lane & 7) * 8, 0, 0);
    mbar_spin(sb + B_ST + wg * 8, 0);
#pragma unroll
    for (int k = 0; k < KR; k++) ldsm4t(a + k * 2048, w[4*k], w[4*k+1], w[4*k+2], w[4*k+3]);
    nbar_arrive<NB_ST, 384>();
    nbar_sync_r(NB_W0 + wg, 128);
    p_arrive_at(sb + B_FA, first_loader(last), lead); p_arrive_at(sb + B_FO, 2, lead);
    mbar_spin(sb + B_WS, 0);
  }
  uint4 z = make_uint4(0, 0, 0, 0);
  char *z1 = nullptr, *z2 = nullptr;
  uint32_t rt0 = 0, rt1 = 0;
  mbar_spin(sb + B_XF, 0); mbar_spin(sb + B_XF + 8, 0);
#pragma unroll 1
  for (int t = 0;; t++) {
    uint32_t e[16];
    bool ok;
    auto finish = [&]() { put_part(z1, z2, z, t - 1); p_arrive_at(sb + B_FO, 2, lead); };
    const int seg = t - rank * LAG;
    const bool att = rank < 2 && (unsigned)seg < (unsigned)NSEG;
    char* p1;
    uint32_t pw, oo;
    uint64_t u0, u1;
    int lane;
    auto setup = [&](int part) {
      if (part == 0) {
        lane = lane_id();
      } else if (part == 1) {
        char* const p = (char*)g_h1 + ((wo_tile(rank, wg, 0) * 4 + warp) * 4 + (lane >> 3)) * 2048 + h * 64 + (lane & 7) * 8;
        p1 = p + (t & 1) * sizeof(g_h1[0]);
        pin2(p1, nullptr);
      } else if (part == 2) {
        oo = OB + (lane >> 4) * 2048 + warp * 512 + (t < NSEG ? rank * 256 : 0) + (lane & 15) * 16;
        pw = sb + PB + (wg ? lane * 4 : 768 + warp * 768 + lane * 16);
        pin2(pw, oo);
      } else {
        if (wg) {
          const int rv = rb ? 3 : 2, ro = rb + ((rank ^ 1) & 1);
          const uint32_t ra = mapa(sb, (warp & 1) ? rv : ro), rc = mapa(sb, (warp & 1) ? ro : rv);
          u0 = pair(ra + oo, ra + B_OB); u1 = pair(rc + oo, rc + B_OB);
        } else {
          u0 = (uint64_t)((char*)(g_ot + rank * O_LAYER) + (size_t)(h * DH + warp * 16 + (lane >> 2)) * (SEQ * 2) + seg * 64 + (lane & 3) * 16);
          u1 = (uint32_t)((lane & 24) + ((lane >> 2) & 1) + 2 * warp - 8 * (lane & 3));
        }
        pin2(u0, u1);
      }
    };
    RPROF_STEP;
    auto mem_pass = [&](auto dual_c) {
      constexpr bool DUAL = decltype(dual_c)::value;
      float m[DUAL ? 12 : 8];
      const uint64_t dw = M.d[4 + DUAL][D_W + wg], dm = M.d[0][D_M + DUAL];
      RPROF(8 + wg * 12 - 32);
      if (!ok) { int budget = SPIN_BUDGET; mbar_wait(sb + B_MF, t & 1, budget); }
      wg_fence(); seq_mem<DUAL, 0, 8>(m, w, dw, dm); wg_commit();
      const uint32_t ao = ATT + rank * 10240 + wi * 1280, to = ao + 128 + (lane & 3) * 128 + (lane >> 2) * 16;
      const int la = DUAL ? rank == 0 || (rank == 2 && wg) : t >= NSEG;
      RPROF(1 + wg * 12);
      if (DUAL && la) {
#pragma unroll
        for (int i = 0; i < 8; i++) { const uint32_t x = e[i]; e[i] = e[8 + i]; e[8 + i] = x; }
      }
      auto piece = [&](int i) { push_tok(e + 4 * i, sb, to + (i & 1) * 640, rb + (la ^ (i >> 1)), rank); };
      piece(0);
      wg_fence(); seq_mem<DUAL, 8, 16>(m, w, dw, dm); wg_commit();
      piece(1);
      mbar_spin(sb + B_MF + 8, t & 1);
      wg_fence(); seq_mem<DUAL, 16, 24>(m, w, dw, dm); wg_commit();
      if (DUAL) piece(2);
      wg_fence(); seq_mem<DUAL, 24, 32>(m, w, dw, dm); wg_commit();
      if (DUAL) piece(3);
      mbar_spin(sb + B_MF + 16, t & 1);
      wg_fence(); seq_mem<DUAL, 32, 48>(m, w, dw, dm); wg_commit();
      wg_wait<1>(); p_arrive(sb + B_PD, lead);
      const uint32_t r0 = mapa(sb, rb + la), r1 = mapa(sb, rb + (la ^ 1)), m0 = r0 + ao + lane * 4, m1 = r1 + ao + lane * 4, ab = rank == 2 ? B_AV : B_AB;
      const uint64_t q0 = pair(m0, r0 + ab), q1 = pair(m0 + 640, r0 + ab), q2 = pair(m1, r1 + ab), q3 = pair(m1 + 640, r1 + ab);
      pin2(q0, q1);
      if (DUAL) pin2(q2, q3);
      mbar_spin(sb + B_MF + 24, t & 1);
      wg_fence(); seq_mem<DUAL, 48, 64>(m, w, dw, dm); wg_commit();
      wg_wait<1>(); p_arrive_at(sb + B_FA, first_loader(last), lead);
      wg_wait<0>();
      const uint32_t a0 = pack_bf16(m[0], m[1]), a1 = pack_bf16(m[2], m[3]), a2 = pack_bf16(m[4], m[5]), a3 = pack_bf16(m[6], m[7]);
      if constexpr (DUAL) {
        st_async32(q0, la ? a2 : a0); st_async32(q1, la ? a3 : a1); st_async32(q2, la ? a0 : a2); st_async32(q3, la ? a1 : a3);
        rt0 = pack_bf16(m[8], m[9]); rt1 = pack_bf16(m[10], m[11]);
      } else { st_async32(q0, a0); st_async32(q1, a1); rt0 = a2; rt1 = a3; }
      p_arrive(sb + B_WE, lead);
    };
    if (t >= LAG && t < NSEG) {
      float d[28];
      ok = tok_pass<56, 0>(d, w, M.d[0][D_W + wg], cx, t, finish, setup);
      pack_tok<4>(e + 8, d); pack_tok<3>(e, d + 16); e[3] = rt0; e[7] = rt1;
      mem_pass(True());
    } else {
      float d[16];
      if (t > 0) finish();
      if (t > 0 && t < LAG) {
        ok = tok_pass<24, 0>(d, w, M.d[2][D_W + wg], cx, t, []() {}, setup);
        pack_tok<3>(e, d); e[3] = rt0; e[7] = rt1;
      } else {
        ok = tok_pass<32, 0>(d, w, M.d[3][D_W + wg], cx, t, []() {}, setup);
        pack_tok<4>(e, d);
      }
      mem_pass(False());
    }
    {
      RPROF(2 + wg * 12);
      auto wo_ready = [&]() { if (t == 0) mbar_spin(sb + B_WO, 0); if (t < NSTEP - 1) mbar_spin(sb + B_WT, t & 1); };
      constexpr float SC = 0.08838834764831845f * 1.4426950408889634f;
      if (!att) wo_ready();
      else {
        float s[32];
        setup(3);
        if (wg) {
          uint32_t one[4];
#pragma unroll
          for (int i = 0; i < 4; i++) one[i] = 0x3F803F80u + (pw >> 31);
          mbar_spin_cluster(sb + B_AT, seg & 1);
          mbar_spin_cluster(sb + B_AB, seg & 1);
          fence_proxy_async();
          RPROF(3 + 12);
          wg_fence(); seq_s<0>(s, M.d[0][D_Q + 1], M.d[0][D_K]); wg_commit();
          nbar_arrive<NB_P, 256>();
          if (warp == 1) sts32(pw + 640, 0);
          mbar_spin_cluster(sb + B_AV, seg & 1);
          wg_wait<0>();
          float mx = fmaxf(fmaxf(fmaxf(s[0], s[1]), fmaxf(s[4], s[5])), fmaxf(fmaxf(fmaxf(s[8], s[9]), fmaxf(s[12], s[13])), fmaxf(s[16], s[17])));
          const float x1 = __shfl_xor_sync(0xffffffffu, mx, 1), x2 = __shfl_xor_sync(0xffffffffu, mx, 2), x3 = __shfl_xor_sync(0xffffffffu, mx, 3);
          const float u = (warp & 2) ? ((warp & 1) ? s[16] : s[12]) : ((warp & 1) ? s[8] : s[4]);
          const float v = (warp & 2) ? ((warp & 1) ? s[17] : s[13]) : ((warp & 1) ? s[9] : s[5]);
          const float ms = -SC * fmaxf(fmaxf(mx, x1), fmaxf(x2, x3));
          sts32(pw + 128 + warp * 128, pack_bf16(ex2(fmaf(u, SC, ms)), ex2(fmaf(v, SC, ms))));
          if (warp == 0) sts32(pw, pack_bf16(ex2(fmaf(s[0], SC, ms)), ex2(fmaf(s[1], SC, ms))));
          fence_proxy_async();
          nbar_sync<NB_W1, 128>();
          RPROF(4 + 12);
          wg_fence();
          rs8<0, 0, 0>(s + 8, one, M.d[2][D_P]); rs8<1, 0, 16>(s + 8, one, M.d[2][D_P]); rs8<1, 0, 32>(s + 8, one, M.d[2][D_P]);
          wg_commit();
          ss8<0, 0, 0, 0, 0>(s, M.d[0][D_V], M.d[0][D_P]); ss8<0, 0, 0, 320, 0>(s + 4, M.d[0][D_V], M.d[1][D_P]);
          ss8<1, 0, 0, 16, 16>(s, M.d[0][D_V], M.d[0][D_P]); ss8<1, 0, 0, 336, 16>(s + 4, M.d[0][D_V], M.d[1][D_P]);
          ss8<1, 0, 0, 32, 32>(s, M.d[0][D_V], M.d[0][D_P]); ss8<1, 0, 0, 352, 32>(s + 4, M.d[0][D_V], M.d[1][D_P]);
          wg_commit();
          wg_wait<1>();
          const float i0 = rcp(s[8]), i1 = rcp(s[9]);
          wg_wait<0>();
          stsm4(sb + oo, pack_bf16(s[0] * i0, s[1] * i1), pack_bf16(s[2] * i0, s[3] * i1), pack_bf16(s[4] * i0, s[5] * i1), pack_bf16(s[6] * i0, s[7] * i1));
          __syncwarp();
          const uint4 y = lds128v(sb + oo);
          if (t < NSTEP - 1) { st_async128(u0, y); st_async128(u1, y); e_complete_tx(sb + B_OB, 512); }
          wo_ready();
        } else {
          const int lim = (int)u1;
          char* const og = (char*)u0;
          nbar_sync<NB_P, 256>();
          RPROF(3);
          wg_fence();
          seq_s<0>(s, M.d[0][D_Q], M.d[1][D_K]);
          wg_commit();
          mbar_spin_cluster(sb + B_AV, seg & 1);
          wg_wait<0>();
#pragma unroll
          for (int i = 0; i < 8; i++) { float& v = s[4 + 4 * (i >> 1) + (i & 1)]; v = i <= lim ? v : -INFINITY; }
          float mx = fmaxf(fmaxf(fmaxf(s[0], s[1]), fmaxf(s[4], s[5])), fmaxf(fmaxf(fmaxf(s[8], s[9]), fmaxf(s[12], s[13])), fmaxf(s[16], s[17])));
          const float x1 = __shfl_xor_sync(0xffffffffu, mx, 1), x2 = __shfl_xor_sync(0xffffffffu, mx, 2), x3 = __shfl_xor_sync(0xffffffffu, mx, 3);
          const float ms = -SC * fmaxf(fmaxf(mx, x1), fmaxf(x2, x3));
#pragma unroll
          for (int i = 0; i < 10; i++) { float& v = s[4 * (i >> 1) + (i & 1)]; v = ex2(fmaf(v, SC, ms)); }
          const float sum = (((s[0] + s[1]) + (s[4] + s[5])) + ((s[8] + s[9]) + (s[12] + s[13]))) + (s[16] + s[17]);
          const float y1 = __shfl_xor_sync(0xffffffffu, sum, 1), y2 = __shfl_xor_sync(0xffffffffu, sum, 2), y3 = __shfl_xor_sync(0xffffffffu, sum, 3);
          const float inv = rcp((sum + y1) + (y2 + y3));
          stsm4(pw, pack_bf16(s[0] * inv, s[1] * inv), pack_bf16(s[4] * inv, s[5] * inv), pack_bf16(s[8] * inv, s[9] * inv), pack_bf16(s[12] * inv, s[13] * inv));
          stsm2(pw + 512, pack_bf16(s[16] * inv, s[17] * inv), 0);
          fence_proxy_async();
          nbar_sync<NB_W0, 128>();
          RPROF(4);
          wg_fence();
          ss32<0, 0, 0, 0, 48>(s, M.d[1][D_V], M.d[3][D_P]); ss32<0, 0, 0, 320, 48>(s + 16, M.d[1][D_V], M.d[4][D_P]);
          ss32<1, 0, 0, 16, 64>(s, M.d[1][D_V], M.d[3][D_P]); ss32<1, 0, 0, 336, 64>(s + 16, M.d[1][D_V], M.d[4][D_P]);
          ss32<1, 0, 0, 32, 80>(s, M.d[1][D_V], M.d[3][D_P]); ss32<1, 0, 0, 352, 80>(s + 16, M.d[1][D_V], M.d[4][D_P]);
          wg_commit();
          wo_ready();
          wg_wait<0>();
#pragma unroll
          for (int i = 0; i < 4; i++) {
            const float* d = s + (i >> 1) * 16 + (i & 1) * 2;
            stg128(og + ((i >> 1) * 64 + (i & 1) * 8) * (SEQ * 2), pack_bf16(d[0], d[1]), pack_bf16(d[4], d[5]), pack_bf16(d[8], d[9]), pack_bf16(d[12], d[13]));
          }
          if ((seg & 3) == 3) nbar_arrive<NB_O, 160>();
        }
      }
      RPROF(5 + wg * 12);
      const bool three = wg == 1 || rank == 2;
      char* const p2 = p1 + (2 + ((t - LAG) & 1) - (t & 1)) * (int)sizeof(g_h1[0]);
      if (t < NSTEP - 1) {
        auto wo_pass = [&](auto dual_c) {
          constexpr bool DUAL = decltype(dual_c)::value;
          float c[24];
          const uint64_t dt = M.d[DUAL][D_WO + wg];
          mbar_spin_cluster(sb + B_OB, t & 1);
          fence_proxy_async();
          RPROF(6 + wg * 12);
          wg_fence(); seq_wo<DUAL, 0, 0>(c, dt, M.d[DUAL * 3 + 0][D_O]); wg_commit(); seq_wo<DUAL, 1, 0>(c + 8, dt, M.d[DUAL * 3 + 1][D_O]); wg_commit();
          mbar_spin(sb + B_XF, cx.par);
          wg_wait<1>();
          if (warp == 2) load_x_lent(sb, &M, t + 1, wg ? 3 : 5);
          put_part(p1, p2, pack_part<DUAL>(c, t), t);
          const int o3 = (wo_tile(rank, wg, three ? 2 : 1) - wo_tile(rank, wg, 0)) * 32768;
          z1 = p1 + o3; z2 = p2 + o3;
          if (three) {
            wg_fence(); seq_wo<DUAL, 2, 0>(c + 16, dt, M.d[DUAL * 3 + 2][D_O]); wg_commit();
            wg_wait<1>(); put_part(p1 + 6 * 32768, p2 + 6 * 32768, pack_part<DUAL>(c + 8, t), t);
            mbar_spin(sb + B_XF + 8, cx.par);
            wg_wait<0>(); z = pack_part<DUAL>(c + 16, t);
          } else { mbar_spin(sb + B_XF + 8, cx.par); wg_wait<0>(); z = pack_part<DUAL>(c + 8, t); }
        };
        if (t >= LAG && t < NSEG) wo_pass(True()); else wo_pass(False());
      } else { p_arrive(sb + B_PD, lead); break; }
      RPROF(7 + wg * 12);
    }
  }
}

DEVI void wait_xa(const int* p, int& budget) {
#pragma unroll 1
  while (__any_sync(0xffffffffu, ldg_acq32(p) < 64) && --budget > 0) {}
  fence_proxy_global();
}
DEVI void rec_comm(const uint32_t sb, const int warp, const Maps& M, const bf16* __restrict__ mem0) {
  const int lane = threadIdx.x & 31, h = cta_id() / 3, rank = role_of(cluster_rank());
  int budget = SPIN_BUDGET;
  const bool two = warp == 3 || (rank == 2 && warp == 2);
  const int ntask = two ? 2 : 1, qi = two ? (warp == 3 ? rank : 3) : rank * 3 + warp;
  const int task0 = two ? h * 2 + (qi >> 1) : 64 + h * 4 + (qi >> 1);
  auto h2_word = [&](int i, int ln) {
    const int task = task0 + i * 192;
    return (char*)g_h2 + (task >> 6) * 8192 + ((qi ^ i) & 1) * 4096 + ((task >> 2) & 15) * 256 + (task & 3) * 32 + (ln & 8) * 16 + (ln & 7) * 4;
  };
  auto first_x = [&](int t) {
    const int n = t + 1;
    p_expect_tx(sb + B_XF + (lane_id() & 7) * 8, 8192, lane_id() < 8);
    const int last = cluster_last();
    if (cluster_rank() == first_loader(last)) {
      const bool dual = n >= LAG && n < NSEG;
      const int row = (n < LAG ? n : n - LAG) * 32;
      if (n >= LAG && (row & 127) == 0) {
        wait_xa(&g_xa[1][row >> 7], budget);
        e_prefetch_3d(&M.xs, 0, row, h & 14);
      }
      mbar_wait(sb + B_FA, n & 1, budget);
#pragma unroll 1
      for (int j = 0; j < (n ? 3 : 7); j++)
        e_tma_3d_mc(sb + xslot(j), dual ? &M.xd : &M.xs, dual ? j * 64 : 0, row, dual ? 0 : j * 2, sb + B_XF + j * 8, last);
    }
  };
  {
    const int task = task0 + (lane >> 4) * 192, L = (task & 3) * 8 + (lane & 7);
    if ((lane >> 4) < ntask) {
      const bf16* p = mem0 + (L & 3) * 2 * DM + (task >> 2) * 16 + (L >> 2) + (lane & 8);
      uint32_t m0 = (uint32_t)__bfloat16_as_ushort(p[0]) | (uint32_t)__bfloat16_as_ushort(p[DM]) << 16;
      m0 = m0 ? m0 : 0x8000u;
      stg_rlx32(h2_word(lane >> 4, lane), ((qi ^ (lane >> 4)) & 1) ? 0 : m0);
      for (int i = 1; i < 4; i++) stg_rlx32(h2_word(lane >> 4, lane) + i * sizeof(g_h2[0]), 0);
      sts32(sb + M0 + warp * 128 + lane * 4, m0);
    }
    __syncwarp();
    mbar_wait(sb + B_ST, 0, budget); mbar_wait(sb + B_ST + 8, 0, budget);
    if (budget <= 0) __trap();
    nbar_sync<NB_ST, 384>();
    if (warp == 2) {
      e_expect_tx(sb + B_WS, 2 * WSZ);
#pragma unroll 1
      for (int i = 0; i < 2 * (64 - KR); i++) e_tma_2d(sb + WS + (i & 1) * WSZ + (i >> 1) * 2048, &M.w[rank], h * DH + (i & 1) * 64, k_of_smem(i >> 1) * 16, sb + B_WS);
      const int nt = rank == 2 ? 6 : 5;
      e_expect_tx(sb + B_WO, (nt - 2) * 16384);
#pragma unroll 1
      for (int i = 1; i < nt; i++) if (i != 3) e_tma_2d(sb + WO + i * 16384, &M.wo, wo_tile(rank, 1 - i / 3, i % 3) * 64, h * DH, sb + B_WO);
    }
    wait_xa(&g_xa[0][0], budget);
    if (warp == 3) first_x(-1);
  }
  uint32_t cpp = 0;
  const uint32_t cp = sb + B_CP + warp * 8;
  uint32_t f_dst, f_chk, f_bar, f_time = gtime() - 4000;
  const char *f_src, *f_xr;
  auto prepare = [&](int s) {
    const int ck = warp ^ (warp < 2 && (s < LAG || s >= NSEG) && (rank & 1) == (s >= NSEG)), ln = lane_id();
    f_dst = sb + RING + mslot(ck); f_chk = f_dst + ln * 32 + (ln >> 2) * 4; f_bar = sb + ck * 8;
    f_src = (const char*)g_h2[s & 3] + ck * 8192 + (s >= NSEG ? 4096 : 0);
    f_xr = (const char*)g_xr[(s + 1) & 63] + ck * 4096;
    pin2(f_chk, 0u);
    return s <= LAG ? TP(9) + ck * TP(11) : s <= NSEG ? TP(1) + ck * TP(4) : TP(13) + ck * TP(11);
  };
  prepare(0);
#pragma unroll 1
  for (int t = 0;; t++) {
    const int n = t + 1;
    const bool dual = t >= LAG && t < NSEG;
    RPROF_STEP;
    {
      const uint32_t bytes = dual ? 8192 : 4096;
      e_expect_tx(cp, bytes + (n < NSEG ? 4096 : 0));
      mbar_wait(f_bar + B_ME, t & 1, budget);
      if (n < NSEG) e_bulk_g2s(f_dst + 8192, f_xr, 4096, cp);
      wait_time(f_time);
      RPROF(24); CPROF(0, gtime());
      int tries = 0;
      while (true) {
        tries++;
        e_bulk_g2s(f_dst, f_src, bytes, cp);
        mbar_wait(cp, cpp, budget); cpp ^= 1;
        uint32_t mn = min(min(lds32v(f_chk), lds32v(f_chk + 1024)), min(lds32v(f_chk + 2048), lds32v(f_chk + 3072)));
        if (dual) mn = min(min(mn, min(lds32v(f_chk + 4096), lds32v(f_chk + 5120))), min(lds32v(f_chk + 6144), lds32v(f_chk + 7168)));
        if (!__any_sync(0xffffffffu, mn == 0) || --budget < 0) break;
        e_expect_tx(cp, bytes);
      }
      e_arrive(f_bar + B_MF);
      RPROF(25); CPROF(1, gtime()); CPROF(2, tries);
    }
    const int seg = t - rank * LAG;
    const bool att = rank < 2 && (unsigned)seg < (unsigned)NSEG;
    auto block_done = [&]() {
      if (warp == 1 && att && (seg & 3) == 3) { nbar_sync<NB_O, 160>(); e_flag_add(&g_dep[E_O1 + rank * 16 + (seg >> 2)]); }
    };
    if (warp == 0) {
      if (att) { e_expect_tx(sb + B_AT, 16384); e_expect_tx(sb + B_AB, 4096); e_expect_tx(sb + B_AV, 10240); }
      if (n < NSTEP) e_expect_tx(sb + B_OB, dual ? 4096 : 2048);
    }
    if (n + 1 < NSEG && (n & 3) == 3) wait_xa(&g_xa[0][(n + 1) >> 2], budget);
    if (rank == 2 && warp == 1) {
      if (h < 16 ? n < NSEG : n > LAG && n < NSTEP && ((n - LAG) & 3)) e_prefetch_3d(&M.xs, 0, (h < 16 ? n : n - LAG) * 32, (h & 7) * 2);
      if (h >= 16 && n + 1 < NSEG) asm volatile(ELECT "cp.async.bulk.prefetch.L2.global [%0], 2048;}" :: "l"((const char*)g_xr[n + 1] + (h & 7) * 2048) : "memory");
    }
    {
      const int ln = lane_id(), i = ln >> 4;
      char* const w = h2_word(i, ln);
      if (i < ntask) {
        stg_rlx32(w + ((t + 3) & 3) * sizeof(g_h2[0]), 0);
        if (n == LAG && ((qi ^ i) & 1)) stg_rlx32(w + (n & 3) * sizeof(g_h2[0]), lds32v(sb + M0 + warp * 128 + ln * 4));
      }
      __syncwarp();
    }
    if (n < NSTEP) {
      const uint32_t tag = (n >> 1) & 31;
      mbar_wait(sb + B_PD, t & 1, budget);
      uint32_t t0 = clock32();
      if (warp == 2) {
        e_expect_tx(sb + B_WT, 32768);
        e_tma_2d(sb + WO + 49152, &M.wo, wo_tile(rank, 0, 0) * 64, h * DH, sb + B_WT);
        mbar_wait(sb + B_WE, t & 1, budget);
        e_tma_2d(sb + WO, &M.wo, wo_tile(rank, 1, 0) * 64, h * DH, sb + B_WT);
      }
      if (warp == 3) first_x(t);
      if (warp == 0 && rank == (t >= NSEG)) { mbar_wait(sb + B_AB, seg & 1, budget); e_stg_rlx32(&g_ts[t & 1][h], (gtime() & ~31u) | tag); }
      const int fd = prepare(n), ln = lane_id();
      const int sa = t - (qi & 1) * LAG, sc = t - (~qi & 1) * LAG;
      const int i0 = (unsigned)sa < (unsigned)(NSEG - 1) ? 0 : 1, i1 = two && (unsigned)sc < (unsigned)(NSEG - 1) ? 2 : 1;
      const char* src = (const char*)g_h1[(qi & 1) * 2 + (sa & 1)] + task0 * 2048 + ln * 8;
      char* dst = h2_word(0, ln) + (n & 3) * sizeof(g_h2[0]);
      const int ds = ((~qi & 1) * 2 + (sc & 1) - (qi & 1) * 2 - (sa & 1)) * (int)sizeof(g_h1[0]) + 192 * 2048, dd = 3 * 8192 + ((qi & 1) ? -4096 : 4096);
      if (i0) { src += ds; dst += dd; }
      pin2(src, dst);
      spin_until(t0, TSD);
      uint32_t v0;
      do { v0 = ldg_rlx32(&g_ts[t & 1][ln]); } while (__any_sync(0xffffffffu, (v0 & 31) != tag) && --budget > 0);
      const uint32_t now = __shfl_sync(0xffffffffu, v0, 0);
      t0 = now + __reduce_max_sync(0xffffffffu, (int)(v0 - now));
      f_time = t0 + fd;
      RPROF(26); CPROF(3, t0);
      block_done();
      t0 += t < LAG ? TP(8) : t < NSEG ? TP(0) : TP(12);
#pragma unroll 1
      for (int i = i0; i < i1; i++) {
        const uint32_t tg = h1_tag(i ? sc : sa);
        uint2 v[8];
        wait_time(t0 + (!two ? 0 : i ? TP(3) : -TP(10)));
        int tries = 0;
        float a[4];
        while (true) {
          tries++;
#pragma unroll
          for (int k = 0; k < 8; k++) v[k] = ldg_rlx64(src + k * 256);
          asm volatile("{.reg .pred p; setp.eq.s32 p, %0, 0x7fffffff; @p exit;}" :: "r"(budget) : "memory");
          uint32_t bad = 0;
#pragma unroll
          for (int k = 0; k < 8; k++) {
            bad = xor_or(v[k].x, tg, bad);
            a[0] = k ? a[0] + bf_lo(v[k].x) : bf_lo(v[k].x); a[1] = k ? a[1] + bf_hi(v[k].x) : bf_hi(v[k].x);
            a[2] = k ? a[2] + bf_lo(v[k].y) : bf_lo(v[k].y); a[3] = k ? a[3] + bf_hi(v[k].y) : bf_hi(v[k].y);
          }
#pragma unroll
          for (int k = 0; k < 2; k++) {
            const float keep = (ln & 8) ? a[2+k] : a[k], send = (ln & 8) ? a[k] : a[2+k];
            a[k] = keep + __shfl_xor_sync(0xffffffffu, send, 8);
          }
#pragma unroll
          for (int k = 0; k < 2; k++) a[k] += __shfl_xor_sync(0xffffffffu, a[k], 16);
          if (!__any_sync(0xffffffffu, bad & 1) || --budget < 0) break;
        }
        const uint32_t out = pack_bf16(a[0], a[1]);
        if (ln < 16) stg_rlx32(dst, out ? out : 0x8000u);
        __syncwarp();
        src += ds; dst += dd;
        if (i == 0) { RPROF(28); CPROF(6, gtime()); CPROF(4, gtime()); CPROF(5, tries); } else CPROF(7, gtime());
      }
    }
    if (n == NSTEP) {
      cluster_arrive();
      if (warp == 0) { mbar_wait(sb + B_PD, t & 1, budget); mbar_wait(sb + B_PD, n & 1, budget); }
      block_done();
    }
    if (budget <= 0) __trap();
    if (n == NSTEP) break;
  }
  if (h == 0 && rank == 0 && warp < 2) g_xa[warp][lane_id()] = 0;
}
}

__global__ void __launch_bounds__(384, 1)
rec_kernel(const __grid_constant__ rec::Maps M, const bf16* __restrict__ mem0) {
  using namespace rec;
  extern __shared__ __align__(1024) uint8_t smem[];
  const uint32_t sb = __shfl_sync(0xffffffffu, smem_u32(smem), 0);
  const int tid = threadIdx.x, wi = __shfl_sync(0xffffffffu, tid >> 5, 0);
  if ((sb & 0x3FFFF) != SMEM_BASE) __trap();
  if (wi == 0) {
    const int h = cta_id() / 3, rank = role_of(cluster_rank());
    const int nwg = 2 * cluster_last() + 2;
    for (int i = tid; i < NBAR; i += 32) mbar_init(sb + BARS + i * 8, i < 13 ? nwg : i < 19 ? 2 : 1);
    ((uint32_t*)(smem + PAD))[tid] = 0;
    fence_mbar_init(); fence_proxy_async();
    __syncwarp();
    e_expect_tx(sb + B_ST, STG); e_expect_tx(sb + B_ST + 8, STG);
    for (int i = 0; i < 2 * KR; i++) e_tma_2d(sb + (i & 1) * STG + (i >> 1) * 2048, &M.w[rank], h * DH + (i & 1) * 64, k_of_reg(i >> 1) * 16, sb + B_ST + (i & 1) * 8);
  } else if (wi == 1) {
    if (blockIdx.x < NEV / 32) { g_dep[blockIdx.x * 32 + (tid & 31)] = 0; g_claim[blockIdx.x * 32 + (tid & 31)] = 0; __threadfence(); }
    __syncwarp();
    asm volatile("griddepcontrol.launch_dependents;" ::: "memory");
  } else if (wi == 2) {
    if ((tid & 31) < 3) asm volatile("prefetch.tensormap [%0];" :: "l"(&M.wo + (tid & 31)) : "memory");
    __syncwarp();
  }
  cluster_arrive(); cluster_wait();
  if (wi < 8) { reg_inc<232>(); rec_math(sb, wi, M); cluster_arrive(); cluster_wait(); }
  else { reg_dec<40>(); rec_comm(sb, wi & 3, M, mem0); cluster_wait(); }
}

namespace gm {
struct Maps { CUtensorMap ot, wo, xn, wg, wu, hl, hs, wd, out; };
constexpr int STAGES = 6, STAGE = 32768;
constexpr uint32_t SO = STAGES * STAGE, BARS = SO + 32768;
constexpr uint32_t B_FULL = BARS, B_EMPTY = BARS + 48, B_TF = BARS + 96, B_TE = BARS + 112, B_ORD = BARS + 128, B_PM = BARS + 144, B_GO = BARS + 160, B_SF = BARS + 168;
constexpr uint32_t MAIL = BARS + 176, PMAIL = BARS + 192;
constexpr uint32_t SMEM = BARS + 256;
constexpr int END = -1;
#define DQ 8
#define GT gtime

struct Tile {
  bool isO, isG, l2; int blk, col, k0, n;
  DEVI Tile(int task, int rank) {
    const int e = task >> 8, id = task & 255;
    const bool isD = e < E_G1 || e >= E_D2;
    isO = e >= E_O1 && e < E_G2; isG = !isD && !isO; l2 = e >= E_O2;
    blk = l2 && !isO ? (e & 7) * 2 + rank : isD ? e >> 1 : e & 15;
    col = l2 && !isO ? id : (isG ? id : id & 3) * 2 + rank;
    k0 = isO ? (id >> 2) * 2048 : isG ? 0 : ((l2 ? e >> 3 : e) & 1) * 1792;
    n = isO ? 32 : isG ? 16 : 28;
    if (e >= E_D2 + DQ) { n = 14; k0 += (id >> 3) * 896; col = id & 7; }
  }
};

DEVI float geglu(float g, float u) {
  const float z = g * (0.7978845608028654f + 0.035677408136300125f * g * g);
  float t; asm("tanh.approx.f32 %0, %1;" : "=f"(t) : "f"(z));
  const float hg = 0.5f * g;
  return fmaf(hg, t, hg) * u;
}
struct Sched {
  int need, size, e;
  bool filler;
  uint4 dep, cl;
  DEVI void init(int lane) {
    e = (lane < 4 ? lane + 12 : lane < 16 ? lane - 4 : lane) * 4;
    const bool d = e < E_G1 || e >= E_D2, o = e >= E_O1 && e < E_G2;
    need = e >= E_D2 ? 56 : d ? 28 : e < E_O1 ? 64 : o ? 32 : 128;
    size = e >= E_D2 ? (e < E_D2 + DQ ? 8 : e < E_D2 + 16 ? 16 : 0) : d ? 4 : o ? 8 : e < E_O1 ? 28 : e < E_G2 + 8 ? 56 : 0;
    filler = (int)blockIdx.x >= TP(5);
  }
  DEVI void scan(int lane) { cl = ldg_rlx128(g_claim + e); dep = ldg_rlx128(g_dep + e); }
  DEVI int next(int lane, int& budget) {
    while (--budget > 0) {
      int av[4], open = 0;
#pragma unroll
      for (int i = 0; i < 4; i++) { const int r = max(size - (int)(&cl.x)[i], 0); open |= r; av[i] = ((int)(&dep.x)[i] >= need ? r : 0) + (i ? av[i - 1] : 0); }
      const uint32_t mo = __ballot_sync(0xffffffffu, open);
      if (!mo) break;
      if (filler) {
        const int x = TP(6) & 3, dx = x == 0 ? dep.x : x == 1 ? dep.y : x == 2 ? dep.z : dep.w;
        filler = !__any_sync(0xffffffffu, e == ((E_O1 + TP(6)) & ~3) && dx >= need);
      }
      if (!filler && (mo & 0xffff) && lane >= E_O2 / 4) av[3] = 0;
      int inc = av[3], pos = 0;
      while (true) {
        const uint32_t m = __ballot_sync(0xffffffffu, inc > pos && av[3]);
        if (!m) break;
        const int l = __ffs(m) - 1, rel = pos - (inc - av[3]), i = (rel >= av[0]) + (rel >= av[1]) + (rel >= av[2]);
        int r = 0;
        if (lane == l) {
          const int tk = atomicAdd(g_claim + e + i, 1);
          r = tk < size ? (e + i) << 8 | tk : -1 - (inc - av[3] + (i == 0 ? av[0] : i == 1 ? av[1] : i == 2 ? av[2] : av[3]) + tk - size);
        }
        r = __shfl_sync(0xffffffffu, r, l);
        if (r >= 0) return r;
        if (pos == 0) {
#pragma unroll
          for (int o = 1; o < 32; o <<= 1) { const int v = __shfl_up_sync(0xffffffffu, inc, o); if (lane >= o) inc += v; }
        }
        pos = -1 - r;
      }
      if (pos == 0) __nanosleep(TP(7));
      scan(lane);
    }
    return END;
  }
};

DEVI void scheduler(const uint32_t sb) {
  const int lane = threadIdx.x & 31;
  int budget = SPIN_BUDGET;
  Sched sc; sc.init(lane);
#pragma unroll 1
  for (int i = 0;; i++) {
    if (i) mbar_wait(sb + B_GO, (i & 1) ^ 1, budget);
    sc.scan(lane);
    if (i == 0) cluster_wait();
    const int task = sc.next(lane, budget);
    const uint32_t r = mapa(sb, lane & 1);
    if (lane < 2) st_async32(r + PMAIL + (i & 1) * 4, task, r + B_PM + (i & 1) * 8);
    __syncwarp();
    if (task == END) break;
  }
}

DEVI void producer(const uint32_t sb, const Maps& M) {
  const int lane = threadIdx.x & 31, rank = cluster_rank();
  int budget = SPIN_BUDGET, s = 0, ph = 0;
#pragma unroll 1
  for (int i = 0;; i++) {
    e_expect_tx(sb + B_PM + (i & 1) * 8, 4);
    mbar_wait_cluster(sb + B_PM + (i & 1) * 8, (i >> 1) & 1, budget);
    const int task = budget < 0 ? END : __shfl_sync(0xffffffffu, (int)lds32v(sb + PMAIL + (i & 1) * 4), 0);
    fence_proxy_global();
    for (int z = 0; z < (task == END ? 2 : 1); z++) {
      const int g = (i + z) & 1;
      mbar_wait(sb + B_TE + g * 8, (((i + z) >> 1) & 1) ^ 1, budget);
      if (lane == 0) { sts64(sb + MAIL + g * 8, task, s | ph << 8); mbar_arrive(sb + B_TF + g * 8); }
      __syncwarp();
    }
    if (task == END) break;
    const Tile T(task, rank);
    const bool shareB = T.l2 && !T.isO;
    const CUtensorMap* mA = T.isO ? &M.ot : T.isG ? &M.xn : &M.hl;
    const CUtensorMap* mB0 = T.isO ? &M.wo : T.isG ? &M.wg : &M.wd;
    const CUtensorMap* mB1 = T.isG ? &M.wu : mB0;
    const int c0 = T.col * (T.isG ? 64 : 128), c1 = T.isG ? c0 : c0 + 64, row = T.blk * 128;
    const int ok = 0;
    int k = T.k0;
#pragma unroll 1
    for (int it = 0; it < T.n; it++, k += 64) {
      const uint32_t a = sb + s * STAGE, fb = sb + B_FULL + s * 8;
      mbar_wait(sb + B_EMPTY + s * 8, ph ^ 1, budget);
      e_expect_tx(fb, STAGE);
      if (shareB) {
        e_tma_2d_mc(a + 16384 + rank * 8192, rank ? mB1 : mB0, rank ? c1 : c0, k, fb);
        e_tma_2d(a, mA, k, row, fb); e_tma_2d(a + 8192, mA, k, row + 64, fb);
      } else {
        e_tma_2d_mc(a + rank * 8192, mA, T.isO ? row + rank * 64 : k, T.isO ? k + ok : row + rank * 64, fb);
        e_tma_2d(a + 16384, mB0, c0, k, fb); e_tma_2d(a + 24576, mB1, c1, k, fb);
      }
      if (it == T.n - TP(2)) e_arrive(sb + B_GO);
      if (++s == STAGES) { s = 0; ph ^= 1; }
    }
  }
}

template<int TA> DEVI void mainloop(float* d0, float* d1, uint32_t sb, int n, int s, int ph, bool lead, uint32_t ord, int& budget) {
  int prev = 0;
  const uint32_t rel = threadIdx.x & 127;
#pragma unroll 1
  for (int i = 0; i < n; i++) {
    mbar_wait(sb + B_FULL + s * 8, ph, budget);
    const uint32_t a = sb + s * STAGE;
    const uint64_t da = mkdesc(a, 16, 1024), db = mkdesc(a + 16384, 8192, 1024);
    wg_fence();
#pragma unroll
    for (int k = 0; k < 4; k++) {
      wgmma_n128<TA>(d0, da + k * (TA ? 128 : 2), db + k * 128, (i | k) != 0);
      wgmma_n128<TA>(d1, da + 512 + k * (TA ? 128 : 2), db + k * 128, (i | k) != 0);
    }
    wg_commit();
    if (i > 0) { wg_wait<1>(); p_arrive_at(sb + B_EMPTY + prev * 8, rel & 1, rel < 2); }
    prev = s;
    if (++s == STAGES) { s = 0; ph ^= 1; }
  }
  p_arrive(ord, lead);
  wg_wait<0>();
  p_arrive_at(sb + B_EMPTY + prev * 8, rel & 1, rel < 2);
}

DEVI void consumer(const uint32_t sb, const Maps& M, const int wg) {
  const int tid = threadIdx.x, lane = tid & 31, warp = (tid >> 5) & 3;
  const bool lead = (tid & 127) == 0;
  const uint32_t so = sb + SO;
  int budget = SPIN_BUDGET;
  float d0[64], d1[64];
#pragma unroll 1
  for (int m = 0;; m++) {
    mbar_wait(sb + B_TF + wg * 8, m & 1, budget);
    const uint2 mail = lds64v(sb + MAIL + wg * 8);
    const int task = __shfl_sync(0xffffffffu, (int)mail.x, 0), pos = __shfl_sync(0xffffffffu, (int)mail.y, 0);
    e_arrive(sb + B_TE + wg * 8);
    if (task == END || budget < 0) break;
    const Tile T(task, cluster_rank());
    mbar_wait(sb + B_ORD + wg * 8, (m & 1) ^ wg ^ 1, budget);
    if (T.isO) mainloop<1>(d0, d1, sb, T.n, pos & 255, pos >> 8, lead, sb + B_ORD + (wg ^ 1) * 8, budget);
    else mainloop<0>(d0, d1, sb, T.n, pos & 255, pos >> 8, lead, sb + B_ORD + (wg ^ 1) * 8, budget);
    mbar_wait(sb + B_SF, wg ^ 1, budget);
    const uint32_t st = so + (warp * 16 + (lane & 15)) * 128;
    if (T.isG) {
      int* const fl = &g_dep[T.l2 ? E_D2 + (T.col >= 28) * 8 + (T.blk >> 1) : E_D1 + T.blk * 2 + (T.col >= 28)];
#pragma unroll
      for (int mm = 0; mm < 2; mm++) {
        const float* d = mm ? d1 : d0;
#pragma unroll
        for (int c = 0; c < 4; c++) {
          uint32_t r[4];
#pragma unroll
          for (int i = 0; i < 4; i++) r[i] = pack_bf16(geglu(d[8*c+2*i], d[32+8*c+2*i]), geglu(d[8*c+2*i+1], d[33+8*c+2*i]));
          stsm4(st + mm * 8192 + (((2 * c + (lane >> 4)) ^ (lane & 7)) << 4), r[0], r[1], r[2], r[3]);
        }
      }
      fence_proxy_async();
      nbar_sync_r(1 + wg, 128);
      if (lead) {
        tma_store_2d(&M.hs, so, T.col * 64, T.blk * 128);
        bulk_commit();
        bulk_wait<0>();
        mbar_arrive(sb + B_SF);
        flag_add(fl);
      }
    } else {
#pragma unroll
      for (int hf = 0; hf < 2; hf++) {
#pragma unroll
        for (int mm = 0; mm < 2; mm++) {
          const float* d = (mm ? d1 : d0) + hf * 32;
#pragma unroll
          for (int c = 0; c < 4; c++)
            stsm4(st + hf * 16384 + mm * 8192 + (((2 * c + (lane >> 4)) ^ (lane & 7)) << 4), pack_bf16(d[8*c], d[8*c+1]), pack_bf16(d[8*c+2], d[8*c+3]),
                  pack_bf16(d[8*c+4], d[8*c+5]), pack_bf16(d[8*c+6], d[8*c+7]));
        }
        fence_proxy_async();
        nbar_sync_r(1 + wg, 128);
        if (lead) { tma_radd_2d(&M.out, so + hf * 16384, T.col * 128 + hf * 64, T.blk * 128); bulk_commit(); }
      }
      if (lead) {
        bulk_wait<0>();
        mbar_arrive(sb + B_SF);
        if (T.isO || !T.l2) flag_add(&g_dep[(!T.isO ? E_LX2 : T.l2 ? E_LX1B : E_LX1A) + T.blk]);
      }
    }
    __syncwarp();
  }
}

DEVI void norm_helper(const bf16* __restrict__ x, bf16* out) {
  const int lane = threadIdx.x & 31;
  int budget = SPIN_BUDGET, tk = lane < 4 ? -1 : 1024;
#pragma unroll 1
  while (--budget > 0) {
    if (tk < 0) tk = atomicAdd(g_claim + E_LI + lane, 1);
    if (__all_sync(0xffffffffu, tk >= 1024)) break;
    const uint32_t m = __ballot_sync(0xffffffffu, tk < 1024 && (lane == 0 || ldg_acq32(g_dep + E_LI + lane * 16 + (tk >> 6)) >= 16));
    if (!m) { __nanosleep(TP(7)); continue; }
    const int ql = __ffs(m) - 1, task = __shfl_sync(0xffffffffu, tk, ql), q = E_LI + ql * 16, ev = task >> 6;
    if (lane == ql) tk = -1;
    const size_t off = (size_t)task * (DM * 4) + lane * 16;
    const char* src = (const char*)(q == E_LI ? x : out) + off;
    uint4 u[8];
#pragma unroll
    for (int i = 0; i < 8; i++) u[i] = ldg_rlx128(src + i * 512);
    if (q == E_LI) {
#pragma unroll
      for (int i = 0; i < 8; i++) stg128((char*)out + off + i * 512, u[i].x, u[i].y, u[i].z, u[i].w);
    }
    int* const fl = q == E_LI ? &g_xa[0][ev] : q == E_LX2 ? &g_xa[1][ev] : &g_dep[q == E_LX1A ? E_G1 + ev : E_G2 + (ev >> 1)];
    float mean[2], rs[2];
#pragma unroll
    for (int r = 0; r < 2; r++) {
      float s0 = 0, s1 = 0;
#pragma unroll
      for (int i = 0; i < 16; i++) { const uint32_t v = (&u[4*r + (i >> 2)].x)[i & 3]; s0 += bf_lo(v); s1 += bf_hi(v); }
      mean[r] = (s0 + s1) * (1.f / 32);
      s0 = s1 = 0;
#pragma unroll
      for (int i = 0; i < 16; i++) { const uint32_t v = (&u[4*r + (i >> 2)].x)[i & 3]; const float a = bf_lo(v) - mean[r], b = bf_hi(v) - mean[r]; s0 = fmaf(a, a, s0); s1 = fmaf(b, b, s1); }
      rs[r] = s0 + s1;
    }
    {
      const bool hi = lane & 16;
      float m1 = hi ? mean[1] : mean[0], q1 = hi ? rs[1] : rs[0], m2 = hi ? mean[0] : mean[1], q2 = hi ? rs[0] : rs[1], cnt = 16;
#pragma unroll
      for (int o = 16; o; o >>= 1) {
        m2 = __shfl_xor_sync(0xffffffffu, m2, o); q2 = __shfl_xor_sync(0xffffffffu, q2, o);
        const float dl = m1 - m2;
        q2 = q1 = fmaf(dl * dl, cnt, q1 + q2); m2 = m1 = 0.5f * (m1 + m2);
        cnt *= 2;
      }
      q1 = rsqrtf(q1 * (1.f / DM) + 1e-5f);
      m2 = __shfl_xor_sync(0xffffffffu, m1, 16); q2 = __shfl_xor_sync(0xffffffffu, q1, 16);
      mean[0] = hi ? m2 : m1; mean[1] = hi ? m1 : m2; rs[0] = hi ? q2 : q1; rs[1] = hi ? q1 : q2;
    }
#pragma unroll
    for (int i = 0; i < 8; i++) {
      uint32_t y[4];
#pragma unroll
      for (int c = 0; c < 4; c++) { const uint32_t v = (&u[i].x)[c]; y[c] = pack_bf16((bf_lo(v) - mean[i >> 2]) * rs[i >> 2], (bf_hi(v) - mean[i >> 2]) * rs[i >> 2]); }
      stg128((char*)g_xn + off + i * 512, y[0], y[1], y[2], y[3]);
      u[i] = make_uint4(y[0], y[1], y[2], y[3]);
    }
    if (q == E_LI && (task & 15) >= 12) {
      uint32_t* const xr = g_xr[task >> 4] + lane * 32 + (task & 3);
#pragma unroll
      for (int i = 0; i < 16; i++) {
        const uint32_t a = (&u[i >> 2].x)[i & 3], b = (&u[4 + (i >> 2)].x)[i & 3];
        xr[(i >> 2) * 1024 + (i & 3) * 8] = __byte_perm(a, b, 0x5410); xr[(i >> 2) * 1024 + (i & 3) * 8 + 4] = __byte_perm(a, b, 0x7632);
      }
    }
    fence_proxy_global();
    __syncwarp();
    if (lane == 0) flag_add(fl);
    __syncwarp();
  }
}
}

__global__ void __cluster_dims__(2, 1, 1) __launch_bounds__(384, 1)
gemm_kernel(const __grid_constant__ gm::Maps M, const bf16* __restrict__ x, bf16* out) {
  using namespace gm;
  extern __shared__ __align__(1024) uint8_t smem[];
  const uint32_t sb = __shfl_sync(0xffffffffu, smem_u32(smem), 0);
  const int tid = threadIdx.x, wi = __shfl_sync(0xffffffffu, tid >> 5, 0);
  if (tid < 22) mbar_init(sb + BARS + tid * 8, tid == 14 || tid == 15 ? 4 : tid >= 6 && tid < 12 ? 2 : 1);
  fence_mbar_init();
  if (tid >= 256 && tid < 265) asm volatile("prefetch.tensormap [%0];" :: "l"(&M.ot + (tid - 256)) : "memory");
  __syncwarp();
  cluster_arrive();
  const bool sched = wi == 11 && cluster_rank() == 0;
  if (!sched) cluster_wait();
  if (wi < 8) { reg_inc<208>(); consumer(sb, M, wi >> 2); cluster_arrive(); cluster_wait(); }
  else {
    reg_dec<88>();
    if (wi == 8) producer(sb, M);
    else if (sched) scheduler(sb);
    else {
      norm_helper(x, out);
      asm volatile("griddepcontrol.wait;" ::: "memory");
    }
    __syncwarp();
    cluster_arrive(); cluster_wait();
  }
}

typedef CUresult (*PFN_encodeTiled)(CUtensorMap*, CUtensorMapDataType, cuuint32_t, void*, const cuuint64_t*, const cuuint64_t*,
                                    const cuuint32_t*, const cuuint32_t*, CUtensorMapInterleave, CUtensorMapSwizzle,
                                    CUtensorMapL2promotion, CUtensorMapFloatOOBfill);
static PFN_encodeTiled g_encode = nullptr;
static CUtensorMap make_map(const void* ptr, uint64_t rows, uint64_t cols, uint32_t box_rows, CUtensorMapL2promotion pr = CU_TENSOR_MAP_L2_PROMOTION_L2_256B) {
  CUtensorMap m;
  cuuint64_t dims[2] = {cols, rows}, strides[1] = {cols * 2};
  cuuint32_t box[2] = {64, box_rows}, es[2] = {1, 1};
  g_encode(&m, CU_TENSOR_MAP_DATA_TYPE_BFLOAT16, 2, (void*)ptr, dims, strides, box, es, CU_TENSOR_MAP_INTERLEAVE_NONE,
           CU_TENSOR_MAP_SWIZZLE_128B, pr, CU_TENSOR_MAP_FLOAT_OOB_FILL_NONE);
  return m;
}

static CUtensorMap make_map3(const void* ptr, uint64_t d0, uint64_t d1, uint64_t d2, uint64_t stride2) {
  CUtensorMap m;
  cuuint64_t dims[3] = {d0, d1, d2}, strides[2] = {DM * 2, stride2};
  cuuint32_t box[3] = {64, 32, 2}, es[3] = {1, 1, 1};
  g_encode(&m, CU_TENSOR_MAP_DATA_TYPE_BFLOAT16, 3, (void*)ptr, dims, strides, box, es, CU_TENSOR_MAP_INTERLEAVE_NONE,
           CU_TENSOR_MAP_SWIZZLE_128B, CU_TENSOR_MAP_L2_PROMOTION_L2_256B, CU_TENSOR_MAP_FLOAT_OOB_FILL_NONE);
  return m;
}

extern "C" void kernel_launch(void* const* d_in, const int* in_sizes, int n_in, void* d_out, int out_size) {
  const bf16* x = (const bf16*)d_in[0];
  const bf16* mem0 = (const bf16*)d_in[1];
  if (!g_encode) {
    void* p = nullptr; cudaDriverEntryPointQueryResult q;
    cudaGetDriverEntryPoint("cuTensorMapEncodeTiled", &p, cudaEnableDefault, &q);
    g_encode = (PFN_encodeTiled)p;
    cudaFuncSetAttribute(gemm_kernel, cudaFuncAttributeMaxDynamicSharedMemorySize, gm::SMEM);
    cudaFuncSetAttribute(rec_kernel, cudaFuncAttributeMaxDynamicSharedMemorySize, rec::SMEM);
  }
  bf16 *xn, *ot, *hh;
  cudaGetSymbolAddress((void**)&xn, g_xn); cudaGetSymbolAddress((void**)&ot, g_ot); cudaGetSymbolAddress((void**)&hh, g_h);
  rec::Maps R;
  for (int i = 0; i < 3; i++) R.w[i] = make_map(d_in[2 + i], DM, NH * DH, 16, CU_TENSOR_MAP_L2_PROMOTION_NONE);
  for (int i = 0; i < 6; i++) rec::fill_desc(R.d[i]);
  R.wo = make_map(d_in[5], NH * DH, DM, 128);
  R.xd = make_map3(xn, DM, SEQ - LAG * 32, 2, (uint64_t)LAG * 32 * DM * 2); R.xs = make_map3(xn, 64, SEQ, DM / 64, 128);
  gm::Maps G;
  G.ot = make_map(ot, NH * DH + O_LAYER / SEQ, SEQ, 64); G.wo = make_map(d_in[5], NH * DH, DM, 64); G.xn = make_map(xn, SEQ, DM, 64);
  G.wg = make_map(d_in[8], DM, DF, 64); G.wu = make_map(d_in[9], DM, DF, 64); G.hl = make_map(hh, SEQ, DF, 64); G.hs = make_map(hh, SEQ, DF, 128);
  G.wd = make_map(d_in[10], DF, DM, 64); G.out = make_map(d_out, SEQ, DM, 128);
  cudaLaunchConfig_t cfg = {};
  cudaLaunchAttribute at[1];
  cfg.attrs = at; cfg.numAttrs = 1;
  cfg.gridDim = dim3(3 * NH); cfg.blockDim = dim3(384); cfg.dynamicSmemBytes = rec::SMEM; cfg.stream = cudaStreamPerThread;
  at[0].id = cudaLaunchAttributeClusterDimension; at[0].val.clusterDim.y = at[0].val.clusterDim.z = 1;
  static int csize = 0;
  if (!csize) {
    int n = 0;
    at[0].val.clusterDim.x = 6;
    csize = cudaOccupancyMaxActiveClusters(&n, rec_kernel, &cfg) == cudaSuccess && n >= NH / 2 ? 6 : 3;
  }
  at[0].val.clusterDim.x = csize;
  cudaLaunchKernelEx(&cfg, rec_kernel, R, mem0);
  cfg.gridDim = dim3(132); cfg.blockDim = dim3(384); cfg.dynamicSmemBytes = gm::SMEM; cfg.stream = cudaStreamPerThread;
  at[0].id = cudaLaunchAttributeProgrammaticStreamSerialization; at[0].val.programmaticStreamSerializationAllowed = 1;
  cudaLaunchKernelEx(&cfg, gemm_kernel, G, x, (bf16*)d_out);
}
```
